```python
import torch

def _softmax(x, axis=-1):
    return torch.softmax(x, dim=axis)
def _gelu(x):
    return torch.nn.functional.gelu(x, approximate="tanh")
def _silu(x):
    return torch.nn.functional.silu(x)
def _sigmoid(x):
    return torch.sigmoid(x)
def _layernorm(x, axis=-1, eps=1e-5):
    m = x.mean(dim=axis, keepdim=True)
    v = x.var(dim=axis, keepdim=True, unbiased=False)
    return (x - m) / torch.sqrt(v + eps)
def _scatter_add(tgt, idx, src, axis=0):
    return tgt.clone().index_add_(axis, idx, src)
def _segment_sum(src, seg, n):
    out = torch.zeros((n,) + src.shape[1:], dtype=src.dtype)
    return out.index_add_(0, seg, src)
def _pad(x, pw):
    flat = tuple(v for pair in reversed(pw) for v in pair)
    return torch.nn.functional.pad(x, flat)

kernel_name = 'standalone__deep_cross_pnn__recsys'

def setup_inputs():

    _w = (lambda a: (lambda t: t.to(torch.bfloat16) if t.is_floating_point() else t)(torch.as_tensor(a)))
    B, F, D, V = 16384, 100, 128, min(1000, 100000)
    H = 4 * D
    return {
        "idx": _w((lambda lo, hi, *s: torch.randint(lo, hi, s))(0, V, B, F).to(torch.int64)),
        "table": _w((lambda *s: torch.randn(*s, dtype=torch.bfloat16) * 1.6)(V, D) * (D ** -0.5)),
        "w_p": _w((lambda *s: torch.randn(*s, dtype=torch.bfloat16) * 0.05)(F * F) * ((F * F) ** -0.5)),
        "w1": _w((lambda *s: torch.randn(*s, dtype=torch.bfloat16) * 1.6)(F * D, H) * ((F * D) ** -0.5)),
        "b1": _w((lambda *s: torch.randn(*s, dtype=torch.bfloat16) * 12.8)(H) * 0.01),
        "w2": _w((lambda *s: torch.randn(*s, dtype=torch.bfloat16) * 0.05)(H) * (H ** -0.5)),
        "b2": _w((lambda *s: torch.randn(*s, dtype=torch.bfloat16) * 1.6)(1) * 0.01),
    }

def reference(idx, table, w_p, w1, b1, w2, b2):
    emb = table[idx]
    B = emb.shape[0]; F = emb.shape[1]; D = emb.shape[2]
    ip = torch.einsum('bid,bjd->bij', emb, emb)
    ip = ip.reshape(B, F * F)
    logit_p = ip @ w_p
    z = emb.reshape(B, F * D)
    h = _gelu(z @ w1 + b1)
    logit_d = h @ w2 + b2
    return logit_p + logit_d
```

```cpp
#include <cuda_runtime.h>
#include <cuda_bf16.h>
#include <cuda_fp16.h>
#include <stdint.h>
#include <cuda.h>

namespace {

constexpr int B_ = 16384, F_ = 100, D_ = 128, V_ = 1000, H_ = 512;
constexpr int NC = 9;
constexpr int PT_OFF = 0;
constexpr int PL_OFF = 64 * 10 * 1024;
constexpr int PS_OFF = PL_OFF + 64 * NC * 8000;
constexpr int IX_OFF = PS_OFF + 64 * NC * 2000;
constexpr int I0_OFF = IX_OFF + 2 * NC * 8192;
constexpr int I9_OFF = I0_OFF + 4096;
constexpr int SCR_N = I9_OFF + 4096;

__device__ __align__(1024) uint4 g_scr[SCR_N];
__device__ float g_partD[64 * B_];
__device__ float g_partP[16 * B_];

#define TS(k, i)
#define TR(slot)

__device__ __forceinline__ uint32_t addbf2(uint32_t a, uint32_t b) { uint32_t r; asm("add.rn.bf16x2 %0,%1,%2;" : "=r"(r) : "r"(a), "r"(b)); return r; }
__device__ __forceinline__ uint4 add4(const uint4& a, const uint4& b) { return make_uint4(addbf2(a.x, b.x), addbf2(a.y, b.y), addbf2(a.z, b.z), addbf2(a.w, b.w)); }
__device__ __forceinline__ void acc4(uint4& a, const uint4& b, int never) {
  asm("{.reg .pred p; setp.eq.s32 p,%8,0;\n"
      "@p add.rn.bf16x2 %0,%0,%4; @p add.rn.bf16x2 %1,%1,%5; @p add.rn.bf16x2 %2,%2,%6; @p add.rn.bf16x2 %3,%3,%7;}"
      : "+r"(a.x), "+r"(a.y), "+r"(a.z), "+r"(a.w) : "r"(b.x), "r"(b.y), "r"(b.z), "r"(b.w), "r"(never));
}
__device__ __forceinline__ uint4 ldtex(cudaTextureObject_t t, int i) {
  uint4 v; asm volatile("tex.1d.v4.u32.s32 {%0,%1,%2,%3},[%4,{%5}];" : "=r"(v.x), "=r"(v.y), "=r"(v.z), "=r"(v.w) : "l"(t), "r"(i)); return v;
}
__device__ __forceinline__ uint4 lds128(uint32_t a) {
  uint4 v; asm volatile("ld.volatile.shared.v4.u32 {%0,%1,%2,%3},[%4];" : "=r"(v.x), "=r"(v.y), "=r"(v.z), "=r"(v.w) : "r"(a)); return v;
}
__device__ __forceinline__ void sts128(uint32_t a, const uint4& v) {
  asm volatile("st.shared.v4.u32 [%0],{%1,%2,%3,%4};" :: "r"(a), "r"(v.x), "r"(v.y), "r"(v.z), "r"(v.w) : "memory");
}
__device__ __forceinline__ void mbar_init(uint32_t bar, int n) { asm volatile("mbarrier.init.shared::cta.b64 [%0],%1;" :: "r"(bar), "r"(n) : "memory"); }
__device__ __forceinline__ void mbar_wait(uint32_t bar, uint32_t parity) {
  uint32_t ok; int it = 0;
  do { asm volatile("{.reg .pred p; mbarrier.try_wait.parity.shared::cta.b64 p,[%1],%2; selp.u32 %0,1,0,p;}" : "=r"(ok) : "r"(bar), "r"(parity) : "memory"); } while (!ok && ++it < (1 << 22));
}
__device__ __forceinline__ void mbar_expect(uint32_t bar, uint32_t bytes) { asm volatile("mbarrier.arrive.expect_tx.shared::cta.b64 _,[%0],%1;" :: "r"(bar), "r"(bytes) : "memory"); }
__device__ __forceinline__ void bulk_g2s(uint32_t dst, const void* src, uint32_t bytes, uint32_t bar) {
  asm volatile("cp.async.bulk.shared::cluster.global.mbarrier::complete_tx::bytes [%0],[%1],%2,[%3];" :: "r"(dst), "l"(src), "r"(bytes), "r"(bar) : "memory");
}
__device__ __forceinline__ void bulk_pf(const void* src, uint32_t bytes) { asm volatile("cp.async.bulk.prefetch.L2.global [%0],%1;" :: "l"(src), "r"(bytes) : "memory"); }
#define PORD 0
#define QORD(n) (n)
#define DYD 4
#define DPF 4
#define DDEPTH 4
#define FENCE_N 8
#define INPL 0
#define STAG 1100
#define PACE 800
#define PM4 "pmevent 1; pmevent 2; pmevent 3; pmevent 4;"
#define PMFILL "pmevent 1;"
#define SCHED_FENCE(never, k) asm volatile("{.reg .pred p; setp.ne.u32 p,%0,%1; @p bra.uni SKIP_%=;" PMFILL "SKIP_%=: }" :: "r"(never), "r"(0x7fff0000 + (k)) : "memory")

__global__ void k_prod_naive(const __nv_bfloat16* __restrict__ table, const __nv_bfloat16* __restrict__ w1) {
  __shared__ float t[8][D_];
  int f = blockIdx.y, v0 = blockIdx.x * 8, h = threadIdx.x;
  for (int i = h; i < 8 * D_; i += 512) t[i / D_][i % D_] = __bfloat162float(table[v0 * D_ + i]);
  __syncthreads();
  float s[8] = {0, 0, 0, 0, 0, 0, 0, 0};
  for (int d = 0; d < D_; d++) { float w = __bfloat162float(w1[(size_t)(f * D_ + d) * H_ + h]);
#pragma unroll
    for (int k = 0; k < 8; k++) s[k] += t[k][d] * w; }
  __nv_bfloat16* P = (__nv_bfloat16*)g_scr;
  int c = h >> 3;
  for (int k = 0; k < 8; k++) {
    size_t e = f < 72 ? (size_t)PL_OFF + ((size_t)(c * NC + (f >> 3)) * 1000 + v0 + k) * 8 + (f & 7)
             : f < 90 ? (size_t)PS_OFF + ((size_t)(c * NC + ((f - 72) >> 1)) * 1000 + v0 + k) * 2 + (f & 1)
                      : (size_t)PT_OFF + (size_t)(c * 10 + f - 90) * 1024 + v0 + k;
    P[e * 8 + (h & 7)] = __float2bfloat16(s[k]);
  }
}
__global__ void k_pnn_naive(const int* __restrict__ idx, const __nv_bfloat16* __restrict__ table, const __nv_bfloat16* __restrict__ wp) {
  __shared__ float e[F_][33];
  int b = blockIdx.x, d0 = blockIdx.y * 32, tid = threadIdx.x;
  for (int i = tid; i < F_ * 32; i += 128) e[i >> 5][i & 31] = __bfloat162float(table[idx[b * F_ + (i >> 5)] * D_ + d0 + (i & 31)]);
  __syncthreads();
  float s = 0; int d = tid & 31;
  for (int i = tid >> 5; i < F_; i += 4) { float u = 0; for (int j = 0; j < F_; j++) u += __bfloat162float(wp[i * F_ + j]) * e[j][d]; s += u * e[i][d]; }
  for (int o = 16; o; o >>= 1) s += __shfl_xor_sync(~0u, s, o);
  if (d == 0) g_partP[(blockIdx.y * 4 + (tid >> 5)) * B_ + b] = s;
}
__device__ __forceinline__ uint32_t s_cell(uint32_t v, int q) {
  const int forb = (v + 3) & 3;
  uint32_t m = (1u << ((forb - q) & 3)) | (16u << ((forb + q) & 3));
  m |= __shfl_xor_sync(0xffffffffu, m, 1); m |= __shfl_xor_sync(0xffffffffu, m, 2);
  int col;
  if ((m & 15) != 15) col = (q + __ffs(~m) - 1) & 3;
  else if (m != 255) col = (__ffs(~m) - 5 - q) & 3;
  else col = (q == forb) ? ((q + 1) & 3) : q;
  return ((col - v) & 3) * 1001 + v;
}
constexpr int TH = 256, NS = 8192 / TH, YD = DYD;
__host__ __device__ constexpr int ye_of(int s) { return s == 3 ? 0 : s == 11 ? 1 : s == 19 ? 2 : s == 23 ? 3 : -1; }
__global__ void k_pack(const int* __restrict__ idx) {
  int i = blockIdx.x * blockDim.x + threadIdx.x;
  int tid = i % TH, s = (i / TH) % NS, k = (i >> 13) % NC, half = i / (NC * 8192);
  int b = half * 8192 + s * TH + tid, l = tid & 7;
  uint32_t e[8];
#pragma unroll
  for (int j = 0; j < 8; j++) e[j] = idx[b * F_ + k * 8 + ((l + j) & 7)] + (l + j < 8);
  uint32_t x = s + YD < NS ? idx[(b + YD * TH) * F_ + 90 + k] : 0;
  const int f0 = l >> 2, ks = (k + 1) % NC, b3 = b + (3 - (s & 3)) * TH;
  const uint32_t cw = s_cell(idx[b * F_ + 72 + 2 * ks + f0], l & 3) | s_cell(idx[b * F_ + 72 + 2 * ks + (f0 ^ 1)], l & 3) << 12;
  const uint32_t c3 = s_cell(idx[b3 * F_ + 72 + 2 * ks + f0], l & 3) | s_cell(idx[b3 * F_ + 72 + 2 * ks + (f0 ^ 1)], l & 3) << 12;
  uint32_t w3 = cw | (c3 >> (8 * (s & 3))) << 24;
  auto pk = [](uint32_t a, uint32_t b2, uint32_t c) { return a << 7 | b2 << 17 | c << 27 | c >> 5; };
  if (k == NC - 1) {
    ((uint32_t*)(g_scr + I0_OFF))[((half * 8 + (s >> 2)) * TH + tid) * 4 + (s & 3)] = cw;
    ((uint32_t*)(g_scr + I9_OFF))[((half * 8 + (s >> 2)) * TH + tid) * 4 + (s & 3)] = idx[b * F_ + 99];
    w3 = 0;
  }
  if (ye_of(s) >= 0) w3 = idx[(half * 8192 + ye_of(s) * TH + tid) * F_ + 90 + k];
  g_scr[IX_OFF + i] = make_uint4(pk(e[0], e[1], e[2]), pk(e[3], e[4], e[5]), pk(e[6], e[7], x), w3);
}

template <int N> __device__ __forceinline__ void wgmma_h(uint32_t* d, const uint32_t* a, uint64_t desc, int acc);
template <> __device__ __forceinline__ void wgmma_h<64>(uint32_t* d, const uint32_t* a, uint64_t desc, int acc) {
  asm volatile("{.reg .pred p; setp.ne.s32 p,%21,0;\n"
    "wgmma.mma_async.sync.aligned.m64n64k16.f16.f16.f16 {%0,%1,%2,%3,%4,%5,%6,%7,%8,%9,%10,%11,%12,%13,%14,%15},{%16,%17,%18,%19},%20,p,1,1,0;}"
    : "+r"(d[0]),"+r"(d[1]),"+r"(d[2]),"+r"(d[3]),"+r"(d[4]),"+r"(d[5]),"+r"(d[6]),"+r"(d[7]),"+r"(d[8]),"+r"(d[9]),"+r"(d[10]),"+r"(d[11]),"+r"(d[12]),"+r"(d[13]),"+r"(d[14]),"+r"(d[15])
    : "r"(a[0]), "r"(a[1]), "r"(a[2]), "r"(a[3]), "l"(desc), "r"(acc));
}
template <> __device__ __forceinline__ void wgmma_h<56>(uint32_t* d, const uint32_t* a, uint64_t desc, int acc) {
  asm volatile("{.reg .pred p; setp.ne.s32 p,%19,0;\n"
    "wgmma.mma_async.sync.aligned.m64n56k16.f16.f16.f16 {%0,%1,%2,%3,%4,%5,%6,%7,%8,%9,%10,%11,%12,%13},{%14,%15,%16,%17},%18,p,1,1,0;}"
    : "+r"(d[0]),"+r"(d[1]),"+r"(d[2]),"+r"(d[3]),"+r"(d[4]),"+r"(d[5]),"+r"(d[6]),"+r"(d[7]),"+r"(d[8]),"+r"(d[9]),"+r"(d[10]),"+r"(d[11]),"+r"(d[12]),"+r"(d[13])
    : "r"(a[0]), "r"(a[1]), "r"(a[2]), "r"(a[3]), "l"(desc), "r"(acc));
}
template <> __device__ __forceinline__ void wgmma_h<48>(uint32_t* d, const uint32_t* a, uint64_t desc, int acc) {
  asm volatile("{.reg .pred p; setp.ne.s32 p,%17,0;\n"
    "wgmma.mma_async.sync.aligned.m64n48k16.f16.f16.f16 {%0,%1,%2,%3,%4,%5,%6,%7,%8,%9,%10,%11},{%12,%13,%14,%15},%16,p,1,1,0;}"
    : "+r"(d[0]),"+r"(d[1]),"+r"(d[2]),"+r"(d[3]),"+r"(d[4]),"+r"(d[5]),"+r"(d[6]),"+r"(d[7]),"+r"(d[8]),"+r"(d[9]),"+r"(d[10]),"+r"(d[11])
    : "r"(a[0]), "r"(a[1]), "r"(a[2]), "r"(a[3]), "l"(desc), "r"(acc));
}
template <> __device__ __forceinline__ void wgmma_h<40>(uint32_t* d, const uint32_t* a, uint64_t desc, int acc) {
  asm volatile("{.reg .pred p; setp.ne.s32 p,%15,0;\n"
    "wgmma.mma_async.sync.aligned.m64n40k16.f16.f16.f16 {%0,%1,%2,%3,%4,%5,%6,%7,%8,%9},{%10,%11,%12,%13},%14,p,1,1,0;}"
    : "+r"(d[0]),"+r"(d[1]),"+r"(d[2]),"+r"(d[3]),"+r"(d[4]),"+r"(d[5]),"+r"(d[6]),"+r"(d[7]),"+r"(d[8]),"+r"(d[9])
    : "r"(a[0]), "r"(a[1]), "r"(a[2]), "r"(a[3]), "l"(desc), "r"(acc));
}
template <> __device__ __forceinline__ void wgmma_h<32>(uint32_t* d, const uint32_t* a, uint64_t desc, int acc) {
  asm volatile("{.reg .pred p; setp.ne.s32 p,%13,0;\n"
    "wgmma.mma_async.sync.aligned.m64n32k16.f16.f16.f16 {%0,%1,%2,%3,%4,%5,%6,%7},{%8,%9,%10,%11},%12,p,1,1,0;}"
    : "+r"(d[0]),"+r"(d[1]),"+r"(d[2]),"+r"(d[3]),"+r"(d[4]),"+r"(d[5]),"+r"(d[6]),"+r"(d[7])
    : "r"(a[0]), "r"(a[1]), "r"(a[2]), "r"(a[3]), "l"(desc), "r"(acc));
}
__device__ __forceinline__ void wgmma_p(float* d, const uint32_t* a, uint64_t desc, int acc) {
  asm volatile("{.reg .pred p; setp.ne.s32 p,%37,0;\n"
    "wgmma.mma_async.sync.aligned.m64n64k16.f32.bf16.bf16 {%0,%1,%2,%3,%4,%5,%6,%7,%8,%9,%10,%11,%12,%13,%14,%15,%16,%17,%18,%19,%20,%21,%22,%23,%24,%25,%26,%27,%28,%29,%30,%31},{%32,%33,%34,%35},%36,p,1,1,1;}"
    : "+f"(d[0]),"+f"(d[1]),"+f"(d[2]),"+f"(d[3]),"+f"(d[4]),"+f"(d[5]),"+f"(d[6]),"+f"(d[7]),"+f"(d[8]),"+f"(d[9]),"+f"(d[10]),"+f"(d[11]),"+f"(d[12]),"+f"(d[13]),"+f"(d[14]),"+f"(d[15]),"+f"(d[16]),"+f"(d[17]),"+f"(d[18]),"+f"(d[19]),"+f"(d[20]),"+f"(d[21]),"+f"(d[22]),"+f"(d[23]),"+f"(d[24]),"+f"(d[25]),"+f"(d[26]),"+f"(d[27]),"+f"(d[28]),"+f"(d[29]),"+f"(d[30]),"+f"(d[31])
    : "r"(a[0]), "r"(a[1]), "r"(a[2]), "r"(a[3]), "l"(desc), "r"(acc));
}

__device__ __forceinline__ void mma16816h(uint32_t* c, const uint32_t* a, uint32_t b0, uint32_t b1) {
  asm("mma.sync.aligned.m16n8k16.row.col.f16.f16.f16.f16 {%0,%1},{%2,%3,%4,%5},{%6,%7},{%0,%1};"
      : "+r"(c[0]), "+r"(c[1]) : "r"(a[0]), "r"(a[1]), "r"(a[2]), "r"(a[3]), "r"(b0), "r"(b1));
}
__device__ __forceinline__ void mma1688h(uint32_t* c, uint32_t a0, uint32_t a1, uint32_t b) {
  asm("mma.sync.aligned.m16n8k8.row.col.f16.f16.f16.f16 {%0,%1},{%2,%3},{%4},{%0,%1};" : "+r"(c[0]), "+r"(c[1]) : "r"(a0), "r"(a1), "r"(b));
}
__device__ __forceinline__ void mma16816f(float* c, const uint32_t* a, uint32_t b) {
  asm("mma.sync.aligned.m16n8k16.row.col.f32.f16.f16.f32 {%0,%1,%2,%3},{%4,%5,%6,%7},{%8,%8},{%0,%1,%2,%3};"
      : "+f"(c[0]), "+f"(c[1]), "+f"(c[2]), "+f"(c[3]) : "r"(a[0]), "r"(a[1]), "r"(a[2]), "r"(a[3]), "r"(b));
}
__device__ __forceinline__ uint32_t hfma2(uint32_t a, uint32_t b, uint32_t c) { uint32_t r; asm("fma.rn.f16x2 %0,%1,%2,%3;" : "=r"(r) : "r"(a), "r"(b), "r"(c)); return r; }
__device__ __forceinline__ uint32_t pack_bf2(float lo, float hi) { uint32_t r; asm("cvt.rn.bf16x2.f32 %0,%1,%2;" : "=r"(r) : "f"(hi), "f"(lo)); return r; }
__device__ __forceinline__ uint32_t pack_h2(float lo, float hi) { uint32_t r; asm("cvt.rn.f16x2.f32 %0,%1,%2;" : "=r"(r) : "f"(hi), "f"(lo)); return r; }
__device__ __forceinline__ float bf_lo(uint32_t w) { return __uint_as_float(w << 16); }
__device__ __forceinline__ float bf_hi(uint32_t w) { return __uint_as_float(w & 0xffff0000u); }
__device__ __forceinline__ uint32_t absmax4(const uint4& v, uint32_t m) {
  return __vmaxu2(__vmaxu2(__vmaxu2(v.x & 0x7fff7fffu, v.y & 0x7fff7fffu), __vmaxu2(v.z & 0x7fff7fffu, v.w & 0x7fff7fffu)), m);
}
__device__ __forceinline__ float pow2_scale(uint32_t mbits, int p) { return __uint_as_float((uint32_t)min(max(253 + p - (int)(mbits >> 7), 2), 252) << 23); }

__host__ __device__ constexpr int pnn_field(int oct, int r) {
  return oct == 12 ? (r < 4 ? 96 + r : -1) : (oct >> 1) < 4 ? 4 * ((oct & 1) * 8 + r) + (oct >> 1) : 64 + 2 * ((oct & 1) * 8 + r) + (oct >> 1) - 4;
}
#define PV 0
constexpr int G_O0 = 7, G_O1 = 3, G_O2 = 0, G_N0 = 6, G_N1 = 4, G_N2 = 0, G_K0 = 4, G_K1 = 2, G_K2 = 0;
__host__ __device__ constexpr bool unit_wg(int kb, int on) {
  return (on >= G_O0 && on < G_O0 + G_N0 && kb < G_K0) || (on >= G_O1 && on < G_O1 + G_N1 && kb < G_K1) || (on >= G_O2 && on < G_O2 + G_N2 && kb < G_K2);
}
__host__ __device__ constexpr bool oct_wg(int on) { return unit_wg(0, on); }
constexpr int G_U1 = G_N0 * G_K0, G_U2 = G_U1 + G_N1 * G_K1, G_U = G_U2 + G_N2 * G_K2;
constexpr int K1_B = 130048, K1_STG = K1_B + 3 * 16384, K1_W = K1_STG + 2 * 16384, K1_BAR = K1_W + 48 * 256, K1_SMEM = K1_BAR + 64;
constexpr int WS = 106;

__global__ void __launch_bounds__(384, 1)
k_tens(const __grid_constant__ CUtensorMap mapW, const __grid_constant__ CUtensorMap mapL, const __grid_constant__ CUtensorMap mapS,
       const __grid_constant__ CUtensorMap mapT, cudaTextureObject_t ti4, cudaTextureObject_t ti2, cudaTextureObject_t ti1,
       const __nv_bfloat16* __restrict__ table, const __nv_bfloat16* __restrict__ wp, int never) {
  extern __shared__ __align__(1024) uint4 sm[];
  const int tid = threadIdx.x, lane = tid & 31, cta = blockIdx.x;
  const uint32_t sbase = (uint32_t)__cvta_generic_to_shared(sm);
  const int g = lane >> 2, r = lane & 3;
  TS(0, 0);
  if (tid >= 256) {
    const int w = (tid >> 5) & 3, rb = cta & 7, hc = cta >> 3;
    const uint32_t full = sbase + K1_BAR;
    auto load_pair = [&](int p, int st) {
      mbar_expect(full + st * 8, 16384);
      asm volatile("cp.async.bulk.tensor.2d.shared::cluster.global.mbarrier::complete_tx::bytes [%0],[%1,{%2,%3}],[%4];"
                   :: "r"(sbase + K1_B + st * 16384), "l"(&mapW), "r"(hc * 32), "r"(QORD(p >> 1) * 512 + (p & 1) * 256), "r"(full + st * 8) : "memory");
    };
    if (tid == 256) {
      mbar_init(full, 1); mbar_init(full + 8, 1); mbar_init(full + 16, 1);
      asm volatile("fence.proxy.async.shared::cta;" ::: "memory");
      load_pair(0, 0); load_pair(1, 1); load_pair(2, 2);
    }
    uint32_t a[2][8][4];
#pragma unroll
    for (int mt = 0; mt < 2; mt++) {
      const int v0 = rb * 128 + mt * 64 + w * 16 + g;
      const uint32_t* p0 = (const uint32_t*)(table + min(v0, V_ - 1) * D_) + r;
      const uint32_t* p1 = (const uint32_t*)(table + min(v0 + 8, V_ - 1) * D_) + r;
#pragma unroll
      for (int ks = 0; ks < 8; ks++) { a[mt][ks][0] = p0[ks * 8]; a[mt][ks][1] = p1[ks * 8]; a[mt][ks][2] = p0[ks * 8 + 4]; a[mt][ks][3] = p1[ks * 8 + 4]; }
    }
    asm volatile("bar.sync 2,128;" ::: "memory");
    const int srow = w * 16 + (lane & 7) + ((lane >> 3) & 1) * 8, sc = lane >> 4;
    const uint64_t desc0 = (uint64_t)(((sbase + K1_B) & 0x3FFFF) >> 4) | ((uint64_t)(8192 >> 4) << 16) | ((uint64_t)(512 >> 4) << 32) | (2ull << 62);
    float d[2][32];
    auto issue = [&](int mt, int st) {
      asm volatile("wgmma.fence.sync.aligned;" ::: "memory");
#pragma unroll
      for (int ks = 0; ks < 8; ks++) wgmma_p(d[mt], a[mt][ks], desc0 + st * 1024 + ks * 64, ks);
      asm volatile("wgmma.commit_group.sync.aligned;" ::: "memory");
    };
    auto drain = [&](int mt, int p) {
      const int quad = QORD(p >> 1), h = p & 1, pr = quad * 2 + h;
      const bool isL = quad < 18, isS = pr < 45;
      const uint32_t stg = sbase + K1_STG + mt * 16384, cs = isL ? 4096 : 2048;
#pragma unroll
      for (int j = 0; j < 2; j++) {
        const uint32_t ad = stg + sc * cs + (isL ? srow * 64 + (((h * 2 + j) ^ (srow >> 1)) & 3) * 16
                                                 : h * 8192 + (isS ? srow * 32 + (((j ^ (srow >> 2)) & 1) * 16) : j * 1024 + srow * 16));
#pragma unroll
        for (int cp = 0; cp < 2; cp++) {
          const float* e = d[mt] + (j * 4 + cp * 2) * 4;
          asm volatile("stmatrix.sync.aligned.m8n8.x4.shared.b16 [%0],{%1,%2,%3,%4};"
                       :: "r"(ad + cp * 2 * cs), "r"(pack_bf2(e[0], e[1])), "r"(pack_bf2(e[2], e[3])), "r"(pack_bf2(e[4], e[5])), "r"(pack_bf2(e[6], e[7])) : "memory");
        }
      }
      if (h) {
        asm volatile("fence.proxy.async.shared::cta;" ::: "memory");
        asm volatile("bar.sync 2,128;" ::: "memory");
        if (tid == 256) {
          const int v0 = rb * 128 + mt * 64;
          if (isL) {
            asm volatile("cp.async.bulk.tensor.4d.global.shared::cta.bulk_group [%0,{%1,%2,%3,%4}],[%5];"
                         :: "l"(&mapL), "r"((quad & 1) * 32), "r"(v0), "r"(quad >> 1), "r"(hc * 4), "r"(stg) : "memory");
          } else {
#pragma unroll
            for (int hh = 0; hh < 2; hh++) {
              const int pq = quad * 2 + hh;
              if (pq < 45) asm volatile("cp.async.bulk.tensor.4d.global.shared::cta.bulk_group [%0,{%1,%2,%3,%4}],[%5];"
                         :: "l"(&mapS), "r"(0), "r"(v0), "r"(pq - 36), "r"(hc * 4), "r"(stg + hh * 8192) : "memory");
              else asm volatile("cp.async.bulk.tensor.3d.global.shared::cta.bulk_group [%0,{%1,%2,%3}],[%4];"
                         :: "l"(&mapT), "r"(v0 * 2), "r"((pq - 45) * 2), "r"(hc * 4), "r"(stg + hh * 8192) : "memory");
            }
          }
          asm volatile("cp.async.bulk.commit_group;" ::: "memory");
        }
      }
    };
    auto wait_acc = [&](int mt) {
      asm volatile("wgmma.wait_group.sync.aligned 0;" ::: "memory");
#pragma unroll
      for (int q = 0; q < 8; q++) asm volatile("" : "+f"(d[mt][q * 4]), "+f"(d[mt][q * 4 + 1]), "+f"(d[mt][q * 4 + 2]), "+f"(d[mt][q * 4 + 3]) :: "memory");
    };
    mbar_wait(full, 0);
    issue(0, 0);
    int st = 0, ph = 0;
#pragma unroll 1
    for (int p = 0; p < 50; p++) {
      wait_acc(0);
      issue(1, st);
      if (!(p & 1)) {
        if (tid == 256) asm volatile("cp.async.bulk.wait_group.read 1;" ::: "memory");
        asm volatile("bar.sync 2,128;" ::: "memory");
      }
      drain(0, p);
      const int stn = st == 2 ? 0 : st + 1;
      if (stn == 0) ph ^= 1;
      if (p + 1 < 50) mbar_wait(full + stn * 8, ph);
      wait_acc(1);
      issue(0, stn);
      if (tid == 256 && !(p & 1)) asm volatile("cp.async.bulk.wait_group.read 0;" ::: "memory");
      asm volatile("bar.sync 2,128;" ::: "memory");
      if (tid == 256 && p + 3 < 50) load_pair(p + 3, st);
      drain(1, p);
      st = stn;
    }
    asm volatile("wgmma.wait_group.sync.aligned 0;" ::: "memory");
    if (tid == 256) asm volatile("cp.async.bulk.wait_group 0;" ::: "memory");
    return;
  }
  const int slice = cta & 15, wg = tid >> 7, w = (tid >> 5) & 3;
  const int pos = ((lane >> 4) << 3) | (lane & 7);
  const int smp0 = (cta >> 4) * 2048 + (tid >> 5) * 256;
  int smp = smp0 + ((lane >> 3) & 1);
  uint4 i4; uint2 i2; uint32_t i1;
  auto ld_idx = [&]() {
    const int b = min(smp, B_ - 1);
    i4 = ldtex(ti4, b * 25 + pos);
    uint4 t = ldtex(ti2, b * 50 + 32 + pos); i2 = make_uint2(t.x, t.y);
    i1 = ldtex(ti1, b * 100 + 96 + (lane & 3)).x;
    smp += 2;
  };
  ld_idx();
  uint4 trow[4], wrow[5];
#pragma unroll
  for (int q = 0; q < 4; q++) trow[q] = *(const uint4*)(table + min(tid + q * 256, V_ - 1) * D_ + slice * 8);
#pragma unroll
  for (int q = 0; q < 5; q++) wrow[q] = ((const uint4*)wp)[min(tid + q * 256, F_ * F_ / 8 - 1)];
  uint32_t me = 0, mw = 0;
#pragma unroll
  for (int q = 0; q < 4; q++) me = absmax4(trow[q], me);
#pragma unroll
  for (int q = 0; q < 5; q++) { mw = absmax4(wrow[q], mw); if (tid + q * 256 < F_ * F_ / 8) sm[tid + q * 256] = wrow[q]; }
  me = __reduce_max_sync(0xffffffffu, max(me & 0xffff, me >> 16));
  mw = __reduce_max_sync(0xffffffffu, max(mw & 0xffff, mw >> 16));
  uint32_t* sred = (uint32_t*)((char*)sm + 128000);
  if (lane == 0) sred[tid >> 5] = me | mw << 16;
  asm volatile("bar.sync 1,256;" ::: "memory");
  { uint32_t m = 0;
#pragma unroll
    for (int q = 0; q < 8; q++) m = __vmaxu2(m, sred[q]);
    me = m & 0xffff; mw = m >> 16; }
  const float se = pow2_scale(me, 3), sW = pow2_scale(mw, -2);
  const __nv_bfloat16* sw = (const __nv_bfloat16*)sm;
  __half* wq = (__half*)((char*)sm + 32768);
  if (tid < 208) {
    const int kp = tid % 104, ok = kp >> 3, fi = pnn_field(ok, kp & 7);
#pragma unroll 4
    for (int np = tid / 104; np < 104; np += 2) {
      const int on = np >> 3, fj = pnn_field(on, np & 7);
      float v = 0.f;
      if (fi >= 0 && fj >= 0 && ok <= on) { v = __bfloat162float(sw[fj * F_ + fi]); if (ok != on) v += __bfloat162float(sw[fi * F_ + fj]); }
      wq[np * WS + kp] = __float2half_rn(v * sW);
    }
  }
  asm volatile("bar.sync 1,256;" ::: "memory");
  const uint32_t* wq32 = (const uint32_t*)wq;
  for (int i = tid; i < G_U * 64; i += 256) {
    const int u = i >> 6;
    const int u0 = u < G_U1 ? u : u < G_U2 ? u - G_U1 : u - G_U2, gn = u < G_U1 ? G_N0 : u < G_U2 ? G_N1 : G_N2, go = u < G_U1 ? G_O0 : u < G_U2 ? G_O1 : G_O2;
    const int on = go + u0 % gn, ok = 2 * (u0 / gn) + ((i >> 5) & 1);
    ((uint32_t*)((char*)sm + K1_W))[i] = wq32[(on * 8 + ((i >> 2) & 7)) * (WS / 2) + ok * 4 + (i & 3)];
  }
  uint32_t bd[7], bh[6][13][2];
#pragma unroll
  for (int q = 0; q < 7; q++) if (!unit_wg(q, 2 * q)) bd[q] = wq32[(q * 16 + g) * (WS / 2) + q * 8 + r];
#pragma unroll
  for (int kb = 0; kb < 6; kb++)
#pragma unroll
    for (int on = 2 * kb + 1; on < 13; on++)
      if (!unit_wg(kb, on)) { bh[kb][on][0] = wq32[(on * 8 + g) * (WS / 2) + kb * 8 + r]; bh[kb][on][1] = wq32[(on * 8 + g) * (WS / 2) + kb * 8 + 4 + r]; }
  asm volatile("fence.proxy.async.shared::cta;" ::: "memory");
  asm volatile("bar.sync 1,256;" ::: "memory");
#pragma unroll
  for (int q = 0; q < 4; q++) {
    const uint4 t = trow[q];
    const uint4 hv = make_uint4(pack_h2(bf_lo(t.x) * se, bf_hi(t.x) * se), pack_h2(bf_lo(t.y) * se, bf_hi(t.y) * se),
                                pack_h2(bf_lo(t.z) * se, bf_hi(t.z) * se), pack_h2(bf_lo(t.w) * se, bf_hi(t.w) * se));
    if (tid + q * 256 < V_)
#pragma unroll
      for (int s = 0; s < 8; s++) sts128(sbase + (tid + q * 256) * 128 + ((s + lane) & 7) * 16, hv);
  }
  const float unscale = __uint_as_float(0x7f000000u - __float_as_uint(se)), unscale2 = __uint_as_float(0x7f000000u - __float_as_uint(sW));
  asm volatile("bar.sync 1,256;" ::: "memory");
  TS(0, 1);
  const uint32_t abase = sbase + (lane & 7) * 16;
  const uint64_t wdesc = (uint64_t)(((sbase + K1_W) & 0x3FFFF) >> 4) | ((uint64_t)(128 >> 4) << 16) | ((uint64_t)(256 >> 4) << 32);
  uint32_t a[2][7][4], d[2][26];
  float red[4] = {0.f, 0.f, 0.f, 0.f};
  auto gather = [&](int x) {
    const uint32_t iv[6] = {i4.x, i4.y, i4.z, i4.w, i2.x, i2.y};
#pragma unroll
    for (int kb = 0; kb < 6; kb++)
      asm volatile("ldmatrix.sync.aligned.m8n8.x4.trans.shared.b16 {%0,%1,%2,%3},[%4];"
                   : "=r"(a[x][kb][0]), "=r"(a[x][kb][1]), "=r"(a[x][kb][2]), "=r"(a[x][kb][3]) : "r"(abase + iv[kb] * 128));
    asm volatile("ldmatrix.sync.aligned.m8n8.x2.trans.shared.b16 {%0,%1},[%2];" : "=r"(a[x][6][0]), "=r"(a[x][6][1]) : "r"(abase + i1 * 128));
    ld_idx();
  };
  auto issue = [&](int x) {
    asm volatile("wgmma.fence.sync.aligned;" ::: "memory");
#pragma unroll
    for (int kb = 0; kb < 6; kb++) {
      if (kb < G_K0) wgmma_h<G_N0 * 8>(d[x] + G_O0 * 2, a[x][kb], wdesc + kb * G_N0 * 16, kb);
      if (kb < G_K1) wgmma_h<G_N1 * 8>(d[x] + G_O1 * 2, a[x][kb], wdesc + (G_U1 + kb * G_N1) * 16, kb);
      if (kb < G_K2) wgmma_h<32>(d[x] + G_O2 * 2, a[x][kb], wdesc + (G_U2 + kb * G_N2) * 16, kb);
    }
    asm volatile("wgmma.commit_group.sync.aligned;" ::: "memory");
  };
  uint32_t s[4];
  auto hmma_part = [&](int x) {
#pragma unroll
    for (int o = 0; o < 13; o++) {
      if (oct_wg(o)) asm volatile("" : "+r"(d[x][o * 2]), "+r"(d[x][o * 2 + 1]) :: "memory"); else d[x][o * 2] = d[x][o * 2 + 1] = 0;
    }
#pragma unroll
    for (int kb = 0; kb < 6; kb++)
#pragma unroll
      for (int o = 2 * kb + 1; o < 13; o++)
        if (!unit_wg(kb, o)) mma16816h(d[x] + o * 2, a[x][kb], bh[kb][o][0], bh[kb][o][1]);
#pragma unroll
    for (int q = 0; q < 7; q++) if (!unit_wg(q, 2 * q)) mma1688h(d[x] + q * 4, a[x][q][0], a[x][q][1], bd[q]);
  };
  auto dot_part = [&](int x) {
    s[0] = s[1] = s[2] = s[3] = 0;
#pragma unroll
    for (int o = 0; o < 13; o++) {
      s[(o & 1) * 2] = hfma2(d[x][o * 2], a[x][o >> 1][(o & 1) * 2], s[(o & 1) * 2]);
      s[(o & 1) * 2 + 1] = hfma2(d[x][o * 2 + 1], a[x][o >> 1][(o & 1) * 2 + 1], s[(o & 1) * 2 + 1]);
    }
  };
  float* outp = g_partP + slice * B_ + smp0 + r * 4 + ((lane >> 3) & 1) * 2 + (lane >> 4);
  gather(0); issue(0); gather(1);
  asm volatile("wgmma.wait_group.sync.aligned 0;" ::: "memory");
  hmma_part(0);
#pragma unroll 1
  for (int n = 0; n < 128; n += 2) {
#pragma unroll
    for (int x = 0; x < 2; x++) {
      issue(x ^ 1);
      SCHED_FENCE(never, x * 4);
      dot_part(x);
      gather(x);
      SCHED_FENCE(never, x * 4 + 1);
      asm volatile("wgmma.wait_group.sync.aligned 0;" ::: "memory");
      SCHED_FENCE(never, x * 4 + 2);
      mma16816f(red, s, g == ((n + x) & 7) ? 0x3c003c00u : 0u);
      hmma_part(x ^ 1);
      SCHED_FENCE(never, x * 4 + 3);
    }
    if ((n & 7) == 6) {
      const bool u16 = lane & 16, u8 = lane & 8;
      float p0 = (u16 ? red[2] : red[0]) + __shfl_xor_sync(0xffffffffu, u16 ? red[0] : red[2], 16);
      float p1 = (u16 ? red[3] : red[1]) + __shfl_xor_sync(0xffffffffu, u16 ? red[1] : red[3], 16);
      float q0 = (u8 ? p1 : p0) + __shfl_xor_sync(0xffffffffu, u8 ? p0 : p1, 8);
      q0 += __shfl_xor_sync(0xffffffffu, q0, 4);
      if (!(lane & 4)) *outp = q0 * unscale * unscale * unscale2;
      outp += 16;
      red[0] = red[1] = red[2] = red[3] = 0.f;
    }
  }
  (void)wg; (void)w;
  TS(0, 2);
}

constexpr int SM_U = 130048, SM_BAR = SM_U + 3 * 32032, DEEP_SMEM = SM_BAR + 32;
constexpr uint64_t POL_EF = 0x12F0000000000000ull;

__device__ __forceinline__ void mbar_wait_fast(uint32_t bar, uint32_t parity) {
  asm volatile("{.reg .pred p; .reg .u32 n;\n"
               "mbarrier.try_wait.parity.shared::cta.b64 p,[%0],%1;\n"
               "@p bra DONE_%=;\n"
               "mov.u32 n,0;\n"
               "LOOP_%=: mbarrier.try_wait.parity.shared::cta.b64 p,[%0],%1;\n"
               "add.u32 n,n,1; setp.gt.or.u32 p,n,4000000,p;\n"
               "@!p bra LOOP_%=;\n"
               "DONE_%=: }" :: "r"(bar), "r"(parity) : "memory");
}
__device__ __forceinline__ void arrive_both(uint32_t bar, int lane) {
  asm volatile("{.reg .pred p; .reg .u32 a; setp.lt.u32 p,%1,2; mapa.shared::cluster.u32 a,%0,%1;\n"
               "@p mbarrier.arrive.shared::cluster.b64 _,[a];}" :: "r"(bar), "r"(lane) : "memory");
}
__device__ __forceinline__ void bulk_mc(uint32_t dst, const void* src, uint32_t bytes, uint32_t bar, uint64_t pol) {
  asm volatile("cp.async.bulk.shared::cluster.global.mbarrier::complete_tx::bytes.multicast::cluster.L2::cache_hint [%0],[%1],%2,[%3],%4,%5;"
               :: "r"(dst), "l"(src), "r"(bytes), "r"(bar), "h"((unsigned short)3), "l"(pol) : "memory");
}
__device__ __forceinline__ void sleep_until(uint32_t t0, uint32_t dt) { while ((uint32_t)clock() - t0 < dt) __nanosleep(40); }

__global__ void __cluster_dims__(2, 1, 1) __launch_bounds__(TH + 128, 1)
k_deep(cudaTextureObject_t tex, const __nv_bfloat16* __restrict__ b1, const __nv_bfloat16* __restrict__ w2, int never) {
  extern __shared__ __align__(1024) uint4 sm[];
  constexpr int PF = DPF, DEPTH = DDEPTH, NW = TH / 32;
  constexpr uint64_t POL_N = 0x1000000000000000ull;
  static_assert(YD == 4, "");
  const int tid = threadIdx.x;
  const int c = blockIdx.x >> 1, half = blockIdx.x & 1;
  const uint32_t sbase = (uint32_t)__cvta_generic_to_shared(sm);
  const uint32_t fullL = sbase + SM_BAR, fullU = fullL + 8, emptyL = fullL + 16, emptyU = fullL + 24;
  TS(1, 0);
  if (tid == 0) {
    mbar_init(fullL, 1); mbar_init(fullU, 1); mbar_init(emptyL, 2 * NW); mbar_init(emptyU, 2 * NW);
    asm volatile("fence.mbarrier_init.release.cluster;" ::: "memory");
  }
  __syncwarp();
  asm volatile("barrier.cluster.arrive.relaxed.aligned; barrier.cluster.wait.aligned;" ::: "memory");
  if (__builtin_expect(tid >= TH, 1)) {
    asm volatile("setmaxnreg.dec.sync.aligned.u32 24;");
    if (tid == TH) {
      const char* base = (const char*)g_scr;
      uint32_t oL = (PL_OFF + c * NC * 8000) * 16u + half * 64000, oS = (PS_OFF + c * NC * 2000) * 16u + half * 16000;
      uint32_t oT = (PT_OFF + c * 10 * 1024) * 16u + half * 8000, oI = (IX_OFF + half * NC * 8192 + c * 128) * 16u;
      uint32_t t0 = clock();
      mbar_expect(fullU, 96000);
#pragma unroll 1
      for (int m = 0; m < 3; m++) bulk_mc(sbase + SM_U + m * 32032 + half * 16000, base + oS, 16000, fullU, m == 2 ? POL_EF : POL_N);
      bulk_pf(base + oI, 2048); bulk_pf(base + oT, 8000);
      mbar_expect(fullL, 128000);
      sleep_until(t0, (c & 3) * STAG);
      bulk_mc(sbase + half * 64000, base + oL, 64000, fullL, POL_EF);
#pragma unroll 1
      for (int k = 0; k + 1 < NC; k++) {
        oL += 128000; oS += 32000; oT += 16384; oI += 131072;
        mbar_wait(fullL, k & 1);
        t0 = clock();
        bulk_pf(base + oI, 2048); bulk_pf(base + oS, 16000);
        mbar_wait(emptyU, k & 1);
        mbar_expect(fullU, 96000);
#pragma unroll 1
        for (int q = 0; q < 8; q++) {
          sleep_until(t0, q * PACE);
          bulk_pf(base + oL + q * 8000, 8000);
          if (q >= 2) bulk_mc(sbase + SM_U + ((q - 2) >> 1) * 32032 + half * 16000 + (q & 1) * 8000, base + oS + (q & 1) * 8000, 8000, fullU, q >= 6 ? POL_EF : POL_N);
        }
        bulk_pf(base + oT, 8000);
        mbar_expect(fullL, 128000);
        mbar_wait(emptyL, k & 1);
        bulk_mc(sbase + half * 64000, base + oL, 64000, fullL, POL_EF);
      }
      bulk_pf(base + oT + 16384, 8000);
      bulk_pf(base + (I9_OFF + half * 2048 + c * 32) * 16u, 512);
    }
    return;
  }
  asm volatile("setmaxnreg.inc.sync.aligned.u32 240;");
  const int lane = tid & 31;
  const int tbase = PT_OFF + c * 10 * 1024;
  const int ibase = IX_OFF + half * NC * 8192 + tid;
  const uint32_t lc = (tid & 7) << 4;
  uint4 acc[NS], wq[PF], x[DEPTH], y[YD], ye;
  uint32_t sw[NS] = {};
  auto sget = [&](int s) { return (s & 3) == 3 ? __byte_perm(__byte_perm(sw[s - 3], sw[s - 2], 0x0073), sw[s - 1], 0x0710) : sw[s]; };
  auto sa0 = [&](uint32_t v) { return sbase + SM_U + (((v << 5) & 0x1ffe0) | ((lc >> 2) & 16)); };
  auto sa1 = [&](uint32_t v) { return sbase + SM_U + (((v >> 7) & 0x1ffe0) | ((~lc >> 2) & 16)); };
  {
    uint4 i0[8];
#pragma unroll
    for (int q = 0; q < 8; q++) i0[q] = ldtex(tex, I0_OFF + (half * 8 + q) * TH + tid);
#pragma unroll
    for (int i = 0; i < PF; i++) wq[i] = ldtex(tex, ibase + i * TH);
    auto wd = [&](int k) { return (k & 3) == 0 ? i0[k >> 2].x : (k & 3) == 1 ? i0[k >> 2].y : (k & 3) == 2 ? i0[k >> 2].z : i0[k >> 2].w; };
    mbar_wait_fast(fullU, 0);
    TS(1, 1);
#pragma unroll
    for (int s = 0; s < NS; s++) acc[s] = add4(lds128(sa0(wd(s))), lds128(sa1(wd(s))));
    arrive_both(emptyU, lane);
  }
#pragma unroll 1
  for (int k = 0; k < NC; k++) {
    const int ti = ibase + k * 8192;
    const int tb = tbase + k * 1024;
    const bool more = k + 1 < NC;
    TR(k * 4);
    mbar_wait_fast(fullL, k & 1);
    TR(k * 4 + 2);
    uint4 w, cc; uint32_t yc, yn;
    constexpr int TL = NS * 8, TT = TL + NS * 2;
#pragma unroll
    for (int t = 0; t < TT + DEPTH; t += 2) {
      if (t == TL + DEPTH && !more) break;
      if (t >= DEPTH) {
        const int u = t - DEPTH;
        uint4 p = add4(x[u % DEPTH], x[(u + 1) % DEPTH]);
        if (u < TL) {
          const int s = u >> 3, j = u & 7;
          if (j == 0) {
            cc = s >= YD ? add4(y[s % YD], p) : p;
            if (s + YD < NS) y[s % YD] = ldtex(tex, tb | (yc & 1023));
          } else cc = add4(cc, p);
          if (j == 6) acc[s] = add4(acc[s], cc);
        } else {
          const int s = (u - TL) >> 1;
          acc[s] = add4(acc[s], p);
        }
      }
      if (DEPTH == 8 && (t & 7) == 2) yc = yn;
      if (t < TL) {
        const int s = t >> 3, j = t & 7;
        if (j == 0) {
          w = wq[s % PF]; wq[s % PF] = ldtex(tex, ti + (s + PF) * TH);
          yn = __funnelshift_l(w.z, w.z, 5); if (DEPTH < 8) yc = yn;
          if ((s & 3) != 3) asm volatile("add.u32 %0,%1,%2;" : "=r"(sw[s]) : "r"(w.w), "r"(never));
          if (ye_of(s - YD) >= 0) acc[ye_of(s - YD) & 3] = add4(acc[ye_of(s - YD) & 3], ye);
          if (ye_of(s) >= 0) ye = ldtex(tex, tb | w.w);
        }
#pragma unroll
        for (int jj = j; jj < j + 2; jj++) {
          const uint32_t ww = jj < 3 ? w.x : jj < 6 ? w.y : w.z;
          const uint32_t sh = jj % 3 == 0 ? ww : jj % 3 == 1 ? ww >> 10 : __funnelshift_l(ww, ww, 12);
          x[(t + jj - j) % DEPTH] = lds128(sbase + ((sh & 0x1ff80) | lc) + jj * 16 - 128);
        }
      } else if (t < TT) {
        const int s = (t - TL) >> 1;
        if (s == 0) { arrive_both(emptyL, more ? lane : 9); TR(k * 4 + 3); mbar_wait_fast(fullU, (more ? k + 1 : k) & 1); }
        const uint32_t sv = sget(s);
        x[t % DEPTH] = lds128(sa0(sv));
        x[(t + 1) % DEPTH] = lds128(sa1(sv));
      } else if (t == TT) arrive_both(emptyU, k + 2 < NC ? lane : 9);
      if ((t & (FENCE_N - 1)) == FENCE_N - 2) SCHED_FENCE(never, t);
    }
  }
  TS(1, 2);
  uint4 i9 = ldtex(tex, I9_OFF + half * 2048 + tid), i9n = ldtex(tex, I9_OFF + half * 2048 + TH + tid);
  const uint4 b1v = *(const uint4*)(b1 + c * 8), w2v = *(const uint4*)(w2 + c * 8);
  asm volatile("bar.sync 1,%0;" :: "n"(TH) : "memory");
#pragma unroll
  for (int s = 0; s < NS; s++) sts128(sbase + (s * TH + tid) * 16, acc[s]);
  const int t9 = tbase + 9 * 1024;
  y[0] = ldtex(tex, t9 | i9.x); y[1] = ldtex(tex, t9 | i9.y); y[2] = ldtex(tex, t9 | i9.z); y[3] = ldtex(tex, t9 | i9.w);
  float bb[8], hw[8];
  {
    const uint32_t bw[4] = {b1v.x, b1v.y, b1v.z, b1v.w}, ww[4] = {w2v.x, w2v.y, w2v.z, w2v.w};
#pragma unroll
    for (int k = 0; k < 8; k++) {
      bb[k] = __uint_as_float((k & 1) ? (bw[k >> 1] & 0xffff0000u) : (bw[k >> 1] << 16));
      hw[k] = 0.5f * __uint_as_float((k & 1) ? (ww[k >> 1] & 0xffff0000u) : (ww[k >> 1] << 16));
    }
  }
  float* outp = g_partD + c * B_ + half * 8192 + tid;
#pragma unroll 1
  for (int q = 0; q < NS / 4; q++) {
    uint4 z[4];
#pragma unroll
    for (int s = 0; s < 4; s++) z[s] = add4(lds128(sbase + ((q * 4 + s) * TH + tid) * 16), y[s]);
    y[0] = ldtex(tex, t9 | i9n.x); y[1] = ldtex(tex, t9 | i9n.y); y[2] = ldtex(tex, t9 | i9n.z); y[3] = ldtex(tex, t9 | i9n.w);
    i9n = ldtex(tex, I9_OFF + half * 2048 + min(q + 2, NS / 4 - 1) * TH + tid);
#pragma unroll
    for (int s = 0; s < 4; s++) {
      const uint32_t a[4] = {z[s].x, z[s].y, z[s].z, z[s].w};
      float r0 = 0.f, r1 = 0.f;
#pragma unroll
      for (int k = 0; k < 8; k++) {
        float xv = __uint_as_float((k & 1) ? (a[k >> 1] & 0xffff0000u) : (a[k >> 1] << 16)) + bb[k];
        float u = xv * fmaf(xv * xv, 0.7978845608028654f * 0.044715f, 0.7978845608028654f);
        float th; asm("tanh.approx.f32 %0,%1;" : "=f"(th) : "f"(u));
        float hx = xv * hw[k];
        r0 = fmaf(hx, th, r0); r1 += hx;
      }
      outp[(q * 4 + s) * TH] = r0 + r1;
    }
  }
  TS(1, 3);
}

__global__ void k_final(const __nv_bfloat16* __restrict__ b2, __nv_bfloat16* __restrict__ out) {
  __shared__ float red[4][32];
  int lane = threadIdx.x & 31, q = threadIdx.x >> 5, b = blockIdx.x * 32 + lane;
  float s = 0;
#pragma unroll
  for (int k = 0; k < 16; k++) s += g_partD[(q * 16 + k) * B_ + b];
#pragma unroll
  for (int k = 0; k < 4; k++) s += g_partP[(q * 4 + k) * B_ + b];
  red[q][lane] = s;
  __syncthreads();
  if (q == 0) out[b] = __float2bfloat16(red[0][lane] + red[1][lane] + red[2][lane] + red[3][lane] + __bfloat162float(b2[0]));
}

}

extern "C" void kernel_launch(void* const* d_in, const int* in_sizes, int n_in, void* d_out, int out_size) {
  const int* idx = (const int*)d_in[0];
  const __nv_bfloat16* table = (const __nv_bfloat16*)d_in[1];
  const __nv_bfloat16* wp = (const __nv_bfloat16*)d_in[2];
  const __nv_bfloat16* w1 = (const __nv_bfloat16*)d_in[3];
  const __nv_bfloat16* b1 = (const __nv_bfloat16*)d_in[4];
  const __nv_bfloat16* w2 = (const __nv_bfloat16*)d_in[5];
  const __nv_bfloat16* b2 = (const __nv_bfloat16*)d_in[6];
  static cudaTextureObject_t texScr = 0, ti4 = 0, ti2 = 0, ti1 = 0;
  static CUtensorMap mapW, mapL, mapS, mapT;
  static const void *c_idx = nullptr, *c_w1 = nullptr;
  if (c_idx != idx || c_w1 != w1) {
    c_idx = idx; c_w1 = w1;
    char* scr = nullptr; cudaGetSymbolAddress((void**)&scr, g_scr);
    auto mk_tex = [](const void* p, size_t bytes, cudaChannelFormatDesc d) {
      cudaResourceDesc rd = {}; rd.resType = cudaResourceTypeLinear; rd.res.linear.devPtr = (void*)p; rd.res.linear.desc = d; rd.res.linear.sizeInBytes = bytes;
      cudaTextureDesc td = {}; td.readMode = cudaReadModeElementType;
      cudaTextureObject_t t = 0; cudaCreateTextureObject(&t, &rd, &td, nullptr); return t;
    };
    texScr = mk_tex(scr, (size_t)SCR_N * 16, cudaCreateChannelDesc<uint4>());
    ti4 = mk_tex(idx, (size_t)B_ * F_ * 4, cudaCreateChannelDesc<uint4>());
    ti2 = mk_tex(idx, (size_t)B_ * F_ * 4, cudaCreateChannelDesc<uint2>());
    ti1 = mk_tex(idx, (size_t)B_ * F_ * 4, cudaCreateChannelDesc<unsigned>());
    typedef CUresult (*EncFn)(CUtensorMap*, CUtensorMapDataType, cuuint32_t, void*, const cuuint64_t*, const cuuint64_t*, const cuuint32_t*,
                              const cuuint32_t*, CUtensorMapInterleave, CUtensorMapSwizzle, CUtensorMapL2promotion, CUtensorMapFloatOOBfill);
    EncFn enc = nullptr; cudaDriverEntryPointQueryResult qr;
    cudaGetDriverEntryPoint("cuTensorMapEncodeTiled", (void**)&enc, cudaEnableDefault, &qr);
    const cuuint32_t ones[4] = {1, 1, 1, 1};
    auto mk = [&](CUtensorMap* m, CUtensorMapDataType dt, int rank, void* p, const cuuint64_t* dim, const cuuint64_t* str, const cuuint32_t* box, CUtensorMapSwizzle sw) {
      enc(m, dt, rank, p, dim, str, box, ones, CU_TENSOR_MAP_INTERLEAVE_NONE, sw, CU_TENSOR_MAP_L2_PROMOTION_NONE, CU_TENSOR_MAP_FLOAT_OOB_FILL_NONE);
    };
    { cuuint64_t dim[2] = {H_, F_ * D_}, str[1] = {H_ * 2}; cuuint32_t box[2] = {32, 256};
      mk(&mapW, CU_TENSOR_MAP_DATA_TYPE_BFLOAT16, 2, (void*)w1, dim, str, box, CU_TENSOR_MAP_SWIZZLE_64B); }
    { cuuint64_t dim[4] = {64, V_, NC, 64}, str[3] = {128, 128000, 128000 * NC}; cuuint32_t box[4] = {32, 64, 1, 4};
      mk(&mapL, CU_TENSOR_MAP_DATA_TYPE_BFLOAT16, 4, scr + (size_t)PL_OFF * 16, dim, str, box, CU_TENSOR_MAP_SWIZZLE_64B); }
    { cuuint64_t dim[4] = {16, V_, NC, 64}, str[3] = {32, 32000, 32000 * NC}; cuuint32_t box[4] = {16, 64, 1, 4};
      mk(&mapS, CU_TENSOR_MAP_DATA_TYPE_BFLOAT16, 4, scr + (size_t)PS_OFF * 16, dim, str, box, CU_TENSOR_MAP_SWIZZLE_32B); }
    { cuuint64_t dim[3] = {2048, 10, 64}, str[2] = {16384, 163840}; cuuint32_t box[3] = {128, 2, 4};
      mk(&mapT, CU_TENSOR_MAP_DATA_TYPE_UINT64, 3, scr + (size_t)PT_OFF * 16, dim, str, box, CU_TENSOR_MAP_SWIZZLE_NONE); }
    cudaFuncSetAttribute(k_deep, cudaFuncAttributeMaxDynamicSharedMemorySize, DEEP_SMEM);
    cudaFuncSetAttribute(k_tens, cudaFuncAttributeMaxDynamicSharedMemorySize, K1_SMEM);
  }
  k_pack<<<2 * NC * 8192 / 256, 256>>>(idx);
  k_tens<<<128, 384, K1_SMEM>>>(mapW, mapL, mapS, mapT, ti4, ti2, ti1, table, wp, 0);
  k_deep<<<128, TH + 128, DEEP_SMEM>>>(texScr, b1, w2, 0);
  k_final<<<B_ / 32, 128>>>(b2, (__nv_bfloat16*)d_out);
}
```

```cpp
#include <cuda_runtime.h>
#include <cuda_bf16.h>
#include <cuda_fp16.h>
#include <stdint.h>
#include <cuda.h>

namespace {

constexpr int B_ = 16384, F_ = 100, D_ = 128, V_ = 1000, H_ = 512;
constexpr int NC = 9;
constexpr int PT_OFF = 0;
constexpr int PL_OFF = 64 * 10 * 1024;
constexpr int PS_OFF = PL_OFF + 64 * NC * 8000;
constexpr int IX_OFF = PS_OFF + 64 * NC * 2000;
constexpr int I0_OFF = IX_OFF + 2 * NC * 8192;
constexpr int I9_OFF = I0_OFF + 4096;
constexpr int PX_OFF = I9_OFF + 4096;
constexpr int G_OFF = PX_OFF + 64 * 16 * 128;
constexpr int SCR_N = G_OFF + 131072;
static_assert(G_OFF % 32 == 0, "");

__device__ __align__(1024) uint4 g_scr[SCR_N];
__device__ float g_partD[64 * B_];
__device__ float g_partP[17 * B_];
__device__ unsigned g_flag[16 * 32];

#define TS(k, i)
#define TR(slot)
#define PT(slot)

constexpr uint64_t POL_EF = 0x12F0000000000000ull, POL_N = 0x1000000000000000ull;
__device__ __forceinline__ uint32_t addbf2(uint32_t a, uint32_t b) { uint32_t r; asm("add.rn.bf16x2 %0,%1,%2;" : "=r"(r) : "r"(a), "r"(b)); return r; }
__device__ __forceinline__ uint4 add4(const uint4& a, const uint4& b) { return make_uint4(addbf2(a.x, b.x), addbf2(a.y, b.y), addbf2(a.z, b.z), addbf2(a.w, b.w)); }
__device__ __forceinline__ void acc4(uint4& a, const uint4& b, int never) {
  asm("{.reg .pred p; setp.eq.s32 p,%8,0;\n"
      "@p add.rn.bf16x2 %0,%0,%4; @p add.rn.bf16x2 %1,%1,%5; @p add.rn.bf16x2 %2,%2,%6; @p add.rn.bf16x2 %3,%3,%7;}"
      : "+r"(a.x), "+r"(a.y), "+r"(a.z), "+r"(a.w) : "r"(b.x), "r"(b.y), "r"(b.z), "r"(b.w), "r"(never));
}
__device__ __forceinline__ uint4 ldtex(cudaTextureObject_t t, int i) {
  uint4 v; asm volatile("tex.1d.v4.u32.s32 {%0,%1,%2,%3},[%4,{%5}];" : "=r"(v.x), "=r"(v.y), "=r"(v.z), "=r"(v.w) : "l"(t), "r"(i)); return v;
}
__device__ __forceinline__ uint4 lds128(uint32_t a) {
  uint4 v; asm volatile("ld.volatile.shared.v4.u32 {%0,%1,%2,%3},[%4];" : "=r"(v.x), "=r"(v.y), "=r"(v.z), "=r"(v.w) : "r"(a)); return v;
}
__device__ __forceinline__ void sts128(uint32_t a, const uint4& v) {
  asm volatile("st.shared.v4.u32 [%0],{%1,%2,%3,%4};" :: "r"(a), "r"(v.x), "r"(v.y), "r"(v.z), "r"(v.w) : "memory");
}
__device__ __forceinline__ void mbar_init(uint32_t bar, int n) { asm volatile("mbarrier.init.shared::cta.b64 [%0],%1;" :: "r"(bar), "r"(n) : "memory"); }
__device__ __forceinline__ void mbar_wait(uint32_t bar, uint32_t parity) {
  uint32_t ok; int it = 0;
  do { asm volatile("{.reg .pred p; mbarrier.try_wait.parity.shared::cta.b64 p,[%1],%2; selp.u32 %0,1,0,p;}" : "=r"(ok) : "r"(bar), "r"(parity) : "memory"); } while (!ok && ++it < (1 << 22));
}
__device__ __forceinline__ void mbar_expect(uint32_t bar, uint32_t bytes) { asm volatile("mbarrier.arrive.expect_tx.shared::cta.b64 _,[%0],%1;" :: "r"(bar), "r"(bytes) : "memory"); }
__device__ __forceinline__ void bulk_g2s(uint32_t dst, const void* src, uint32_t bytes, uint32_t bar) {
  asm volatile("cp.async.bulk.shared::cluster.global.mbarrier::complete_tx::bytes [%0],[%1],%2,[%3];" :: "r"(dst), "l"(src), "r"(bytes), "r"(bar) : "memory");
}
__device__ __forceinline__ void bulk_pf(const void* src, uint32_t bytes) { asm volatile("cp.async.bulk.prefetch.L2.global [%0],%1;" :: "l"(src), "r"(bytes) : "memory"); }
#define IW 2
#define PP0 10
#define PT0 10000
#define PDT 2200
#define RPNN "152"
#define RAUX "48"
#define NLOOK 128
#define NEF 25
#define ORD 0
#define WFENCE 0
#define IPF 3
#define IPACE 4500
#define WPF 6
#define QORD(n) (n)
#define DYD 4
#define DPF 4
#define DDEPTH 4
#define FENCE_N 8
#define INPL 0
#define STAG 1100
#define PACE 800
#define PM4 "pmevent 1; pmevent 2; pmevent 3; pmevent 4;"
#define PMFILL "pmevent 1;"
#define SCHED_FENCE(never, k) asm volatile("{.reg .pred p; setp.ne.u32 p,%0,%1; @p bra.uni SKIP_%=;" PMFILL "SKIP_%=: }" :: "r"(never), "r"(0x7fff0000 + (k)) : "memory")

__global__ void k_prod_naive(const __nv_bfloat16* __restrict__ table, const __nv_bfloat16* __restrict__ w1) {
  __shared__ float t[8][D_];
  int f = blockIdx.y, v0 = blockIdx.x * 8, h = threadIdx.x;
  for (int i = h; i < 8 * D_; i += 512) t[i / D_][i % D_] = __bfloat162float(table[v0 * D_ + i]);
  __syncthreads();
  float s[8] = {0, 0, 0, 0, 0, 0, 0, 0};
  for (int d = 0; d < D_; d++) { float w = __bfloat162float(w1[(size_t)(f * D_ + d) * H_ + h]);
#pragma unroll
    for (int k = 0; k < 8; k++) s[k] += t[k][d] * w; }
  __nv_bfloat16* P = (__nv_bfloat16*)g_scr;
  int c = h >> 3;
  for (int k = 0; k < 8; k++) {
    size_t e = f < 72 ? (size_t)PL_OFF + ((size_t)(c * NC + (f >> 3)) * 1000 + v0 + k) * 8 + (f & 7)
             : f < 90 ? (size_t)PS_OFF + ((size_t)(c * NC + ((f - 72) >> 1)) * 1000 + v0 + k) * 2 + (f & 1)
                      : (size_t)PT_OFF + (size_t)(c * 10 + f - 90) * 1024 + v0 + k;
    P[e * 8 + (h & 7)] = __float2bfloat16(s[k]);
  }
}
__global__ void k_pnn_naive(const int* __restrict__ idx, const __nv_bfloat16* __restrict__ table, const __nv_bfloat16* __restrict__ wp) {
  __shared__ float e[F_][33];
  int b = blockIdx.x, d0 = blockIdx.y * 32, tid = threadIdx.x;
  for (int i = tid; i < F_ * 32; i += 128) e[i >> 5][i & 31] = __bfloat162float(table[idx[b * F_ + (i >> 5)] * D_ + d0 + (i & 31)]);
  __syncthreads();
  float s = 0; int d = tid & 31;
  for (int i = tid >> 5; i < F_; i += 4) { float u = 0; for (int j = 0; j < F_; j++) u += __bfloat162float(wp[i * F_ + j]) * e[j][d]; s += u * e[i][d]; }
  for (int o = 16; o; o >>= 1) s += __shfl_xor_sync(~0u, s, o);
  if (d == 0) g_partP[(blockIdx.y * 4 + (tid >> 5)) * B_ + b] = s;
}
__device__ __forceinline__ void mbar_wait_fast(uint32_t bar, uint32_t parity) {
  asm volatile("{.reg .pred p; .reg .u32 n;\n"
               "mbarrier.try_wait.parity.shared::cta.b64 p,[%0],%1;\n"
               "@p bra DONE_%=;\n"
               "mov.u32 n,0;\n"
               "LOOP_%=: mbarrier.try_wait.parity.shared::cta.b64 p,[%0],%1;\n"
               "add.u32 n,n,1; setp.gt.or.u32 p,n,4000000,p;\n"
               "@!p bra LOOP_%=;\n"
               "DONE_%=: }" :: "r"(bar), "r"(parity) : "memory");
}
__device__ __forceinline__ void sleep_until(uint32_t t0, uint32_t dt) { while ((uint32_t)clock() - t0 < dt) __nanosleep(40); }
__device__ __forceinline__ uint32_t s_mask(uint32_t v, int q) { return (1u << ((v + 3 - q) & 3)) | (16u << ((v + 3 + q) & 3)); }
__device__ __forceinline__ uint32_t s_cell(uint32_t v, int q, uint32_t m) {
  const int t = __ffs(~m) - 1;
  const int cp = ((t & 4 ? t - q : t + q) - v) & 3;
  return (cp == 3 ? 0 : cp) * 1001 + v;
}
__device__ __forceinline__ uint32_t pk3(uint32_t a, uint32_t b, uint32_t c) {
  const uint32_t w = c + (a << 12) + (b << 22); return __funnelshift_l(w, w, 27);
}
constexpr int TH = 256, NS = 8192 / TH, YD = DYD;
__host__ __device__ constexpr int ye_of(int s) { return s == 3 ? 0 : s == 11 ? 1 : s == 19 ? 2 : s == 23 ? 3 : -1; }
template <int N> __device__ __forceinline__ void wgmma_h(uint32_t* d, const uint32_t* a, uint64_t desc, int acc);
template <> __device__ __forceinline__ void wgmma_h<64>(uint32_t* d, const uint32_t* a, uint64_t desc, int acc) {
  asm volatile("{.reg .pred p; setp.ne.s32 p,%21,0;\n"
    "wgmma.mma_async.sync.aligned.m64n64k16.f16.f16.f16 {%0,%1,%2,%3,%4,%5,%6,%7,%8,%9,%10,%11,%12,%13,%14,%15},{%16,%17,%18,%19},%20,p,1,1,0;}"
    : "+r"(d[0]),"+r"(d[1]),"+r"(d[2]),"+r"(d[3]),"+r"(d[4]),"+r"(d[5]),"+r"(d[6]),"+r"(d[7]),"+r"(d[8]),"+r"(d[9]),"+r"(d[10]),"+r"(d[11]),"+r"(d[12]),"+r"(d[13]),"+r"(d[14]),"+r"(d[15])
    : "r"(a[0]), "r"(a[1]), "r"(a[2]), "r"(a[3]), "l"(desc), "r"(acc));
}
template <> __device__ __forceinline__ void wgmma_h<56>(uint32_t* d, const uint32_t* a, uint64_t desc, int acc) {
  asm volatile("{.reg .pred p; setp.ne.s32 p,%19,0;\n"
    "wgmma.mma_async.sync.aligned.m64n56k16.f16.f16.f16 {%0,%1,%2,%3,%4,%5,%6,%7,%8,%9,%10,%11,%12,%13},{%14,%15,%16,%17},%18,p,1,1,0;}"
    : "+r"(d[0]),"+r"(d[1]),"+r"(d[2]),"+r"(d[3]),"+r"(d[4]),"+r"(d[5]),"+r"(d[6]),"+r"(d[7]),"+r"(d[8]),"+r"(d[9]),"+r"(d[10]),"+r"(d[11]),"+r"(d[12]),"+r"(d[13])
    : "r"(a[0]), "r"(a[1]), "r"(a[2]), "r"(a[3]), "l"(desc), "r"(acc));
}
template <> __device__ __forceinline__ void wgmma_h<48>(uint32_t* d, const uint32_t* a, uint64_t desc, int acc) {
  asm volatile("{.reg .pred p; setp.ne.s32 p,%17,0;\n"
    "wgmma.mma_async.sync.aligned.m64n48k16.f16.f16.f16 {%0,%1,%2,%3,%4,%5,%6,%7,%8,%9,%10,%11},{%12,%13,%14,%15},%16,p,1,1,0;}"
    : "+r"(d[0]),"+r"(d[1]),"+r"(d[2]),"+r"(d[3]),"+r"(d[4]),"+r"(d[5]),"+r"(d[6]),"+r"(d[7]),"+r"(d[8]),"+r"(d[9]),"+r"(d[10]),"+r"(d[11])
    : "r"(a[0]), "r"(a[1]), "r"(a[2]), "r"(a[3]), "l"(desc), "r"(acc));
}
template <> __device__ __forceinline__ void wgmma_h<40>(uint32_t* d, const uint32_t* a, uint64_t desc, int acc) {
  asm volatile("{.reg .pred p; setp.ne.s32 p,%15,0;\n"
    "wgmma.mma_async.sync.aligned.m64n40k16.f16.f16.f16 {%0,%1,%2,%3,%4,%5,%6,%7,%8,%9},{%10,%11,%12,%13},%14,p,1,1,0;}"
    : "+r"(d[0]),"+r"(d[1]),"+r"(d[2]),"+r"(d[3]),"+r"(d[4]),"+r"(d[5]),"+r"(d[6]),"+r"(d[7]),"+r"(d[8]),"+r"(d[9])
    : "r"(a[0]), "r"(a[1]), "r"(a[2]), "r"(a[3]), "l"(desc), "r"(acc));
}
template <> __device__ __forceinline__ void wgmma_h<32>(uint32_t* d, const uint32_t* a, uint64_t desc, int acc) {
  asm volatile("{.reg .pred p; setp.ne.s32 p,%13,0;\n"
    "wgmma.mma_async.sync.aligned.m64n32k16.f16.f16.f16 {%0,%1,%2,%3,%4,%5,%6,%7},{%8,%9,%10,%11},%12,p,1,1,0;}"
    : "+r"(d[0]),"+r"(d[1]),"+r"(d[2]),"+r"(d[3]),"+r"(d[4]),"+r"(d[5]),"+r"(d[6]),"+r"(d[7])
    : "r"(a[0]), "r"(a[1]), "r"(a[2]), "r"(a[3]), "l"(desc), "r"(acc));
}
template <int TB> __device__ __forceinline__ void wgmma_p(float* d, const uint32_t* a, uint64_t desc, int acc) {
  asm volatile("{.reg .pred p; setp.ne.s32 p,%37,0;\n"
    "wgmma.mma_async.sync.aligned.m64n64k16.f32.bf16.bf16 {%0,%1,%2,%3,%4,%5,%6,%7,%8,%9,%10,%11,%12,%13,%14,%15,%16,%17,%18,%19,%20,%21,%22,%23,%24,%25,%26,%27,%28,%29,%30,%31},{%32,%33,%34,%35},%36,p,1,1,%38;}"
    : "+f"(d[0]),"+f"(d[1]),"+f"(d[2]),"+f"(d[3]),"+f"(d[4]),"+f"(d[5]),"+f"(d[6]),"+f"(d[7]),"+f"(d[8]),"+f"(d[9]),"+f"(d[10]),"+f"(d[11]),"+f"(d[12]),"+f"(d[13]),"+f"(d[14]),"+f"(d[15]),"+f"(d[16]),"+f"(d[17]),"+f"(d[18]),"+f"(d[19]),"+f"(d[20]),"+f"(d[21]),"+f"(d[22]),"+f"(d[23]),"+f"(d[24]),"+f"(d[25]),"+f"(d[26]),"+f"(d[27]),"+f"(d[28]),"+f"(d[29]),"+f"(d[30]),"+f"(d[31])
    : "r"(a[0]), "r"(a[1]), "r"(a[2]), "r"(a[3]), "l"(desc), "r"(acc), "n"(TB));
}

__device__ __forceinline__ void mma16816h(uint32_t* c, const uint32_t* a, uint32_t b0, uint32_t b1) {
  asm("mma.sync.aligned.m16n8k16.row.col.f16.f16.f16.f16 {%0,%1},{%2,%3,%4,%5},{%6,%7},{%0,%1};"
      : "+r"(c[0]), "+r"(c[1]) : "r"(a[0]), "r"(a[1]), "r"(a[2]), "r"(a[3]), "r"(b0), "r"(b1));
}
__device__ __forceinline__ void mma1688h(uint32_t* c, uint32_t a0, uint32_t a1, uint32_t b) {
  asm("mma.sync.aligned.m16n8k8.row.col.f16.f16.f16.f16 {%0,%1},{%2,%3},{%4},{%0,%1};" : "+r"(c[0]), "+r"(c[1]) : "r"(a0), "r"(a1), "r"(b));
}
__device__ __forceinline__ void mma16816f(float* c, const uint32_t* a, uint32_t b) {
  asm("mma.sync.aligned.m16n8k16.row.col.f32.f16.f16.f32 {%0,%1,%2,%3},{%4,%5,%6,%7},{%8,%8},{%0,%1,%2,%3};"
      : "+f"(c[0]), "+f"(c[1]), "+f"(c[2]), "+f"(c[3]) : "r"(a[0]), "r"(a[1]), "r"(a[2]), "r"(a[3]), "r"(b));
}
__device__ __forceinline__ uint32_t hfma2(uint32_t a, uint32_t b, uint32_t c) { uint32_t r; asm("fma.rn.f16x2 %0,%1,%2,%3;" : "=r"(r) : "r"(a), "r"(b), "r"(c)); return r; }
__device__ __forceinline__ uint32_t pack_bf2(float lo, float hi) { uint32_t r; asm("cvt.rn.bf16x2.f32 %0,%1,%2;" : "=r"(r) : "f"(hi), "f"(lo)); return r; }
__device__ __forceinline__ uint32_t pack_h2(float lo, float hi) { uint32_t r; asm("cvt.rn.f16x2.f32 %0,%1,%2;" : "=r"(r) : "f"(hi), "f"(lo)); return r; }
__device__ __forceinline__ float bf_lo(uint32_t w) { return __uint_as_float(w << 16); }
__device__ __forceinline__ float bf_hi(uint32_t w) { return __uint_as_float(w & 0xffff0000u); }
__device__ __forceinline__ uint32_t absmax4(const uint4& v, uint32_t m) {
  return __vmaxu2(__vmaxu2(__vmaxu2(v.x & 0x7fff7fffu, v.y & 0x7fff7fffu), __vmaxu2(v.z & 0x7fff7fffu, v.w & 0x7fff7fffu)), m);
}
__device__ __forceinline__ float pow2_scale(uint32_t mbits, int p) { return __uint_as_float((uint32_t)min(max(253 + p - (int)(mbits >> 7), 2), 252) << 23); }

__host__ __device__ constexpr int pnn_field(int oct, int r) {
  return (oct >> 1) < 4 ? 4 * ((oct & 1) * 8 + r) + (oct >> 1) : 64 + 2 * ((oct & 1) * 8 + r) + (oct >> 1) - 4;
}
#define PV 0
constexpr int G_O0 = 8, G_O1 = 4, G_O2 = 0, G_N0 = 4, G_N1 = 4, G_N2 = 4, G_K0 = 5, G_K1 = 3, G_K2 = 1;
__host__ __device__ constexpr bool unit_wg(int kb, int on) {
  return (on >= G_O0 && on < G_O0 + G_N0 && kb < G_K0) || (on >= G_O1 && on < G_O1 + G_N1 && kb < G_K1) || (on >= G_O2 && on < G_O2 + G_N2 && kb < G_K2);
}
__host__ __device__ constexpr bool oct_wg(int on) { return unit_wg(0, on); }
constexpr int G_U1 = G_N0 * G_K0, G_U2 = G_U1 + G_N1 * G_K1, G_U = G_U2 + G_N2 * G_K2;
constexpr int K1_B = 130048, K1_STG = K1_B + 3 * 16384, K1_W = K1_STG + 2 * 16384, K1_BAR = K1_W + 44 * 256, K1_SMEM = K1_BAR + 128;
__host__ __device__ constexpr int frag_index(int ok, int on) {
  int n = 0;
  for (int k = 0; k < 12; k++) for (int o = k; o < 12; o++) { if (k == ok && o == on) return n; if (!unit_wg(k >> 1, o)) n++; }
  return n;
}
constexpr int HU_N = 2 * G_U + frag_index(99, 99);
static_assert(HU_N <= 88, "");
struct FragIdx { int v[12][12]; };
__host__ __device__ constexpr FragIdx make_fi() { FragIdx f = {}; for (int k = 0; k < 12; k++) for (int o = 0; o < 12; o++) f.v[k][o] = frag_index(k, o); return f; }
__host__ __device__ constexpr uint64_t frag_tab(int first) {
  uint64_t t = 0;
  for (int k = 0; k < 12; k++) for (int o = k; o < 12; o++)
    if (!unit_wg(k >> 1, o)) { const int n = frag_index(k, o) - first; if (n >= 0 && n < 8) t |= (uint64_t)(k << 4 | o) << (8 * n); }
  return t;
}
__device__ __forceinline__ int hu_code(int hu) {
  constexpr uint64_t T0 = frag_tab(0), T1 = frag_tab(8), T2 = frag_tab(16), T3 = frag_tab(24);
  const int u = hu >> 1, f = hu - 2 * G_U;
  if (f >= 0) return (int)((f < 8 ? T0 : f < 16 ? T1 : f < 24 ? T2 : T3) >> (8 * (f & 7))) & 255;
  const int u0 = u < G_U1 ? u : u < G_U2 ? u - G_U1 : u - G_U2;
  const int kb = u < G_U1 ? u0 / G_N0 : u < G_U2 ? u0 / G_N1 : u0 / 4, on = u < G_U1 ? G_O0 + u0 % G_N0 : u < G_U2 ? G_O1 + u0 % G_N1 : G_O2 + u0 % 4;
  return (2 * kb + (hu & 1)) << 4 | on;
}

__device__ __forceinline__ void flag_arrive(unsigned* f, int lane) {
  __threadfence(); __syncwarp();
  if (lane == 0) asm volatile("red.release.gpu.global.add.u32 [%0],1;" :: "l"(f) : "memory");
}
__device__ __forceinline__ void flag_wait(const unsigned* f, unsigned n) {
  unsigned v; int it = 0;
  do { asm volatile("ld.acquire.gpu.global.u32 %0,[%1];" : "=r"(v) : "l"(f) : "memory"); if (v < n) __nanosleep(100); } while (v < n && ++it < (1 << 20));
}
__device__ __forceinline__ void mbar_arrive(uint32_t bar) { asm volatile("mbarrier.arrive.shared::cta.b64 _,[%0];" :: "r"(bar) : "memory"); }
__device__ __forceinline__ void mbar_arrive_lane0(uint32_t bar) {
  asm volatile("{.reg .pred p; elect.sync _|p,0xffffffff; @p mbarrier.arrive.shared::cta.b64 _,[%0];}" :: "r"(bar) : "memory");
}

__device__ __forceinline__ void pack_role(const int* __restrict__ idx, uint32_t sbase, int pc) {
  constexpr int CH = 3200 + 32, BUF = 32 * 3328;
  const int tid = threadIdx.x, lane = tid & 31, warp = tid >> 5;
  const uint32_t full = sbase + 2 * BUF, empty = full + 16;
  if (tid == 0) { mbar_init(full, 1); mbar_init(full + 8, 1); mbar_init(empty, 18); mbar_init(empty + 8, 18); asm volatile("fence.proxy.async.shared::cta;" ::: "memory"); }
  __syncthreads();
  auto chunk = [&](int s) { return s * 3200 + (s >> 2) * 288; };
  auto load = [&](int n) {
    const int blk = pc * 16 + n;
    if (lane == 0) mbar_expect(full + (n & 1) * 8, 32 * 3200);
    __syncwarp();
    bulk_g2s(sbase + (n & 1) * BUF + chunk(lane), idx + ((blk >> 5) * 8192 + lane * TH + (blk & 31) * 8) * F_, 3200, full + (n & 1) * 8);
  };
  if (warp == 0) { load(0); load(1); }
  const int l = lane & 7;
  uint32_t rot[8], inc[3];
#pragma unroll
  for (int jj = 0; jj < 8; jj++) rot[jj] = ((l + jj) & 7) * 4;
#pragma unroll
  for (int q = 0; q < 3; q++) inc[q] = (l + 3 * q < 8) << 12 | (l + 3 * q + 1 < 8) << 22 | (q < 2 && l + 3 * q + 2 < 8);
  int loaded = 2;
#pragma unroll 1
  for (int task = warp; task < 288; task += 16) {
    const int n = task / 18, q = (task % 18) * 4 + (lane >> 3), sq = q / 9, k = q % 9;
    if (warp == 0 && n + 1 == loaded && loaded < 16) { mbar_wait(empty + (loaded & 1) * 8, ((loaded >> 1) - 1) & 1); load(loaded); loaded++; }
    mbar_wait(full + (n & 1) * 8, (n >> 1) & 1);
    const uint32_t buf = sbase + (n & 1) * BUF + l * 400, row = buf + chunk(sq * 4);
    auto ld = [&](uint32_t ad) { uint32_t v; asm volatile("ld.shared.u32 %0,[%1];" : "=r"(v) : "r"(ad)); return v; };
    const int blk = pc * 16 + n, half = blk >> 5, col = (blk & 31) * 8 + l;
    const int ks = k == NC - 1 ? 0 : k + 1;
    uint32_t cw[4], sv[8], m[2] = {0, 0};
    { const uint32_t a0 = row + (72 + 2 * ks + (l >> 2)) * 4;
#pragma unroll
      for (int u = 0; u < 8; u++) { sv[u] = ld((a0 ^ ((u >> 2) * 4)) + (u & 3) * 3200); m[u >> 2] |= s_mask(sv[u], l & 3) << (8 * (u & 3)); } }
#pragma unroll
    for (int h = 0; h < 2; h++) { m[h] |= __shfl_xor_sync(0xffffffffu, m[h], 1); m[h] |= __shfl_xor_sync(0xffffffffu, m[h], 2); }
#pragma unroll
    for (int u = 0; u < 4; u++) cw[u] = s_cell(sv[u], l & 3, (m[0] >> (8 * u)) & 255) | s_cell(sv[4 + u], l & 3, (m[1] >> (8 * u)) & 255) << 12;
    if (k == NC - 1) {
      g_scr[I0_OFF + (half * 8 + sq) * TH + col] = make_uint4(cw[0], cw[1], cw[2], cw[3]);
      g_scr[I9_OFF + (half * 8 + sq) * TH + col] = make_uint4(ld(row + 396), ld(row + 3596), ld(row + 6796), ld(row + 9996));
      cw[0] = cw[1] = cw[2] = cw[3] = 0;
    }
    const uint32_t ax = buf + chunk(min(sq + 1, 7) * 4) + (90 + k) * 4;
    const uint32_t yev = ld(buf + ((0x3210 >> (sq * 2 + (sq == 5) * 2)) & 3) * 3200 + (90 + k) * 4);
    uint4* dst = g_scr + IX_OFF + ((half * NC + k) * NS + sq * 4) * TH + col;
#pragma unroll
    for (int u = 0; u < 4; u++) {
      uint32_t e[8];
#pragma unroll
      for (int jj = 0; jj < 8; jj++) e[jj] = ld(row + k * 32 + rot[jj] + u * 3200);
      dst[u * TH] = make_uint4(pk3(e[0], e[1], e[2] + inc[0]), pk3(e[3], e[4], e[5] + inc[1]), pk3(e[6], e[7], ld(ax + u * 3200) + inc[2]),
                               u < 3 ? __byte_perm(cw[u], cw[3], 0x4210 + (u << 12)) : yev);
    }
    mbar_arrive_lane0(empty + (n & 1) * 8);
  }
  (void)CH;
}

__global__ void __launch_bounds__(512, 1)
k_tens(const __grid_constant__ CUtensorMap mapW, const __grid_constant__ CUtensorMap mapL, const __grid_constant__ CUtensorMap mapS,
       const __grid_constant__ CUtensorMap mapT, const __grid_constant__ CUtensorMap mapE, cudaTextureObject_t tex, cudaTextureObject_t texG,
       const int* __restrict__ idx, const __nv_bfloat16* __restrict__ table, const __nv_bfloat16* __restrict__ wp, const __nv_bfloat16* __restrict__ w1, int never) {
  extern __shared__ __align__(1024) uint4 sm[];
  const int tid = threadIdx.x, lane = tid & 31, cta = blockIdx.x;
  const uint32_t sbase = (uint32_t)__cvta_generic_to_shared(sm);
  const int g = lane >> 2, r = lane & 3;
  TS(0, 0);
  asm volatile("griddepcontrol.launch_dependents;");
  if (cta >= 128) { pack_role(idx, sbase, cta - 128); TS(2, 1); return; }
  const uint32_t fullB = sbase + K1_BAR, emptyB = fullB + 24, fullS = fullB + 48, emptyS = fullB + 64, fullE = fullB + 80;
  const int rb = cta & 7, hc = cta >> 3;
  if (tid >= 384) {
    asm volatile("setmaxnreg.dec.sync.aligned.u32 " RAUX ";");
    if (tid == 384) {
      for (int q = 0; q < 3; q++) { mbar_init(fullB + q * 8, 1); mbar_init(emptyB + q * 8, 4); }
      for (int q = 0; q < 2; q++) { mbar_init(fullS + q * 8, 4); mbar_init(emptyS + q * 8, 1); }
      mbar_init(fullE, 1);
      asm volatile("fence.proxy.async.shared::cta;" ::: "memory");
      mbar_expect(fullE, 16384);
      for (int q = 0; q < 2; q++)
        asm volatile("cp.async.bulk.tensor.2d.shared::cluster.global.mbarrier::complete_tx::bytes [%0],[%1,{%2,%3}],[%4];"
                     :: "r"(sbase + K1_STG + q * 8192), "l"(&mapE), "r"(q * 64), "r"(hc * 64), "r"(fullE) : "memory");
      for (int p = 0; p < 3; p++) {
        mbar_expect(fullB + p * 8, 16384);
        asm volatile("cp.async.bulk.tensor.2d.shared::cluster.global.mbarrier::complete_tx::bytes [%0],[%1,{%2,%3}],[%4];"
                     :: "r"(sbase + K1_B + p * 16384), "l"(&mapW), "r"(hc * 32), "r"(QORD(p >> 1) * 512 + (p & 1) * 256), "r"(fullB + p * 8) : "memory");
      }
    }
    if (tid < 416) {
      __syncwarp();
      asm volatile("bar.sync 2,192;" ::: "memory");
      if (tid == 384) {
        auto pf = [&](int p) { if (p < 50) bulk_pf(w1 + QORD(p >> 1) * 262144 + (p & 1) * 131072 + cta * 1024, 2048); };
        for (int p = 3; p < WPF; p++) pf(p);
#pragma unroll 1
        for (int n = 0; n < 50; n++) {
          const int quad = QORD(n >> 1), mt = n & 1, v0 = rb * 128 + mt * 64;
          const uint32_t stg = sbase + K1_STG + mt * 16384;
          const uint64_t pol = n < 2 * NEF ? POL_EF : POL_N;
          mbar_wait(fullS + mt * 8, (n >> 1) & 1);
          asm volatile("fence.proxy.async.shared::cta;" ::: "memory");
          if (quad < 18) {
            asm volatile("cp.async.bulk.tensor.4d.global.shared::cta.bulk_group.L2::cache_hint [%0,{%1,%2,%3,%4}],[%5],%6;"
                         :: "l"(&mapL), "r"((quad & 1) * 32), "r"(v0), "r"(quad >> 1), "r"(hc * 4), "r"(stg), "l"(pol) : "memory");
          } else {
#pragma unroll 1
            for (int hh = 0; hh < 2; hh++) {
              const int pq = quad * 2 + hh;
              if (pq < 45) asm volatile("cp.async.bulk.tensor.4d.global.shared::cta.bulk_group.L2::cache_hint [%0,{%1,%2,%3,%4}],[%5],%6;"
                         :: "l"(&mapS), "r"(0), "r"(v0), "r"(pq - 36), "r"(hc * 4), "r"(stg + hh * 8192), "l"(pol) : "memory");
              else asm volatile("cp.async.bulk.tensor.3d.global.shared::cta.bulk_group.L2::cache_hint [%0,{%1,%2,%3}],[%4],%5;"
                         :: "l"(&mapT), "r"(v0 * 2), "r"((pq - 45) * 2), "r"(hc * 4), "r"(stg + hh * 8192), "l"(pol) : "memory");
            }
          }
          asm volatile("cp.async.bulk.commit_group;" ::: "memory");
          pf(n + WPF);
          asm volatile("cp.async.bulk.wait_group.read 0;" ::: "memory");
          mbar_arrive(emptyS + mt * 8);
        }
        asm volatile("cp.async.bulk.wait_group 0;" ::: "memory");
      }
    } else if (tid < 448) {
      asm volatile("bar.sync 2,192;" ::: "memory");
      if (tid == 416) {
        int st = 0, ph = 0;
#pragma unroll 1
        for (int p = 3; p < 50; p++) {
          mbar_wait(emptyB + st * 8, ph);
          mbar_expect(fullB + st * 8, 16384);
          asm volatile("cp.async.bulk.tensor.2d.shared::cluster.global.mbarrier::complete_tx::bytes [%0],[%1,{%2,%3}],[%4];"
                       :: "r"(sbase + K1_B + st * 16384), "l"(&mapW), "r"(hc * 32), "r"(QORD(p >> 1) * 512 + (p & 1) * 256), "r"(fullB + st * 8) : "memory");
          if (++st == 3) { st = 0; ph ^= 1; }
        }
      }
    } else {
      const int lw = (tid - 448) >> 5;
      float wt[13];
#pragma unroll
      for (int q = 0; q < 12; q++) wt[q] = __bfloat162float(wp[(96 + q / 3) * F_ + lane + 32 * (q % 3)]) + __bfloat162float(wp[(lane + 32 * (q % 3)) * F_ + 96 + q / 3]);
      wt[12] = lane < 16 ? __bfloat162float(wp[(96 + (g & 3)) * F_ + 96 + r]) : 0.f;
      if (lw == 0) { asm volatile("bar.sync 3,160;" ::: "memory"); flag_arrive(&g_flag[8 * 32], lane); }
      if (lw == 1) { asm volatile("bar.sync 4,288;" ::: "memory"); flag_arrive(&g_flag[(cta >> 4) * 32], lane); }
      const int* ip = idx + (cta * 128 + lw) * F_;
      int vj[3], vc; int4 va;
      auto ld_row = [&]() {
        vj[0] = __ldg(ip + lane); vj[1] = __ldg(ip + lane + 32); vj[2] = __ldg(ip + lane + 64);
        va = __ldg((const int4*)(ip + 96)); vc = __ldg(ip + 96 + r);
      };
      ld_row();
      flag_wait(&g_flag[8 * 32], 128);
      uint32_t gv[13] = {};
#pragma unroll 1
      for (int b = lw - 2; b < NLOOK; b += 2) {
        float acc = 0.f;
#pragma unroll
        for (int q = 0; q < 13; q++) {
          acc = fmaf(bf_lo(gv[q]), wt[q], acc);
          const int row = q == 12 ? ((g & 2) ? ((g & 1) ? va.w : va.z) : ((g & 1) ? va.y : va.x)) : q < 3 ? va.x : q < 6 ? va.y : q < 9 ? va.z : va.w;
          gv[q] = ldtex(texG, row * 1024 + (q == 12 ? vc : vj[q % 3])).x;
        }
        SCHED_FENCE(never, 100);
        if (b + 4 < 128) ip += 2 * F_;
        ld_row();
#pragma unroll
        for (int o = 16; o; o >>= 1) acc += __shfl_xor_sync(0xffffffffu, acc, o);
        if (lane == 0 && b >= 0) g_partP[16 * B_ + cta * 128 + b] = acc;
      }
    }
    return;
  }
  if (tid >= 256) {
    asm volatile("setmaxnreg.inc.sync.aligned.u32 160;");
    const int w = (tid >> 5) & 3;
    uint32_t a[2][8][4];
#pragma unroll
    for (int mt = 0; mt < 2; mt++) {
      const int v0 = rb * 128 + mt * 64 + w * 16 + g;
      const uint32_t* p0 = (const uint32_t*)(table + min(v0, V_ - 1) * D_) + r;
      const uint32_t* p1 = (const uint32_t*)(table + min(v0 + 8, V_ - 1) * D_) + r;
#pragma unroll
      for (int ks = 0; ks < 8; ks++) { a[mt][ks][0] = p0[ks * 8]; a[mt][ks][1] = p1[ks * 8]; a[mt][ks][2] = p0[ks * 8 + 4]; a[mt][ks][3] = p1[ks * 8 + 4]; }
    }
    asm volatile("bar.sync 2,192;" ::: "memory");
    const int srow = w * 16 + (lane & 7) + ((lane >> 3) & 1) * 8, sc = lane >> 4;
    const uint32_t baseL = sc * 4096 + srow * 64 + ((srow >> 1) & 3) * 16, baseS = sc * 2048 + srow * 32 + ((srow >> 2) & 1) * 16, baseT = sc * 2048 + srow * 16;
    const uint64_t desc0 = (uint64_t)(((sbase + K1_B) & 0x3FFFF) >> 4) | ((uint64_t)(8192 >> 4) << 16) | ((uint64_t)(512 >> 4) << 32) | (2ull << 62);
    float d[2][32];
    auto issue = [&](int h, int mt, int st) {
      asm volatile("wgmma.fence.sync.aligned;" ::: "memory");
#pragma unroll
      for (int ks = 0; ks < 8; ks++) wgmma_p<1>(d[h], a[mt][ks], desc0 + st * 1024 + ks * 64, ks);
      asm volatile("wgmma.commit_group.sync.aligned;" ::: "memory");
    };
    auto wait_acc = [&](int mt) {
      asm volatile("wgmma.wait_group.sync.aligned 0;" ::: "memory");
#pragma unroll
      for (int q = 0; q < 8; q++) asm volatile("" : "+f"(d[mt][q * 4]), "+f"(d[mt][q * 4 + 1]), "+f"(d[mt][q * 4 + 2]), "+f"(d[mt][q * 4 + 3]) :: "memory");
    };
    {
      const uint64_t de = (uint64_t)(((sbase + K1_STG) & 0x3FFFF) >> 4) | ((uint64_t)1 << 16) | ((uint64_t)(1024 >> 4) << 32) | (1ull << 62);
      mbar_wait_fast(fullE, 0);
      asm volatile("wgmma.fence.sync.aligned;" ::: "memory");
#pragma unroll
      for (int mt = 0; mt < 2; mt++)
#pragma unroll
        for (int ks = 0; ks < 8; ks++) wgmma_p<0>(d[mt], a[mt][ks], de + (ks >> 2) * 512 + (ks & 3) * 2, ks);
      asm volatile("wgmma.commit_group.sync.aligned;" ::: "memory");
      wait_acc(0); wait_acc(1);
      uint32_t* gp = (uint32_t*)(g_scr + G_OFF) + (rb * 128 + w * 16 + g) * 512 + hc * 32 + r;
#pragma unroll
      for (int mt = 0; mt < 2; mt++)
#pragma unroll
        for (int q = 0; q < 16; q++) gp[(mt * 64 + (q & 1) * 8) * 512 + (q >> 1) * 4] = pack_bf2(d[mt][q * 2], d[mt][q * 2 + 1]);
      asm volatile("bar.arrive 3,160;" ::: "memory");
      asm volatile("bar.sync 5,128;" ::: "memory");
    }
    mbar_wait_fast(fullB, 0);
    issue(0, 0, 0);
    int s0 = 0, ph = 0;
#pragma unroll 1
    for (int qn = 0; qn < 25; qn++) {
      const int quad = QORD(qn);
      const int s1 = s0 == 2 ? 0 : s0 + 1, s2 = s1 == 2 ? 0 : s1 + 1, ph1 = ph ^ (s1 == 0), ph2 = ph1 ^ (s2 == 0);
#pragma unroll
      for (int step = 0; step < 4; step++) {
        const int mt = ORD ? step & 1 : step >> 1, h = ORD ? step >> 1 : step & 1, x = step & 1, nx = (step + 1) & 3;
        const bool last = h, isL = quad < 18, isS = quad * 2 + h < 45;
        const uint32_t base = (isL ? baseL ^ (h * 32) : (isS ? baseS : baseT) ^ (h * 8192)), xj = (isL || isS) ? 16 : 1024, xc = isL ? 8192 : 4096;
        PT(qn * 16 + step * 4);
        if (h == 0) mbar_wait_fast(emptyS + mt * 8, (qn & 1) ^ 1);
        if (step == (ORD ? 1 : 0)) mbar_wait_fast(fullB + s1 * 8, ph1);
        if (step == 3) mbar_wait_fast(fullB + s2 * 8, qn == 24 ? ph2 ^ 1 : ph2);
        PT(qn * 16 + step * 4 + 1);
        wait_acc(x);
        PT(qn * 16 + step * 4 + 2);
        if (mt) mbar_arrive_lane0(emptyB + (h ? s1 : s0) * 8);
        issue(x ^ 1, ORD ? nx & 1 : nx >> 1, step == 3 ? s2 : (ORD ? nx >> 1 : nx & 1) ? s1 : s0);
        PT(qn * 16 + step * 4 + 3);
#pragma unroll
        for (int e4 = 0; e4 < 4; e4++) {
          const float* e = d[x] + e4 * 8;
          asm volatile("stmatrix.sync.aligned.m8n8.x4.shared.b16 [%0],{%1,%2,%3,%4};"
                       :: "r"(sbase + K1_STG + mt * 16384 + (base ^ ((e4 >> 1) * xj) ^ ((e4 & 1) * xc))),
                          "r"(pack_bf2(e[0], e[1])), "r"(pack_bf2(e[2], e[3])), "r"(pack_bf2(e[4], e[5])), "r"(pack_bf2(e[6], e[7])) : "memory");
        }
        if (last) { __syncwarp(); mbar_arrive_lane0(fullS + mt * 8); }
      }
      s0 = s2; ph = ph2;
    }
    asm volatile("wgmma.wait_group.sync.aligned 0;" ::: "memory");
    return;
  }
  asm volatile("setmaxnreg.inc.sync.aligned.u32 " RPNN ";");
  const int slice = cta & 15;
  const int range = (cta >> 4) * 8 + (tid >> 5);
  uint4 iv[4];
  uint4 trow[4], wrow[5];
#pragma unroll
  for (int q = 0; q < 4; q++) trow[q] = *(const uint4*)(table + min(tid + q * 256, V_ - 1) * D_ + slice * 8);
#pragma unroll
  for (int q = 0; q < 5; q++) wrow[q] = ((const uint4*)wp)[min(tid + q * 256, F_ * F_ / 8 - 1)];
  int4 r4[8]; int2 r2[8];
  {
    const int pos = ((lane >> 4) << 3) | (lane & 7);
    const int* ip = idx + (range * 256 + slice * 16 + ((lane >> 3) & 1)) * F_;
#pragma unroll
    for (int t = 0; t < 8; t++) {
      asm volatile("ld.global.nc.v4.u32 {%0,%1,%2,%3},[%4];" : "=r"(r4[t].x), "=r"(r4[t].y), "=r"(r4[t].z), "=r"(r4[t].w) : "l"(ip + t * 2 * F_ + pos * 4));
      asm volatile("ld.global.nc.v2.u32 {%0,%1},[%2];" : "=r"(r2[t].x), "=r"(r2[t].y) : "l"(ip + t * 2 * F_ + 64 + pos * 2));
    }
  }
  TS(3, 0);
  uint32_t me = 0, mw = 0;
#pragma unroll
  for (int q = 0; q < 4; q++) me = absmax4(trow[q], me);
#pragma unroll
  for (int q = 0; q < 5; q++) { mw = absmax4(wrow[q], mw); if (tid + q * 256 < F_ * F_ / 8) sm[tid + q * 256] = wrow[q]; }
  me = __reduce_max_sync(0xffffffffu, max(me & 0xffff, me >> 16));
  mw = __reduce_max_sync(0xffffffffu, max(mw & 0xffff, mw >> 16));
  uint32_t* sred = (uint32_t*)((char*)sm + 128000);
  if (lane == 0) sred[tid >> 5] = me | mw << 16;
#pragma unroll
  for (int q = 0; q < 4; q++) {
    iv[q] = make_uint4(pk3(r4[2 * q].x, r4[2 * q].y, r4[2 * q].z), pk3(r4[2 * q].w, r2[2 * q].x, r2[2 * q].y),
                       pk3(r4[2 * q + 1].x, r4[2 * q + 1].y, r4[2 * q + 1].z), pk3(r4[2 * q + 1].w, r2[2 * q + 1].x, r2[2 * q + 1].y));
    g_scr[PX_OFF + (range * 16 + slice) * 128 + q * 32 + lane] = iv[q];
  }
  asm volatile("bar.arrive 4,288;" ::: "memory");
  asm volatile("bar.sync 1,256;" ::: "memory");
  { uint32_t m = 0;
#pragma unroll
    for (int q = 0; q < 8; q++) m = __vmaxu2(m, sred[q]);
    me = m & 0xffff; mw = m >> 16; }
  const float se = pow2_scale(me, 3), sW = pow2_scale(mw, -2);
  TS(3, 1);
  auto put_rows = [&](int q, bool on) {
    const uint4 t = trow[q];
    const uint4 hv = make_uint4(pack_h2(bf_lo(t.x) * se, bf_hi(t.x) * se), pack_h2(bf_lo(t.y) * se, bf_hi(t.y) * se),
                                pack_h2(bf_lo(t.z) * se, bf_hi(t.z) * se), pack_h2(bf_lo(t.w) * se, bf_hi(t.w) * se));
    if (on)
#pragma unroll
      for (int s = 0; s < 8; s++) sts128(sbase + (tid + q * 256) * 128 + ((s + lane) & 7) * 16, hv);
  };
  {
    const int wu = tid >> 5;
    const int mycode = hu_code(min(wu * 11 + min(lane, 10), HU_N - 1));
    const int ok_ = mycode >> 4, on_ = mycode & 15;
    const int mypar = pnn_field(ok_, 0) | pnn_field(on_, 0) << 8 | (ok_ < 8 ? 4 : 2) << 16 | (on_ < 8 ? 4 : 2) << 20 |
                      (ok_ > on_) << 24 | (ok_ == on_) << 25;
    uint32_t raw[11][4];
#pragma unroll
    for (int q = 0; q < 11; q++) {
      const int par = __shfl_sync(0xffffffffu, mypar, q), sk = (par >> 16) & 15;
      const int fi = (par & 255) + sk * 2 * r, fj = ((par >> 8) & 255) + ((par >> 20) & 15) * g;
      auto ld16 = [&](int e) { uint32_t v; asm volatile("ld.shared.u16 %0,[%1];" : "=r"(v) : "r"(sbase + e * 2)); return v; };
      raw[q][0] = ld16(fj * F_ + fi); raw[q][1] = ld16(fj * F_ + fi + sk); raw[q][2] = ld16(fi * F_ + fj); raw[q][3] = ld16((fi + sk) * F_ + fj);
    }
    put_rows(1, true); put_rows(2, true); put_rows(3, tid + 768 < V_);
#pragma unroll
    for (int q = 0; q < 11; q++) {
      const int par = __shfl_sync(0xffffffffu, mypar, q);
      const float m0 = (par & (1 << 24)) ? 0.f : sW, m1 = (par >> 25) ? 0.f : m0;
      const uint32_t v = pack_h2(fmaf(bf_lo(raw[q][0]), m0, bf_lo(raw[q][2]) * m1), fmaf(bf_lo(raw[q][1]), m0, bf_lo(raw[q][3]) * m1));
      asm volatile("st.shared.u32 [%0],%1;" :: "r"(sbase + K1_W + (wu * 11 + q) * 128 + lane * 4), "r"(v) : "memory");
    }
  }
  TS(3, 2);
  asm volatile("fence.proxy.async.shared::cta;" ::: "memory");
  asm volatile("bar.sync 1,256;" ::: "memory");
  TS(3, 3);
  put_rows(0, true);
  uint32_t bf[HU_N - 2 * G_U];
#pragma unroll
  for (int q = 0; q < HU_N - 2 * G_U; q++) asm volatile("ld.shared.u32 %0,[%1];" : "=r"(bf[q]) : "r"(sbase + K1_W + (2 * G_U + q) * 128 + lane * 4));
  const float unscale = __uint_as_float(0x7f000000u - __float_as_uint(se)), unscale2 = __uint_as_float(0x7f000000u - __float_as_uint(sW));
  asm volatile("bar.sync 1,256;" ::: "memory");
  TS(0, 1);
  const uint32_t lc = (lane & 7) * 16;
  const uint64_t wdesc = (uint64_t)(((sbase + K1_W) & 0x3FFFF) >> 4) | ((uint64_t)(128 >> 4) << 16) | ((uint64_t)(256 >> 4) << 32);
  uint32_t a[2][6][4], d[2][24];
  float red[4] = {0.f, 0.f, 0.f, 0.f};
  auto gather = [&](int t) {
    const int x = t & 1;
    const uint4 v = iv[(t >> 1) & 3];
#pragma unroll
    for (int kb = 0; kb < 6; kb++) {
      const uint32_t ww = x ? (kb < 3 ? v.z : v.w) : (kb < 3 ? v.x : v.y);
      const uint32_t sh = kb % 3 == 0 ? ww : kb % 3 == 1 ? ww >> 10 : __funnelshift_l(ww, ww, 12);
      asm volatile("ldmatrix.sync.aligned.m8n8.x4.trans.shared.b16 {%0,%1,%2,%3},[%4];"
                   : "=r"(a[x][kb][0]), "=r"(a[x][kb][1]), "=r"(a[x][kb][2]), "=r"(a[x][kb][3]) : "r"(sbase + ((sh & 0x1ff80) | lc)));
    }
  };
  auto issue = [&](int x) {
    asm volatile("wgmma.fence.sync.aligned;" ::: "memory");
#pragma unroll
    for (int kb = 0; kb < 6; kb++) {
      if (kb < G_K0) wgmma_h<G_N0 * 8>(d[x] + G_O0 * 2, a[x][kb], wdesc + kb * G_N0 * 16, kb);
      if (kb < G_K1) wgmma_h<G_N1 * 8>(d[x] + G_O1 * 2, a[x][kb], wdesc + (G_U1 + kb * G_N1) * 16, kb);
      if (kb < G_K2) wgmma_h<32>(d[x] + G_O2 * 2, a[x][kb], wdesc + (G_U2 + kb * G_N2) * 16, kb);
    }
    asm volatile("wgmma.commit_group.sync.aligned;" ::: "memory");
  };
  uint32_t s[4];
  auto hmma_part = [&](int x) {
    constexpr FragIdx FI = make_fi();
#pragma unroll
    for (int o = 0; o < 12; o++) {
      if (oct_wg(o)) asm volatile("" : "+r"(d[x][o * 2]), "+r"(d[x][o * 2 + 1]) :: "memory"); else d[x][o * 2] = d[x][o * 2 + 1] = 0;
    }
#pragma unroll
    for (int kb = 0; kb < 6; kb++)
#pragma unroll
      for (int o = 2 * kb + 1; o < 12; o++)
        if (!unit_wg(kb, o)) mma16816h(d[x] + o * 2, a[x][kb], bf[FI.v[2 * kb][o]], bf[FI.v[2 * kb + 1][o]]);
#pragma unroll
    for (int q = 0; q < 6; q++) if (!unit_wg(q, 2 * q)) mma1688h(d[x] + q * 4, a[x][q][0], a[x][q][1], bf[FI.v[2 * q][2 * q]]);
  };
  auto dot_part = [&](int x) {
    s[0] = s[1] = s[2] = s[3] = 0;
#pragma unroll
    for (int o = 0; o < 12; o++) {
      s[(o & 1) * 2] = hfma2(d[x][o * 2], a[x][o >> 1][(o & 1) * 2], s[(o & 1) * 2]);
      s[(o & 1) * 2 + 1] = hfma2(d[x][o * 2 + 1], a[x][o >> 1][(o & 1) * 2 + 1], s[(o & 1) * 2 + 1]);
    }
  };
  float* outp = g_partP + slice * B_ + range * 256 + r * 4 + ((lane >> 3) & 1) * 2 + (lane >> 4);
  const int px = PX_OFF + range * 2048 + lane;
  gather(0); issue(0); gather(1);
  asm volatile("wgmma.wait_group.sync.aligned 0;" ::: "memory");
  hmma_part(0);
  flag_wait(&g_flag[(cta >> 4) * 32], 16);
  TS(4, 1);
#pragma unroll 1
  for (int n = slice; n < slice + 16; n++) {
    const int pn = px + ((n + 1) & 15) * 128;
#pragma unroll
    for (int t = 0; t < 8; t++) {
      const int x = t & 1;
      issue(x ^ 1);
      SCHED_FENCE(never, t * 4);
      if (t == 0) { iv[3] = ldtex(tex, px + (n & 15) * 128 + 96); iv[0] = ldtex(tex, pn); }
      if (t == 2) iv[1] = ldtex(tex, pn + 32);
      if (t == 4) iv[2] = ldtex(tex, pn + 64);
      dot_part(x);
      SCHED_FENCE(never, t * 4 + 1);
      gather(t + 2);
      asm volatile("wgmma.wait_group.sync.aligned 0;" ::: "memory");
      SCHED_FENCE(never, t * 4 + 2);
      mma16816f(red, s, g == t ? 0x3c003c00u : 0u);
      hmma_part(x ^ 1);
      SCHED_FENCE(never, t * 4 + 3);
    }
    {
      const bool u16 = lane & 16, u8 = lane & 8;
      float p0 = (u16 ? red[2] : red[0]) + __shfl_xor_sync(0xffffffffu, u16 ? red[0] : red[2], 16);
      float p1 = (u16 ? red[3] : red[1]) + __shfl_xor_sync(0xffffffffu, u16 ? red[1] : red[3], 16);
      float q0 = (u8 ? p1 : p0) + __shfl_xor_sync(0xffffffffu, u8 ? p0 : p1, 8);
      q0 += __shfl_xor_sync(0xffffffffu, q0, 4);
      if (!(lane & 4)) outp[(n & 15) * 16] = q0 * unscale * unscale * unscale2;
      red[0] = red[1] = red[2] = red[3] = 0.f;
    }
  }
  TS(0, 2);
}

constexpr int SM_U = 130048, SM_BAR = SM_U + 3 * 32032, DEEP_SMEM = SM_BAR + 128 + 4096;

__device__ __forceinline__ void arrive_both(uint32_t bar, int lane) {
  asm volatile("{.reg .pred p; .reg .u32 a; setp.lt.u32 p,%1,2; mapa.shared::cluster.u32 a,%0,%1;\n"
               "@p mbarrier.arrive.shared::cluster.b64 _,[a];}" :: "r"(bar), "r"(lane) : "memory");
}
__device__ __forceinline__ void bulk_mc(uint32_t dst, const void* src, uint32_t bytes, uint32_t bar, uint64_t pol) {
  asm volatile("cp.async.bulk.shared::cluster.global.mbarrier::complete_tx::bytes.multicast::cluster.L2::cache_hint [%0],[%1],%2,[%3],%4,%5;"
               :: "r"(dst), "l"(src), "r"(bytes), "r"(bar), "h"((unsigned short)3), "l"(pol) : "memory");
}

__global__ void __cluster_dims__(2, 1, 1) __launch_bounds__(TH + 128, 1)
k_deep(cudaTextureObject_t tex, const __nv_bfloat16* __restrict__ b1, const __nv_bfloat16* __restrict__ w2, int never) {
  extern __shared__ __align__(1024) uint4 sm[];
  constexpr int PF = DPF, DEPTH = DDEPTH, NW = TH / 32;
  static_assert(YD == 4, "");
  const int tid = threadIdx.x;
  const int c = blockIdx.x >> 1, half = blockIdx.x & 1;
  const uint32_t sbase = (uint32_t)__cvta_generic_to_shared(sm);
  const uint32_t fullL = sbase + SM_BAR, fullU = fullL + 8, emptyL = fullL + 16, emptyU = fullL + 24;
  TS(1, 0);
  if (tid == 0) {
    mbar_init(fullL, 1); mbar_init(fullU, 1); mbar_init(emptyL, 2 * NW); mbar_init(emptyU, 2 * NW);
    asm volatile("fence.mbarrier_init.release.cluster;" ::: "memory");
  }
  __syncwarp();
  asm volatile("barrier.cluster.arrive.relaxed.aligned; barrier.cluster.wait.aligned;" ::: "memory");
  if (__builtin_expect(tid >= TH, 1)) {
    asm volatile("setmaxnreg.dec.sync.aligned.u32 24;");
    if (tid == TH) {
      const char* base = (const char*)g_scr;
      uint32_t oL = (PL_OFF + c * NC * 8000) * 16u + half * 64000, oS = (PS_OFF + c * NC * 2000) * 16u + half * 16000;
      uint32_t oT = (PT_OFF + c * 10 * 1024) * 16u + half * 8000, oI = (IX_OFF + half * NC * 8192 + c * 128) * 16u;
      uint32_t t0 = clock();
      mbar_expect(fullU, 96000);
#pragma unroll 1
      for (int m = 0; m < 3; m++) bulk_mc(sbase + SM_U + m * 32032 + half * 16000, base + oS, 16000, fullU, m == 2 ? POL_EF : POL_N);
      bulk_pf(base + oI, 2048); bulk_pf(base + oT, 8000);
      for (int k = 1; k < NC; k++) bulk_pf(base + oI + k * 131072, 2048);
      mbar_expect(fullL, 128000);
      sleep_until(t0, (c & 3) * STAG);
      bulk_mc(sbase + half * 64000, base + oL, 64000, fullL, POL_EF);
#pragma unroll 1
      for (int k = 0; k + 1 < NC; k++) {
        oL += 128000; oS += 32000; oT += 16384; oI += 131072;
        mbar_wait(fullL, k & 1);
        t0 = clock();
        bulk_pf(base + oS, 16000);
        mbar_wait(emptyU, k & 1);
        mbar_expect(fullU, 96000 + 8192);
        { const uint32_t oW = (IX_OFF + (half * NC + min(k + 2, NC - 1)) * 8192 + ((c + (c >> 4) * 5) & 15) * 512) * 16u;
          bulk_g2s(sbase + SM_BAR + 128, base + oW, 4096, fullU); bulk_g2s(sbase + SM_BAR + 128, base + oW + 4096, 4096, fullU); }
#pragma unroll 1
        for (int q = 0; q < 8; q++) {
          sleep_until(t0, q * PACE);
          bulk_pf(base + oL + q * 8000, 8000);
          if (q >= 2) bulk_mc(sbase + SM_U + ((q - 2) >> 1) * 32032 + half * 16000 + (q & 1) * 8000, base + oS + (q & 1) * 8000, 8000, fullU, q >= 6 ? POL_EF : POL_N);
        }
        bulk_pf(base + oT, 8000);
        mbar_expect(fullL, 128000);
        mbar_wait(emptyL, k & 1);
        bulk_mc(sbase + half * 64000, base + oL, 64000, fullL, POL_EF);
      }
      bulk_pf(base + oT + 16384, 8000);
      bulk_pf(base + (I9_OFF + half * 2048 + c * 32) * 16u, 512);
    }
    return;
  }
  asm volatile("setmaxnreg.inc.sync.aligned.u32 240;");
  const int lane = tid & 31;
  const int tbase = PT_OFF + c * 10 * 1024;
  const int ibase = IX_OFF + half * NC * 8192 + tid;
  const uint32_t lc = (tid & 7) << 4;
  uint4 acc[NS], wq[PF], x[DEPTH], y[YD], ye;
  uint32_t sw[NS] = {};
  auto sget = [&](int s) { return (s & 3) == 3 ? __byte_perm(__byte_perm(sw[s - 3], sw[s - 2], 0x0073), sw[s - 1], 0x0710) : sw[s]; };
  auto sa0 = [&](uint32_t v) { return sbase + SM_U + (((v << 5) & 0x1ffe0) | ((lc >> 2) & 16)); };
  auto sa1 = [&](uint32_t v) { return sbase + SM_U + (((v >> 7) & 0x1ffe0) | ((~lc >> 2) & 16)); };
  {
    uint4 i0[8];
#pragma unroll
    for (int q = 0; q < 8; q++) i0[q] = ldtex(tex, I0_OFF + (half * 8 + q) * TH + tid);
#pragma unroll
    for (int i = 0; i < PF; i++) wq[i] = ldtex(tex, ibase + i * TH);
    auto wd = [&](int k) { return (k & 3) == 0 ? i0[k >> 2].x : (k & 3) == 1 ? i0[k >> 2].y : (k & 3) == 2 ? i0[k >> 2].z : i0[k >> 2].w; };
    mbar_wait_fast(fullU, 0);
    TS(1, 1);
#pragma unroll
    for (int s = 0; s < NS; s++) acc[s] = add4(lds128(sa0(wd(s))), lds128(sa1(wd(s))));
    arrive_both(emptyU, lane);
  }
#pragma unroll 1
  for (int k = 0; k < NC; k++) {
    const int ti = ibase + k * 8192;
    const int tb = tbase + k * 1024;
    const bool more = k + 1 < NC;
    TR(k * 4);
    mbar_wait_fast(fullL, k & 1);
    TR(k * 4 + 2);
    uint4 w, cc; uint32_t yc, yn;
    constexpr int TL = NS * 8, TT = TL + NS * 2;
#pragma unroll
    for (int t = 0; t < TT + DEPTH; t += 2) {
      if (t == TL + DEPTH && !more) break;
      if (t >= DEPTH) {
        const int u = t - DEPTH;
        uint4 p = add4(x[u % DEPTH], x[(u + 1) % DEPTH]);
        if (u < TL) {
          const int s = u >> 3, j = u & 7;
          if (j == 0) {
            cc = s >= YD ? add4(y[s % YD], p) : p;
            if (s + YD < NS) y[s % YD] = ldtex(tex, tb | (yc & 1023));
          } else cc = add4(cc, p);
          if (j == 6) acc[s] = add4(acc[s], cc);
        } else {
          const int s = (u - TL) >> 1;
          acc[s] = add4(acc[s], p);
        }
      }
      if (DEPTH == 8 && (t & 7) == 2) yc = yn;
      if (t < TL) {
        const int s = t >> 3, j = t & 7;
        if (j == 0) {
          w = wq[s % PF]; wq[s % PF] = ldtex(tex, ti + (s + PF) * TH);
          yn = __funnelshift_l(w.z, w.z, 5); if (DEPTH < 8) yc = yn;
          if ((s & 3) != 3) asm volatile("add.u32 %0,%1,%2;" : "=r"(sw[s]) : "r"(w.w), "r"(never));
          if (ye_of(s - YD) >= 0) acc[ye_of(s - YD) & 3] = add4(acc[ye_of(s - YD) & 3], ye);
          if (ye_of(s) >= 0) ye = ldtex(tex, tb | w.w);
        }
#pragma unroll
        for (int jj = j; jj < j + 2; jj++) {
          const uint32_t ww = jj < 3 ? w.x : jj < 6 ? w.y : w.z;
          const uint32_t sh = jj % 3 == 0 ? ww : jj % 3 == 1 ? ww >> 10 : __funnelshift_l(ww, ww, 12);
          x[(t + jj - j) % DEPTH] = lds128(sbase + ((sh & 0x1ff80) | lc) + jj * 16 - 128);
        }
      } else if (t < TT) {
        const int s = (t - TL) >> 1;
        if (s == 0) { arrive_both(emptyL, more ? lane : 9); TR(k * 4 + 3); mbar_wait_fast(fullU, (more ? k + 1 : k) & 1); }
        const uint32_t sv = sget(s);
        x[t % DEPTH] = lds128(sa0(sv));
        x[(t + 1) % DEPTH] = lds128(sa1(sv));
      } else if (t == TT) arrive_both(emptyU, k + 2 < NC ? lane : 9);
      if ((t & (FENCE_N - 1)) == FENCE_N - 2) SCHED_FENCE(never, t);
    }
  }
  TS(1, 2);
  uint4 i9 = ldtex(tex, I9_OFF + half * 2048 + tid), i9n = ldtex(tex, I9_OFF + half * 2048 + TH + tid);
  const uint4 b1v = *(const uint4*)(b1 + c * 8), w2v = *(const uint4*)(w2 + c * 8);
  asm volatile("bar.sync 1,%0;" :: "n"(TH) : "memory");
#pragma unroll
  for (int s = 0; s < NS; s++) sts128(sbase + (s * TH + tid) * 16, acc[s]);
  const int t9 = tbase + 9 * 1024;
  y[0] = ldtex(tex, t9 | i9.x); y[1] = ldtex(tex, t9 | i9.y); y[2] = ldtex(tex, t9 | i9.z); y[3] = ldtex(tex, t9 | i9.w);
  float bb[8], hw[8];
  {
    const uint32_t bw[4] = {b1v.x, b1v.y, b1v.z, b1v.w}, ww[4] = {w2v.x, w2v.y, w2v.z, w2v.w};
#pragma unroll
    for (int k = 0; k < 8; k++) {
      bb[k] = __uint_as_float((k & 1) ? (bw[k >> 1] & 0xffff0000u) : (bw[k >> 1] << 16));
      hw[k] = 0.5f * __uint_as_float((k & 1) ? (ww[k >> 1] & 0xffff0000u) : (ww[k >> 1] << 16));
    }
  }
  float* outp = g_partD + c * B_ + half * 8192 + tid;
#pragma unroll 1
  for (int q = 0; q < NS / 4; q++) {
    uint4 z[4];
#pragma unroll
    for (int s = 0; s < 4; s++) z[s] = add4(lds128(sbase + ((q * 4 + s) * TH + tid) * 16), y[s]);
    y[0] = ldtex(tex, t9 | i9n.x); y[1] = ldtex(tex, t9 | i9n.y); y[2] = ldtex(tex, t9 | i9n.z); y[3] = ldtex(tex, t9 | i9n.w);
    i9n = ldtex(tex, I9_OFF + half * 2048 + min(q + 2, NS / 4 - 1) * TH + tid);
#pragma unroll
    for (int s = 0; s < 4; s++) {
      const uint32_t a[4] = {z[s].x, z[s].y, z[s].z, z[s].w};
      float r0 = 0.f, r1 = 0.f;
#pragma unroll
      for (int k = 0; k < 8; k++) {
        float xv = __uint_as_float((k & 1) ? (a[k >> 1] & 0xffff0000u) : (a[k >> 1] << 16)) + bb[k];
        float u = xv * fmaf(xv * xv, 0.7978845608028654f * 0.044715f, 0.7978845608028654f);
        float th; asm("tanh.approx.f32 %0,%1;" : "=f"(th) : "f"(u));
        float hx = xv * hw[k];
        r0 = fmaf(hx, th, r0); r1 += hx;
      }
      outp[(q * 4 + s) * TH] = r0 + r1;
    }
  }
  TS(1, 3);
}

__global__ void k_final(const __nv_bfloat16* __restrict__ b2, __nv_bfloat16* __restrict__ out) {
  __shared__ float red[4][32];
  int lane = threadIdx.x & 31, q = threadIdx.x >> 5, b = blockIdx.x * 32 + lane;
  float s = 0;
#pragma unroll
  for (int k = 0; k < 16; k++) s += g_partD[(q * 16 + k) * B_ + b];
#pragma unroll
  for (int k = 0; k < 4; k++) s += g_partP[(q * 4 + k) * B_ + b];
  if (q == 0) s += g_partP[16 * B_ + b];
  if (blockIdx.x == 0 && threadIdx.x < 9) g_flag[threadIdx.x * 32] = 0;
  red[q][lane] = s;
  __syncthreads();
  if (q == 0) out[b] = __float2bfloat16(red[0][lane] + red[1][lane] + red[2][lane] + red[3][lane] + __bfloat162float(b2[0]));
}

}

extern "C" void kernel_launch(void* const* d_in, const int* in_sizes, int n_in, void* d_out, int out_size) {
  const int* idx = (const int*)d_in[0];
  const __nv_bfloat16* table = (const __nv_bfloat16*)d_in[1];
  const __nv_bfloat16* wp = (const __nv_bfloat16*)d_in[2];
  const __nv_bfloat16* w1 = (const __nv_bfloat16*)d_in[3];
  const __nv_bfloat16* b1 = (const __nv_bfloat16*)d_in[4];
  const __nv_bfloat16* w2 = (const __nv_bfloat16*)d_in[5];
  const __nv_bfloat16* b2 = (const __nv_bfloat16*)d_in[6];
  static cudaTextureObject_t texScr = 0, texG = 0;
  static CUtensorMap mapW, mapL, mapS, mapT, mapE;
  static const void *c_tab = nullptr, *c_w1 = nullptr;
  if (c_tab != table || c_w1 != w1) {
    c_tab = table; c_w1 = w1;
    char* scr = nullptr; cudaGetSymbolAddress((void**)&scr, g_scr);
    auto mk_tex = [](const void* p, size_t bytes, cudaChannelFormatDesc d) {
      cudaResourceDesc rd = {}; rd.resType = cudaResourceTypeLinear; rd.res.linear.devPtr = (void*)p; rd.res.linear.desc = d; rd.res.linear.sizeInBytes = bytes;
      cudaTextureDesc td = {}; td.readMode = cudaReadModeElementType;
      cudaTextureObject_t t = 0; cudaCreateTextureObject(&t, &rd, &td, nullptr); return t;
    };
    if (!texScr) {
      texScr = mk_tex(scr, (size_t)SCR_N * 16, cudaCreateChannelDesc<uint4>());
      texG = mk_tex(scr + (size_t)G_OFF * 16, (size_t)2 << 20, cudaCreateChannelDesc<unsigned short>());
    }
    typedef CUresult (*EncFn)(CUtensorMap*, CUtensorMapDataType, cuuint32_t, void*, const cuuint64_t*, const cuuint64_t*, const cuuint32_t*,
                              const cuuint32_t*, CUtensorMapInterleave, CUtensorMapSwizzle, CUtensorMapL2promotion, CUtensorMapFloatOOBfill);
    EncFn enc = nullptr; cudaDriverEntryPointQueryResult qr;
    cudaGetDriverEntryPoint("cuTensorMapEncodeTiled", (void**)&enc, cudaEnableDefault, &qr);
    const cuuint32_t ones[4] = {1, 1, 1, 1};
    auto mk = [&](CUtensorMap* m, CUtensorMapDataType dt, int rank, void* p, const cuuint64_t* dim, const cuuint64_t* str, const cuuint32_t* box, CUtensorMapSwizzle sw) {
      enc(m, dt, rank, p, dim, str, box, ones, CU_TENSOR_MAP_INTERLEAVE_NONE, sw, CU_TENSOR_MAP_L2_PROMOTION_NONE, CU_TENSOR_MAP_FLOAT_OOB_FILL_NONE);
    };
    { cuuint64_t dim[2] = {H_, F_ * D_}, str[1] = {H_ * 2}; cuuint32_t box[2] = {32, 256};
      mk(&mapW, CU_TENSOR_MAP_DATA_TYPE_BFLOAT16, 2, (void*)w1, dim, str, box, CU_TENSOR_MAP_SWIZZLE_64B); }
    { cuuint64_t dim[4] = {64, V_, NC, 64}, str[3] = {128, 128000, 128000 * NC}; cuuint32_t box[4] = {32, 64, 1, 4};
      mk(&mapL, CU_TENSOR_MAP_DATA_TYPE_BFLOAT16, 4, scr + (size_t)PL_OFF * 16, dim, str, box, CU_TENSOR_MAP_SWIZZLE_64B); }
    { cuuint64_t dim[4] = {16, V_, NC, 64}, str[3] = {32, 32000, 32000 * NC}; cuuint32_t box[4] = {16, 64, 1, 4};
      mk(&mapS, CU_TENSOR_MAP_DATA_TYPE_BFLOAT16, 4, scr + (size_t)PS_OFF * 16, dim, str, box, CU_TENSOR_MAP_SWIZZLE_32B); }
    { cuuint64_t dim[3] = {2048, 10, 64}, str[2] = {16384, 163840}; cuuint32_t box[3] = {128, 2, 4};
      mk(&mapT, CU_TENSOR_MAP_DATA_TYPE_UINT64, 3, scr + (size_t)PT_OFF * 16, dim, str, box, CU_TENSOR_MAP_SWIZZLE_NONE); }
    { cuuint64_t dim[2] = {D_, V_}, str[1] = {D_ * 2}; cuuint32_t box[2] = {64, 64};
      mk(&mapE, CU_TENSOR_MAP_DATA_TYPE_BFLOAT16, 2, (void*)table, dim, str, box, CU_TENSOR_MAP_SWIZZLE_128B); }
    cudaFuncSetAttribute(k_deep, cudaFuncAttributeMaxDynamicSharedMemorySize, DEEP_SMEM);
    cudaFuncSetAttribute(k_tens, cudaFuncAttributeMaxDynamicSharedMemorySize, K1_SMEM);
  }
  k_tens<<<132, 512, K1_SMEM>>>(mapW, mapL, mapS, mapT, mapE, texScr, texG, idx, table, wp, w1, 0);
  k_deep<<<128, TH + 128, DEEP_SMEM>>>(texScr, b1, w2, 0);
  k_final<<<B_ / 32, 128>>>(b2, (__nv_bfloat16*)d_out);
}
```

```cpp
#include <cuda_runtime.h>
#include <cuda_bf16.h>
#include <cuda_fp16.h>
#include <stdint.h>
#include <cuda.h>

namespace {

constexpr int B_ = 16384, F_ = 100, D_ = 128, V_ = 1000, H_ = 512;
constexpr int NC = 9;
constexpr int PT_OFF = 0;
constexpr int PL_OFF = 64 * 10 * 1024;
constexpr int PS_OFF = PL_OFF + 64 * NC * 8000;
constexpr int IX_OFF = PS_OFF + 64 * NC * 2000;
constexpr int I0_OFF = IX_OFF + 2 * NC * 8192;
constexpr int I9_OFF = I0_OFF + 4096;
constexpr int PX_OFF = I9_OFF + 4096;
constexpr int SCR_N = PX_OFF + 64 * 16 * 136;
static_assert(PX_OFF % 32 == 0, "");

__device__ __align__(1024) uint4 g_scr[SCR_N];
__device__ float g_partD[64 * B_];
__device__ float g_partP[16 * B_];
__device__ unsigned g_flag[16 * 32];

#define TS(k, i)
#define TR(slot)
#define PT(slot)

constexpr uint64_t POL_EF = 0x12F0000000000000ull, POL_N = 0x1000000000000000ull;
__device__ __forceinline__ uint32_t addbf2(uint32_t a, uint32_t b) { uint32_t r; asm("add.rn.bf16x2 %0,%1,%2;" : "=r"(r) : "r"(a), "r"(b)); return r; }
__device__ __forceinline__ uint4 add4(const uint4& a, const uint4& b) { return make_uint4(addbf2(a.x, b.x), addbf2(a.y, b.y), addbf2(a.z, b.z), addbf2(a.w, b.w)); }
__device__ __forceinline__ void acc4(uint4& a, const uint4& b, int never) {
  asm("{.reg .pred p; setp.eq.s32 p,%8,0;\n"
      "@p add.rn.bf16x2 %0,%0,%4; @p add.rn.bf16x2 %1,%1,%5; @p add.rn.bf16x2 %2,%2,%6; @p add.rn.bf16x2 %3,%3,%7;}"
      : "+r"(a.x), "+r"(a.y), "+r"(a.z), "+r"(a.w) : "r"(b.x), "r"(b.y), "r"(b.z), "r"(b.w), "r"(never));
}
__device__ __forceinline__ uint4 ldtex(cudaTextureObject_t t, int i) {
  uint4 v; asm volatile("tex.1d.v4.u32.s32 {%0,%1,%2,%3},[%4,{%5}];" : "=r"(v.x), "=r"(v.y), "=r"(v.z), "=r"(v.w) : "l"(t), "r"(i)); return v;
}
__device__ __forceinline__ uint4 lds128(uint32_t a) {
  uint4 v; asm volatile("ld.volatile.shared.v4.u32 {%0,%1,%2,%3},[%4];" : "=r"(v.x), "=r"(v.y), "=r"(v.z), "=r"(v.w) : "r"(a)); return v;
}
__device__ __forceinline__ void sts128(uint32_t a, const uint4& v) {
  asm volatile("st.shared.v4.u32 [%0],{%1,%2,%3,%4};" :: "r"(a), "r"(v.x), "r"(v.y), "r"(v.z), "r"(v.w) : "memory");
}
__device__ __forceinline__ void mbar_init(uint32_t bar, int n) { asm volatile("mbarrier.init.shared::cta.b64 [%0],%1;" :: "r"(bar), "r"(n) : "memory"); }
__device__ __forceinline__ void mbar_wait(uint32_t bar, uint32_t parity) {
  uint32_t ok; int it = 0;
  do { asm volatile("{.reg .pred p; mbarrier.try_wait.parity.shared::cta.b64 p,[%1],%2; selp.u32 %0,1,0,p;}" : "=r"(ok) : "r"(bar), "r"(parity) : "memory"); } while (!ok && ++it < (1 << 22));
}
__device__ __forceinline__ void mbar_expect(uint32_t bar, uint32_t bytes) { asm volatile("mbarrier.arrive.expect_tx.shared::cta.b64 _,[%0],%1;" :: "r"(bar), "r"(bytes) : "memory"); }
__device__ __forceinline__ void bulk_g2s(uint32_t dst, const void* src, uint32_t bytes, uint32_t bar) {
  asm volatile("cp.async.bulk.shared::cluster.global.mbarrier::complete_tx::bytes [%0],[%1],%2,[%3];" :: "r"(dst), "l"(src), "r"(bytes), "r"(bar) : "memory");
}
__device__ __forceinline__ void bulk_pf(const void* src, uint32_t bytes) { asm volatile("cp.async.bulk.prefetch.L2.global [%0],%1;" :: "l"(src), "r"(bytes) : "memory"); }
#define IW 2
#define PP0 10
#define PT0 10000
#define PDT 2200
#define RPNN "160"
#define RAUX "32"
#define RPRO "160"
#define PARK 0
#define NLOOK 128
#define NEF 25
#define ORD 0
#define WFENCE 0
#define IPF 3
#define IPACE 4500
#define WPF 3
#define QORD(n) (n)
#define DYD 4
#define DPF 4
#define DDEPTH 4
#define FENCE_N 8
#define INPL 0
#define STAG 1100
#define PACE 800
#define PM4 "pmevent 1; pmevent 2; pmevent 3; pmevent 4;"
#define PMFILL "pmevent 1;"
#define SCHED_FENCE(never, k) asm volatile("{.reg .pred p; setp.ne.u32 p,%0,%1; @p bra.uni SKIP_%=;" PMFILL "SKIP_%=: }" :: "r"(never), "r"(0x7fff0000 + (k)) : "memory")

__global__ void k_prod_naive(const __nv_bfloat16* __restrict__ table, const __nv_bfloat16* __restrict__ w1) {
  __shared__ float t[8][D_];
  int f = blockIdx.y, v0 = blockIdx.x * 8, h = threadIdx.x;
  for (int i = h; i < 8 * D_; i += 512) t[i / D_][i % D_] = __bfloat162float(table[v0 * D_ + i]);
  __syncthreads();
  float s[8] = {0, 0, 0, 0, 0, 0, 0, 0};
  for (int d = 0; d < D_; d++) { float w = __bfloat162float(w1[(size_t)(f * D_ + d) * H_ + h]);
#pragma unroll
    for (int k = 0; k < 8; k++) s[k] += t[k][d] * w; }
  __nv_bfloat16* P = (__nv_bfloat16*)g_scr;
  int c = h >> 3;
  for (int k = 0; k < 8; k++) {
    size_t e = f < 72 ? (size_t)PL_OFF + ((size_t)(c * NC + (f >> 3)) * 1000 + v0 + k) * 8 + (f & 7)
             : f < 90 ? (size_t)PS_OFF + ((size_t)(c * NC + ((f - 72) >> 1)) * 1000 + v0 + k) * 2 + (f & 1)
                      : (size_t)PT_OFF + (size_t)(c * 10 + f - 90) * 1024 + v0 + k;
    P[e * 8 + (h & 7)] = __float2bfloat16(s[k]);
  }
}
__global__ void k_pnn_naive(const int* __restrict__ idx, const __nv_bfloat16* __restrict__ table, const __nv_bfloat16* __restrict__ wp) {
  __shared__ float e[F_][33];
  int b = blockIdx.x, d0 = blockIdx.y * 32, tid = threadIdx.x;
  for (int i = tid; i < F_ * 32; i += 128) e[i >> 5][i & 31] = __bfloat162float(table[idx[b * F_ + (i >> 5)] * D_ + d0 + (i & 31)]);
  __syncthreads();
  float s = 0; int d = tid & 31;
  for (int i = tid >> 5; i < F_; i += 4) { float u = 0; for (int j = 0; j < F_; j++) u += __bfloat162float(wp[i * F_ + j]) * e[j][d]; s += u * e[i][d]; }
  for (int o = 16; o; o >>= 1) s += __shfl_xor_sync(~0u, s, o);
  if (d == 0) g_partP[(blockIdx.y * 4 + (tid >> 5)) * B_ + b] = s;
}
__device__ __forceinline__ void mbar_wait_fast(uint32_t bar, uint32_t parity) {
  asm volatile("{.reg .pred p; .reg .u32 n;\n"
               "mbarrier.try_wait.parity.shared::cta.b64 p,[%0],%1;\n"
               "@p bra DONE_%=;\n"
               "mov.u32 n,0;\n"
               "LOOP_%=: mbarrier.try_wait.parity.shared::cta.b64 p,[%0],%1;\n"
               "add.u32 n,n,1; setp.gt.or.u32 p,n,4000000,p;\n"
               "@!p bra LOOP_%=;\n"
               "DONE_%=: }" :: "r"(bar), "r"(parity) : "memory");
}
__device__ __forceinline__ void sleep_until(uint32_t t0, uint32_t dt) { while ((uint32_t)clock() - t0 < dt) __nanosleep(40); }
__device__ __forceinline__ uint32_t s_mask(uint32_t v, int q) { return (1u << ((v + 3 - q) & 3)) | (16u << ((v + 3 + q) & 3)); }
__device__ __forceinline__ uint32_t s_cell(uint32_t v, int q, uint32_t m) {
  const int t = __ffs(~m) - 1;
  const int cp = ((t & 4 ? t - q : t + q) - v) & 3;
  return (cp == 3 ? 0 : cp) * 1001 + v;
}
__device__ __forceinline__ uint32_t pk3(uint32_t a, uint32_t b, uint32_t c) {
  const uint32_t w = c + (a << 12) + (b << 22); return __funnelshift_l(w, w, 27);
}
constexpr int TH = 256, NS = 8192 / TH, YD = DYD;
__host__ __device__ constexpr int ye_of(int s) { return s == 3 ? 0 : s == 11 ? 1 : s == 19 ? 2 : s == 23 ? 3 : -1; }
template <int N> __device__ __forceinline__ void wgmma_h(uint32_t* d, const uint32_t* a, uint64_t desc, int acc);
template <> __device__ __forceinline__ void wgmma_h<64>(uint32_t* d, const uint32_t* a, uint64_t desc, int acc) {
  asm volatile("{.reg .pred p; setp.ne.s32 p,%21,0;\n"
    "wgmma.mma_async.sync.aligned.m64n64k16.f16.f16.f16 {%0,%1,%2,%3,%4,%5,%6,%7,%8,%9,%10,%11,%12,%13,%14,%15},{%16,%17,%18,%19},%20,p,1,1,0;}"
    : "+r"(d[0]),"+r"(d[1]),"+r"(d[2]),"+r"(d[3]),"+r"(d[4]),"+r"(d[5]),"+r"(d[6]),"+r"(d[7]),"+r"(d[8]),"+r"(d[9]),"+r"(d[10]),"+r"(d[11]),"+r"(d[12]),"+r"(d[13]),"+r"(d[14]),"+r"(d[15])
    : "r"(a[0]), "r"(a[1]), "r"(a[2]), "r"(a[3]), "l"(desc), "r"(acc));
}
template <> __device__ __forceinline__ void wgmma_h<56>(uint32_t* d, const uint32_t* a, uint64_t desc, int acc) {
  asm volatile("{.reg .pred p; setp.ne.s32 p,%19,0;\n"
    "wgmma.mma_async.sync.aligned.m64n56k16.f16.f16.f16 {%0,%1,%2,%3,%4,%5,%6,%7,%8,%9,%10,%11,%12,%13},{%14,%15,%16,%17},%18,p,1,1,0;}"
    : "+r"(d[0]),"+r"(d[1]),"+r"(d[2]),"+r"(d[3]),"+r"(d[4]),"+r"(d[5]),"+r"(d[6]),"+r"(d[7]),"+r"(d[8]),"+r"(d[9]),"+r"(d[10]),"+r"(d[11]),"+r"(d[12]),"+r"(d[13])
    : "r"(a[0]), "r"(a[1]), "r"(a[2]), "r"(a[3]), "l"(desc), "r"(acc));
}
template <> __device__ __forceinline__ void wgmma_h<48>(uint32_t* d, const uint32_t* a, uint64_t desc, int acc) {
  asm volatile("{.reg .pred p; setp.ne.s32 p,%17,0;\n"
    "wgmma.mma_async.sync.aligned.m64n48k16.f16.f16.f16 {%0,%1,%2,%3,%4,%5,%6,%7,%8,%9,%10,%11},{%12,%13,%14,%15},%16,p,1,1,0;}"
    : "+r"(d[0]),"+r"(d[1]),"+r"(d[2]),"+r"(d[3]),"+r"(d[4]),"+r"(d[5]),"+r"(d[6]),"+r"(d[7]),"+r"(d[8]),"+r"(d[9]),"+r"(d[10]),"+r"(d[11])
    : "r"(a[0]), "r"(a[1]), "r"(a[2]), "r"(a[3]), "l"(desc), "r"(acc));
}
template <> __device__ __forceinline__ void wgmma_h<40>(uint32_t* d, const uint32_t* a, uint64_t desc, int acc) {
  asm volatile("{.reg .pred p; setp.ne.s32 p,%15,0;\n"
    "wgmma.mma_async.sync.aligned.m64n40k16.f16.f16.f16 {%0,%1,%2,%3,%4,%5,%6,%7,%8,%9},{%10,%11,%12,%13},%14,p,1,1,0;}"
    : "+r"(d[0]),"+r"(d[1]),"+r"(d[2]),"+r"(d[3]),"+r"(d[4]),"+r"(d[5]),"+r"(d[6]),"+r"(d[7]),"+r"(d[8]),"+r"(d[9])
    : "r"(a[0]), "r"(a[1]), "r"(a[2]), "r"(a[3]), "l"(desc), "r"(acc));
}
template <> __device__ __forceinline__ void wgmma_h<32>(uint32_t* d, const uint32_t* a, uint64_t desc, int acc) {
  asm volatile("{.reg .pred p; setp.ne.s32 p,%13,0;\n"
    "wgmma.mma_async.sync.aligned.m64n32k16.f16.f16.f16 {%0,%1,%2,%3,%4,%5,%6,%7},{%8,%9,%10,%11},%12,p,1,1,0;}"
    : "+r"(d[0]),"+r"(d[1]),"+r"(d[2]),"+r"(d[3]),"+r"(d[4]),"+r"(d[5]),"+r"(d[6]),"+r"(d[7])
    : "r"(a[0]), "r"(a[1]), "r"(a[2]), "r"(a[3]), "l"(desc), "r"(acc));
}
__device__ __forceinline__ void wgmma_p(float* d, const uint32_t* a, uint64_t desc, int acc) {
  asm volatile("{.reg .pred p; setp.ne.s32 p,%37,0;\n"
    "wgmma.mma_async.sync.aligned.m64n64k16.f32.bf16.bf16 {%0,%1,%2,%3,%4,%5,%6,%7,%8,%9,%10,%11,%12,%13,%14,%15,%16,%17,%18,%19,%20,%21,%22,%23,%24,%25,%26,%27,%28,%29,%30,%31},{%32,%33,%34,%35},%36,p,1,1,1;}"
    : "+f"(d[0]),"+f"(d[1]),"+f"(d[2]),"+f"(d[3]),"+f"(d[4]),"+f"(d[5]),"+f"(d[6]),"+f"(d[7]),"+f"(d[8]),"+f"(d[9]),"+f"(d[10]),"+f"(d[11]),"+f"(d[12]),"+f"(d[13]),"+f"(d[14]),"+f"(d[15]),"+f"(d[16]),"+f"(d[17]),"+f"(d[18]),"+f"(d[19]),"+f"(d[20]),"+f"(d[21]),"+f"(d[22]),"+f"(d[23]),"+f"(d[24]),"+f"(d[25]),"+f"(d[26]),"+f"(d[27]),"+f"(d[28]),"+f"(d[29]),"+f"(d[30]),"+f"(d[31])
    : "r"(a[0]), "r"(a[1]), "r"(a[2]), "r"(a[3]), "l"(desc), "r"(acc));
}

__device__ __forceinline__ void mma16816h(uint32_t* c, const uint32_t* a, uint32_t b0, uint32_t b1) {
  asm("mma.sync.aligned.m16n8k16.row.col.f16.f16.f16.f16 {%0,%1},{%2,%3,%4,%5},{%6,%7},{%0,%1};"
      : "+r"(c[0]), "+r"(c[1]) : "r"(a[0]), "r"(a[1]), "r"(a[2]), "r"(a[3]), "r"(b0), "r"(b1));
}
__device__ __forceinline__ void mma1688h(uint32_t* c, uint32_t a0, uint32_t a1, uint32_t b) {
  asm("mma.sync.aligned.m16n8k8.row.col.f16.f16.f16.f16 {%0,%1},{%2,%3},{%4},{%0,%1};" : "+r"(c[0]), "+r"(c[1]) : "r"(a0), "r"(a1), "r"(b));
}
__device__ __forceinline__ void mma16816f(float* c, const uint32_t* a, uint32_t b) {
  asm("mma.sync.aligned.m16n8k16.row.col.f32.f16.f16.f32 {%0,%1,%2,%3},{%4,%5,%6,%7},{%8,%8},{%0,%1,%2,%3};"
      : "+f"(c[0]), "+f"(c[1]), "+f"(c[2]), "+f"(c[3]) : "r"(a[0]), "r"(a[1]), "r"(a[2]), "r"(a[3]), "r"(b));
}
__device__ __forceinline__ uint32_t hfma2(uint32_t a, uint32_t b, uint32_t c) { uint32_t r; asm("fma.rn.f16x2 %0,%1,%2,%3;" : "=r"(r) : "r"(a), "r"(b), "r"(c)); return r; }
__device__ __forceinline__ uint32_t pack_bf2(float lo, float hi) { uint32_t r; asm("cvt.rn.bf16x2.f32 %0,%1,%2;" : "=r"(r) : "f"(hi), "f"(lo)); return r; }
__device__ __forceinline__ uint32_t pack_h2(float lo, float hi) { uint32_t r; asm("cvt.rn.f16x2.f32 %0,%1,%2;" : "=r"(r) : "f"(hi), "f"(lo)); return r; }
__device__ __forceinline__ float bf_lo(uint32_t w) { return __uint_as_float(w << 16); }
__device__ __forceinline__ float bf_hi(uint32_t w) { return __uint_as_float(w & 0xffff0000u); }
__device__ __forceinline__ uint32_t absmax4(const uint4& v, uint32_t m) {
  return __vmaxu2(__vmaxu2(__vmaxu2(v.x & 0x7fff7fffu, v.y & 0x7fff7fffu), __vmaxu2(v.z & 0x7fff7fffu, v.w & 0x7fff7fffu)), m);
}
__device__ __forceinline__ float pow2_scale(uint32_t mbits, int p) { return __uint_as_float((uint32_t)min(max(253 + p - (int)(mbits >> 7), 2), 252) << 23); }

#define PV 4
constexpr int G_O0 = 8, G_O1 = 4, G_O2 = 0, G_N0 = 5, G_N1 = 4, G_N2 = 4, G_K0 = 5, G_K1 = 3, G_K2 = 1;
__host__ __device__ constexpr bool unit_wg(int kb, int on) {
  return (on >= G_O0 && on < G_O0 + G_N0 && kb < G_K0) || (on >= G_O1 && on < G_O1 + G_N1 && kb < G_K1) || (on >= G_O2 && on < G_O2 + G_N2 && kb < G_K2);
}
__host__ __device__ constexpr bool oct_wg(int on) { return unit_wg(0, on); }
constexpr int G_U1 = G_N0 * G_K0, G_U2 = G_U1 + G_N1 * G_K1, G_U = G_U2 + G_N2 * G_K2;
constexpr int K1_B = 130048, K1_STG = K1_B + 3 * 16384, K1_W = K1_STG + 2 * 16384, K1_BAR = K1_W + 48 * 256, K1_SMEM = K1_BAR + 128;
__host__ __device__ constexpr int frag_index(int ok, int on) {
  int n = 0;
  for (int k = 0; k < 13; k++) for (int o = k; o < 13; o++) { if (k == ok && o == on) return n; if (!unit_wg(k >> 1, o)) n++; }
  return n;
}
constexpr int HU_N = 2 * G_U + frag_index(99, 99);
static_assert(HU_N <= 96, "");
struct FragIdx { int v[13][13]; };
__host__ __device__ constexpr FragIdx make_fi() { FragIdx f = {}; for (int k = 0; k < 13; k++) for (int o = 0; o < 13; o++) f.v[k][o] = frag_index(k, o); return f; }
__host__ __device__ constexpr uint64_t frag_tab(int first) {
  uint64_t t = 0;
  for (int k = 0; k < 13; k++) for (int o = k; o < 13; o++)
    if (!unit_wg(k >> 1, o)) { const int n = frag_index(k, o) - first; if (n >= 0 && n < 8) t |= (uint64_t)(k << 4 | o) << (8 * n); }
  return t;
}
__device__ __forceinline__ int hu_code(int hu) {
  constexpr uint64_t T0 = frag_tab(0), T1 = frag_tab(8), T2 = frag_tab(16), T3 = frag_tab(24);
  const int u = hu >> 1, f = hu - 2 * G_U;
  if (f >= 0) return (int)((f < 8 ? T0 : f < 16 ? T1 : f < 24 ? T2 : T3) >> (8 * (f & 7))) & 255;
  const int u0 = u < G_U1 ? u : u < G_U2 ? u - G_U1 : u - G_U2;
  const int kb = u < G_U1 ? u0 / G_N0 : u < G_U2 ? u0 / G_N1 : u0 / 4, on = u < G_U1 ? G_O0 + u0 % G_N0 : u < G_U2 ? G_O1 + u0 % G_N1 : G_O2 + u0 % 4;
  return (2 * kb + (hu & 1)) << 4 | on;
}

__device__ __forceinline__ void flag_arrive(unsigned* f, int lane) {
  __threadfence(); __syncwarp();
  if (lane == 0) asm volatile("red.release.gpu.global.add.u32 [%0],1;" :: "l"(f) : "memory");
}
__device__ __forceinline__ void flag_wait(const unsigned* f, unsigned n) {
  unsigned v; int it = 0;
  do { asm volatile("ld.acquire.gpu.global.u32 %0,[%1];" : "=r"(v) : "l"(f) : "memory"); if (v < n) __nanosleep(100); } while (v < n && ++it < (1 << 20));
}
__device__ __forceinline__ void mbar_arrive(uint32_t bar) { asm volatile("mbarrier.arrive.shared::cta.b64 _,[%0];" :: "r"(bar) : "memory"); }
__device__ __forceinline__ void mbar_arrive_lane0(uint32_t bar) {
  asm volatile("{.reg .pred p; elect.sync _|p,0xffffffff; @p mbarrier.arrive.shared::cta.b64 _,[%0];}" :: "r"(bar) : "memory");
}

__device__ __forceinline__ void pack_role(const int* __restrict__ idx, uint32_t sbase, int pc) {
  constexpr int CH = 3200 + 32, BUF = 32 * 3328;
  const int tid = threadIdx.x, lane = tid & 31, warp = tid >> 5;
  const uint32_t full = sbase + 2 * BUF, empty = full + 16;
  if (tid == 0) { mbar_init(full, 1); mbar_init(full + 8, 1); mbar_init(empty, 18); mbar_init(empty + 8, 18); asm volatile("fence.proxy.async.shared::cta;" ::: "memory"); }
  __syncthreads();
  auto chunk = [&](int s) { return s * 3200 + (s >> 2) * 288; };
  auto load = [&](int n) {
    const int blk = pc * 16 + n;
    if (lane == 0) mbar_expect(full + (n & 1) * 8, 32 * 3200);
    __syncwarp();
    bulk_g2s(sbase + (n & 1) * BUF + chunk(lane), idx + ((blk >> 5) * 8192 + lane * TH + (blk & 31) * 8) * F_, 3200, full + (n & 1) * 8);
  };
  if (warp == 0) { load(0); load(1); }
  const int l = lane & 7;
  uint32_t rot[8], inc[3];
#pragma unroll
  for (int jj = 0; jj < 8; jj++) rot[jj] = ((l + jj) & 7) * 4;
#pragma unroll
  for (int q = 0; q < 3; q++) inc[q] = (l + 3 * q < 8) << 12 | (l + 3 * q + 1 < 8) << 22 | (q < 2 && l + 3 * q + 2 < 8);
  int loaded = 2;
#pragma unroll 1
  for (int task = warp; task < 288; task += 16) {
    const int n = task / 18, q = (task % 18) * 4 + (lane >> 3), sq = q / 9, k = q % 9;
    if (warp == 0 && n + 1 == loaded && loaded < 16) { mbar_wait(empty + (loaded & 1) * 8, ((loaded >> 1) - 1) & 1); load(loaded); loaded++; }
    mbar_wait(full + (n & 1) * 8, (n >> 1) & 1);
    const uint32_t buf = sbase + (n & 1) * BUF + l * 400, row = buf + chunk(sq * 4);
    auto ld = [&](uint32_t ad) { uint32_t v; asm volatile("ld.shared.u32 %0,[%1];" : "=r"(v) : "r"(ad)); return v; };
    const int blk = pc * 16 + n, half = blk >> 5, col = (blk & 31) * 8 + l;
    const int ks = k == NC - 1 ? 0 : k + 1;
    uint32_t cw[4], sv[8], m[2] = {0, 0};
    { const uint32_t a0 = row + (72 + 2 * ks + (l >> 2)) * 4;
#pragma unroll
      for (int u = 0; u < 8; u++) { sv[u] = ld((a0 ^ ((u >> 2) * 4)) + (u & 3) * 3200); m[u >> 2] |= s_mask(sv[u], l & 3) << (8 * (u & 3)); } }
#pragma unroll
    for (int h = 0; h < 2; h++) { m[h] |= __shfl_xor_sync(0xffffffffu, m[h], 1); m[h] |= __shfl_xor_sync(0xffffffffu, m[h], 2); }
#pragma unroll
    for (int u = 0; u < 4; u++) cw[u] = s_cell(sv[u], l & 3, (m[0] >> (8 * u)) & 255) | s_cell(sv[4 + u], l & 3, (m[1] >> (8 * u)) & 255) << 12;
    if (k == NC - 1) {
      g_scr[I0_OFF + (half * 8 + sq) * TH + col] = make_uint4(cw[0], cw[1], cw[2], cw[3]);
      g_scr[I9_OFF + (half * 8 + sq) * TH + col] = make_uint4(ld(row + 396), ld(row + 3596), ld(row + 6796), ld(row + 9996));
      cw[0] = cw[1] = cw[2] = cw[3] = 0;
    }
    const uint32_t ax = buf + chunk(min(sq + 1, 7) * 4) + (90 + k) * 4;
    const uint32_t yev = ld(buf + ((0x3210 >> (sq * 2 + (sq == 5) * 2)) & 3) * 3200 + (90 + k) * 4);
    uint4* dst = g_scr + IX_OFF + ((half * NC + k) * NS + sq * 4) * TH + col;
#pragma unroll
    for (int u = 0; u < 4; u++) {
      uint32_t e[8];
#pragma unroll
      for (int jj = 0; jj < 8; jj++) e[jj] = ld(row + k * 32 + rot[jj] + u * 3200);
      dst[u * TH] = make_uint4(pk3(e[0], e[1], e[2] + inc[0]), pk3(e[3], e[4], e[5] + inc[1]), pk3(e[6], e[7], ld(ax + u * 3200) + inc[2]),
                               u < 3 ? __byte_perm(cw[u], cw[3], 0x4210 + (u << 12)) : yev);
    }
    mbar_arrive_lane0(empty + (n & 1) * 8);
  }
  (void)CH;
}

__global__ void __launch_bounds__(512, 1)
k_tens(const __grid_constant__ CUtensorMap mapW, const __grid_constant__ CUtensorMap mapL, const __grid_constant__ CUtensorMap mapS,
       const __grid_constant__ CUtensorMap mapT, const __grid_constant__ CUtensorMap mapE, cudaTextureObject_t tex, cudaTextureObject_t texX,
       const int* __restrict__ idx, const __nv_bfloat16* __restrict__ table, const __nv_bfloat16* __restrict__ wp, const __nv_bfloat16* __restrict__ w1, int never) {
  extern __shared__ __align__(1024) uint4 sm[];
  const int tid = threadIdx.x, lane = tid & 31, cta = blockIdx.x;
  const uint32_t sbase = (uint32_t)__cvta_generic_to_shared(sm);
  const int g = lane >> 2, r = lane & 3;
  TS(0, 0);
  asm volatile("griddepcontrol.launch_dependents;");
  if (cta >= 128) { pack_role(idx, sbase, cta - 128); TS(2, 1); return; }
  const uint32_t fullB = sbase + K1_BAR, emptyB = fullB + 24, fullS = fullB + 48, emptyS = fullB + 64, fullE = fullB + 80;
  const int rb = cta & 7, hc = cta >> 3;
  if (tid >= 384) {
    asm volatile("setmaxnreg.dec.sync.aligned.u32 " RAUX ";");
    if (tid < 416) {
      auto load_pair = [&](int p, int st) {
        mbar_expect(fullB + st * 8, 16384);
        asm volatile("cp.async.bulk.tensor.2d.shared::cluster.global.mbarrier::complete_tx::bytes [%0],[%1,{%2,%3}],[%4];"
                     :: "r"(sbase + K1_B + st * 16384), "l"(&mapW), "r"(hc * 32), "r"(QORD(p >> 1) * 512 + (p & 1) * 256), "r"(fullB + st * 8) : "memory");
        p += WPF;
        if (p < 50) bulk_pf(w1 + QORD(p >> 1) * 262144 + (p & 1) * 131072 + cta * 1024, 2048);
      };
      if (tid == 384) {
        for (int q = 0; q < 3; q++) { mbar_init(fullB + q * 8, 1); mbar_init(emptyB + q * 8, 4); }
        for (int q = 0; q < 2; q++) { mbar_init(fullS + q * 8, 4); mbar_init(emptyS + q * 8, 1); }
        mbar_init(fullE, 1);
        asm volatile("fence.proxy.async.shared::cta;" ::: "memory");
        mbar_expect(fullE, 32768);
        for (int q = 0; q < 2; q++)
          asm volatile("cp.async.bulk.tensor.2d.shared::cluster.global.mbarrier::complete_tx::bytes [%0],[%1,{%2,%3}],[%4];"
                       :: "r"(sbase + K1_STG + q * 16384), "l"(&mapE), "r"(q * 64), "r"(rb * 128), "r"(fullE) : "memory");
      }
      __syncwarp();
      asm volatile("bar.arrive 2,192;" ::: "memory");
      if (tid == 384) {
        int st = 0, ph = 1;
#pragma unroll 1
        for (int p = 0; p < 50; p++) {
          mbar_wait(emptyB + st * 8, ph);
          load_pair(p, st);
          if (++st == 3) { st = 0; ph ^= 1; }
        }
      }
    } else if (tid < 448) {
      asm volatile("bar.sync 2,192;" ::: "memory");
      asm volatile("bar.sync 4,288;" ::: "memory");
      flag_arrive(&g_flag[(cta >> 4) * 32], lane);
      if (tid == 416) {
#pragma unroll 1
        for (int n = 0; n < 50; n++) {
          const int quad = QORD(n >> 1), mt = n & 1, v0 = rb * 128 + mt * 64;
          const uint32_t stg = sbase + K1_STG + mt * 16384;
          const uint64_t pol = n < 2 * NEF ? POL_EF : POL_N;
          mbar_wait(fullS + mt * 8, (n >> 1) & 1);
          asm volatile("fence.proxy.async.shared::cta;" ::: "memory");
          if (quad < 18) {
            asm volatile("cp.async.bulk.tensor.4d.global.shared::cta.bulk_group.L2::cache_hint [%0,{%1,%2,%3,%4}],[%5],%6;"
                         :: "l"(&mapL), "r"((quad & 1) * 32), "r"(v0), "r"(quad >> 1), "r"(hc * 4), "r"(stg), "l"(pol) : "memory");
          } else {
#pragma unroll 1
            for (int hh = 0; hh < 2; hh++) {
              const int pq = quad * 2 + hh;
              if (pq < 45) asm volatile("cp.async.bulk.tensor.4d.global.shared::cta.bulk_group.L2::cache_hint [%0,{%1,%2,%3,%4}],[%5],%6;"
                         :: "l"(&mapS), "r"(0), "r"(v0), "r"(pq - 36), "r"(hc * 4), "r"(stg + hh * 8192), "l"(pol) : "memory");
              else asm volatile("cp.async.bulk.tensor.3d.global.shared::cta.bulk_group.L2::cache_hint [%0,{%1,%2,%3}],[%4],%5;"
                         :: "l"(&mapT), "r"(v0 * 2), "r"((pq - 45) * 2), "r"(hc * 4), "r"(stg + hh * 8192), "l"(pol) : "memory");
            }
          }
          asm volatile("cp.async.bulk.commit_group;" ::: "memory");
          asm volatile("cp.async.bulk.wait_group.read 0;" ::: "memory");
          mbar_arrive(emptyS + mt * 8);
        }
        asm volatile("cp.async.bulk.wait_group 0;" ::: "memory");
      }
    }
    return;
  }
  if (tid >= 256) {
    asm volatile("setmaxnreg.inc.sync.aligned.u32 " RPRO ";");
    const int w = (tid >> 5) & 3;
    const int srow = w * 16 + (lane & 7) + ((lane >> 3) & 1) * 8, sc = lane >> 4;
    uint32_t a[2][8][4];
    asm volatile("bar.sync 2,192;" ::: "memory");
    mbar_wait_fast(fullE, 0);
#pragma unroll
    for (int mt = 0; mt < 2; mt++)
#pragma unroll
      for (int ks = 0; ks < 8; ks++)
        asm volatile("ldmatrix.sync.aligned.m8n8.x4.shared.b16 {%0,%1,%2,%3},[%4];"
                     : "=r"(a[mt][ks][0]), "=r"(a[mt][ks][1]), "=r"(a[mt][ks][2]), "=r"(a[mt][ks][3])
                     : "r"(sbase + K1_STG + (ks >> 2) * 16384 + (mt * 64 + srow) * 128 + ((((ks & 3) * 2 + sc) ^ (lane & 7)) * 16)) : "memory");
    asm volatile("bar.sync 5,128;" ::: "memory");
    const uint32_t baseL = sc * 4096 + srow * 64 + ((srow >> 1) & 3) * 16, baseS = sc * 2048 + srow * 32 + ((srow >> 2) & 1) * 16, baseT = sc * 2048 + srow * 16;
    const uint64_t desc0 = (uint64_t)(((sbase + K1_B) & 0x3FFFF) >> 4) | ((uint64_t)(8192 >> 4) << 16) | ((uint64_t)(512 >> 4) << 32) | (2ull << 62);
    float d[2][32];
    auto issue = [&](int x, int mt, int st) {
      uint32_t a7[4];
#pragma unroll
      for (int e = 0; e < 4; e++) { if (PARK) asm volatile("add.u32 %0,%1,%2;" : "=r"(a7[e]) : "r"(a[mt][7][e]), "r"(never)); else a7[e] = a[mt][7][e]; }
      asm volatile("wgmma.fence.sync.aligned;" ::: "memory");
#pragma unroll
      for (int ks = 0; ks < 8; ks++) wgmma_p(d[x], ks < 7 ? a[mt][ks] : a7, desc0 + st * 1024 + ks * 64, ks);
      asm volatile("wgmma.commit_group.sync.aligned;" ::: "memory");
    };
    auto wait_acc = [&](int x) {
      asm volatile("wgmma.wait_group.sync.aligned 0;" ::: "memory");
#pragma unroll
      for (int q = 0; q < 8; q++) asm volatile("" : "+f"(d[x][q * 4]), "+f"(d[x][q * 4 + 1]), "+f"(d[x][q * 4 + 2]), "+f"(d[x][q * 4 + 3]) :: "memory");
    };
    mbar_wait_fast(fullB, 0);
    issue(0, 0, 0);
    int s0 = 0, ph = 0;
#pragma unroll 1
    for (int qn = 0; qn < 25; qn++) {
      const int quad = QORD(qn);
      const int s1 = s0 == 2 ? 0 : s0 + 1, s2 = s1 == 2 ? 0 : s1 + 1, ph1 = ph ^ (s1 == 0), ph2 = ph1 ^ (s2 == 0);
#pragma unroll
      for (int step = 0; step < 4; step++) {
        const int mt = ORD ? step & 1 : step >> 1, h = ORD ? step >> 1 : step & 1, x = step & 1, nx = (step + 1) & 3;
        const bool isL = quad < 18, isS = quad * 2 + h < 45;
        const uint32_t base = (isL ? baseL ^ (h * 32) : (isS ? baseS : baseT) ^ (h * 8192)), xj = (isL || isS) ? 16 : 1024, xc = isL ? 8192 : 4096;
        PT(qn * 16 + step * 4);
        if (h == 0) mbar_wait_fast(emptyS + mt * 8, (qn & 1) ^ 1);
        if (step == (ORD ? 1 : 0)) mbar_wait_fast(fullB + s1 * 8, ph1);
        if (step == 3) mbar_wait_fast(fullB + s2 * 8, qn == 24 ? ph2 ^ 1 : ph2);
        PT(qn * 16 + step * 4 + 1);
        wait_acc(x);
        PT(qn * 16 + step * 4 + 2);
        if (mt) mbar_arrive_lane0(emptyB + (h ? s1 : s0) * 8);
        issue(x ^ 1, ORD ? nx & 1 : nx >> 1, step == 3 ? s2 : (ORD ? nx >> 1 : nx & 1) ? s1 : s0);
        PT(qn * 16 + step * 4 + 3);
#pragma unroll
        for (int e4 = 0; e4 < 4; e4++) {
          const float* e = d[x] + e4 * 8;
          asm volatile("stmatrix.sync.aligned.m8n8.x4.shared.b16 [%0],{%1,%2,%3,%4};"
                       :: "r"(sbase + K1_STG + mt * 16384 + (base ^ ((e4 >> 1) * xj) ^ ((e4 & 1) * xc))),
                          "r"(pack_bf2(e[0], e[1])), "r"(pack_bf2(e[2], e[3])), "r"(pack_bf2(e[4], e[5])), "r"(pack_bf2(e[6], e[7])) : "memory");
        }
        if (h) { __syncwarp(); mbar_arrive_lane0(fullS + mt * 8); }
      }
      s0 = s2; ph = ph2;
    }
    asm volatile("wgmma.wait_group.sync.aligned 0;" ::: "memory");
    return;
  }
  asm volatile("setmaxnreg.inc.sync.aligned.u32 " RPNN ";");
  const int slice = cta & 15;
  const int range = (cta >> 4) * 8 + (tid >> 5);
  uint4 iv[4], trow[4]; uint32_t ix;
  uint2 wrow[10];
#pragma unroll
  for (int q = 0; q < 4; q++) trow[q] = *(const uint4*)(table + min(tid + q * 256, V_ - 1) * D_ + slice * 8);
#pragma unroll
  for (int q = 0; q < 10; q++) wrow[q] = ((const uint2*)wp)[min(tid + q * 256, 2499)];
  uint32_t ri[8][6], rx[2];
  {
    const int* ip = idx + (range * 256 + slice * 16) * F_;
    const int* p0 = ip + ((lane >> 3) & 1) * F_ + (lane >> 4) * 8 + (lane & 7);
#pragma unroll
    for (int t = 0; t < 8; t++)
#pragma unroll
      for (int kb = 0; kb < 6; kb++) asm volatile("ld.global.nc.u32 %0,[%1];" : "=r"(ri[t][kb]) : "l"(p0 + t * 2 * F_ + kb * 16));
#pragma unroll
    for (int u = 0; u < 2; u++) asm volatile("ld.global.nc.u32 %0,[%1];" : "=r"(rx[u]) : "l"(ip + (u * 8 + g) * F_ + 96 + r));
  }
  SCHED_FENCE(never, 200);
  uint32_t me = 0, mw = 0;
#pragma unroll
  for (int q = 0; q < 4; q++) me = absmax4(trow[q], me);
#pragma unroll
  for (int q = 0; q < 10; q++) {
    mw = __vmaxu2(__vmaxu2(wrow[q].x & 0x7fff7fffu, wrow[q].y & 0x7fff7fffu), mw);
    const int e = min(tid + q * 256, 2499), row = e / 25;
    asm volatile("st.shared.v2.u32 [%0],{%1,%2};" :: "r"(sbase + (e + row) * 8), "r"(wrow[q].x), "r"(wrow[q].y) : "memory");
    if (e - row * 25 == 24) asm volatile("st.shared.v2.u32 [%0],{%1,%2};" :: "r"(sbase + (e + row) * 8 + 8), "r"(wrow[q].x), "r"(wrow[q].y) : "memory");
  }
  me = __reduce_max_sync(0xffffffffu, max(me & 0xffff, me >> 16));
  mw = __reduce_max_sync(0xffffffffu, max(mw & 0xffff, mw >> 16));
  uint32_t* sred = (uint32_t*)((char*)sm + 128000);
  if (lane == 0) sred[tid >> 5] = me | mw << 16;
  TS(3, 0);
  asm volatile("bar.sync 1,256;" ::: "memory");
  { uint32_t m = 0;
#pragma unroll
    for (int q = 0; q < 8; q++) m = __vmaxu2(m, sred[q]);
    me = m & 0xffff; mw = m >> 16; }
  const float se = pow2_scale(me, 3), sW = pow2_scale(mw, -2);
  TS(3, 1);
  auto put_rows = [&](int q, bool on) {
    const uint4 t = trow[q];
    const uint4 hv = make_uint4(pack_h2(bf_lo(t.x) * se, bf_hi(t.x) * se), pack_h2(bf_lo(t.y) * se, bf_hi(t.y) * se),
                                pack_h2(bf_lo(t.z) * se, bf_hi(t.z) * se), pack_h2(bf_lo(t.w) * se, bf_hi(t.w) * se));
    if (on)
#pragma unroll
      for (int s = 0; s < 8; s++) sts128(sbase + (tid + q * 256) * 128 + ((s + lane) & 7) * 16, hv);
  };
#pragma unroll 1
  for (int it = 0; it < 3; it++) {
    const int hu = ((tid >> 5) * 3 + it) * 4, code = hu_code(min(hu + (lane >> 3), HU_N - 1)), ok = code >> 4, on = code & 15;
    uint32_t x[4], y[4];
    asm volatile("ldmatrix.sync.aligned.m8n8.x4.shared.b16 {%0,%1,%2,%3},[%4];" : "=r"(x[0]), "=r"(x[1]), "=r"(x[2]), "=r"(x[3])
                 : "r"(sbase + (on * 8 + (lane & (on == 12 ? 3 : 7))) * 208 + ok * 16) : "memory");
    asm volatile("ldmatrix.sync.aligned.m8n8.x4.trans.shared.b16 {%0,%1,%2,%3},[%4];" : "=r"(y[0]), "=r"(y[1]), "=r"(y[2]), "=r"(y[3])
                 : "r"(sbase + (ok * 8 + (lane & (ok == 12 ? 3 : 7))) * 208 + on * 16) : "memory");
    const uint32_t lo = __ballot_sync(0xffffffffu, ok > on), dg = __ballot_sync(0xffffffffu, ok >= on);
#pragma unroll
    for (int q = 0; q < 4; q++) {
      const float m0 = (lo >> (8 * q)) & 1 ? 0.f : sW, m1 = (dg >> (8 * q)) & 1 ? 0.f : sW;
      asm volatile("st.shared.u32 [%0],%1;" :: "r"(sbase + K1_W + (hu + q) * 128 + lane * 4),
                   "r"(pack_h2(fmaf(bf_lo(x[q]), m0, bf_lo(y[q]) * m1), fmaf(bf_hi(x[q]), m0, bf_hi(y[q]) * m1))) : "memory");
    }
  }
  put_rows(1, true); put_rows(2, true); put_rows(3, tid + 768 < V_);
  TS(3, 2);
  asm volatile("fence.proxy.async.shared::cta;" ::: "memory");
  asm volatile("bar.sync 1,256;" ::: "memory");
  put_rows(0, true);
  uint32_t bf[HU_N - 2 * G_U];
#pragma unroll
  for (int q = 0; q < HU_N - 2 * G_U; q++) asm volatile("ld.shared.u32 %0,[%1];" : "=r"(bf[q]) : "r"(sbase + K1_W + (2 * G_U + q) * 128 + lane * 4));
  const float unscale = __uint_as_float(0x7f000000u - __float_as_uint(se)), unscale2 = __uint_as_float(0x7f000000u - __float_as_uint(sW));
  TS(3, 3);
  const int px = range * 16 * 136;
#pragma unroll
  for (int q = 0; q < 4; q++) {
    iv[q] = make_uint4(pk3(ri[2 * q][0], ri[2 * q][1], ri[2 * q][2]), pk3(ri[2 * q][3], ri[2 * q][4], ri[2 * q][5]),
                       pk3(ri[2 * q + 1][0], ri[2 * q + 1][1], ri[2 * q + 1][2]), pk3(ri[2 * q + 1][3], ri[2 * q + 1][4], ri[2 * q + 1][5]));
    g_scr[PX_OFF + px + slice * 136 + q * 32 + lane] = iv[q];
  }
  ix = pk3(rx[0], rx[1], 0);
  ((uint32_t*)(g_scr + PX_OFF + px + slice * 136 + 128))[lane] = ix;
  asm volatile("bar.arrive 4,288;" ::: "memory");
  asm volatile("bar.sync 1,256;" ::: "memory");
  TS(0, 1);
  const uint32_t lc = (lane & 7) * 16;
  const uint64_t wdesc = (uint64_t)(((sbase + K1_W) & 0x3FFFF) >> 4) | ((uint64_t)(128 >> 4) << 16) | ((uint64_t)(256 >> 4) << 32);
  uint32_t a[2][6][4], d[2][26], ex[4] = {}, s[4] = {};
  float red[4] = {0.f, 0.f, 0.f, 0.f};
  auto ldsm = [&](uint32_t* o, uint32_t sh) {
    asm volatile("ldmatrix.sync.aligned.m8n8.x4.trans.shared.b16 {%0,%1,%2,%3},[%4];"
                 : "=r"(o[0]), "=r"(o[1]), "=r"(o[2]), "=r"(o[3]) : "r"(sbase + ((sh & 0x1ff80) | lc)));
  };
  auto gather = [&](int t) {
    const int x = t & 1;
    const uint4 v = iv[(t >> 1) & 3];
#pragma unroll
    for (int kb = 0; kb < 6; kb++) {
      const uint32_t ww = x ? (kb < 3 ? v.z : v.w) : (kb < 3 ? v.x : v.y);
      ldsm(a[x][kb], kb % 3 == 0 ? ww : kb % 3 == 1 ? ww >> 10 : __funnelshift_l(ww, ww, 12));
    }
  };
  auto issue = [&](int x) {
    asm volatile("wgmma.fence.sync.aligned;" ::: "memory");
#pragma unroll
    for (int kb = 0; kb < 6; kb++) {
      if (kb < G_K0) wgmma_h<G_N0 * 8>(d[x] + G_O0 * 2, a[x][kb], wdesc + kb * G_N0 * 16, kb);
      if (kb < G_K1) wgmma_h<G_N1 * 8>(d[x] + G_O1 * 2, a[x][kb], wdesc + (G_U1 + kb * G_N1) * 16, kb);
      if (kb < G_K2) wgmma_h<32>(d[x] + G_O2 * 2, a[x][kb], wdesc + (G_U2 + kb * G_N2) * 16, kb);
    }
    asm volatile("wgmma.commit_group.sync.aligned;" ::: "memory");
  };
  auto hmma_part = [&](int t) {
    constexpr FragIdx FI = make_fi();
    const int x = t & 1;
#pragma unroll
    for (int o = 0; o < 13; o++) {
      if (oct_wg(o)) asm volatile("" : "+r"(d[x][o * 2]), "+r"(d[x][o * 2 + 1]) :: "memory"); else d[x][o * 2] = d[x][o * 2 + 1] = 0;
    }
#pragma unroll
    for (int kb = 0; kb < 6; kb++)
#pragma unroll
      for (int o = 2 * kb + 1; o < 13; o++)
        if (!unit_wg(kb, o)) mma16816h(d[x] + o * 2, a[x][kb], bf[FI.v[2 * kb][o]], bf[FI.v[2 * kb + 1][o]]);
#pragma unroll
    for (int q = 0; q < 6; q++) if (!unit_wg(q, 2 * q)) mma1688h(d[x] + q * 4, a[x][q][0], a[x][q][1], bf[FI.v[2 * q][2 * q]]);
    mma1688h(d[x] + 24, r < 2 ? ex[t & 3] : 0u, r < 2 ? 0u : ex[t & 3], bf[FI.v[12][12]]);
  };
  auto dot_part = [&](int t) {
    const int x = t & 1;
    const uint32_t pe = hfma2(r < 2 ? d[x][24] : d[x][25], ex[t & 3], 0u);
    s[0] = r < 2 ? pe : 0u; s[1] = r < 2 ? 0u : pe; s[2] = s[3] = 0;
#pragma unroll
    for (int q = 0; q < 6; q++)
#pragma unroll
      for (int e = 0; e < 4; e++) s[e] = hfma2(d[x][q * 4 + e], a[x][q][e], s[e]);
  };
  float* outp = g_partP + slice * B_ + range * 256 + r * 4 + ((lane >> 3) & 1) * 2 + (lane >> 4);
  gather(0); issue(0); ldsm(ex, ix); gather(1);
  asm volatile("wgmma.wait_group.sync.aligned 0;" ::: "memory");
  hmma_part(0);
  flag_wait(&g_flag[(cta >> 4) * 32], 16);
  TS(4, 1);
  int cur = slice;
#pragma unroll 1
  for (int n = 0; n < 16; n++) {
    const int nxt = (n + (n >= slice)) & 15;
    const int pn = PX_OFF + px + nxt * 136 + lane;
#pragma unroll
    for (int t = 0; t < 8; t++) {
      issue((t & 1) ^ 1);
      SCHED_FENCE(never, t * 4);
      if (t == 0) { iv[3] = ldtex(tex, PX_OFF + px + cur * 136 + lane + 96); iv[0] = ldtex(tex, pn); }
      if (t == 2) iv[1] = ldtex(tex, pn + 32);
      if (t == 4) { ix = ldtex(texX, (px + nxt * 136 + 128) * 4 + lane).x; iv[2] = ldtex(tex, pn + 64); }
      dot_part(t);
      SCHED_FENCE(never, t * 4 + 1);
      if (t == 3) ldsm(ex, ix >> 10);
      if (t == 7) ldsm(ex, ix);
      gather(t + 2);
      asm volatile("wgmma.wait_group.sync.aligned 0;" ::: "memory");
      SCHED_FENCE(never, t * 4 + 2);
      mma16816f(red, s, g == t ? 0x3c003c00u : 0u);
      hmma_part(t + 1);
      SCHED_FENCE(never, t * 4 + 3);
    }
    {
      const bool u16 = lane & 16, u8 = lane & 8;
      float p0 = (u16 ? red[2] : red[0]) + __shfl_xor_sync(0xffffffffu, u16 ? red[0] : red[2], 16);
      float p1 = (u16 ? red[3] : red[1]) + __shfl_xor_sync(0xffffffffu, u16 ? red[1] : red[3], 16);
      float q0 = (u8 ? p1 : p0) + __shfl_xor_sync(0xffffffffu, u8 ? p0 : p1, 8);
      q0 += __shfl_xor_sync(0xffffffffu, q0, 4);
      if (!(lane & 4)) outp[cur * 16] = q0 * unscale * unscale * unscale2;
      red[0] = red[1] = red[2] = red[3] = 0.f;
      cur = nxt;
    }
  }
  TS(0, 2);
}

constexpr int SM_U = 130048, SM_BAR = SM_U + 3 * 32032, DEEP_SMEM = SM_BAR + 128 + 4096;

__device__ __forceinline__ void arrive_both(uint32_t bar, int lane) {
  asm volatile("{.reg .pred p; .reg .u32 a; setp.lt.u32 p,%1,2; mapa.shared::cluster.u32 a,%0,%1;\n"
               "@p mbarrier.arrive.shared::cluster.b64 _,[a];}" :: "r"(bar), "r"(lane) : "memory");
}
__device__ __forceinline__ void bulk_mc(uint32_t dst, const void* src, uint32_t bytes, uint32_t bar, uint64_t pol) {
  asm volatile("cp.async.bulk.shared::cluster.global.mbarrier::complete_tx::bytes.multicast::cluster.L2::cache_hint [%0],[%1],%2,[%3],%4,%5;"
               :: "r"(dst), "l"(src), "r"(bytes), "r"(bar), "h"((unsigned short)3), "l"(pol) : "memory");
}

__global__ void __cluster_dims__(2, 1, 1) __launch_bounds__(TH + 128, 1)
k_deep(cudaTextureObject_t tex, const __nv_bfloat16* __restrict__ b1, const __nv_bfloat16* __restrict__ w2, int never) {
  extern __shared__ __align__(1024) uint4 sm[];
  constexpr int PF = DPF, DEPTH = DDEPTH, NW = TH / 32;
  static_assert(YD == 4, "");
  const int tid = threadIdx.x;
  const int c = blockIdx.x >> 1, half = blockIdx.x & 1;
  const uint32_t sbase = (uint32_t)__cvta_generic_to_shared(sm);
  const uint32_t fullL = sbase + SM_BAR, fullU = fullL + 8, emptyL = fullL + 16, emptyU = fullL + 24;
  TS(1, 0);
  if (tid == 0) {
    mbar_init(fullL, 1); mbar_init(fullU, 1); mbar_init(emptyL, 2 * NW); mbar_init(emptyU, 2 * NW);
    asm volatile("fence.mbarrier_init.release.cluster;" ::: "memory");
  }
  __syncwarp();
  asm volatile("barrier.cluster.arrive.relaxed.aligned; barrier.cluster.wait.aligned;" ::: "memory");
  if (__builtin_expect(tid >= TH, 1)) {
    asm volatile("setmaxnreg.dec.sync.aligned.u32 24;");
    if (tid == TH) {
      const char* base = (const char*)g_scr;
      uint32_t oL = (PL_OFF + c * NC * 8000) * 16u + half * 64000, oS = (PS_OFF + c * NC * 2000) * 16u + half * 16000;
      uint32_t oT = (PT_OFF + c * 10 * 1024) * 16u + half * 8000, oI = (IX_OFF + half * NC * 8192 + c * 128) * 16u;
      uint32_t t0 = clock();
      mbar_expect(fullU, 96000);
#pragma unroll 1
      for (int m = 0; m < 3; m++) bulk_mc(sbase + SM_U + m * 32032 + half * 16000, base + oS, 16000, fullU, m == 2 ? POL_EF : POL_N);
      bulk_pf(base + oI, 2048); bulk_pf(base + oT, 8000);
      for (int k = 1; k < NC; k++) bulk_pf(base + oI + k * 131072, 2048);
      mbar_expect(fullL, 128000);
      sleep_until(t0, (c & 3) * STAG);
      bulk_mc(sbase + half * 64000, base + oL, 64000, fullL, POL_EF);
#pragma unroll 1
      for (int k = 0; k + 1 < NC; k++) {
        oL += 128000; oS += 32000; oT += 16384; oI += 131072;
        mbar_wait(fullL, k & 1);
        t0 = clock();
        bulk_pf(base + oS, 16000);
        mbar_wait(emptyU, k & 1);
        mbar_expect(fullU, 96000 + 8192);
        { const uint32_t oW = (IX_OFF + (half * NC + min(k + 2, NC - 1)) * 8192 + ((c + (c >> 4) * 5) & 15) * 512) * 16u;
          bulk_g2s(sbase + SM_BAR + 128, base + oW, 4096, fullU); bulk_g2s(sbase + SM_BAR + 128, base + oW + 4096, 4096, fullU); }
#pragma unroll 1
        for (int q = 0; q < 8; q++) {
          sleep_until(t0, q * PACE);
          bulk_pf(base + oL + q * 8000, 8000);
          if (q >= 2) bulk_mc(sbase + SM_U + ((q - 2) >> 1) * 32032 + half * 16000 + (q & 1) * 8000, base + oS + (q & 1) * 8000, 8000, fullU, q >= 6 ? POL_EF : POL_N);
        }
        bulk_pf(base + oT, 8000);
        mbar_expect(fullL, 128000);
        mbar_wait(emptyL, k & 1);
        bulk_mc(sbase + half * 64000, base + oL, 64000, fullL, POL_EF);
      }
      bulk_pf(base + oT + 16384, 8000);
      bulk_pf(base + (I9_OFF + half * 2048 + c * 32) * 16u, 512);
    }
    return;
  }
  asm volatile("setmaxnreg.inc.sync.aligned.u32 240;");
  const int lane = tid & 31;
  const int tbase = PT_OFF + c * 10 * 1024;
  const int ibase = IX_OFF + half * NC * 8192 + tid;
  const uint32_t lc = (tid & 7) << 4;
  uint4 acc[NS], wq[PF], x[DEPTH], y[YD], ye;
  uint32_t sw[NS] = {};
  auto sget = [&](int s) { return (s & 3) == 3 ? __byte_perm(__byte_perm(sw[s - 3], sw[s - 2], 0x0073), sw[s - 1], 0x0710) : sw[s]; };
  auto sa0 = [&](uint32_t v) { return sbase + SM_U + (((v << 5) & 0x1ffe0) | ((lc >> 2) & 16)); };
  auto sa1 = [&](uint32_t v) { return sbase + SM_U + (((v >> 7) & 0x1ffe0) | ((~lc >> 2) & 16)); };
  {
    uint4 i0[8];
#pragma unroll
    for (int q = 0; q < 8; q++) i0[q] = ldtex(tex, I0_OFF + (half * 8 + q) * TH + tid);
#pragma unroll
    for (int i = 0; i < PF; i++) wq[i] = ldtex(tex, ibase + i * TH);
    auto wd = [&](int k) { return (k & 3) == 0 ? i0[k >> 2].x : (k & 3) == 1 ? i0[k >> 2].y : (k & 3) == 2 ? i0[k >> 2].z : i0[k >> 2].w; };
    mbar_wait_fast(fullU, 0);
    TS(1, 1);
#pragma unroll
    for (int s = 0; s < NS; s++) acc[s] = add4(lds128(sa0(wd(s))), lds128(sa1(wd(s))));
    arrive_both(emptyU, lane);
  }
#pragma unroll 1
  for (int k = 0; k < NC; k++) {
    const int ti = ibase + k * 8192;
    const int tb = tbase + k * 1024;
    const bool more = k + 1 < NC;
    TR(k * 4);
    mbar_wait_fast(fullL, k & 1);
    TR(k * 4 + 2);
    uint4 w, cc; uint32_t yc, yn;
    constexpr int TL = NS * 8, TT = TL + NS * 2;
#pragma unroll
    for (int t = 0; t < TT + DEPTH; t += 2) {
      if (t == TL + DEPTH && !more) break;
      if (t >= DEPTH) {
        const int u = t - DEPTH;
        uint4 p = add4(x[u % DEPTH], x[(u + 1) % DEPTH]);
        if (u < TL) {
          const int s = u >> 3, j = u & 7;
          if (j == 0) {
            cc = s >= YD ? add4(y[s % YD], p) : p;
            if (s + YD < NS) y[s % YD] = ldtex(tex, tb | (yc & 1023));
          } else cc = add4(cc, p);
          if (j == 6) acc[s] = add4(acc[s], cc);
        } else {
          const int s = (u - TL) >> 1;
          acc[s] = add4(acc[s], p);
        }
      }
      if (DEPTH == 8 && (t & 7) == 2) yc = yn;
      if (t < TL) {
        const int s = t >> 3, j = t & 7;
        if (j == 0) {
          w = wq[s % PF]; wq[s % PF] = ldtex(tex, ti + (s + PF) * TH);
          yn = __funnelshift_l(w.z, w.z, 5); if (DEPTH < 8) yc = yn;
          if ((s & 3) != 3) asm volatile("add.u32 %0,%1,%2;" : "=r"(sw[s]) : "r"(w.w), "r"(never));
          if (ye_of(s - YD) >= 0) acc[ye_of(s - YD) & 3] = add4(acc[ye_of(s - YD) & 3], ye);
          if (ye_of(s) >= 0) ye = ldtex(tex, tb | w.w);
        }
#pragma unroll
        for (int jj = j; jj < j + 2; jj++) {
          const uint32_t ww = jj < 3 ? w.x : jj < 6 ? w.y : w.z;
          const uint32_t sh = jj % 3 == 0 ? ww : jj % 3 == 1 ? ww >> 10 : __funnelshift_l(ww, ww, 12);
          x[(t + jj - j) % DEPTH] = lds128(sbase + ((sh & 0x1ff80) | lc) + jj * 16 - 128);
        }
      } else if (t < TT) {
        const int s = (t - TL) >> 1;
        if (s == 0) { arrive_both(emptyL, more ? lane : 9); TR(k * 4 + 3); mbar_wait_fast(fullU, (more ? k + 1 : k) & 1); }
        const uint32_t sv = sget(s);
        x[t % DEPTH] = lds128(sa0(sv));
        x[(t + 1) % DEPTH] = lds128(sa1(sv));
      } else if (t == TT) arrive_both(emptyU, k + 2 < NC ? lane : 9);
      if ((t & (FENCE_N - 1)) == FENCE_N - 2) SCHED_FENCE(never, t);
    }
  }
  TS(1, 2);
  uint4 i9 = ldtex(tex, I9_OFF + half * 2048 + tid), i9n = ldtex(tex, I9_OFF + half * 2048 + TH + tid);
  const uint4 b1v = *(const uint4*)(b1 + c * 8), w2v = *(const uint4*)(w2 + c * 8);
  asm volatile("bar.sync 1,%0;" :: "n"(TH) : "memory");
#pragma unroll
  for (int s = 0; s < NS; s++) sts128(sbase + (s * TH + tid) * 16, acc[s]);
  const int t9 = tbase + 9 * 1024;
  y[0] = ldtex(tex, t9 | i9.x); y[1] = ldtex(tex, t9 | i9.y); y[2] = ldtex(tex, t9 | i9.z); y[3] = ldtex(tex, t9 | i9.w);
  float bb[8], hw[8];
  {
    const uint32_t bw[4] = {b1v.x, b1v.y, b1v.z, b1v.w}, ww[4] = {w2v.x, w2v.y, w2v.z, w2v.w};
#pragma unroll
    for (int k = 0; k < 8; k++) {
      bb[k] = __uint_as_float((k & 1) ? (bw[k >> 1] & 0xffff0000u) : (bw[k >> 1] << 16));
      hw[k] = 0.5f * __uint_as_float((k & 1) ? (ww[k >> 1] & 0xffff0000u) : (ww[k >> 1] << 16));
    }
  }
  float* outp = g_partD + c * B_ + half * 8192 + tid;
#pragma unroll 1
  for (int q = 0; q < NS / 4; q++) {
    uint4 z[4];
#pragma unroll
    for (int s = 0; s < 4; s++) z[s] = add4(lds128(sbase + ((q * 4 + s) * TH + tid) * 16), y[s]);
    y[0] = ldtex(tex, t9 | i9n.x); y[1] = ldtex(tex, t9 | i9n.y); y[2] = ldtex(tex, t9 | i9n.z); y[3] = ldtex(tex, t9 | i9n.w);
    i9n = ldtex(tex, I9_OFF + half * 2048 + min(q + 2, NS / 4 - 1) * TH + tid);
#pragma unroll
    for (int s = 0; s < 4; s++) {
      const uint32_t a[4] = {z[s].x, z[s].y, z[s].z, z[s].w};
      float r0 = 0.f, r1 = 0.f;
#pragma unroll
      for (int k = 0; k < 8; k++) {
        float xv = __uint_as_float((k & 1) ? (a[k >> 1] & 0xffff0000u) : (a[k >> 1] << 16)) + bb[k];
        float u = xv * fmaf(xv * xv, 0.7978845608028654f * 0.044715f, 0.7978845608028654f);
        float th; asm("tanh.approx.f32 %0,%1;" : "=f"(th) : "f"(u));
        float hx = xv * hw[k];
        r0 = fmaf(hx, th, r0); r1 += hx;
      }
      outp[(q * 4 + s) * TH] = r0 + r1;
    }
  }
  TS(1, 3);
}

__global__ void k_final(const __nv_bfloat16* __restrict__ b2, __nv_bfloat16* __restrict__ out) {
  __shared__ float red[4][32];
  int lane = threadIdx.x & 31, q = threadIdx.x >> 5, b = blockIdx.x * 32 + lane;
  float s = 0;
#pragma unroll
  for (int k = 0; k < 16; k++) s += g_partD[(q * 16 + k) * B_ + b];
#pragma unroll
  for (int k = 0; k < 4; k++) s += g_partP[(q * 4 + k) * B_ + b];
  if (blockIdx.x == 0 && threadIdx.x < 8) g_flag[threadIdx.x * 32] = 0;
  red[q][lane] = s;
  __syncthreads();
  if (q == 0) out[b] = __float2bfloat16(red[0][lane] + red[1][lane] + red[2][lane] + red[3][lane] + __bfloat162float(b2[0]));
}

}

extern "C" void kernel_launch(void* const* d_in, const int* in_sizes, int n_in, void* d_out, int out_size) {
  const int* idx = (const int*)d_in[0];
  const __nv_bfloat16* table = (const __nv_bfloat16*)d_in[1];
  const __nv_bfloat16* wp = (const __nv_bfloat16*)d_in[2];
  const __nv_bfloat16* w1 = (const __nv_bfloat16*)d_in[3];
  const __nv_bfloat16* b1 = (const __nv_bfloat16*)d_in[4];
  const __nv_bfloat16* w2 = (const __nv_bfloat16*)d_in[5];
  const __nv_bfloat16* b2 = (const __nv_bfloat16*)d_in[6];
  static cudaTextureObject_t texScr = 0, texG = 0;
  static CUtensorMap mapW, mapL, mapS, mapT, mapE;
  static const void *c_tab = nullptr, *c_w1 = nullptr;
  if (c_tab != table || c_w1 != w1) {
    c_tab = table; c_w1 = w1;
    char* scr = nullptr; cudaGetSymbolAddress((void**)&scr, g_scr);
    auto mk_tex = [](const void* p, size_t bytes, cudaChannelFormatDesc d) {
      cudaResourceDesc rd = {}; rd.resType = cudaResourceTypeLinear; rd.res.linear.devPtr = (void*)p; rd.res.linear.desc = d; rd.res.linear.sizeInBytes = bytes;
      cudaTextureDesc td = {}; td.readMode = cudaReadModeElementType;
      cudaTextureObject_t t = 0; cudaCreateTextureObject(&t, &rd, &td, nullptr); return t;
    };
    if (!texScr) {
      texScr = mk_tex(scr, (size_t)SCR_N * 16, cudaCreateChannelDesc<uint4>());
      texG = mk_tex(scr + (size_t)PX_OFF * 16, (size_t)(SCR_N - PX_OFF) * 16, cudaCreateChannelDesc<unsigned>());
    }
    typedef CUresult (*EncFn)(CUtensorMap*, CUtensorMapDataType, cuuint32_t, void*, const cuuint64_t*, const cuuint64_t*, const cuuint32_t*,
                              const cuuint32_t*, CUtensorMapInterleave, CUtensorMapSwizzle, CUtensorMapL2promotion, CUtensorMapFloatOOBfill);
    EncFn enc = nullptr; cudaDriverEntryPointQueryResult qr;
    cudaGetDriverEntryPoint("cuTensorMapEncodeTiled", (void**)&enc, cudaEnableDefault, &qr);
    const cuuint32_t ones[4] = {1, 1, 1, 1};
    auto mk = [&](CUtensorMap* m, CUtensorMapDataType dt, int rank, void* p, const cuuint64_t* dim, const cuuint64_t* str, const cuuint32_t* box, CUtensorMapSwizzle sw) {
      enc(m, dt, rank, p, dim, str, box, ones, CU_TENSOR_MAP_INTERLEAVE_NONE, sw, CU_TENSOR_MAP_L2_PROMOTION_NONE, CU_TENSOR_MAP_FLOAT_OOB_FILL_NONE);
    };
    { cuuint64_t dim[2] = {H_, F_ * D_}, str[1] = {H_ * 2}; cuuint32_t box[2] = {32, 256};
      mk(&mapW, CU_TENSOR_MAP_DATA_TYPE_BFLOAT16, 2, (void*)w1, dim, str, box, CU_TENSOR_MAP_SWIZZLE_64B); }
    { cuuint64_t dim[4] = {64, V_, NC, 64}, str[3] = {128, 128000, 128000 * NC}; cuuint32_t box[4] = {32, 64, 1, 4};
      mk(&mapL, CU_TENSOR_MAP_DATA_TYPE_BFLOAT16, 4, scr + (size_t)PL_OFF * 16, dim, str, box, CU_TENSOR_MAP_SWIZZLE_64B); }
    { cuuint64_t dim[4] = {16, V_, NC, 64}, str[3] = {32, 32000, 32000 * NC}; cuuint32_t box[4] = {16, 64, 1, 4};
      mk(&mapS, CU_TENSOR_MAP_DATA_TYPE_BFLOAT16, 4, scr + (size_t)PS_OFF * 16, dim, str, box, CU_TENSOR_MAP_SWIZZLE_32B); }
    { cuuint64_t dim[3] = {2048, 10, 64}, str[2] = {16384, 163840}; cuuint32_t box[3] = {128, 2, 4};
      mk(&mapT, CU_TENSOR_MAP_DATA_TYPE_UINT64, 3, scr + (size_t)PT_OFF * 16, dim, str, box, CU_TENSOR_MAP_SWIZZLE_NONE); }
    { cuuint64_t dim[2] = {D_, V_}, str[1] = {D_ * 2}; cuuint32_t box[2] = {64, 128};
      mk(&mapE, CU_TENSOR_MAP_DATA_TYPE_BFLOAT16, 2, (void*)table, dim, str, box, CU_TENSOR_MAP_SWIZZLE_128B); }
    cudaFuncSetAttribute(k_deep, cudaFuncAttributeMaxDynamicSharedMemorySize, DEEP_SMEM);
    cudaFuncSetAttribute(k_tens, cudaFuncAttributeMaxDynamicSharedMemorySize, K1_SMEM);
  }
  k_tens<<<132, 512, K1_SMEM>>>(mapW, mapL, mapS, mapT, mapE, texScr, texG, idx, table, wp, w1, 0);
  k_deep<<<128, TH + 128, DEEP_SMEM>>>(texScr, b1, w2, 0);
  k_final<<<B_ / 32, 128>>>(b2, (__nv_bfloat16*)d_out);
}
```

```cpp
#include <cuda_runtime.h>
#include <cuda_bf16.h>
#include <cuda_fp16.h>
#include <stdint.h>
#include <cuda.h>

namespace {

constexpr int B_ = 16384, F_ = 100, D_ = 128, V_ = 1000, H_ = 512;
constexpr int NC = 9;
constexpr int PT_OFF = 0;
constexpr int PL_OFF = 64 * 10 * 1024;
constexpr int PS_OFF = PL_OFF + 64 * NC * 8000;
constexpr int IX_OFF = PS_OFF + 64 * NC * 2000;
constexpr int I0_OFF = IX_OFF + 2 * NC * 8192;
constexpr int I9_OFF = I0_OFF + 4096;
constexpr int PX_OFF = I9_OFF + 4096;
constexpr int SCR_N = PX_OFF + 64 * 16 * 136;
static_assert(PX_OFF % 32 == 0, "");

__device__ __align__(1024) uint4 g_scr[SCR_N];
__device__ float g_partD[64 * B_];
__device__ float g_partP[16 * B_];
__device__ unsigned g_flag[16 * 32];

#define TS(k, i)
#define TR(slot)
#define PT(slot)

constexpr uint64_t POL_EF = 0x12F0000000000000ull, POL_N = 0x1000000000000000ull;
__device__ __forceinline__ uint32_t addbf2(uint32_t a, uint32_t b) { uint32_t r; asm("add.rn.bf16x2 %0,%1,%2;" : "=r"(r) : "r"(a), "r"(b)); return r; }
__device__ __forceinline__ uint4 add4(const uint4& a, const uint4& b) { return make_uint4(addbf2(a.x, b.x), addbf2(a.y, b.y), addbf2(a.z, b.z), addbf2(a.w, b.w)); }
__device__ __forceinline__ void acc4(uint4& a, const uint4& b, int never) {
  asm("{.reg .pred p; setp.eq.s32 p,%8,0;\n"
      "@p add.rn.bf16x2 %0,%0,%4; @p add.rn.bf16x2 %1,%1,%5; @p add.rn.bf16x2 %2,%2,%6; @p add.rn.bf16x2 %3,%3,%7;}"
      : "+r"(a.x), "+r"(a.y), "+r"(a.z), "+r"(a.w) : "r"(b.x), "r"(b.y), "r"(b.z), "r"(b.w), "r"(never));
}
__device__ __forceinline__ uint4 ldtex(cudaTextureObject_t t, int i) {
  uint4 v; asm volatile("tex.1d.v4.u32.s32 {%0,%1,%2,%3},[%4,{%5}];" : "=r"(v.x), "=r"(v.y), "=r"(v.z), "=r"(v.w) : "l"(t), "r"(i)); return v;
}
__device__ __forceinline__ uint4 lds128(uint32_t a) {
  uint4 v; asm volatile("ld.volatile.shared.v4.u32 {%0,%1,%2,%3},[%4];" : "=r"(v.x), "=r"(v.y), "=r"(v.z), "=r"(v.w) : "r"(a)); return v;
}
__device__ __forceinline__ void sts128(uint32_t a, const uint4& v) {
  asm volatile("st.shared.v4.u32 [%0],{%1,%2,%3,%4};" :: "r"(a), "r"(v.x), "r"(v.y), "r"(v.z), "r"(v.w) : "memory");
}
__device__ __forceinline__ void mbar_init(uint32_t bar, int n) { asm volatile("mbarrier.init.shared::cta.b64 [%0],%1;" :: "r"(bar), "r"(n) : "memory"); }
__device__ __forceinline__ void mbar_wait(uint32_t bar, uint32_t parity) {
  uint32_t ok; int it = 0;
  do { asm volatile("{.reg .pred p; mbarrier.try_wait.parity.shared::cta.b64 p,[%1],%2; selp.u32 %0,1,0,p;}" : "=r"(ok) : "r"(bar), "r"(parity) : "memory"); } while (!ok && ++it < (1 << 22));
}
__device__ __forceinline__ void mbar_expect(uint32_t bar, uint32_t bytes) { asm volatile("mbarrier.arrive.expect_tx.shared::cta.b64 _,[%0],%1;" :: "r"(bar), "r"(bytes) : "memory"); }
__device__ __forceinline__ void bulk_g2s(uint32_t dst, const void* src, uint32_t bytes, uint32_t bar) {
  asm volatile("cp.async.bulk.shared::cluster.global.mbarrier::complete_tx::bytes [%0],[%1],%2,[%3];" :: "r"(dst), "l"(src), "r"(bytes), "r"(bar) : "memory");
}
__device__ __forceinline__ void bulk_pf(const void* src, uint32_t bytes) { asm volatile("cp.async.bulk.prefetch.L2.global [%0],%1;" :: "l"(src), "r"(bytes) : "memory"); }
#define IW 2
#define PP0 10
#define PT0 10000
#define PDT 2200
#define RPNN "160"
#define RAUX "32"
#define RPRO "160"
#define PARK 0
#define NLOOK 128
#define NEF 25
#define ORD 0
#define WFENCE 0
#define SPLIT 0
#define IORD 3
#define IPF 3
#define IPACE 4500
#define WPF 3
#define QORD(n) (n)
#define DYD 4
#define DPF 4
#define DDEPTH 4
#define FENCE_N 8
#define INPL 0
#define STAG 1100
#define PACE 800
#define PM4 "pmevent 1; pmevent 2; pmevent 3; pmevent 4;"
#define PMFILL "pmevent 1;"
#define SCHED_FENCE(never, k) asm volatile("{.reg .pred p; setp.ne.u32 p,%0,%1; @p bra.uni SKIP_%=;" PMFILL "SKIP_%=: }" :: "r"(never), "r"(0x7fff0000 + (k)) : "memory")

__global__ void k_prod_naive(const __nv_bfloat16* __restrict__ table, const __nv_bfloat16* __restrict__ w1) {
  __shared__ float t[8][D_];
  int f = blockIdx.y, v0 = blockIdx.x * 8, h = threadIdx.x;
  for (int i = h; i < 8 * D_; i += 512) t[i / D_][i % D_] = __bfloat162float(table[v0 * D_ + i]);
  __syncthreads();
  float s[8] = {0, 0, 0, 0, 0, 0, 0, 0};
  for (int d = 0; d < D_; d++) { float w = __bfloat162float(w1[(size_t)(f * D_ + d) * H_ + h]);
#pragma unroll
    for (int k = 0; k < 8; k++) s[k] += t[k][d] * w; }
  __nv_bfloat16* P = (__nv_bfloat16*)g_scr;
  int c = h >> 3;
  for (int k = 0; k < 8; k++) {
    size_t e = f < 72 ? (size_t)PL_OFF + ((size_t)(c * NC + (f >> 3)) * 1000 + v0 + k) * 8 + (f & 7)
             : f < 90 ? (size_t)PS_OFF + ((size_t)(c * NC + ((f - 72) >> 1)) * 1000 + v0 + k) * 2 + (f & 1)
                      : (size_t)PT_OFF + (size_t)(c * 10 + f - 90) * 1024 + v0 + k;
    P[e * 8 + (h & 7)] = __float2bfloat16(s[k]);
  }
}
__global__ void k_pnn_naive(const int* __restrict__ idx, const __nv_bfloat16* __restrict__ table, const __nv_bfloat16* __restrict__ wp) {
  __shared__ float e[F_][33];
  int b = blockIdx.x, d0 = blockIdx.y * 32, tid = threadIdx.x;
  for (int i = tid; i < F_ * 32; i += 128) e[i >> 5][i & 31] = __bfloat162float(table[idx[b * F_ + (i >> 5)] * D_ + d0 + (i & 31)]);
  __syncthreads();
  float s = 0; int d = tid & 31;
  for (int i = tid >> 5; i < F_; i += 4) { float u = 0; for (int j = 0; j < F_; j++) u += __bfloat162float(wp[i * F_ + j]) * e[j][d]; s += u * e[i][d]; }
  for (int o = 16; o; o >>= 1) s += __shfl_xor_sync(~0u, s, o);
  if (d == 0) g_partP[(blockIdx.y * 4 + (tid >> 5)) * B_ + b] = s;
}
__device__ __forceinline__ void mbar_wait_fast(uint32_t bar, uint32_t parity) {
  asm volatile("{.reg .pred p; .reg .u32 n;\n"
               "mbarrier.try_wait.parity.shared::cta.b64 p,[%0],%1;\n"
               "@p bra DONE_%=;\n"
               "mov.u32 n,0;\n"
               "LOOP_%=: mbarrier.try_wait.parity.shared::cta.b64 p,[%0],%1;\n"
               "add.u32 n,n,1; setp.gt.or.u32 p,n,4000000,p;\n"
               "@!p bra LOOP_%=;\n"
               "DONE_%=: }" :: "r"(bar), "r"(parity) : "memory");
}
__device__ __forceinline__ void sleep_until(uint32_t t0, uint32_t dt) { while ((uint32_t)clock() - t0 < dt) __nanosleep(40); }
__device__ __forceinline__ uint32_t s_mask(uint32_t v, int q) { return (1u << ((v + 3 - q) & 3)) | (16u << ((v + 3 + q) & 3)); }
__device__ __forceinline__ uint32_t s_cell(uint32_t v, int q, uint32_t m) {
  const int t = __ffs(~m) - 1;
  const int cp = ((t & 4 ? t - q : t + q) - v) & 3;
  return (cp == 3 ? 0 : cp) * 1001 + v;
}
__device__ __forceinline__ uint32_t pk3(uint32_t a, uint32_t b, uint32_t c) {
  const uint32_t w = c + (a << 12) + (b << 22); return __funnelshift_l(w, w, 27);
}
constexpr int TH = 256, NS = 8192 / TH, YD = DYD;
__host__ __device__ constexpr int ye_of(int s) { return s == 3 ? 0 : s == 11 ? 1 : s == 19 ? 2 : s == 23 ? 3 : -1; }
template <int N> __device__ __forceinline__ void wgmma_h(uint32_t* d, const uint32_t* a, uint64_t desc, int acc);
template <> __device__ __forceinline__ void wgmma_h<64>(uint32_t* d, const uint32_t* a, uint64_t desc, int acc) {
  asm volatile("{.reg .pred p; setp.ne.s32 p,%21,0;\n"
    "wgmma.mma_async.sync.aligned.m64n64k16.f16.f16.f16 {%0,%1,%2,%3,%4,%5,%6,%7,%8,%9,%10,%11,%12,%13,%14,%15},{%16,%17,%18,%19},%20,p,1,1,0;}"
    : "+r"(d[0]),"+r"(d[1]),"+r"(d[2]),"+r"(d[3]),"+r"(d[4]),"+r"(d[5]),"+r"(d[6]),"+r"(d[7]),"+r"(d[8]),"+r"(d[9]),"+r"(d[10]),"+r"(d[11]),"+r"(d[12]),"+r"(d[13]),"+r"(d[14]),"+r"(d[15])
    : "r"(a[0]), "r"(a[1]), "r"(a[2]), "r"(a[3]), "l"(desc), "r"(acc));
}
template <> __device__ __forceinline__ void wgmma_h<56>(uint32_t* d, const uint32_t* a, uint64_t desc, int acc) {
  asm volatile("{.reg .pred p; setp.ne.s32 p,%19,0;\n"
    "wgmma.mma_async.sync.aligned.m64n56k16.f16.f16.f16 {%0,%1,%2,%3,%4,%5,%6,%7,%8,%9,%10,%11,%12,%13},{%14,%15,%16,%17},%18,p,1,1,0;}"
    : "+r"(d[0]),"+r"(d[1]),"+r"(d[2]),"+r"(d[3]),"+r"(d[4]),"+r"(d[5]),"+r"(d[6]),"+r"(d[7]),"+r"(d[8]),"+r"(d[9]),"+r"(d[10]),"+r"(d[11]),"+r"(d[12]),"+r"(d[13])
    : "r"(a[0]), "r"(a[1]), "r"(a[2]), "r"(a[3]), "l"(desc), "r"(acc));
}
template <> __device__ __forceinline__ void wgmma_h<48>(uint32_t* d, const uint32_t* a, uint64_t desc, int acc) {
  asm volatile("{.reg .pred p; setp.ne.s32 p,%17,0;\n"
    "wgmma.mma_async.sync.aligned.m64n48k16.f16.f16.f16 {%0,%1,%2,%3,%4,%5,%6,%7,%8,%9,%10,%11},{%12,%13,%14,%15},%16,p,1,1,0;}"
    : "+r"(d[0]),"+r"(d[1]),"+r"(d[2]),"+r"(d[3]),"+r"(d[4]),"+r"(d[5]),"+r"(d[6]),"+r"(d[7]),"+r"(d[8]),"+r"(d[9]),"+r"(d[10]),"+r"(d[11])
    : "r"(a[0]), "r"(a[1]), "r"(a[2]), "r"(a[3]), "l"(desc), "r"(acc));
}
template <> __device__ __forceinline__ void wgmma_h<40>(uint32_t* d, const uint32_t* a, uint64_t desc, int acc) {
  asm volatile("{.reg .pred p; setp.ne.s32 p,%15,0;\n"
    "wgmma.mma_async.sync.aligned.m64n40k16.f16.f16.f16 {%0,%1,%2,%3,%4,%5,%6,%7,%8,%9},{%10,%11,%12,%13},%14,p,1,1,0;}"
    : "+r"(d[0]),"+r"(d[1]),"+r"(d[2]),"+r"(d[3]),"+r"(d[4]),"+r"(d[5]),"+r"(d[6]),"+r"(d[7]),"+r"(d[8]),"+r"(d[9])
    : "r"(a[0]), "r"(a[1]), "r"(a[2]), "r"(a[3]), "l"(desc), "r"(acc));
}
template <> __device__ __forceinline__ void wgmma_h<32>(uint32_t* d, const uint32_t* a, uint64_t desc, int acc) {
  asm volatile("{.reg .pred p; setp.ne.s32 p,%13,0;\n"
    "wgmma.mma_async.sync.aligned.m64n32k16.f16.f16.f16 {%0,%1,%2,%3,%4,%5,%6,%7},{%8,%9,%10,%11},%12,p,1,1,0;}"
    : "+r"(d[0]),"+r"(d[1]),"+r"(d[2]),"+r"(d[3]),"+r"(d[4]),"+r"(d[5]),"+r"(d[6]),"+r"(d[7])
    : "r"(a[0]), "r"(a[1]), "r"(a[2]), "r"(a[3]), "l"(desc), "r"(acc));
}
__device__ __forceinline__ void wgmma_p(float* d, const uint32_t* a, uint64_t desc, int acc) {
  asm volatile("{.reg .pred p; setp.ne.s32 p,%37,0;\n"
    "wgmma.mma_async.sync.aligned.m64n64k16.f32.bf16.bf16 {%0,%1,%2,%3,%4,%5,%6,%7,%8,%9,%10,%11,%12,%13,%14,%15,%16,%17,%18,%19,%20,%21,%22,%23,%24,%25,%26,%27,%28,%29,%30,%31},{%32,%33,%34,%35},%36,p,1,1,1;}"
    : "+f"(d[0]),"+f"(d[1]),"+f"(d[2]),"+f"(d[3]),"+f"(d[4]),"+f"(d[5]),"+f"(d[6]),"+f"(d[7]),"+f"(d[8]),"+f"(d[9]),"+f"(d[10]),"+f"(d[11]),"+f"(d[12]),"+f"(d[13]),"+f"(d[14]),"+f"(d[15]),"+f"(d[16]),"+f"(d[17]),"+f"(d[18]),"+f"(d[19]),"+f"(d[20]),"+f"(d[21]),"+f"(d[22]),"+f"(d[23]),"+f"(d[24]),"+f"(d[25]),"+f"(d[26]),"+f"(d[27]),"+f"(d[28]),"+f"(d[29]),"+f"(d[30]),"+f"(d[31])
    : "r"(a[0]), "r"(a[1]), "r"(a[2]), "r"(a[3]), "l"(desc), "r"(acc));
}

__device__ __forceinline__ void mma16816h(uint32_t* c, const uint32_t* a, uint32_t b0, uint32_t b1) {
  asm("mma.sync.aligned.m16n8k16.row.col.f16.f16.f16.f16 {%0,%1},{%2,%3,%4,%5},{%6,%7},{%0,%1};"
      : "+r"(c[0]), "+r"(c[1]) : "r"(a[0]), "r"(a[1]), "r"(a[2]), "r"(a[3]), "r"(b0), "r"(b1));
}
__device__ __forceinline__ void mma1688h(uint32_t* c, uint32_t a0, uint32_t a1, uint32_t b) {
  asm("mma.sync.aligned.m16n8k8.row.col.f16.f16.f16.f16 {%0,%1},{%2,%3},{%4},{%0,%1};" : "+r"(c[0]), "+r"(c[1]) : "r"(a0), "r"(a1), "r"(b));
}
__device__ __forceinline__ void mma16816f(float* c, const uint32_t* a, uint32_t b) {
  asm("mma.sync.aligned.m16n8k16.row.col.f32.f16.f16.f32 {%0,%1,%2,%3},{%4,%5,%6,%7},{%8,%8},{%0,%1,%2,%3};"
      : "+f"(c[0]), "+f"(c[1]), "+f"(c[2]), "+f"(c[3]) : "r"(a[0]), "r"(a[1]), "r"(a[2]), "r"(a[3]), "r"(b));
}
__device__ __forceinline__ uint32_t hfma2(uint32_t a, uint32_t b, uint32_t c) { uint32_t r; asm("fma.rn.f16x2 %0,%1,%2,%3;" : "=r"(r) : "r"(a), "r"(b), "r"(c)); return r; }
__device__ __forceinline__ uint32_t pack_bf2(float lo, float hi) { uint32_t r; asm("cvt.rn.bf16x2.f32 %0,%1,%2;" : "=r"(r) : "f"(hi), "f"(lo)); return r; }
__device__ __forceinline__ uint32_t pack_h2(float lo, float hi) { uint32_t r; asm("cvt.rn.f16x2.f32 %0,%1,%2;" : "=r"(r) : "f"(hi), "f"(lo)); return r; }
__device__ __forceinline__ float bf_lo(uint32_t w) { return __uint_as_float(w << 16); }
__device__ __forceinline__ float bf_hi(uint32_t w) { return __uint_as_float(w & 0xffff0000u); }
__device__ __forceinline__ uint32_t absmax4(const uint4& v, uint32_t m) {
  return __vmaxu2(__vmaxu2(__vmaxu2(v.x & 0x7fff7fffu, v.y & 0x7fff7fffu), __vmaxu2(v.z & 0x7fff7fffu, v.w & 0x7fff7fffu)), m);
}
__device__ __forceinline__ float pow2_scale(uint32_t mbits, int p) { return __uint_as_float((uint32_t)min(max(253 + p - (int)(mbits >> 7), 2), 252) << 23); }

#define PV 4
constexpr int G_O0 = 8, G_O1 = 4, G_O2 = 0, G_N0 = 5, G_N1 = 4, G_N2 = 4, G_K0 = 5, G_K1 = 3, G_K2 = 1;
__host__ __device__ constexpr bool unit_wg(int kb, int on) {
  return (on >= G_O0 && on < G_O0 + G_N0 && kb < G_K0) || (on >= G_O1 && on < G_O1 + G_N1 && kb < G_K1) || (on >= G_O2 && on < G_O2 + G_N2 && kb < G_K2);
}
__host__ __device__ constexpr bool oct_wg(int on) { return unit_wg(0, on); }
constexpr int G_U1 = G_N0 * G_K0, G_U2 = G_U1 + G_N1 * G_K1, G_U = G_U2 + G_N2 * G_K2;
constexpr int K1_B = 130048, K1_STG = K1_B + 3 * 16384, K1_W = K1_STG + 2 * 16384, K1_BAR = K1_W + 48 * 256, K1_SMEM = K1_BAR + 128;
__host__ __device__ constexpr int frag_index(int ok, int on) {
  int n = 0;
  for (int k = 0; k < 13; k++) for (int o = k; o < 13; o++) { if (k == ok && o == on) return n; if (!unit_wg(k >> 1, o)) n++; }
  return n;
}
constexpr int HU_N = 2 * G_U + frag_index(99, 99);
static_assert(HU_N <= 96, "");
struct FragIdx { int v[13][13]; };
__host__ __device__ constexpr FragIdx make_fi() { FragIdx f = {}; for (int k = 0; k < 13; k++) for (int o = 0; o < 13; o++) f.v[k][o] = frag_index(k, o); return f; }
__host__ __device__ constexpr uint64_t frag_tab(int first) {
  uint64_t t = 0;
  for (int k = 0; k < 13; k++) for (int o = k; o < 13; o++)
    if (!unit_wg(k >> 1, o)) { const int n = frag_index(k, o) - first; if (n >= 0 && n < 8) t |= (uint64_t)(k << 4 | o) << (8 * n); }
  return t;
}
__device__ __forceinline__ int hu_code(int hu) {
  constexpr uint64_t T0 = frag_tab(0), T1 = frag_tab(8), T2 = frag_tab(16), T3 = frag_tab(24);
  const int u = hu >> 1, f = hu - 2 * G_U;
  if (f >= 0) return (int)((f < 8 ? T0 : f < 16 ? T1 : f < 24 ? T2 : T3) >> (8 * (f & 7))) & 255;
  const int u0 = u < G_U1 ? u : u < G_U2 ? u - G_U1 : u - G_U2;
  const int kb = u < G_U1 ? u0 / G_N0 : u < G_U2 ? u0 / G_N1 : u0 / 4, on = u < G_U1 ? G_O0 + u0 % G_N0 : u < G_U2 ? G_O1 + u0 % G_N1 : G_O2 + u0 % 4;
  return (2 * kb + (hu & 1)) << 4 | on;
}

__device__ __forceinline__ void flag_arrive(unsigned* f, int lane) {
  __threadfence(); __syncwarp();
  if (lane == 0) asm volatile("red.release.gpu.global.add.u32 [%0],1;" :: "l"(f) : "memory");
}
__device__ __forceinline__ void flag_wait(const unsigned* f, unsigned n) {
  unsigned v; int it = 0;
  do { asm volatile("ld.acquire.gpu.global.u32 %0,[%1];" : "=r"(v) : "l"(f) : "memory"); if (v < n) __nanosleep(100); } while (v < n && ++it < (1 << 20));
}
__device__ __forceinline__ void mbar_arrive(uint32_t bar) { asm volatile("mbarrier.arrive.shared::cta.b64 _,[%0];" :: "r"(bar) : "memory"); }
__device__ __forceinline__ void mbar_arrive_lane0(uint32_t bar) {
  asm volatile("{.reg .pred p; elect.sync _|p,0xffffffff; @p mbarrier.arrive.shared::cta.b64 _,[%0];}" :: "r"(bar) : "memory");
}

__device__ __forceinline__ void pack_role(const int* __restrict__ idx, uint32_t sbase, int pc) {
  constexpr int CH = 3200 + 32, BUF = 32 * 3328;
  const int tid = threadIdx.x, lane = tid & 31, warp = tid >> 5;
  const uint32_t full = sbase + 2 * BUF, empty = full + 16;
  if (tid == 0) { mbar_init(full, 1); mbar_init(full + 8, 1); mbar_init(empty, 18); mbar_init(empty + 8, 18); asm volatile("fence.proxy.async.shared::cta;" ::: "memory"); }
  __syncthreads();
  auto chunk = [&](int s) { return s * 3200 + (s >> 2) * 288; };
  auto load = [&](int n) {
    const int blk = pc * 16 + n;
    if (lane == 0) mbar_expect(full + (n & 1) * 8, 32 * 3200);
    __syncwarp();
    bulk_g2s(sbase + (n & 1) * BUF + chunk(lane), idx + ((blk >> 5) * 8192 + lane * TH + (blk & 31) * 8) * F_, 3200, full + (n & 1) * 8);
  };
  if (warp == 0) { load(0); load(1); }
  const int l = lane & 7;
  uint32_t rot[8], inc[3];
#pragma unroll
  for (int jj = 0; jj < 8; jj++) rot[jj] = ((l + jj) & 7) * 4;
#pragma unroll
  for (int q = 0; q < 3; q++) inc[q] = (l + 3 * q < 8) << 12 | (l + 3 * q + 1 < 8) << 22 | (q < 2 && l + 3 * q + 2 < 8);
  int loaded = 2;
#pragma unroll 1
  for (int task = warp; task < 288; task += 16) {
    const int n = task / 18, q = (task % 18) * 4 + (lane >> 3), sq = q / 9, k = q % 9;
    if (warp == 0 && n + 1 == loaded && loaded < 16) { mbar_wait(empty + (loaded & 1) * 8, ((loaded >> 1) - 1) & 1); load(loaded); loaded++; }
    mbar_wait(full + (n & 1) * 8, (n >> 1) & 1);
    const uint32_t buf = sbase + (n & 1) * BUF + l * 400, row = buf + chunk(sq * 4);
    auto ld = [&](uint32_t ad) { uint32_t v; asm volatile("ld.shared.u32 %0,[%1];" : "=r"(v) : "r"(ad)); return v; };
    const int blk = pc * 16 + n, half = blk >> 5, col = (blk & 31) * 8 + l;
    const int ks = k == NC - 1 ? 0 : k + 1;
    uint32_t cw[4], sv[8], m[2] = {0, 0};
    { const uint32_t a0 = row + (72 + 2 * ks + (l >> 2)) * 4;
#pragma unroll
      for (int u = 0; u < 8; u++) { sv[u] = ld((a0 ^ ((u >> 2) * 4)) + (u & 3) * 3200); m[u >> 2] |= s_mask(sv[u], l & 3) << (8 * (u & 3)); } }
#pragma unroll
    for (int h = 0; h < 2; h++) { m[h] |= __shfl_xor_sync(0xffffffffu, m[h], 1); m[h] |= __shfl_xor_sync(0xffffffffu, m[h], 2); }
#pragma unroll
    for (int u = 0; u < 4; u++) cw[u] = s_cell(sv[u], l & 3, (m[0] >> (8 * u)) & 255) | s_cell(sv[4 + u], l & 3, (m[1] >> (8 * u)) & 255) << 12;
    if (k == NC - 1) {
      g_scr[I0_OFF + (half * 8 + sq) * TH + col] = make_uint4(cw[0], cw[1], cw[2], cw[3]);
      g_scr[I9_OFF + (half * 8 + sq) * TH + col] = make_uint4(ld(row + 396), ld(row + 3596), ld(row + 6796), ld(row + 9996));
      cw[0] = cw[1] = cw[2] = cw[3] = 0;
    }
    const uint32_t ax = buf + chunk(min(sq + 1, 7) * 4) + (90 + k) * 4;
    const uint32_t yev = ld(buf + ((0x3210 >> (sq * 2 + (sq == 5) * 2)) & 3) * 3200 + (90 + k) * 4);
    uint4* dst = g_scr + IX_OFF + ((half * NC + k) * NS + sq * 4) * TH + col;
#pragma unroll
    for (int u = 0; u < 4; u++) {
      uint32_t e[8];
#pragma unroll
      for (int jj = 0; jj < 8; jj++) e[jj] = ld(row + k * 32 + rot[jj] + u * 3200);
      dst[u * TH] = make_uint4(pk3(e[0], e[1], e[2] + inc[0]), pk3(e[3], e[4], e[5] + inc[1]), pk3(e[6], e[7], ld(ax + u * 3200) + inc[2]),
                               u < 3 ? __byte_perm(cw[u], cw[3], 0x4210 + (u << 12)) : yev);
    }
    mbar_arrive_lane0(empty + (n & 1) * 8);
  }
  (void)CH;
}

__global__ void __launch_bounds__(512, 1)
k_tens(const __grid_constant__ CUtensorMap mapW, const __grid_constant__ CUtensorMap mapL, const __grid_constant__ CUtensorMap mapS,
       const __grid_constant__ CUtensorMap mapT, const __grid_constant__ CUtensorMap mapE, const __grid_constant__ CUtensorMap mapC, cudaTextureObject_t tex, cudaTextureObject_t texX,
       const int* __restrict__ idx, const __nv_bfloat16* __restrict__ table, const __nv_bfloat16* __restrict__ wp, const __nv_bfloat16* __restrict__ w1, int never) {
  extern __shared__ __align__(1024) uint4 sm[];
  const int tid = threadIdx.x, lane = tid & 31, cta = blockIdx.x;
  const uint32_t sbase = (uint32_t)__cvta_generic_to_shared(sm);
  const int g = lane >> 2, r = lane & 3;
  TS(0, 0);
  asm volatile("griddepcontrol.launch_dependents;");
  if (cta >= 128) { pack_role(idx, sbase, cta - 128); TS(2, 1); return; }
  const uint32_t fullB = sbase + K1_BAR, emptyB = fullB + 24, fullS = fullB + 48, emptyS = fullB + 64, fullE = fullB + 80, fullC = fullB + 88, fullI = fullB + 96;
  const int rb = cta & 7, hc = cta >> 3;
  if (tid >= 384) {
    asm volatile("setmaxnreg.dec.sync.aligned.u32 " RAUX ";");
    if (tid < 416) {
      auto load_pair = [&](int p, int st) {
        mbar_expect(fullB + st * 8, 16384);
        asm volatile("cp.async.bulk.tensor.2d.shared::cluster.global.mbarrier::complete_tx::bytes [%0],[%1,{%2,%3}],[%4];"
                     :: "r"(sbase + K1_B + st * 16384), "l"(&mapW), "r"(hc * 32), "r"(QORD(p >> 1) * 512 + (p & 1) * 256), "r"(fullB + st * 8) : "memory");
        p += WPF;
        if (p < 50) bulk_pf(w1 + QORD(p >> 1) * 262144 + (p & 1) * 131072 + cta * 1024, 2048);
      };
      if (tid == 384) {
        for (int q = 0; q < 3; q++) { mbar_init(fullB + q * 8, 1); mbar_init(emptyB + q * 8, 4); }
        for (int q = 0; q < 2; q++) { mbar_init(fullS + q * 8, 4); mbar_init(emptyS + q * 8, 1); }
        mbar_init(fullE, 1); mbar_init(fullC, 1); mbar_init(fullI, 1);
        asm volatile("fence.proxy.async.shared::cta;" ::: "memory");
        mbar_expect(fullC, 16384);
        for (int q = 0; q < 4; q++)
          asm volatile("cp.async.bulk.tensor.2d.shared::cluster.global.mbarrier::complete_tx::bytes [%0],[%1,{%2,%3}],[%4];"
                       :: "r"(sbase + 32768 + q * 4096), "l"(&mapC), "r"((cta & 15) * 8), "r"(q * 256), "r"(fullC) : "memory");
        mbar_expect(fullE, 32768);
        for (int q = 0; q < 2; q++)
          asm volatile("cp.async.bulk.tensor.2d.shared::cluster.global.mbarrier::complete_tx::bytes [%0],[%1,{%2,%3}],[%4];"
                       :: "r"(sbase + K1_STG + q * 16384), "l"(&mapE), "r"(q * 64), "r"(rb * 128), "r"(fullE) : "memory");
      }
      __syncwarp();
      asm volatile("bar.arrive 2,448;" ::: "memory");
      if (tid == 384) {
        int st = 0, ph = 1;
#pragma unroll 1
        for (int p = 0; p < 50; p++) {
          if (p == IORD) {
            mbar_expect(fullI, 51200);
#pragma unroll 1
            for (int q = 0; q < 8; q++) bulk_g2s(sbase + 76800 + q * 6400, idx + (((cta >> 4) * 8 + q) * 256 + (cta & 15) * 16) * F_, 6400, fullI);
          }
          mbar_wait(emptyB + st * 8, ph);
          load_pair(p, st);
          if (++st == 3) { st = 0; ph ^= 1; }
        }
      }
    } else if (tid < 448) {
      asm volatile("bar.sync 2,448;" ::: "memory");
      asm volatile("bar.sync 4,288;" ::: "memory");
      flag_arrive(&g_flag[(cta >> 4) * 32], lane);
      if (tid == 416) {
#pragma unroll 1
        for (int n = 0; n < 50; n++) {
          const int quad = QORD(n >> 1), mt = n & 1, v0 = rb * 128 + mt * 64;
          const uint32_t stg = sbase + K1_STG + mt * 16384;
          const uint64_t pol = n < 2 * NEF ? POL_EF : POL_N;
          mbar_wait(fullS + mt * 8, (n >> 1) & 1);
          asm volatile("fence.proxy.async.shared::cta;" ::: "memory");
          if (quad < 18) {
            asm volatile("cp.async.bulk.tensor.4d.global.shared::cta.bulk_group.L2::cache_hint [%0,{%1,%2,%3,%4}],[%5],%6;"
                         :: "l"(&mapL), "r"((quad & 1) * 32), "r"(v0), "r"(quad >> 1), "r"(hc * 4), "r"(stg), "l"(pol) : "memory");
          } else {
#pragma unroll 1
            for (int hh = 0; hh < 2; hh++) {
              const int pq = quad * 2 + hh;
              if (pq < 45) asm volatile("cp.async.bulk.tensor.4d.global.shared::cta.bulk_group.L2::cache_hint [%0,{%1,%2,%3,%4}],[%5],%6;"
                         :: "l"(&mapS), "r"(0), "r"(v0), "r"(pq - 36), "r"(hc * 4), "r"(stg + hh * 8192), "l"(pol) : "memory");
              else asm volatile("cp.async.bulk.tensor.3d.global.shared::cta.bulk_group.L2::cache_hint [%0,{%1,%2,%3}],[%4],%5;"
                         :: "l"(&mapT), "r"(v0 * 2), "r"((pq - 45) * 2), "r"(hc * 4), "r"(stg + hh * 8192), "l"(pol) : "memory");
            }
          }
          asm volatile("cp.async.bulk.commit_group;" ::: "memory");
          asm volatile("cp.async.bulk.wait_group.read 0;" ::: "memory");
          mbar_arrive(emptyS + mt * 8);
        }
        asm volatile("cp.async.bulk.wait_group 0;" ::: "memory");
      }
    }
    return;
  }
  if (tid >= 256) {
    asm volatile("setmaxnreg.inc.sync.aligned.u32 " RPRO ";");
    const int w = (tid >> 5) & 3;
    const int srow = w * 16 + (lane & 7) + ((lane >> 3) & 1) * 8, sc = lane >> 4;
    uint32_t a[2][8][4];
    asm volatile("bar.sync 2,448;" ::: "memory");
    mbar_wait_fast(fullE, 0);
#pragma unroll
    for (int mt = 0; mt < 2; mt++)
#pragma unroll
      for (int ks = 0; ks < 8; ks++)
        asm volatile("ldmatrix.sync.aligned.m8n8.x4.shared.b16 {%0,%1,%2,%3},[%4];"
                     : "=r"(a[mt][ks][0]), "=r"(a[mt][ks][1]), "=r"(a[mt][ks][2]), "=r"(a[mt][ks][3])
                     : "r"(sbase + K1_STG + (ks >> 2) * 16384 + (mt * 64 + srow) * 128 + ((((ks & 3) * 2 + sc) ^ (lane & 7)) * 16)) : "memory");
    asm volatile("bar.sync 5,128;" ::: "memory");
    const uint32_t baseL = sc * 4096 + srow * 64 + ((srow >> 1) & 3) * 16, baseS = sc * 2048 + srow * 32 + ((srow >> 2) & 1) * 16, baseT = sc * 2048 + srow * 16;
    const uint64_t desc0 = (uint64_t)(((sbase + K1_B) & 0x3FFFF) >> 4) | ((uint64_t)(8192 >> 4) << 16) | ((uint64_t)(512 >> 4) << 32) | (2ull << 62);
    float d[2][32];
    auto issue = [&](int x, int mt, int st) {
      uint32_t a7[4];
#pragma unroll
      for (int e = 0; e < 4; e++) { if (PARK) asm volatile("add.u32 %0,%1,%2;" : "=r"(a7[e]) : "r"(a[mt][7][e]), "r"(never)); else a7[e] = a[mt][7][e]; }
      asm volatile("wgmma.fence.sync.aligned;" ::: "memory");
#pragma unroll
      for (int ks = 0; ks < 8; ks++) wgmma_p(d[x], ks < 7 ? a[mt][ks] : a7, desc0 + st * 1024 + ks * 64, ks);
      asm volatile("wgmma.commit_group.sync.aligned;" ::: "memory");
    };
    auto wait_acc = [&](int x) {
      asm volatile("wgmma.wait_group.sync.aligned 0;" ::: "memory");
#pragma unroll
      for (int q = 0; q < 8; q++) asm volatile("" : "+f"(d[x][q * 4]), "+f"(d[x][q * 4 + 1]), "+f"(d[x][q * 4 + 2]), "+f"(d[x][q * 4 + 3]) :: "memory");
    };
    mbar_wait_fast(fullB, 0);
    issue(0, 0, 0);
    int s0 = 0, ph = 0;
#pragma unroll 1
    for (int qn = 0; qn < 25; qn++) {
      const int quad = QORD(qn);
      const int s1 = s0 == 2 ? 0 : s0 + 1, s2 = s1 == 2 ? 0 : s1 + 1, ph1 = ph ^ (s1 == 0), ph2 = ph1 ^ (s2 == 0);
#pragma unroll
      for (int step = 0; step < 4; step++) {
        const int mt = ORD ? step & 1 : step >> 1, h = ORD ? step >> 1 : step & 1, x = step & 1, nx = (step + 1) & 3;
        const bool isL = quad < 18, isS = quad * 2 + h < 45;
        const uint32_t base = (isL ? baseL ^ (h * 32) : (isS ? baseS : baseT) ^ (h * 8192)), xj = (isL || isS) ? 16 : 1024, xc = isL ? 8192 : 4096;
        PT(qn * 16 + step * 4);
        if (h == 0) mbar_wait_fast(emptyS + mt * 8, (qn & 1) ^ 1);
        if (step == (ORD ? 1 : 0)) mbar_wait_fast(fullB + s1 * 8, ph1);
        if (step == 3) mbar_wait_fast(fullB + s2 * 8, qn == 24 ? ph2 ^ 1 : ph2);
        PT(qn * 16 + step * 4 + 1);
        wait_acc(x);
        PT(qn * 16 + step * 4 + 2);
        if (mt) mbar_arrive_lane0(emptyB + (h ? s1 : s0) * 8);
        issue(x ^ 1, ORD ? nx & 1 : nx >> 1, step == 3 ? s2 : (ORD ? nx >> 1 : nx & 1) ? s1 : s0);
        PT(qn * 16 + step * 4 + 3);
#pragma unroll
        for (int e4 = 0; e4 < 4; e4++) {
          const float* e = d[x] + e4 * 8;
          asm volatile("stmatrix.sync.aligned.m8n8.x4.shared.b16 [%0],{%1,%2,%3,%4};"
                       :: "r"(sbase + K1_STG + mt * 16384 + (base ^ ((e4 >> 1) * xj) ^ ((e4 & 1) * xc))),
                          "r"(pack_bf2(e[0], e[1])), "r"(pack_bf2(e[2], e[3])), "r"(pack_bf2(e[4], e[5])), "r"(pack_bf2(e[6], e[7])) : "memory");
        }
        if (h) { __syncwarp(); mbar_arrive_lane0(fullS + mt * 8); }
      }
      s0 = s2; ph = ph2;
    }
    asm volatile("wgmma.wait_group.sync.aligned 0;" ::: "memory");
    return;
  }
  asm volatile("setmaxnreg.inc.sync.aligned.u32 " RPNN ";");
  const int slice = cta & 15;
  const int range = (cta >> 4) * 8 + (tid >> 5);
  uint4 iv[4], trow[4]; uint32_t ix;
  uint2 wrow[10];
#pragma unroll
  for (int q = 0; q < 10; q++) asm volatile("ld.global.nc.v2.u32 {%0,%1},[%2];" : "=r"(wrow[q].x), "=r"(wrow[q].y) : "l"((const uint2*)wp + min(tid + q * 256, 2499)));
  asm volatile("bar.sync 2,448;" ::: "memory");
  uint32_t me = 0, mw = 0;
#pragma unroll
  for (int q = 0; q < 10; q++) {
    mw = __vmaxu2(__vmaxu2(wrow[q].x & 0x7fff7fffu, wrow[q].y & 0x7fff7fffu), mw);
    const int e = min(tid + q * 256, 2499), row = e / 25;
    asm volatile("st.shared.v2.u32 [%0],{%1,%2};" :: "r"(sbase + (e + row) * 8), "r"(wrow[q].x), "r"(wrow[q].y) : "memory");
    if (e - row * 25 == 24) asm volatile("st.shared.v2.u32 [%0],{%1,%2};" :: "r"(sbase + (e + row) * 8 + 8), "r"(wrow[q].x), "r"(wrow[q].y) : "memory");
  }
  mbar_wait_fast(fullC, 0);
#pragma unroll
  for (int q = 0; q < 4; q++) { trow[q] = lds128(sbase + 32768 + (tid + q * 256) * 16); me = absmax4(trow[q], me); }
  me = __reduce_max_sync(0xffffffffu, max(me & 0xffff, me >> 16));
  mw = __reduce_max_sync(0xffffffffu, max(mw & 0xffff, mw >> 16));
  uint32_t* sred = (uint32_t*)((char*)sm + 128000);
  if (lane == 0) sred[tid >> 5] = me | mw << 16;
  TS(3, 0);
  asm volatile("bar.sync 1,256;" ::: "memory");
  { uint32_t m = 0;
#pragma unroll
    for (int q = 0; q < 8; q++) m = __vmaxu2(m, sred[q]);
    me = m & 0xffff; mw = m >> 16; }
  const float se = pow2_scale(me, 3), sW = pow2_scale(mw, -2);
  TS(3, 1);
  auto put_rows = [&](int q, bool on) {
    const uint4 t = trow[q];
    const uint4 hv = make_uint4(pack_h2(bf_lo(t.x) * se, bf_hi(t.x) * se), pack_h2(bf_lo(t.y) * se, bf_hi(t.y) * se),
                                pack_h2(bf_lo(t.z) * se, bf_hi(t.z) * se), pack_h2(bf_lo(t.w) * se, bf_hi(t.w) * se));
    if (on)
#pragma unroll
      for (int s = 0; s < 8; s++) sts128(sbase + (tid + q * 256) * 128 + ((s + lane) & 7) * 16, hv);
  };
#pragma unroll 1
  for (int it = 0; it < 3; it++) {
    const int hu = ((tid >> 5) * 3 + it) * 4, code = hu_code(min(hu + (lane >> 3), HU_N - 1)), ok = code >> 4, on = code & 15;
    uint32_t x[4], y[4];
    asm volatile("ldmatrix.sync.aligned.m8n8.x4.shared.b16 {%0,%1,%2,%3},[%4];" : "=r"(x[0]), "=r"(x[1]), "=r"(x[2]), "=r"(x[3])
                 : "r"(sbase + (on * 8 + (lane & (on == 12 ? 3 : 7))) * 208 + ok * 16) : "memory");
    asm volatile("ldmatrix.sync.aligned.m8n8.x4.trans.shared.b16 {%0,%1,%2,%3},[%4];" : "=r"(y[0]), "=r"(y[1]), "=r"(y[2]), "=r"(y[3])
                 : "r"(sbase + (ok * 8 + (lane & (ok == 12 ? 3 : 7))) * 208 + on * 16) : "memory");
    const uint32_t lo = __ballot_sync(0xffffffffu, ok > on), dg = __ballot_sync(0xffffffffu, ok >= on);
#pragma unroll
    for (int q = 0; q < 4; q++) {
      const float m0 = (lo >> (8 * q)) & 1 ? 0.f : sW, m1 = (dg >> (8 * q)) & 1 ? 0.f : sW;
      asm volatile("st.shared.u32 [%0],%1;" :: "r"(sbase + K1_W + (hu + q) * 128 + lane * 4),
                   "r"(pack_h2(fmaf(bf_lo(x[q]), m0, bf_lo(y[q]) * m1), fmaf(bf_hi(x[q]), m0, bf_hi(y[q]) * m1))) : "memory");
    }
  }
  put_rows(1, true); put_rows(2, tid < 88);
  TS(3, 2);
  asm volatile("fence.proxy.async.shared::cta;" ::: "memory");
  asm volatile("bar.sync 1,256;" ::: "memory");
  put_rows(0, true);
  uint32_t bf[HU_N - 2 * G_U];
#pragma unroll
  for (int q = 0; q < HU_N - 2 * G_U; q++) asm volatile("ld.shared.u32 %0,[%1];" : "=r"(bf[q]) : "r"(sbase + K1_W + (2 * G_U + q) * 128 + lane * 4));
  const float unscale = __uint_as_float(0x7f000000u - __float_as_uint(se)), unscale2 = __uint_as_float(0x7f000000u - __float_as_uint(sW));
  TS(3, 3);
  const int px = range * 16 * 136;
  mbar_wait_fast(fullI, 0);
  {
    const uint32_t ib = sbase + 76800 + (tid >> 5) * 6400, p0 = ib + ((lane >> 3) & 1) * 400 + ((lane >> 4) * 8 + (lane & 7)) * 4;
    auto ld = [&](uint32_t ad) { uint32_t v; asm volatile("ld.shared.u32 %0,[%1];" : "=r"(v) : "r"(ad)); return v; };
    auto wd = [&](int t, int h) { return pk3(ld(p0 + t * 800 + h * 192), ld(p0 + t * 800 + h * 192 + 64), ld(p0 + t * 800 + h * 192 + 128)); };
#pragma unroll
    for (int q = 0; q < 4; q++) {
      iv[q] = make_uint4(wd(2 * q, 0), wd(2 * q, 1), wd(2 * q + 1, 0), wd(2 * q + 1, 1));
      g_scr[PX_OFF + px + slice * 136 + q * 32 + lane] = iv[q];
    }
    ix = pk3(ld(ib + g * 400 + 384 + r * 4), ld(ib + (8 + g) * 400 + 384 + r * 4), 0);
    ((uint32_t*)(g_scr + PX_OFF + px + slice * 136 + 128))[lane] = ix;
  }
  asm volatile("bar.arrive 4,288;" ::: "memory");
  asm volatile("bar.sync 1,256;" ::: "memory");
  put_rows(2, tid >= 88); put_rows(3, tid + 768 < V_);
  asm volatile("bar.sync 1,256;" ::: "memory");
  TS(0, 1);
  const uint32_t lc = (lane & 7) * 16;
  const uint64_t wdesc = (uint64_t)(((sbase + K1_W) & 0x3FFFF) >> 4) | ((uint64_t)(128 >> 4) << 16) | ((uint64_t)(256 >> 4) << 32);
  uint32_t a[2][6][4], d[2][26], ex[4] = {}, s[4] = {};
  float red[4] = {0.f, 0.f, 0.f, 0.f};
  auto ldsm = [&](uint32_t* o, uint32_t sh) {
    asm volatile("ldmatrix.sync.aligned.m8n8.x4.trans.shared.b16 {%0,%1,%2,%3},[%4];"
                 : "=r"(o[0]), "=r"(o[1]), "=r"(o[2]), "=r"(o[3]) : "r"(sbase + ((sh & 0x1ff80) | lc)));
  };
  auto gather = [&](int t, int hf) {
    const int x = t & 1;
    const uint4 v = iv[(t >> 1) & 3];
#pragma unroll
    for (int kb = 3 * hf; kb < 3 * hf + 3; kb++) {
      const uint32_t ww = x ? (kb < 3 ? v.z : v.w) : (kb < 3 ? v.x : v.y);
      ldsm(a[x][kb], kb % 3 == 0 ? ww : kb % 3 == 1 ? ww >> 10 : __funnelshift_l(ww, ww, 12));
    }
  };
  auto issue = [&](int x) {
    asm volatile("wgmma.fence.sync.aligned;" ::: "memory");
#pragma unroll
    for (int kb = 0; kb < 6; kb++) {
      if (kb < G_K0) wgmma_h<G_N0 * 8>(d[x] + G_O0 * 2, a[x][kb], wdesc + kb * G_N0 * 16, kb);
      if (kb < G_K1) wgmma_h<G_N1 * 8>(d[x] + G_O1 * 2, a[x][kb], wdesc + (G_U1 + kb * G_N1) * 16, kb);
      if (kb < G_K2) wgmma_h<32>(d[x] + G_O2 * 2, a[x][kb], wdesc + (G_U2 + kb * G_N2) * 16, kb);
    }
    asm volatile("wgmma.commit_group.sync.aligned;" ::: "memory");
  };
  auto hmma_part = [&](int t) {
    constexpr FragIdx FI = make_fi();
    const int x = t & 1;
#pragma unroll
    for (int o = 0; o < 13; o++) {
      if (oct_wg(o)) asm volatile("" : "+r"(d[x][o * 2]), "+r"(d[x][o * 2 + 1]) :: "memory"); else d[x][o * 2] = d[x][o * 2 + 1] = 0;
    }
#pragma unroll
    for (int kb = 0; kb < 6; kb++)
#pragma unroll
      for (int o = 2 * kb + 1; o < 13; o++)
        if (!unit_wg(kb, o)) mma16816h(d[x] + o * 2, a[x][kb], bf[FI.v[2 * kb][o]], bf[FI.v[2 * kb + 1][o]]);
#pragma unroll
    for (int q = 0; q < 6; q++) if (!unit_wg(q, 2 * q)) mma1688h(d[x] + q * 4, a[x][q][0], a[x][q][1], bf[FI.v[2 * q][2 * q]]);
    mma1688h(d[x] + 24, r < 2 ? ex[t & 3] : 0u, r < 2 ? 0u : ex[t & 3], bf[FI.v[12][12]]);
  };
  auto dot_part = [&](int t, int hf) {
    const int x = t & 1;
    if (hf == 0) {
      const uint32_t pe = hfma2(r < 2 ? d[x][24] : d[x][25], ex[t & 3], 0u);
      s[0] = r < 2 ? pe : 0u; s[1] = r < 2 ? 0u : pe; s[2] = s[3] = 0;
    }
#pragma unroll
    for (int q = 3 * hf; q < 3 * hf + 3; q++)
#pragma unroll
      for (int e = 0; e < 4; e++) s[e] = hfma2(d[x][q * 4 + e], a[x][q][e], s[e]);
  };
  float* outp = g_partP + slice * B_ + range * 256 + r * 4 + ((lane >> 3) & 1) * 2 + (lane >> 4);
  float k0 = 0.f, k1 = 0.f, x0 = 0.f, x1 = 0.f;
  auto red_stage = [&](int st, int grp) {
    const bool u16 = lane & 16, u8 = lane & 8;
    if (st == 0) {
      k0 = u16 ? red[2] : red[0]; x0 = __shfl_xor_sync(0xffffffffu, u16 ? red[0] : red[2], 16);
      k1 = u16 ? red[3] : red[1]; x1 = __shfl_xor_sync(0xffffffffu, u16 ? red[1] : red[3], 16);
      red[0] = red[1] = red[2] = red[3] = 0.f;
    }
    if (st == 1) { const float p0 = k0 + x0, p1 = k1 + x1; k0 = u8 ? p1 : p0; x0 = __shfl_xor_sync(0xffffffffu, u8 ? p0 : p1, 8); }
    if (st == 2) { k0 += x0; x0 = __shfl_xor_sync(0xffffffffu, k0, 4); }
    if (st == 3 && !(lane & 4)) outp[grp * 16] = (k0 + x0) * unscale * unscale * unscale2;
  };
  auto group = [&](bool first, int prv, int cur, int nxt) {
    const int pn = PX_OFF + px + nxt * 136 + lane;
#pragma unroll
    for (int t = 0; t < 8; t++) {
      issue((t & 1) ^ 1);
      SCHED_FENCE(never, t * 8);
      if (!first) {
        if (t == 0) { iv[3] = ldtex(tex, PX_OFF + px + cur * 136 + lane + 96); iv[0] = ldtex(tex, pn); }
        if (t == 2) iv[1] = ldtex(tex, pn + 32);
        if (t < 4) red_stage(t, prv);
      } else if (t == 4) {
        flag_wait(&g_flag[(cta >> 4) * 32], 16);
        iv[0] = ldtex(tex, pn); iv[1] = ldtex(tex, pn + 32);
      }
      if (t == 4) { ix = ldtex(texX, (px + nxt * 136 + 128) * 4 + lane).x; iv[2] = ldtex(tex, pn + 64); }
      dot_part(t, 0); dot_part(t, 1);
      SCHED_FENCE(never, t * 8 + 1);
      if (t == 3) ldsm(ex, ix >> 10);
      if (t == 7) ldsm(ex, ix);
      gather(t + 2, 0); gather(t + 2, 1);
      asm volatile("wgmma.wait_group.sync.aligned 0;" ::: "memory");
      SCHED_FENCE(never, t * 8 + 2);
      mma16816f(red, s, g == t ? 0x3c003c00u : 0u);
      hmma_part(t + 1);
      SCHED_FENCE(never, t * 8 + 3);
    }
  };
  gather(0, 0); gather(0, 1); issue(0); ldsm(ex, ix); gather(1, 0); gather(1, 1);
  asm volatile("wgmma.wait_group.sync.aligned 0;" ::: "memory");
  hmma_part(0);
  int prv = slice, cur = slice == 0;
  group(true, 0, prv, cur);
  TS(4, 1);
#pragma unroll 1
  for (int n = 1; n < 16; n++) {
    const int nxt = (n + (n >= slice)) & 15;
    group(false, prv, cur, nxt);
    prv = cur; cur = nxt;
  }
#pragma unroll
  for (int st = 0; st < 4; st++) red_stage(st, prv);
  TS(0, 2);
}

constexpr int SM_U = 130048, SM_BAR = SM_U + 3 * 32032, DEEP_SMEM = SM_BAR + 128 + 4096;

__device__ __forceinline__ void arrive_both(uint32_t bar, int lane) {
  asm volatile("{.reg .pred p; .reg .u32 a; setp.lt.u32 p,%1,2; mapa.shared::cluster.u32 a,%0,%1;\n"
               "@p mbarrier.arrive.shared::cluster.b64 _,[a];}" :: "r"(bar), "r"(lane) : "memory");
}
__device__ __forceinline__ void bulk_mc(uint32_t dst, const void* src, uint32_t bytes, uint32_t bar, uint64_t pol) {
  asm volatile("cp.async.bulk.shared::cluster.global.mbarrier::complete_tx::bytes.multicast::cluster.L2::cache_hint [%0],[%1],%2,[%3],%4,%5;"
               :: "r"(dst), "l"(src), "r"(bytes), "r"(bar), "h"((unsigned short)3), "l"(pol) : "memory");
}

__global__ void __cluster_dims__(2, 1, 1) __launch_bounds__(TH + 128, 1)
k_deep(cudaTextureObject_t tex, const __nv_bfloat16* __restrict__ b1, const __nv_bfloat16* __restrict__ w2, int never) {
  extern __shared__ __align__(1024) uint4 sm[];
  constexpr int PF = DPF, DEPTH = DDEPTH, NW = TH / 32;
  static_assert(YD == 4, "");
  const int tid = threadIdx.x;
  const int c = blockIdx.x >> 1, half = blockIdx.x & 1;
  const uint32_t sbase = (uint32_t)__cvta_generic_to_shared(sm);
  const uint32_t fullL = sbase + SM_BAR, fullU = fullL + 8, emptyL = fullL + 16, emptyU = fullL + 24;
  TS(1, 0);
  if (tid == 0) {
    mbar_init(fullL, 1); mbar_init(fullU, 1); mbar_init(emptyL, 2 * NW); mbar_init(emptyU, 2 * NW);
    asm volatile("fence.mbarrier_init.release.cluster;" ::: "memory");
  }
  __syncwarp();
  asm volatile("barrier.cluster.arrive.relaxed.aligned; barrier.cluster.wait.aligned;" ::: "memory");
  if (__builtin_expect(tid >= TH, 1)) {
    asm volatile("setmaxnreg.dec.sync.aligned.u32 24;");
    if (tid == TH) {
      const char* base = (const char*)g_scr;
      uint32_t oL = (PL_OFF + c * NC * 8000) * 16u + half * 64000, oS = (PS_OFF + c * NC * 2000) * 16u + half * 16000;
      uint32_t oT = (PT_OFF + c * 10 * 1024) * 16u + half * 8000, oI = (IX_OFF + half * NC * 8192 + c * 128) * 16u;
      uint32_t t0 = clock();
      mbar_expect(fullU, 96000);
#pragma unroll 1
      for (int m = 0; m < 3; m++) bulk_mc(sbase + SM_U + m * 32032 + half * 16000, base + oS, 16000, fullU, m == 2 ? POL_EF : POL_N);
      bulk_pf(base + oI, 2048); bulk_pf(base + oT, 8000);
      for (int k = 1; k < NC; k++) bulk_pf(base + oI + k * 131072, 2048);
      mbar_expect(fullL, 128000);
      sleep_until(t0, (c & 3) * STAG);
      bulk_mc(sbase + half * 64000, base + oL, 64000, fullL, POL_EF);
#pragma unroll 1
      for (int k = 0; k + 1 < NC; k++) {
        oL += 128000; oS += 32000; oT += 16384; oI += 131072;
        mbar_wait(fullL, k & 1);
        t0 = clock();
        bulk_pf(base + oS, 16000);
        mbar_wait(emptyU, k & 1);
        mbar_expect(fullU, 96000 + 8192);
        { const uint32_t oW = (IX_OFF + (half * NC + min(k + 2, NC - 1)) * 8192 + ((c + (c >> 4) * 5) & 15) * 512) * 16u;
          bulk_g2s(sbase + SM_BAR + 128, base + oW, 4096, fullU); bulk_g2s(sbase + SM_BAR + 128, base + oW + 4096, 4096, fullU); }
#pragma unroll 1
        for (int q = 0; q < 8; q++) {
          sleep_until(t0, q * PACE);
          bulk_pf(base + oL + q * 8000, 8000);
          if (q >= 2) bulk_mc(sbase + SM_U + ((q - 2) >> 1) * 32032 + half * 16000 + (q & 1) * 8000, base + oS + (q & 1) * 8000, 8000, fullU, q >= 6 ? POL_EF : POL_N);
        }
        bulk_pf(base + oT, 8000);
        mbar_expect(fullL, 128000);
        mbar_wait(emptyL, k & 1);
        bulk_mc(sbase + half * 64000, base + oL, 64000, fullL, POL_EF);
      }
      bulk_pf(base + oT + 16384, 8000);
      bulk_pf(base + (I9_OFF + half * 2048 + c * 32) * 16u, 512);
    }
    return;
  }
  asm volatile("setmaxnreg.inc.sync.aligned.u32 240;");
  const int lane = tid & 31;
  const int tbase = PT_OFF + c * 10 * 1024;
  const int ibase = IX_OFF + half * NC * 8192 + tid;
  const uint32_t lc = (tid & 7) << 4;
  uint4 acc[NS], wq[PF], x[DEPTH], y[YD], ye;
  uint32_t sw[NS] = {};
  auto sget = [&](int s) { return (s & 3) == 3 ? __byte_perm(__byte_perm(sw[s - 3], sw[s - 2], 0x0073), sw[s - 1], 0x0710) : sw[s]; };
  auto sa0 = [&](uint32_t v) { return sbase + SM_U + (((v << 5) & 0x1ffe0) | ((lc >> 2) & 16)); };
  auto sa1 = [&](uint32_t v) { return sbase + SM_U + (((v >> 7) & 0x1ffe0) | ((~lc >> 2) & 16)); };
  {
    uint4 i0[8];
#pragma unroll
    for (int q = 0; q < 8; q++) i0[q] = ldtex(tex, I0_OFF + (half * 8 + q) * TH + tid);
#pragma unroll
    for (int i = 0; i < PF; i++) wq[i] = ldtex(tex, ibase + i * TH);
    auto wd = [&](int k) { return (k & 3) == 0 ? i0[k >> 2].x : (k & 3) == 1 ? i0[k >> 2].y : (k & 3) == 2 ? i0[k >> 2].z : i0[k >> 2].w; };
    mbar_wait_fast(fullU, 0);
    TS(1, 1);
#pragma unroll
    for (int s = 0; s < NS; s++) acc[s] = add4(lds128(sa0(wd(s))), lds128(sa1(wd(s))));
    arrive_both(emptyU, lane);
  }
#pragma unroll 1
  for (int k = 0; k < NC; k++) {
    const int ti = ibase + k * 8192;
    const int tb = tbase + k * 1024;
    const bool more = k + 1 < NC;
    TR(k * 4);
    mbar_wait_fast(fullL, k & 1);
    TR(k * 4 + 2);
    uint4 w, cc; uint32_t yc, yn;
    constexpr int TL = NS * 8, TT = TL + NS * 2;
#pragma unroll
    for (int t = 0; t < TT + DEPTH; t += 2) {
      if (t == TL + DEPTH && !more) break;
      if (t >= DEPTH) {
        const int u = t - DEPTH;
        uint4 p = add4(x[u % DEPTH], x[(u + 1) % DEPTH]);
        if (u < TL) {
          const int s = u >> 3, j = u & 7;
          if (j == 0) {
            cc = s >= YD ? add4(y[s % YD], p) : p;
            if (s + YD < NS) y[s % YD] = ldtex(tex, tb | (yc & 1023));
          } else cc = add4(cc, p);
          if (j == 6) acc[s] = add4(acc[s], cc);
        } else {
          const int s = (u - TL) >> 1;
          acc[s] = add4(acc[s], p);
        }
      }
      if (DEPTH == 8 && (t & 7) == 2) yc = yn;
      if (t < TL) {
        const int s = t >> 3, j = t & 7;
        if (j == 0) {
          w = wq[s % PF]; wq[s % PF] = ldtex(tex, ti + (s + PF) * TH);
          yn = __funnelshift_l(w.z, w.z, 5); if (DEPTH < 8) yc = yn;
          if ((s & 3) != 3) asm volatile("add.u32 %0,%1,%2;" : "=r"(sw[s]) : "r"(w.w), "r"(never));
          if (ye_of(s - YD) >= 0) acc[ye_of(s - YD) & 3] = add4(acc[ye_of(s - YD) & 3], ye);
          if (ye_of(s) >= 0) ye = ldtex(tex, tb | w.w);
        }
#pragma unroll
        for (int jj = j; jj < j + 2; jj++) {
          const uint32_t ww = jj < 3 ? w.x : jj < 6 ? w.y : w.z;
          const uint32_t sh = jj % 3 == 0 ? ww : jj % 3 == 1 ? ww >> 10 : __funnelshift_l(ww, ww, 12);
          x[(t + jj - j) % DEPTH] = lds128(sbase + ((sh & 0x1ff80) | lc) + jj * 16 - 128);
        }
      } else if (t < TT) {
        const int s = (t - TL) >> 1;
        if (s == 0) { arrive_both(emptyL, more ? lane : 9); TR(k * 4 + 3); mbar_wait_fast(fullU, (more ? k + 1 : k) & 1); }
        const uint32_t sv = sget(s);
        x[t % DEPTH] = lds128(sa0(sv));
        x[(t + 1) % DEPTH] = lds128(sa1(sv));
      } else if (t == TT) arrive_both(emptyU, k + 2 < NC ? lane : 9);
      if ((t & (FENCE_N - 1)) == FENCE_N - 2) SCHED_FENCE(never, t);
    }
  }
  TS(1, 2);
  uint4 i9 = ldtex(tex, I9_OFF + half * 2048 + tid), i9n = ldtex(tex, I9_OFF + half * 2048 + TH + tid);
  const uint4 b1v = *(const uint4*)(b1 + c * 8), w2v = *(const uint4*)(w2 + c * 8);
  asm volatile("bar.sync 1,%0;" :: "n"(TH) : "memory");
#pragma unroll
  for (int s = 0; s < NS; s++) sts128(sbase + (s * TH + tid) * 16, acc[s]);
  const int t9 = tbase + 9 * 1024;
  y[0] = ldtex(tex, t9 | i9.x); y[1] = ldtex(tex, t9 | i9.y); y[2] = ldtex(tex, t9 | i9.z); y[3] = ldtex(tex, t9 | i9.w);
  float bb[8], hw[8];
  {
    const uint32_t bw[4] = {b1v.x, b1v.y, b1v.z, b1v.w}, ww[4] = {w2v.x, w2v.y, w2v.z, w2v.w};
#pragma unroll
    for (int k = 0; k < 8; k++) {
      bb[k] = __uint_as_float((k & 1) ? (bw[k >> 1] & 0xffff0000u) : (bw[k >> 1] << 16));
      hw[k] = 0.5f * __uint_as_float((k & 1) ? (ww[k >> 1] & 0xffff0000u) : (ww[k >> 1] << 16));
    }
  }
  float* outp = g_partD + c * B_ + half * 8192 + tid;
#pragma unroll 1
  for (int q = 0; q < NS / 4; q++) {
    uint4 z[4];
#pragma unroll
    for (int s = 0; s < 4; s++) z[s] = add4(lds128(sbase + ((q * 4 + s) * TH + tid) * 16), y[s]);
    y[0] = ldtex(tex, t9 | i9n.x); y[1] = ldtex(tex, t9 | i9n.y); y[2] = ldtex(tex, t9 | i9n.z); y[3] = ldtex(tex, t9 | i9n.w);
    i9n = ldtex(tex, I9_OFF + half * 2048 + min(q + 2, NS / 4 - 1) * TH + tid);
#pragma unroll
    for (int s = 0; s < 4; s++) {
      const uint32_t a[4] = {z[s].x, z[s].y, z[s].z, z[s].w};
      float r0 = 0.f, r1 = 0.f;
#pragma unroll
      for (int k = 0; k < 8; k++) {
        float xv = __uint_as_float((k & 1) ? (a[k >> 1] & 0xffff0000u) : (a[k >> 1] << 16)) + bb[k];
        float u = xv * fmaf(xv * xv, 0.7978845608028654f * 0.044715f, 0.7978845608028654f);
        float th; asm("tanh.approx.f32 %0,%1;" : "=f"(th) : "f"(u));
        float hx = xv * hw[k];
        r0 = fmaf(hx, th, r0); r1 += hx;
      }
      outp[(q * 4 + s) * TH] = r0 + r1;
    }
  }
  TS(1, 3);
}

__global__ void k_final(const __nv_bfloat16* __restrict__ b2, __nv_bfloat16* __restrict__ out) {
  __shared__ float red[4][32];
  int lane = threadIdx.x & 31, q = threadIdx.x >> 5, b = blockIdx.x * 32 + lane;
  float s = 0;
#pragma unroll
  for (int k = 0; k < 16; k++) s += g_partD[(q * 16 + k) * B_ + b];
#pragma unroll
  for (int k = 0; k < 4; k++) s += g_partP[(q * 4 + k) * B_ + b];
  if (blockIdx.x == 0 && threadIdx.x < 8) g_flag[threadIdx.x * 32] = 0;
  red[q][lane] = s;
  __syncthreads();
  if (q == 0) out[b] = __float2bfloat16(red[0][lane] + red[1][lane] + red[2][lane] + red[3][lane] + __bfloat162float(b2[0]));
}

}

extern "C" void kernel_launch(void* const* d_in, const int* in_sizes, int n_in, void* d_out, int out_size) {
  const int* idx = (const int*)d_in[0];
  const __nv_bfloat16* table = (const __nv_bfloat16*)d_in[1];
  const __nv_bfloat16* wp = (const __nv_bfloat16*)d_in[2];
  const __nv_bfloat16* w1 = (const __nv_bfloat16*)d_in[3];
  const __nv_bfloat16* b1 = (const __nv_bfloat16*)d_in[4];
  const __nv_bfloat16* w2 = (const __nv_bfloat16*)d_in[5];
  const __nv_bfloat16* b2 = (const __nv_bfloat16*)d_in[6];
  static cudaTextureObject_t texScr = 0, texG = 0;
  static CUtensorMap mapW, mapL, mapS, mapT, mapE, mapC;
  static const void *c_tab = nullptr, *c_w1 = nullptr;
  if (c_tab != table || c_w1 != w1) {
    c_tab = table; c_w1 = w1;
    char* scr = nullptr; cudaGetSymbolAddress((void**)&scr, g_scr);
    auto mk_tex = [](const void* p, size_t bytes, cudaChannelFormatDesc d) {
      cudaResourceDesc rd = {}; rd.resType = cudaResourceTypeLinear; rd.res.linear.devPtr = (void*)p; rd.res.linear.desc = d; rd.res.linear.sizeInBytes = bytes;
      cudaTextureDesc td = {}; td.readMode = cudaReadModeElementType;
      cudaTextureObject_t t = 0; cudaCreateTextureObject(&t, &rd, &td, nullptr); return t;
    };
    if (!texScr) {
      texScr = mk_tex(scr, (size_t)SCR_N * 16, cudaCreateChannelDesc<uint4>());
      texG = mk_tex(scr + (size_t)PX_OFF * 16, (size_t)(SCR_N - PX_OFF) * 16, cudaCreateChannelDesc<unsigned>());
    }
    typedef CUresult (*EncFn)(CUtensorMap*, CUtensorMapDataType, cuuint32_t, void*, const cuuint64_t*, const cuuint64_t*, const cuuint32_t*,
                              const cuuint32_t*, CUtensorMapInterleave, CUtensorMapSwizzle, CUtensorMapL2promotion, CUtensorMapFloatOOBfill);
    EncFn enc = nullptr; cudaDriverEntryPointQueryResult qr;
    cudaGetDriverEntryPoint("cuTensorMapEncodeTiled", (void**)&enc, cudaEnableDefault, &qr);
    const cuuint32_t ones[4] = {1, 1, 1, 1};
    auto mk = [&](CUtensorMap* m, CUtensorMapDataType dt, int rank, void* p, const cuuint64_t* dim, const cuuint64_t* str, const cuuint32_t* box, CUtensorMapSwizzle sw) {
      enc(m, dt, rank, p, dim, str, box, ones, CU_TENSOR_MAP_INTERLEAVE_NONE, sw, CU_TENSOR_MAP_L2_PROMOTION_NONE, CU_TENSOR_MAP_FLOAT_OOB_FILL_NONE);
    };
    { cuuint64_t dim[2] = {H_, F_ * D_}, str[1] = {H_ * 2}; cuuint32_t box[2] = {32, 256};
      mk(&mapW, CU_TENSOR_MAP_DATA_TYPE_BFLOAT16, 2, (void*)w1, dim, str, box, CU_TENSOR_MAP_SWIZZLE_64B); }
    { cuuint64_t dim[4] = {64, V_, NC, 64}, str[3] = {128, 128000, 128000 * NC}; cuuint32_t box[4] = {32, 64, 1, 4};
      mk(&mapL, CU_TENSOR_MAP_DATA_TYPE_BFLOAT16, 4, scr + (size_t)PL_OFF * 16, dim, str, box, CU_TENSOR_MAP_SWIZZLE_64B); }
    { cuuint64_t dim[4] = {16, V_, NC, 64}, str[3] = {32, 32000, 32000 * NC}; cuuint32_t box[4] = {16, 64, 1, 4};
      mk(&mapS, CU_TENSOR_MAP_DATA_TYPE_BFLOAT16, 4, scr + (size_t)PS_OFF * 16, dim, str, box, CU_TENSOR_MAP_SWIZZLE_32B); }
    { cuuint64_t dim[3] = {2048, 10, 64}, str[2] = {16384, 163840}; cuuint32_t box[3] = {128, 2, 4};
      mk(&mapT, CU_TENSOR_MAP_DATA_TYPE_UINT64, 3, scr + (size_t)PT_OFF * 16, dim, str, box, CU_TENSOR_MAP_SWIZZLE_NONE); }
    { cuuint64_t dim[2] = {D_, V_}, str[1] = {D_ * 2}; cuuint32_t box[2] = {64, 128};
      mk(&mapE, CU_TENSOR_MAP_DATA_TYPE_BFLOAT16, 2, (void*)table, dim, str, box, CU_TENSOR_MAP_SWIZZLE_128B);
      cuuint32_t box2[2] = {8, 256};
      mk(&mapC, CU_TENSOR_MAP_DATA_TYPE_BFLOAT16, 2, (void*)table, dim, str, box2, CU_TENSOR_MAP_SWIZZLE_NONE); }
    cudaFuncSetAttribute(k_deep, cudaFuncAttributeMaxDynamicSharedMemorySize, DEEP_SMEM);
    cudaFuncSetAttribute(k_tens, cudaFuncAttributeMaxDynamicSharedMemorySize, K1_SMEM);
  }
  k_tens<<<132, 512, K1_SMEM>>>(mapW, mapL, mapS, mapT, mapE, mapC, texScr, texG, idx, table, wp, w1, 0);
  k_deep<<<128, TH + 128, DEEP_SMEM>>>(texScr, b1, w2, 0);
  k_final<<<B_ / 32, 128>>>(b2, (__nv_bfloat16*)d_out);
}
```

```cpp
#include <cuda_runtime.h>
#include <cuda_bf16.h>
#include <cuda_fp16.h>
#include <stdint.h>
#include <cuda.h>

namespace {

constexpr int B_ = 16384, F_ = 100, D_ = 128, V_ = 1000, H_ = 512;
constexpr int NC = 9;
constexpr int PT_OFF = 0;
constexpr int PL_OFF = 64 * 10 * 1024;
constexpr int PS_OFF = PL_OFF + 64 * NC * 8000;
constexpr int IXH = NC * 8192 + 2048;
constexpr int IX_OFF = PS_OFF + 64 * NC * 2000;
constexpr int I0_OFF = IX_OFF + 2 * IXH;
constexpr int PX_OFF = I0_OFF + 4096;
constexpr int SCR_N = PX_OFF + 64 * 16 * 136;
static_assert(PX_OFF % 32 == 0, "");

__device__ __align__(1024) uint4 g_scr[SCR_N];
__device__ float g_acc[B_];
__device__ unsigned g_done[64];
__device__ float g_partP[16 * B_];
__device__ unsigned g_flag[16 * 32];

#define TS(k, i)
#define TR(slot)
#define PT(slot)

constexpr uint64_t POL_EF = 0x12F0000000000000ull, POL_N = 0x1000000000000000ull;
__device__ __forceinline__ uint32_t addbf2(uint32_t a, uint32_t b) { uint32_t r; asm("add.rn.bf16x2 %0,%1,%2;" : "=r"(r) : "r"(a), "r"(b)); return r; }
__device__ __forceinline__ uint4 add4(const uint4& a, const uint4& b) { return make_uint4(addbf2(a.x, b.x), addbf2(a.y, b.y), addbf2(a.z, b.z), addbf2(a.w, b.w)); }
__device__ __forceinline__ void acc4(uint4& a, const uint4& b, int never) {
  asm("{.reg .pred p; setp.eq.s32 p,%8,0;\n"
      "@p add.rn.bf16x2 %0,%0,%4; @p add.rn.bf16x2 %1,%1,%5; @p add.rn.bf16x2 %2,%2,%6; @p add.rn.bf16x2 %3,%3,%7;}"
      : "+r"(a.x), "+r"(a.y), "+r"(a.z), "+r"(a.w) : "r"(b.x), "r"(b.y), "r"(b.z), "r"(b.w), "r"(never));
}
__device__ __forceinline__ uint4 ldtex(cudaTextureObject_t t, int i) {
  uint4 v; asm volatile("tex.1d.v4.u32.s32 {%0,%1,%2,%3},[%4,{%5}];" : "=r"(v.x), "=r"(v.y), "=r"(v.z), "=r"(v.w) : "l"(t), "r"(i)); return v;
}
__device__ __forceinline__ uint4 lds128(uint32_t a) {
  uint4 v; asm volatile("ld.volatile.shared.v4.u32 {%0,%1,%2,%3},[%4];" : "=r"(v.x), "=r"(v.y), "=r"(v.z), "=r"(v.w) : "r"(a)); return v;
}
__device__ __forceinline__ void sts128(uint32_t a, const uint4& v) {
  asm volatile("st.shared.v4.u32 [%0],{%1,%2,%3,%4};" :: "r"(a), "r"(v.x), "r"(v.y), "r"(v.z), "r"(v.w) : "memory");
}
__device__ __forceinline__ void mbar_init(uint32_t bar, int n) { asm volatile("mbarrier.init.shared::cta.b64 [%0],%1;" :: "r"(bar), "r"(n) : "memory"); }
__device__ __forceinline__ void mbar_wait(uint32_t bar, uint32_t parity) {
  uint32_t ok; int it = 0;
  do { asm volatile("{.reg .pred p; mbarrier.try_wait.parity.shared::cta.b64 p,[%1],%2; selp.u32 %0,1,0,p;}" : "=r"(ok) : "r"(bar), "r"(parity) : "memory"); } while (!ok && ++it < (1 << 19));
}
__device__ __forceinline__ void mbar_expect(uint32_t bar, uint32_t bytes) { asm volatile("mbarrier.arrive.expect_tx.shared::cta.b64 _,[%0],%1;" :: "r"(bar), "r"(bytes) : "memory"); }
__device__ __forceinline__ void bulk_g2s(uint32_t dst, const void* src, uint32_t bytes, uint32_t bar) {
  asm volatile("cp.async.bulk.shared::cluster.global.mbarrier::complete_tx::bytes [%0],[%1],%2,[%3];" :: "r"(dst), "l"(src), "r"(bytes), "r"(bar) : "memory");
}
__device__ __forceinline__ void bulk_pf(const void* src, uint32_t bytes) { asm volatile("cp.async.bulk.prefetch.L2.global [%0],%1;" :: "l"(src), "r"(bytes) : "memory"); }
#define NOMMA 0
#define NGRP 16
#define PDL 0
#define FIN_S 128
#define WR8 0
#define TW 1
#define PP0 10
#define PT0 10000
#define PDT 2200
#define RPNN "160"
#define RAUX "32"
#define RPRO "160"
#define PARK 0
#define NLOOK 128
#define NEF 18
#define ORD 0
#define WFENCE 0
#define SPLIT 0
#define IORD 3
#define IPF 3
#define IPACE 4500
#define WPF 3
#define QV 0
#define QORD(n) (n)
#define DYD 4
#define DPF 4
#define DDEPTH 4
#define FENCE_N 8
#define INPL 0
#define STAG 600
#define PACE 800
#define PM4 "pmevent 1; pmevent 2; pmevent 3; pmevent 4;"
#define PMFILL "pmevent 1;"
#define SCHED_FENCE(never, k) asm volatile("{.reg .pred p; setp.ne.u32 p,%0,%1; @p bra.uni SKIP_%=;" PMFILL "SKIP_%=: }" :: "r"(never), "r"(0x7fff0000 + (k)) : "memory")

__global__ void k_prod_naive(const __nv_bfloat16* __restrict__ table, const __nv_bfloat16* __restrict__ w1) {
  __shared__ float t[8][D_];
  int f = blockIdx.y, v0 = blockIdx.x * 8, h = threadIdx.x;
  for (int i = h; i < 8 * D_; i += 512) t[i / D_][i % D_] = __bfloat162float(table[v0 * D_ + i]);
  __syncthreads();
  float s[8] = {0, 0, 0, 0, 0, 0, 0, 0};
  for (int d = 0; d < D_; d++) { float w = __bfloat162float(w1[(size_t)(f * D_ + d) * H_ + h]);
#pragma unroll
    for (int k = 0; k < 8; k++) s[k] += t[k][d] * w; }
  __nv_bfloat16* P = (__nv_bfloat16*)g_scr;
  int c = h >> 3;
  for (int k = 0; k < 8; k++) {
    size_t e = f < 72 ? (size_t)PL_OFF + ((size_t)(c * NC + (f >> 3)) * 1000 + v0 + k) * 8 + (f & 7)
             : f < 90 ? (size_t)PS_OFF + ((size_t)(c * NC + ((f - 72) >> 1)) * 1000 + v0 + k) * 2 + (f & 1)
                      : (size_t)PT_OFF + (size_t)(c * 10 + f - 90) * 1024 + v0 + k;
    P[e * 8 + (h & 7)] = __float2bfloat16(s[k]);
  }
}
__global__ void k_pnn_naive(const int* __restrict__ idx, const __nv_bfloat16* __restrict__ table, const __nv_bfloat16* __restrict__ wp) {
  __shared__ float e[F_][33];
  int b = blockIdx.x, d0 = blockIdx.y * 32, tid = threadIdx.x;
  for (int i = tid; i < F_ * 32; i += 128) e[i >> 5][i & 31] = __bfloat162float(table[idx[b * F_ + (i >> 5)] * D_ + d0 + (i & 31)]);
  __syncthreads();
  float s = 0; int d = tid & 31;
  for (int i = tid >> 5; i < F_; i += 4) { float u = 0; for (int j = 0; j < F_; j++) u += __bfloat162float(wp[i * F_ + j]) * e[j][d]; s += u * e[i][d]; }
  for (int o = 16; o; o >>= 1) s += __shfl_xor_sync(~0u, s, o);
  if (d == 0) g_partP[(blockIdx.y * 4 + (tid >> 5)) * B_ + b] = s;
}
__device__ __forceinline__ void mbar_wait_fast(uint32_t bar, uint32_t parity) {
  asm volatile("{.reg .pred p; .reg .u32 n;\n"
               "mbarrier.try_wait.parity.shared::cta.b64 p,[%0],%1;\n"
               "@p bra DONE_%=;\n"
               "mov.u32 n,0;\n"
               "LOOP_%=: mbarrier.try_wait.parity.shared::cta.b64 p,[%0],%1;\n"
               "add.u32 n,n,1; setp.gt.or.u32 p,n,400000,p;\n"
               "@!p bra LOOP_%=;\n"
               "DONE_%=: }" :: "r"(bar), "r"(parity) : "memory");
}
__device__ __forceinline__ void sleep_until(uint32_t t0, uint32_t dt) { while ((uint32_t)clock() - t0 < dt) __nanosleep(40); }
__device__ __forceinline__ uint32_t s_mask(uint32_t v, int q) { return (1u << ((v + 3 - q) & 3)) | (16u << ((v + 3 + q) & 3)); }
__device__ __forceinline__ uint32_t s_cell(uint32_t v, int q, uint32_t m) {
  const int t = __ffs(~m) - 1;
  const int cp = ((t & 4 ? t - q : t + q) - v) & 3;
  return (cp == 3 ? 0 : cp) * 1001 + v;
}
__device__ __forceinline__ uint32_t pk3(uint32_t a, uint32_t b, uint32_t c) {
  const uint32_t w = c + (a << 12) + (b << 22); return __funnelshift_l(w, w, 27);
}
constexpr int TH = 256, NS = 8192 / TH, YD = DYD;
__host__ __device__ constexpr int ye_of(int s) { return s == 3 ? 0 : s == 11 ? 1 : s == 19 ? 2 : s == 23 ? 3 : -1; }
template <int N> __device__ __forceinline__ void wgmma_h(uint32_t* d, const uint32_t* a, uint64_t desc, int acc);
template <> __device__ __forceinline__ void wgmma_h<64>(uint32_t* d, const uint32_t* a, uint64_t desc, int acc) {
  asm volatile("{.reg .pred p; setp.ne.s32 p,%21,0;\n"
    "wgmma.mma_async.sync.aligned.m64n64k16.f16.f16.f16 {%0,%1,%2,%3,%4,%5,%6,%7,%8,%9,%10,%11,%12,%13,%14,%15},{%16,%17,%18,%19},%20,p,1,1,0;}"
    : "+r"(d[0]),"+r"(d[1]),"+r"(d[2]),"+r"(d[3]),"+r"(d[4]),"+r"(d[5]),"+r"(d[6]),"+r"(d[7]),"+r"(d[8]),"+r"(d[9]),"+r"(d[10]),"+r"(d[11]),"+r"(d[12]),"+r"(d[13]),"+r"(d[14]),"+r"(d[15])
    : "r"(a[0]), "r"(a[1]), "r"(a[2]), "r"(a[3]), "l"(desc), "r"(acc));
}
template <> __device__ __forceinline__ void wgmma_h<56>(uint32_t* d, const uint32_t* a, uint64_t desc, int acc) {
  asm volatile("{.reg .pred p; setp.ne.s32 p,%19,0;\n"
    "wgmma.mma_async.sync.aligned.m64n56k16.f16.f16.f16 {%0,%1,%2,%3,%4,%5,%6,%7,%8,%9,%10,%11,%12,%13},{%14,%15,%16,%17},%18,p,1,1,0;}"
    : "+r"(d[0]),"+r"(d[1]),"+r"(d[2]),"+r"(d[3]),"+r"(d[4]),"+r"(d[5]),"+r"(d[6]),"+r"(d[7]),"+r"(d[8]),"+r"(d[9]),"+r"(d[10]),"+r"(d[11]),"+r"(d[12]),"+r"(d[13])
    : "r"(a[0]), "r"(a[1]), "r"(a[2]), "r"(a[3]), "l"(desc), "r"(acc));
}
template <> __device__ __forceinline__ void wgmma_h<48>(uint32_t* d, const uint32_t* a, uint64_t desc, int acc) {
  asm volatile("{.reg .pred p; setp.ne.s32 p,%17,0;\n"
    "wgmma.mma_async.sync.aligned.m64n48k16.f16.f16.f16 {%0,%1,%2,%3,%4,%5,%6,%7,%8,%9,%10,%11},{%12,%13,%14,%15},%16,p,1,1,0;}"
    : "+r"(d[0]),"+r"(d[1]),"+r"(d[2]),"+r"(d[3]),"+r"(d[4]),"+r"(d[5]),"+r"(d[6]),"+r"(d[7]),"+r"(d[8]),"+r"(d[9]),"+r"(d[10]),"+r"(d[11])
    : "r"(a[0]), "r"(a[1]), "r"(a[2]), "r"(a[3]), "l"(desc), "r"(acc));
}
template <> __device__ __forceinline__ void wgmma_h<40>(uint32_t* d, const uint32_t* a, uint64_t desc, int acc) {
  asm volatile("{.reg .pred p; setp.ne.s32 p,%15,0;\n"
    "wgmma.mma_async.sync.aligned.m64n40k16.f16.f16.f16 {%0,%1,%2,%3,%4,%5,%6,%7,%8,%9},{%10,%11,%12,%13},%14,p,1,1,0;}"
    : "+r"(d[0]),"+r"(d[1]),"+r"(d[2]),"+r"(d[3]),"+r"(d[4]),"+r"(d[5]),"+r"(d[6]),"+r"(d[7]),"+r"(d[8]),"+r"(d[9])
    : "r"(a[0]), "r"(a[1]), "r"(a[2]), "r"(a[3]), "l"(desc), "r"(acc));
}
template <> __device__ __forceinline__ void wgmma_h<32>(uint32_t* d, const uint32_t* a, uint64_t desc, int acc) {
  asm volatile("{.reg .pred p; setp.ne.s32 p,%13,0;\n"
    "wgmma.mma_async.sync.aligned.m64n32k16.f16.f16.f16 {%0,%1,%2,%3,%4,%5,%6,%7},{%8,%9,%10,%11},%12,p,1,1,0;}"
    : "+r"(d[0]),"+r"(d[1]),"+r"(d[2]),"+r"(d[3]),"+r"(d[4]),"+r"(d[5]),"+r"(d[6]),"+r"(d[7])
    : "r"(a[0]), "r"(a[1]), "r"(a[2]), "r"(a[3]), "l"(desc), "r"(acc));
}
__device__ __forceinline__ void wgmma_p(float* d, const uint32_t* a, uint64_t desc, int acc) {
  asm volatile("{.reg .pred p; setp.ne.s32 p,%37,0;\n"
    "wgmma.mma_async.sync.aligned.m64n64k16.f32.bf16.bf16 {%0,%1,%2,%3,%4,%5,%6,%7,%8,%9,%10,%11,%12,%13,%14,%15,%16,%17,%18,%19,%20,%21,%22,%23,%24,%25,%26,%27,%28,%29,%30,%31},{%32,%33,%34,%35},%36,p,1,1,1;}"
    : "+f"(d[0]),"+f"(d[1]),"+f"(d[2]),"+f"(d[3]),"+f"(d[4]),"+f"(d[5]),"+f"(d[6]),"+f"(d[7]),"+f"(d[8]),"+f"(d[9]),"+f"(d[10]),"+f"(d[11]),"+f"(d[12]),"+f"(d[13]),"+f"(d[14]),"+f"(d[15]),"+f"(d[16]),"+f"(d[17]),"+f"(d[18]),"+f"(d[19]),"+f"(d[20]),"+f"(d[21]),"+f"(d[22]),"+f"(d[23]),"+f"(d[24]),"+f"(d[25]),"+f"(d[26]),"+f"(d[27]),"+f"(d[28]),"+f"(d[29]),"+f"(d[30]),"+f"(d[31])
    : "r"(a[0]), "r"(a[1]), "r"(a[2]), "r"(a[3]), "l"(desc), "r"(acc));
}

__device__ __forceinline__ void mma16816h(uint32_t* c, const uint32_t* a, uint32_t b0, uint32_t b1) {
  asm("mma.sync.aligned.m16n8k16.row.col.f16.f16.f16.f16 {%0,%1},{%2,%3,%4,%5},{%6,%7},{%0,%1};"
      : "+r"(c[0]), "+r"(c[1]) : "r"(a[0]), "r"(a[1]), "r"(a[2]), "r"(a[3]), "r"(b0), "r"(b1));
}
__device__ __forceinline__ void mma1688h(uint32_t* c, uint32_t a0, uint32_t a1, uint32_t b) {
  asm("mma.sync.aligned.m16n8k8.row.col.f16.f16.f16.f16 {%0,%1},{%2,%3},{%4},{%0,%1};" : "+r"(c[0]), "+r"(c[1]) : "r"(a0), "r"(a1), "r"(b));
}
__device__ __forceinline__ void mma16816f(float* c, const uint32_t* a, uint32_t b) {
  asm("mma.sync.aligned.m16n8k16.row.col.f32.f16.f16.f32 {%0,%1,%2,%3},{%4,%5,%6,%7},{%8,%8},{%0,%1,%2,%3};"
      : "+f"(c[0]), "+f"(c[1]), "+f"(c[2]), "+f"(c[3]) : "r"(a[0]), "r"(a[1]), "r"(a[2]), "r"(a[3]), "r"(b));
}
__device__ __forceinline__ uint32_t hfma2(uint32_t a, uint32_t b, uint32_t c) { uint32_t r; asm("fma.rn.f16x2 %0,%1,%2,%3;" : "=r"(r) : "r"(a), "r"(b), "r"(c)); return r; }
__device__ __forceinline__ uint32_t pack_bf2(float lo, float hi) { uint32_t r; asm("cvt.rn.bf16x2.f32 %0,%1,%2;" : "=r"(r) : "f"(hi), "f"(lo)); return r; }
__device__ __forceinline__ uint32_t pack_h2(float lo, float hi) { uint32_t r; asm("cvt.rn.f16x2.f32 %0,%1,%2;" : "=r"(r) : "f"(hi), "f"(lo)); return r; }
__device__ __forceinline__ float bf_lo(uint32_t w) { return __uint_as_float(w << 16); }
__device__ __forceinline__ float bf_hi(uint32_t w) { return __uint_as_float(w & 0xffff0000u); }
__device__ __forceinline__ uint32_t absmax4(const uint4& v, uint32_t m) {
  return __vmaxu2(__vmaxu2(__vmaxu2(v.x & 0x7fff7fffu, v.y & 0x7fff7fffu), __vmaxu2(v.z & 0x7fff7fffu, v.w & 0x7fff7fffu)), m);
}
__device__ __forceinline__ float pow2_scale(uint32_t mbits, int p) { return __uint_as_float((uint32_t)min(max(253 + p - (int)(mbits >> 7), 2), 252) << 23); }

#define PV 4
constexpr int G_O0 = 8, G_O1 = 4, G_O2 = 0, G_N0 = 5, G_N1 = 4, G_N2 = 4, G_K0 = 5, G_K1 = 3, G_K2 = 1;
__host__ __device__ constexpr bool unit_wg(int kb, int on) {
  return (on >= G_O0 && on < G_O0 + G_N0 && kb < G_K0) || (on >= G_O1 && on < G_O1 + G_N1 && kb < G_K1) || (on >= G_O2 && on < G_O2 + G_N2 && kb < G_K2);
}
__host__ __device__ constexpr bool oct_wg(int on) { return unit_wg(0, on); }
constexpr int G_U1 = G_N0 * G_K0, G_U2 = G_U1 + G_N1 * G_K1, G_U = G_U2 + G_N2 * G_K2;
constexpr int K1_B = 130048, K1_STG = K1_B + 3 * 16384, K1_W = K1_STG + 2 * 16384, K1_BAR = K1_W + 48 * 256, K1_SMEM = K1_BAR + 128;
__host__ __device__ constexpr int frag_index(int ok, int on) {
  int n = 0;
  for (int k = 0; k < 13; k++) for (int o = k; o < 13; o++) { if (k == ok && o == on) return n; if (!unit_wg(k >> 1, o)) n++; }
  return n;
}
constexpr int HU_N = 2 * G_U + frag_index(99, 99);
static_assert(HU_N <= 96, "");
struct FragIdx { int v[13][13]; };
__host__ __device__ constexpr FragIdx make_fi() { FragIdx f = {}; for (int k = 0; k < 13; k++) for (int o = 0; o < 13; o++) f.v[k][o] = frag_index(k, o); return f; }
__host__ __device__ constexpr uint64_t frag_tab(int first) {
  uint64_t t = 0;
  for (int k = 0; k < 13; k++) for (int o = k; o < 13; o++)
    if (!unit_wg(k >> 1, o)) { const int n = frag_index(k, o) - first; if (n >= 0 && n < 8) t |= (uint64_t)(k << 4 | o) << (8 * n); }
  return t;
}
__device__ __forceinline__ int hu_code(int hu) {
  constexpr uint64_t T0 = frag_tab(0), T1 = frag_tab(8), T2 = frag_tab(16), T3 = frag_tab(24);
  const int u = hu >> 1, f = hu - 2 * G_U;
  if (f >= 0) return (int)((f < 8 ? T0 : f < 16 ? T1 : f < 24 ? T2 : T3) >> (8 * (f & 7))) & 255;
  const int u0 = u < G_U1 ? u : u < G_U2 ? u - G_U1 : u - G_U2;
  const int kb = u < G_U1 ? u0 / G_N0 : u < G_U2 ? u0 / G_N1 : u0 / 4, on = u < G_U1 ? G_O0 + u0 % G_N0 : u < G_U2 ? G_O1 + u0 % G_N1 : G_O2 + u0 % 4;
  return (2 * kb + (hu & 1)) << 4 | on;
}

__device__ __forceinline__ void flag_arrive(unsigned* f, int lane) {
  __threadfence(); __syncwarp();
  if (lane == 0) asm volatile("red.release.gpu.global.add.u32 [%0],1;" :: "l"(f) : "memory");
}
__device__ __forceinline__ void flag_wait(const unsigned* f, unsigned n) {
  unsigned v; int it = 0;
  do { asm volatile("ld.acquire.gpu.global.u32 %0,[%1];" : "=r"(v) : "l"(f) : "memory"); if (v < n) __nanosleep(100); } while (v < n && ++it < (1 << 20));
}
__device__ __forceinline__ void mbar_arrive(uint32_t bar) { asm volatile("mbarrier.arrive.shared::cta.b64 _,[%0];" :: "r"(bar) : "memory"); }
__device__ __forceinline__ void mbar_arrive_lane0(uint32_t bar) {
  asm volatile("{.reg .pred p; elect.sync _|p,0xffffffff; @p mbarrier.arrive.shared::cta.b64 _,[%0];}" :: "r"(bar) : "memory");
}

__device__ __forceinline__ void pack_role(const int* __restrict__ idx, uint32_t sbase, int pc) {
  constexpr int CH = 3200 + 32, BUF = 32 * 3328;
  const int tid = threadIdx.x, lane = tid & 31, warp = tid >> 5;
  const uint32_t full = sbase + 2 * BUF, empty = full + 16;
  if (tid == 0) { mbar_init(full, 1); mbar_init(full + 8, 1); mbar_init(empty, 18); mbar_init(empty + 8, 18); asm volatile("fence.proxy.async.shared::cta;" ::: "memory"); }
  __syncthreads();
  auto chunk = [&](int s) { return s * 3200 + (s >> 2) * 288; };
  auto load = [&](int n) {
    const int blk = pc * 16 + n;
    if (lane == 0) mbar_expect(full + (n & 1) * 8, 32 * 3200);
    __syncwarp();
    bulk_g2s(sbase + (n & 1) * BUF + chunk(lane), idx + ((blk >> 5) * 8192 + lane * TH + (blk & 31) * 8) * F_, 3200, full + (n & 1) * 8);
  };
  if (warp == 0) { load(0); load(1); }
  const int l = lane & 7;
  uint32_t rot[8], inc[3];
#pragma unroll
  for (int jj = 0; jj < 8; jj++) rot[jj] = ((l + jj) & 7) * 4;
#pragma unroll
  for (int q = 0; q < 3; q++) inc[q] = (l + 3 * q < 8) << 12 | (l + 3 * q + 1 < 8) << 22 | (q < 2 && l + 3 * q + 2 < 8);
  int loaded = 2;
#pragma unroll 1
  for (int task = warp; task < 288; task += 16) {
    const int n = task / 18, q = (task % 18) * 4 + (lane >> 3), sq = q / 9, k = q % 9;
    if (warp == 0 && n + 1 == loaded && loaded < 16) { mbar_wait(empty + (loaded & 1) * 8, ((loaded >> 1) - 1) & 1); load(loaded); loaded++; }
    mbar_wait(full + (n & 1) * 8, (n >> 1) & 1);
    const uint32_t buf = sbase + (n & 1) * BUF + l * 400, row = buf + chunk(sq * 4);
    auto ld = [&](uint32_t ad) { uint32_t v; asm volatile("ld.shared.u32 %0,[%1];" : "=r"(v) : "r"(ad)); return v; };
    const int blk = pc * 16 + n, half = blk >> 5, col = (blk & 31) * 8 + l;
    const int ks = k == NC - 1 ? 0 : k + 1;
    uint32_t cw[4], sv[8], m[2] = {0, 0};
    { const uint32_t a0 = row + (72 + 2 * ks + (l >> 2)) * 4;
#pragma unroll
      for (int u = 0; u < 8; u++) { sv[u] = ld((a0 ^ ((u >> 2) * 4)) + (u & 3) * 3200); m[u >> 2] |= s_mask(sv[u], l & 3) << (8 * (u & 3)); } }
#pragma unroll
    for (int h = 0; h < 2; h++) { m[h] |= __shfl_xor_sync(0xffffffffu, m[h], 1); m[h] |= __shfl_xor_sync(0xffffffffu, m[h], 2); }
#pragma unroll
    for (int u = 0; u < 4; u++) cw[u] = s_cell(sv[u], l & 3, (m[0] >> (8 * u)) & 255) | s_cell(sv[4 + u], l & 3, (m[1] >> (8 * u)) & 255) << 12;
    if (k == NC - 1) {
      g_scr[I0_OFF + (half * 8 + sq) * TH + col] = make_uint4(cw[0], cw[1], cw[2], cw[3]);
      g_scr[IX_OFF + half * IXH + NC * 8192 + sq * TH + col] = make_uint4(ld(row + 396), ld(row + 3596), ld(row + 6796), ld(row + 9996));
      cw[0] = cw[1] = cw[2] = cw[3] = 0;
    }
    const uint32_t ax = buf + chunk(min(sq + 1, 7) * 4) + (90 + k) * 4;
    const uint32_t yev = ld(buf + ((0x3210 >> (sq * 2 + (sq == 5) * 2)) & 3) * 3200 + (90 + k) * 4);
    uint4* dst = g_scr + IX_OFF + half * IXH + (k * NS + sq * 4) * TH + col;
#pragma unroll
    for (int u = 0; u < 4; u++) {
      uint32_t e[8];
#pragma unroll
      for (int jj = 0; jj < 8; jj++) e[jj] = ld(row + k * 32 + rot[jj] + u * 3200);
      dst[u * TH] = make_uint4(pk3(e[0], e[1], e[2] + inc[0]), pk3(e[3], e[4], e[5] + inc[1]), pk3(e[6], e[7], ld(ax + u * 3200) + inc[2]),
                               u < 3 ? __byte_perm(cw[u], cw[3], 0x4210 + (u << 12)) : yev);
    }
    mbar_arrive_lane0(empty + (n & 1) * 8);
  }
  (void)CH;
}

__global__ void __launch_bounds__(512, 1)
k_tens(const __grid_constant__ CUtensorMap mapW, const __grid_constant__ CUtensorMap mapL, const __grid_constant__ CUtensorMap mapS,
       const __grid_constant__ CUtensorMap mapT, const __grid_constant__ CUtensorMap mapE, const __grid_constant__ CUtensorMap mapC, cudaTextureObject_t tex, cudaTextureObject_t texX,
       const int* __restrict__ idx, const __nv_bfloat16* __restrict__ table, const __nv_bfloat16* __restrict__ wp, const __nv_bfloat16* __restrict__ w1,
       const __nv_bfloat16* __restrict__ b1, int never) {
  extern __shared__ __align__(1024) uint4 sm[];
  const int tid = threadIdx.x, lane = tid & 31, cta = blockIdx.x;
  const uint32_t sbase = (uint32_t)__cvta_generic_to_shared(sm);
  const int g = lane >> 2, r = lane & 3;
  TS(0, 0);
  asm volatile("griddepcontrol.launch_dependents;");
  if (cta >= 128) { pack_role(idx, sbase, cta - 128); TS(2, 1); return; }
  const uint32_t fullB = sbase + K1_BAR, emptyB = fullB + 24, fullS = fullB + 48, emptyS = fullB + 64, fullE = fullB + 80, fullC = fullB + 88, fullI = fullB + 96;
  const int rb = cta & 7, hc = cta >> 3;
  if (tid >= 384) {
    asm volatile("setmaxnreg.dec.sync.aligned.u32 " RAUX ";");
    if (tid < 416) {
      auto load_pair = [&](int p, int st) {
        mbar_expect(fullB + st * 8, 16384);
        asm volatile("cp.async.bulk.tensor.2d.shared::cluster.global.mbarrier::complete_tx::bytes [%0],[%1,{%2,%3}],[%4];"
                     :: "r"(sbase + K1_B + st * 16384), "l"(&mapW), "r"(hc * 32), "r"(QORD(p >> 1) * 512 + (p & 1) * 256), "r"(fullB + st * 8) : "memory");
        p += WPF;
        if (p < 50) bulk_pf(w1 + QORD(p >> 1) * 262144 + (p & 1) * 131072 + cta * 1024, 2048);
      };
      if (tid == 384) {
        for (int q = 0; q < 3; q++) { mbar_init(fullB + q * 8, 1); mbar_init(emptyB + q * 8, 4); }
        for (int q = 0; q < 2; q++) { mbar_init(fullS + q * 8, 4); mbar_init(emptyS + q * 8, 1); }
        mbar_init(fullE, 1); mbar_init(fullC, 1); mbar_init(fullI, 1);
        asm volatile("fence.proxy.async.shared::cta;" ::: "memory");
        mbar_expect(fullC, 16384);
        for (int q = 0; q < 4; q++)
          asm volatile("cp.async.bulk.tensor.2d.shared::cluster.global.mbarrier::complete_tx::bytes [%0],[%1,{%2,%3}],[%4];"
                       :: "r"(sbase + 32768 + q * 4096), "l"(&mapC), "r"((cta & 15) * 8), "r"(q * 256), "r"(fullC) : "memory");
        mbar_expect(fullE, 32768);
        for (int q = 0; q < 2; q++)
          asm volatile("cp.async.bulk.tensor.2d.shared::cluster.global.mbarrier::complete_tx::bytes [%0],[%1,{%2,%3}],[%4];"
                       :: "r"(sbase + K1_STG + q * 16384), "l"(&mapE), "r"(q * 64), "r"(rb * 128), "r"(fullE) : "memory");
      }
      __syncwarp();
      asm volatile("bar.arrive 2,448;" ::: "memory");
      if (tid == 384) {
        int st = 0, ph = 1;
#pragma unroll 1
        for (int p = 0; p < 50; p++) {
          if (p == IORD) {
            mbar_expect(fullI, 51200);
#pragma unroll 1
            for (int q = 0; q < 8; q++) bulk_g2s(sbase + 76800 + q * 6400, idx + (((cta >> 4) * 8 + q) * 256 + (cta & 15) * 16) * F_, 6400, fullI);
          }
          mbar_wait(emptyB + st * 8, ph);
          load_pair(p, st);
          if (++st == 3) { st = 0; ph ^= 1; }
        }
      }
    } else if (tid < 448) {
      asm volatile("bar.sync 2,448;" ::: "memory");
      asm volatile("bar.sync 4,288;" ::: "memory");
      flag_arrive(&g_flag[(cta >> 4) * 32], lane);
      if (tid == 416) {
#pragma unroll 1
        for (int n = 0; n < 50; n++) {
          const int quad = QORD(n >> 1), mt = n & 1, v0 = rb * 128 + mt * 64;
          const uint32_t stg = sbase + K1_STG + mt * 16384;
          const uint64_t pol = n < 2 * NEF ? POL_EF : POL_N;
          mbar_wait(fullS + mt * 8, (n >> 1) & 1);
          asm volatile("fence.proxy.async.shared::cta;" ::: "memory");
          if (quad < 18) {
            asm volatile("cp.async.bulk.tensor.4d.global.shared::cta.bulk_group.L2::cache_hint [%0,{%1,%2,%3,%4}],[%5],%6;"
                         :: "l"(&mapL), "r"((quad & 1) * 32), "r"(v0), "r"(quad >> 1), "r"(hc * 4), "r"(stg), "l"(pol) : "memory");
          } else {
#pragma unroll 1
            for (int hh = 0; hh < 2; hh++) {
              const int pq = quad * 2 + hh;
              if (pq < 45) asm volatile("cp.async.bulk.tensor.4d.global.shared::cta.bulk_group.L2::cache_hint [%0,{%1,%2,%3,%4}],[%5],%6;"
                         :: "l"(&mapS), "r"(0), "r"(v0), "r"(pq - 36), "r"(hc * 4), "r"(stg + hh * 8192), "l"(pol) : "memory");
              else asm volatile("cp.async.bulk.tensor.3d.global.shared::cta.bulk_group.L2::cache_hint [%0,{%1,%2,%3}],[%4],%5;"
                         :: "l"(&mapT), "r"(v0 * 2), "r"((pq - 45) * 2), "r"(hc * 4), "r"(stg + hh * 8192), "l"(pol) : "memory");
            }
          }
          asm volatile("cp.async.bulk.commit_group;" ::: "memory");
          asm volatile("cp.async.bulk.wait_group.read 0;" ::: "memory");
          mbar_arrive(emptyS + mt * 8);
        }
        asm volatile("cp.async.bulk.wait_group 0;" ::: "memory");
      }
    } else if (tid < 480) {
      ((float4*)g_acc)[cta * 32 + lane] = make_float4(0.f, 0.f, 0.f, 0.f);
    }
    return;
  }
  if (tid >= 256) {
    asm volatile("setmaxnreg.inc.sync.aligned.u32 " RPRO ";");
    const int w = (tid >> 5) & 3;
    const int srow = w * 16 + (lane & 7) + ((lane >> 3) & 1) * 8, sc = lane >> 4;
    uint32_t a[2][8][4];
    asm volatile("bar.sync 2,448;" ::: "memory");
    mbar_wait_fast(fullE, 0);
#pragma unroll
    for (int mt = 0; mt < 2; mt++)
#pragma unroll
      for (int ks = 0; ks < 8; ks++)
        asm volatile("ldmatrix.sync.aligned.m8n8.x4.shared.b16 {%0,%1,%2,%3},[%4];"
                     : "=r"(a[mt][ks][0]), "=r"(a[mt][ks][1]), "=r"(a[mt][ks][2]), "=r"(a[mt][ks][3])
                     : "r"(sbase + K1_STG + (ks >> 2) * 16384 + (mt * 64 + srow) * 128 + ((((ks & 3) * 2 + sc) ^ (lane & 7)) * 16)) : "memory");
    asm volatile("bar.sync 5,128;" ::: "memory");
    const uint32_t baseL = sc * 4096 + srow * 64 + ((srow >> 1) & 3) * 16, baseS = sc * 2048 + srow * 32 + ((srow >> 2) & 1) * 16, baseT = sc * 2048 + srow * 16;
    const uint64_t desc0 = (uint64_t)(((sbase + K1_B) & 0x3FFFF) >> 4) | ((uint64_t)(8192 >> 4) << 16) | ((uint64_t)(512 >> 4) << 32) | (2ull << 62);
    float d[2][32];
    auto issue = [&](int x, int mt, int st) {
      uint32_t a7[4];
#pragma unroll
      for (int e = 0; e < 4; e++) { if (PARK) asm volatile("add.u32 %0,%1,%2;" : "=r"(a7[e]) : "r"(a[mt][7][e]), "r"(never)); else a7[e] = a[mt][7][e]; }
      asm volatile("wgmma.fence.sync.aligned;" ::: "memory");
#pragma unroll
      for (int ks = 0; ks < 8; ks++) wgmma_p(d[x], ks < 7 ? a[mt][ks] : a7, desc0 + st * 1024 + ks * 64, ks);
      asm volatile("wgmma.commit_group.sync.aligned;" ::: "memory");
    };
    auto wait_acc = [&](int x) {
      asm volatile("wgmma.wait_group.sync.aligned 0;" ::: "memory");
#pragma unroll
      for (int q = 0; q < 8; q++) asm volatile("" : "+f"(d[x][q * 4]), "+f"(d[x][q * 4 + 1]), "+f"(d[x][q * 4 + 2]), "+f"(d[x][q * 4 + 3]) :: "memory");
    };
    mbar_wait_fast(fullB, 0);
    issue(0, 0, 0);
    int s0 = 0, ph = 0;
#pragma unroll 1
    for (int qn = 0; qn < 25; qn++) {
      const int quad = QORD(qn);
      const int s1 = s0 == 2 ? 0 : s0 + 1, s2 = s1 == 2 ? 0 : s1 + 1, ph1 = ph ^ (s1 == 0), ph2 = ph1 ^ (s2 == 0);
#pragma unroll
      for (int step = 0; step < 4; step++) {
        const int mt = ORD ? step & 1 : step >> 1, h = ORD ? step >> 1 : step & 1, x = step & 1, nx = (step + 1) & 3;
        const bool isL = quad < 18, isS = quad * 2 + h < 45;
        const uint32_t base = (isL ? baseL ^ (h * 32) : (isS ? baseS : baseT) ^ (h * 8192)), xj = (isL || isS) ? 16 : 1024, xc = isL ? 8192 : 4096;
        PT(qn * 16 + step * 4);
        if (h == 0) mbar_wait_fast(emptyS + mt * 8, (qn & 1) ^ 1);
        if (step == (ORD ? 1 : 0)) mbar_wait_fast(fullB + s1 * 8, ph1);
        if (step == 3) mbar_wait_fast(fullB + s2 * 8, qn == 24 ? ph2 ^ 1 : ph2);
        PT(qn * 16 + step * 4 + 1);
        wait_acc(x);
        PT(qn * 16 + step * 4 + 2);
        if (mt) mbar_arrive_lane0(emptyB + (h ? s1 : s0) * 8);
        issue(x ^ 1, ORD ? nx & 1 : nx >> 1, step == 3 ? s2 : (ORD ? nx >> 1 : nx & 1) ? s1 : s0);
        PT(qn * 16 + step * 4 + 3);
        if (h && quad == 24) {
#pragma unroll
          for (int cq = 0; cq < 4; cq++) {
            const uint32_t bw = __ldg((const uint32_t*)(b1 + hc * 32 + cq * 8) + r);
#pragma unroll
            for (int e = 0; e < 4; e++) d[x][16 + cq * 4 + e] += (e & 1) ? bf_hi(bw) : bf_lo(bw);
          }
        }
#pragma unroll
        for (int e4 = 0; e4 < 4; e4++) {
          const float* e = d[x] + e4 * 8;
          asm volatile("stmatrix.sync.aligned.m8n8.x4.shared.b16 [%0],{%1,%2,%3,%4};"
                       :: "r"(sbase + K1_STG + mt * 16384 + (base ^ ((e4 >> 1) * xj) ^ ((e4 & 1) * xc))),
                          "r"(pack_bf2(e[0], e[1])), "r"(pack_bf2(e[2], e[3])), "r"(pack_bf2(e[4], e[5])), "r"(pack_bf2(e[6], e[7])) : "memory");
        }
        if (h) { __syncwarp(); mbar_arrive_lane0(fullS + mt * 8); }
      }
      s0 = s2; ph = ph2;
    }
    asm volatile("wgmma.wait_group.sync.aligned 0;" ::: "memory");
    return;
  }
  asm volatile("setmaxnreg.inc.sync.aligned.u32 " RPNN ";");
  const int slice = cta & 15;
  const int range = (cta >> 4) * 8 + (tid >> 5);
  uint4 iv[4], trow[4]; uint32_t ix;
  uint2 wrow[10];
#pragma unroll
  for (int q = 0; q < 10; q++) asm volatile("ld.global.nc.v2.u32 {%0,%1},[%2];" : "=r"(wrow[q].x), "=r"(wrow[q].y) : "l"((const uint2*)wp + min(tid + q * 256, 2499)));
  asm volatile("bar.sync 2,448;" ::: "memory");
  uint32_t me = 0, mw = 0;
#pragma unroll
  for (int q = 0; q < 10; q++) {
    mw = __vmaxu2(__vmaxu2(wrow[q].x & 0x7fff7fffu, wrow[q].y & 0x7fff7fffu), mw);
    const int e = min(tid + q * 256, 2499), row = e / 25;
    asm volatile("st.shared.v2.u32 [%0],{%1,%2};" :: "r"(sbase + (e + row) * 8), "r"(wrow[q].x), "r"(wrow[q].y) : "memory");
    if (e - row * 25 == 24) asm volatile("st.shared.v2.u32 [%0],{%1,%2};" :: "r"(sbase + (e + row) * 8 + 8), "r"(wrow[q].x), "r"(wrow[q].y) : "memory");
  }
  mbar_wait_fast(fullC, 0);
#pragma unroll
  for (int q = 0; q < 4; q++) { trow[q] = lds128(sbase + 32768 + (tid + q * 256) * 16); me = absmax4(trow[q], me); }
  me = __reduce_max_sync(0xffffffffu, max(me & 0xffff, me >> 16));
  mw = __reduce_max_sync(0xffffffffu, max(mw & 0xffff, mw >> 16));
  uint32_t* sred = (uint32_t*)((char*)sm + 128000);
  if (lane == 0) sred[tid >> 5] = me | mw << 16;
  TS(3, 0);
  asm volatile("bar.sync 1,256;" ::: "memory");
  { uint32_t m = 0;
#pragma unroll
    for (int q = 0; q < 8; q++) m = __vmaxu2(m, sred[q]);
    me = m & 0xffff; mw = m >> 16; }
  const float se = pow2_scale(me, 3), sW = pow2_scale(mw, -2);
  TS(3, 1);
  auto put_rows = [&](int q, bool on) {
    const uint4 t = trow[q];
    const uint4 hv = make_uint4(pack_h2(bf_lo(t.x) * se, bf_hi(t.x) * se), pack_h2(bf_lo(t.y) * se, bf_hi(t.y) * se),
                                pack_h2(bf_lo(t.z) * se, bf_hi(t.z) * se), pack_h2(bf_lo(t.w) * se, bf_hi(t.w) * se));
    if (on)
#pragma unroll
      for (int s = 0; s < 8; s++) sts128(sbase + (tid + q * 256) * 128 + ((s + lane) & 7) * 16, hv);
  };
#pragma unroll 1
  for (int it = 0; it < 3; it++) {
    const int hu = ((tid >> 5) * 3 + it) * 4, code = hu_code(min(hu + (lane >> 3), HU_N - 1)), ok = code >> 4, on = code & 15;
    uint32_t x[4], y[4];
    asm volatile("ldmatrix.sync.aligned.m8n8.x4.shared.b16 {%0,%1,%2,%3},[%4];" : "=r"(x[0]), "=r"(x[1]), "=r"(x[2]), "=r"(x[3])
                 : "r"(sbase + (on * 8 + (lane & (on == 12 ? 3 : 7))) * 208 + ok * 16) : "memory");
    asm volatile("ldmatrix.sync.aligned.m8n8.x4.trans.shared.b16 {%0,%1,%2,%3},[%4];" : "=r"(y[0]), "=r"(y[1]), "=r"(y[2]), "=r"(y[3])
                 : "r"(sbase + (ok * 8 + (lane & (ok == 12 ? 3 : 7))) * 208 + on * 16) : "memory");
    const uint32_t lo = __ballot_sync(0xffffffffu, ok > on), dg = __ballot_sync(0xffffffffu, ok >= on);
#pragma unroll
    for (int q = 0; q < 4; q++) {
      const float m0 = (lo >> (8 * q)) & 1 ? 0.f : sW, m1 = (dg >> (8 * q)) & 1 ? 0.f : sW;
      asm volatile("st.shared.u32 [%0],%1;" :: "r"(sbase + K1_W + (hu + q) * 128 + lane * 4),
                   "r"(pack_h2(fmaf(bf_lo(x[q]), m0, bf_lo(y[q]) * m1), fmaf(bf_hi(x[q]), m0, bf_hi(y[q]) * m1))) : "memory");
    }
  }
  put_rows(1, true); put_rows(2, tid < 88);
  TS(3, 2);
  asm volatile("fence.proxy.async.shared::cta;" ::: "memory");
  asm volatile("bar.sync 1,256;" ::: "memory");
  put_rows(0, true);
  uint32_t bf[HU_N - 2 * G_U];
#pragma unroll
  for (int q = 0; q < HU_N - 2 * G_U; q++) asm volatile("ld.shared.u32 %0,[%1];" : "=r"(bf[q]) : "r"(sbase + K1_W + (2 * G_U + q) * 128 + lane * 4));
  const float unscale = __uint_as_float(0x7f000000u - __float_as_uint(se)), unscale2 = __uint_as_float(0x7f000000u - __float_as_uint(sW));
  TS(3, 3);
  const int px = range * 16 * 136;
  mbar_wait_fast(fullI, 0);
  {
    const uint32_t ib = sbase + 76800 + (tid >> 5) * 6400, p0 = ib + ((lane >> 3) & 1) * 400 + ((lane >> 4) * 8 + (lane & 7)) * 4;
    auto ld = [&](uint32_t ad) { uint32_t v; asm volatile("ld.shared.u32 %0,[%1];" : "=r"(v) : "r"(ad)); return v; };
    auto wd = [&](int t, int h) { return pk3(ld(p0 + t * 800 + h * 192), ld(p0 + t * 800 + h * 192 + 64), ld(p0 + t * 800 + h * 192 + 128)); };
#pragma unroll
    for (int q = 0; q < 4; q++) {
      iv[q] = make_uint4(wd(2 * q, 0), wd(2 * q, 1), wd(2 * q + 1, 0), wd(2 * q + 1, 1));
      g_scr[PX_OFF + px + slice * 136 + q * 32 + lane] = iv[q];
    }
    ix = pk3(ld(ib + g * 400 + 384 + r * 4), ld(ib + (8 + g) * 400 + 384 + r * 4), 0);
    ((uint32_t*)(g_scr + PX_OFF + px + slice * 136 + 128))[lane] = ix;
  }
  asm volatile("bar.arrive 4,288;" ::: "memory");
  asm volatile("bar.sync 1,256;" ::: "memory");
  put_rows(2, tid >= 88); put_rows(3, tid + 768 < V_);
  asm volatile("bar.sync 1,256;" ::: "memory");
  TS(0, 1);
  const uint32_t lc = (lane & 7) * 16;
  const uint64_t wdesc = (uint64_t)(((sbase + K1_W) & 0x3FFFF) >> 4) | ((uint64_t)(128 >> 4) << 16) | ((uint64_t)(256 >> 4) << 32);
  uint32_t a[2][6][4], d[2][26], ex[4] = {}, s[4] = {};
  float red[4] = {0.f, 0.f, 0.f, 0.f};
  auto ldsm = [&](uint32_t* o, uint32_t sh) {
    asm volatile("ldmatrix.sync.aligned.m8n8.x4.trans.shared.b16 {%0,%1,%2,%3},[%4];"
                 : "=r"(o[0]), "=r"(o[1]), "=r"(o[2]), "=r"(o[3]) : "r"(sbase + ((sh & 0x1ff80) | lc)));
  };
  auto gather = [&](int t, int hf) {
    const int x = t & 1;
    const uint4 v = iv[(t >> 1) & 3];
#pragma unroll
    for (int kb = 3 * hf; kb < 3 * hf + 3; kb++) {
      const uint32_t ww = x ? (kb < 3 ? v.z : v.w) : (kb < 3 ? v.x : v.y);
      ldsm(a[x][kb], kb % 3 == 0 ? ww : kb % 3 == 1 ? ww >> 10 : __funnelshift_l(ww, ww, 12));
    }
  };
  auto issue = [&](int x) {
    asm volatile("wgmma.fence.sync.aligned;" ::: "memory");
#pragma unroll
    for (int kb = 0; kb < 6; kb++) {
      if (kb < G_K0) wgmma_h<G_N0 * 8>(d[x] + G_O0 * 2, a[x][kb], wdesc + kb * G_N0 * 16, kb);
      if (kb < G_K1) wgmma_h<G_N1 * 8>(d[x] + G_O1 * 2, a[x][kb], wdesc + (G_U1 + kb * G_N1) * 16, kb);
      if (kb < G_K2) wgmma_h<32>(d[x] + G_O2 * 2, a[x][kb], wdesc + (G_U2 + kb * G_N2) * 16, kb);
    }
    asm volatile("wgmma.commit_group.sync.aligned;" ::: "memory");
  };
  auto hmma_part = [&](int t) {
    constexpr FragIdx FI = make_fi();
    const int x = t & 1;
#pragma unroll
    for (int o = 0; o < 13; o++) {
      if (oct_wg(o)) asm volatile("" : "+r"(d[x][o * 2]), "+r"(d[x][o * 2 + 1]) :: "memory"); else d[x][o * 2] = d[x][o * 2 + 1] = 0;
    }
#pragma unroll
    for (int kb = 0; kb < 6; kb++)
#pragma unroll
      for (int o = 2 * kb + 1; o < 13; o++)
        if (!unit_wg(kb, o)) mma16816h(d[x] + o * 2, a[x][kb], bf[FI.v[2 * kb][o]], bf[FI.v[2 * kb + 1][o]]);
#pragma unroll
    for (int q = 0; q < 6; q++) if (!unit_wg(q, 2 * q)) mma1688h(d[x] + q * 4, a[x][q][0], a[x][q][1], bf[FI.v[2 * q][2 * q]]);
    mma1688h(d[x] + 24, r < 2 ? ex[t & 3] : 0u, r < 2 ? 0u : ex[t & 3], bf[FI.v[12][12]]);
  };
  auto dot_part = [&](int t, int hf) {
    const int x = t & 1;
    if (hf == 0) {
      const uint32_t pe = hfma2(r < 2 ? d[x][24] : d[x][25], ex[t & 3], 0u);
      s[0] = r < 2 ? pe : 0u; s[1] = r < 2 ? 0u : pe; s[2] = s[3] = 0;
    }
#pragma unroll
    for (int q = 3 * hf; q < 3 * hf + 3; q++)
#pragma unroll
      for (int e = 0; e < 4; e++) s[e] = hfma2(d[x][q * 4 + e], a[x][q][e], s[e]);
  };
  float* outp = g_partP + slice * B_ + range * 256 + r * 4 + ((lane >> 3) & 1) * 2 + (lane >> 4);
  float k0 = 0.f, k1 = 0.f, x0 = 0.f, x1 = 0.f;
  auto red_stage = [&](int st, int grp) {
    const bool u16 = lane & 16, u8 = lane & 8;
    if (st == 0) {
      k0 = u16 ? red[2] : red[0]; x0 = __shfl_xor_sync(0xffffffffu, u16 ? red[0] : red[2], 16);
      k1 = u16 ? red[3] : red[1]; x1 = __shfl_xor_sync(0xffffffffu, u16 ? red[1] : red[3], 16);
      red[0] = red[1] = red[2] = red[3] = 0.f;
    }
    if (st == 1) { const float p0 = k0 + x0, p1 = k1 + x1; k0 = u8 ? p1 : p0; x0 = __shfl_xor_sync(0xffffffffu, u8 ? p0 : p1, 8); }
    if (st == 2) { k0 += x0; x0 = __shfl_xor_sync(0xffffffffu, k0, 4); }
    if (st == 3 && !(lane & 4)) outp[grp * 16] = (k0 + x0) * unscale * unscale * unscale2;
  };
  auto group = [&](bool first, int prv, int cur, int nxt) {
    const int pn = PX_OFF + px + nxt * 136 + lane;
#pragma unroll
    for (int t = 0; t < 8; t++) {
      issue((t & 1) ^ 1);
      SCHED_FENCE(never, t * 8);
      if (!first) {
        if (t == 0) { iv[3] = ldtex(tex, PX_OFF + px + cur * 136 + lane + 96); iv[0] = ldtex(tex, pn); }
        if (t == 2) iv[1] = ldtex(tex, pn + 32);
        if (t < 4) red_stage(t, prv);
      } else if (t == 4) {
        flag_wait(&g_flag[(cta >> 4) * 32], 16);
        iv[0] = ldtex(tex, pn); iv[1] = ldtex(tex, pn + 32);
      }
      if (t == 4) { ix = ldtex(texX, (px + nxt * 136 + 128) * 4 + lane).x; iv[2] = ldtex(tex, pn + 64); }
      dot_part(t, 0); dot_part(t, 1);
      SCHED_FENCE(never, t * 8 + 1);
      if (t == 3) ldsm(ex, ix >> 10);
      if (t == 7) ldsm(ex, ix);
      gather(t + 2, 0); gather(t + 2, 1);
      asm volatile("wgmma.wait_group.sync.aligned 0;" ::: "memory");
      SCHED_FENCE(never, t * 8 + 2);
      mma16816f(red, s, g == t ? 0x3c003c00u : 0u);
      hmma_part(t + 1);
      SCHED_FENCE(never, t * 8 + 3);
    }
  };
  gather(0, 0); gather(0, 1); issue(0); ldsm(ex, ix); gather(1, 0); gather(1, 1);
  asm volatile("wgmma.wait_group.sync.aligned 0;" ::: "memory");
  hmma_part(0);
  int prv = slice, cur = slice == 0;
  group(true, 0, prv, cur);
  TS(4, 1);
#pragma unroll 1
  for (int n = 1; n < NGRP; n++) {
    const int nxt = (n + (n >= slice)) & 15;
    group(false, prv, cur, nxt);
    prv = cur; cur = nxt;
  }
#pragma unroll
  for (int st = 0; st < 4; st++) red_stage(st, prv);
  TS(0, 2);
}

constexpr int SM_U = 130048, SM_BAR = 128000, SM_J = SM_U + 98304, DEEP_SMEM = SM_J + 4096;

__device__ __forceinline__ void arrive_both(uint32_t bar, int lane) {
  asm volatile("{.reg .pred p; .reg .u32 a; setp.lt.u32 p,%1,2; mapa.shared::cluster.u32 a,%0,%1;\n"
               "@p mbarrier.arrive.shared::cluster.b64 _,[a];}" :: "r"(bar), "r"(lane) : "memory");
}
__device__ __forceinline__ void bulk_mc(uint32_t dst, const void* src, uint32_t bytes, uint32_t bar, uint64_t pol) {
  asm volatile("cp.async.bulk.shared::cluster.global.mbarrier::complete_tx::bytes.multicast::cluster.L2::cache_hint [%0],[%1],%2,[%3],%4,%5;"
               :: "r"(dst), "l"(src), "r"(bytes), "r"(bar), "h"((unsigned short)3), "l"(pol) : "memory");
}

__global__ void __cluster_dims__(2, 1, 1) __launch_bounds__(TH + 128, 1)
k_deep(cudaTextureObject_t tex, const __nv_bfloat16* __restrict__ w2, const __nv_bfloat16* __restrict__ b2,
       __nv_bfloat16* __restrict__ out, int never) {
  extern __shared__ __align__(1024) uint4 sm[];
  constexpr int PF = DPF, DEPTH = DDEPTH, NW = TH / 32;
  static_assert(YD == 4 && PF == 4, "");
  const int tid = threadIdx.x;
  const int c = blockIdx.x >> 1, half = blockIdx.x & 1;
  const uint32_t sbase = (uint32_t)__cvta_generic_to_shared(sm);
  const uint32_t fullL = sbase + SM_BAR, fullU = fullL + 8, emptyL = fullL + 16, emptyU = fullL + 24, barJ = fullL + 32;
  TS(1, 0);
  if (tid == 0) {
    mbar_init(fullL, 1); mbar_init(fullU, 1); mbar_init(emptyL, 2 * NW); mbar_init(emptyU, 2 * NW); mbar_init(barJ, 1);
    asm volatile("fence.mbarrier_init.release.cluster;" ::: "memory");
  }
  __syncwarp();
  asm volatile("barrier.cluster.arrive.relaxed.aligned; barrier.cluster.wait.aligned;" ::: "memory");
  asm volatile("griddepcontrol.wait;" ::: "memory");
  TS(5, 1);
  if (__builtin_expect(tid >= TH, 1)) {
    asm volatile("setmaxnreg.dec.sync.aligned.u32 24;");
    if (tid == TH) {
      const char* base = (const char*)g_scr;
      uint32_t oL = (PL_OFF + c * NC * 8000) * 16u + half * 64000, oS = (PS_OFF + c * NC * 2000) * 16u + half * 16000;
      uint32_t oT = (PT_OFF + c * 10 * 1024) * 16u + half * 8192;
      const uint32_t junk = sbase + SM_J, oW = (IX_OFF + half * IXH + (WR8 ? ((c + (c >> 3) * 3) & 7) * 1024 : ((c + (c >> 4) * 5) & 15) * 512)) * 16u;
      auto warm = [&](uint32_t off) {
        asm volatile("mbarrier.expect_tx.relaxed.cta.shared::cta.b64 [%0],%1;" :: "r"(barJ), "r"(8192) : "memory");
        bulk_g2s(junk, base + off, 4096, barJ); bulk_g2s(junk, base + off + 4096, 4096, barJ);
      };
      uint32_t t0 = clock();
      mbar_expect(fullU, 96000);
#pragma unroll 1
      for (int m = 0; m < 3; m++) bulk_mc(sbase + SM_U + m * 32032 + half * 16000, base + oS, 16000, fullU, m == 2 ? POL_EF : POL_N);
      warm(oW); if (WR8) warm(oW + 8192);
      if (TW) warm(oT); else bulk_pf(base + oT, 8192);
      mbar_expect(fullL, 128000);
      sleep_until(t0, (c & 3) * STAG);
      bulk_mc(sbase + half * 64000, base + oL, 64000, fullL, POL_EF);
      warm(oW + 131072); if (WR8) warm(oW + 131072 + 8192);
#pragma unroll 1
      for (int k = 0; k + 1 < NC; k++) {
        oL += 128000; oS += 32000; oT += 16384;
        mbar_wait(fullL, k & 1);
        t0 = clock();
        bulk_pf(base + oS, 16000);
        if (k + 2 < NC) { warm(oW + (k + 2) * 131072); if (WR8) warm(oW + (k + 2) * 131072 + 8192); }
        mbar_wait(emptyU, k & 1);
        mbar_expect(fullU, 96000);
#pragma unroll 1
        for (int q = 0; q < 8; q++) {
          sleep_until(t0, q * PACE);
          bulk_pf(base + oL + q * 8000, 8000);
          if (q >= 2) bulk_mc(sbase + SM_U + ((q - 2) >> 1) * 32032 + half * 16000 + (q & 1) * 8000, base + oS + (q & 1) * 8000, 8000, fullU, q >= 6 ? POL_EF : POL_N);
        }
        if (TW) warm(oT); else bulk_pf(base + oT, 8192);
        mbar_expect(fullL, 128000);
        mbar_wait(emptyL, k & 1);
        bulk_mc(sbase + half * 64000, base + oL, 64000, fullL, POL_EF);
      }
      mbar_wait(fullL, (NC - 1) & 1);
      mbar_wait(emptyU, (NC - 1) & 1);
      mbar_arrive(fullU);
      warm(oT + 16384);
      warm((IX_OFF + half * IXH + NC * 8192 + (c & 3) * 512) * 16u);
      mbar_arrive(barJ); mbar_wait(barJ, 0);
    } else if (tid >= TH + 96) {
      if (tid == TH + 96) sts128(barJ + 32, *(const uint4*)(w2 + c * 8));
      asm volatile("bar.arrive 3,%0;" :: "n"(TH + 32) : "memory");
      const int b = half * 8192 + c * 128 + (tid & 31) * 4;
      const float bias = __bfloat162float(b2[0]);
      float4 s = make_float4(bias, bias, bias, bias);
#pragma unroll 2
      for (int k = 0; k < 16; k++) { const float4 v = __ldcg((const float4*)(g_partP + k * B_ + b)); s.x += v.x; s.y += v.y; s.z += v.z; s.w += v.w; }
      asm volatile("red.global.add.v4.f32 [%0],{%1,%2,%3,%4};" :: "l"(g_acc + b), "f"(s.x), "f"(s.y), "f"(s.z), "f"(s.w) : "memory");
      if (blockIdx.x == 0 && tid < TH + 104) g_flag[(tid & 7) * 32] = 0;
      asm volatile("bar.arrive 1,%0;" :: "n"(TH + 32) : "memory");
    }
    return;
  }
  asm volatile("setmaxnreg.inc.sync.aligned.u32 240;");
  const int lane = tid & 31;
  const int tbase = PT_OFF + c * 10 * 1024;
  const int ibase = IX_OFF + half * IXH + tid;
  const uint32_t lc = (tid & 7) << 4;
  uint4 acc[NS], wq[PF], x[DEPTH], y[YD], ye;
  uint32_t sw[NS] = {};
  auto sget = [&](int s) { return (s & 3) == 3 ? __byte_perm(__byte_perm(sw[s - 3], sw[s - 2], 0x0073), sw[s - 1], 0x0710) : sw[s]; };
  auto sa0 = [&](uint32_t v) { return sbase + SM_U + (((v << 5) & 0x1ffe0) | ((lc >> 2) & 16)); };
  auto sa1 = [&](uint32_t v) { return sbase + SM_U + (((v >> 7) & 0x1ffe0) | ((~lc >> 2) & 16)); };
  {
    uint4 i0[8];
#pragma unroll
    for (int q = 0; q < 8; q++) i0[q] = ldtex(tex, I0_OFF + (half * 8 + q) * TH + tid);
#pragma unroll
    for (int i = 0; i < PF; i++) wq[i] = ldtex(tex, ibase + i * TH);
    auto wd = [&](int k) { return (k & 3) == 0 ? i0[k >> 2].x : (k & 3) == 1 ? i0[k >> 2].y : (k & 3) == 2 ? i0[k >> 2].z : i0[k >> 2].w; };
    asm volatile("bar.sync 3,%0;" :: "n"(TH + 32) : "memory");
    mbar_wait_fast(fullU, 0);
    TS(1, 1);
#pragma unroll
    for (int s = 0; s < NS; s++) acc[s] = add4(lds128(sa0(wd(s))), lds128(sa1(wd(s))));
    arrive_both(emptyU, lane);
  }
#pragma unroll 1
  for (int k = 0; k < NC; k++) {
    const int ti = ibase + k * 8192;
    const int tb = tbase + k * 1024;
    const bool more = k + 1 < NC;
    TR(k * 4);
    mbar_wait_fast(fullL, k & 1);
    TR(k * 4 + 2);
    uint4 w, cc; uint32_t yc, yn;
    constexpr int TL = NS * 8, TT = TL + NS * 2;
#pragma unroll
    for (int t = 0; t < TT + DEPTH; t += 2) {
      if (t == TL + DEPTH && !more) break;
      if (t >= DEPTH) {
        const int u = t - DEPTH;
        uint4 p = add4(x[u % DEPTH], x[(u + 1) % DEPTH]);
        if (u < TL) {
          const int s = u >> 3, j = u & 7;
          if (j == 0) {
            cc = s >= YD ? add4(y[s % YD], p) : p;
            if (s + YD < NS) y[s % YD] = ldtex(tex, tb | (yc & 1023));
          } else cc = add4(cc, p);
          if (j == 6) acc[s] = add4(acc[s], cc);
        } else {
          const int s = (u - TL) >> 1;
          acc[s] = add4(acc[s], p);
        }
      }
      if (DEPTH == 8 && (t & 7) == 2) yc = yn;
      if (t < TL) {
        const int s = t >> 3, j = t & 7;
        if (j == 0) {
          w = wq[s % PF]; wq[s % PF] = ldtex(tex, ti + (s + PF) * TH);
          yn = __funnelshift_l(w.z, w.z, 5); if (DEPTH < 8) yc = yn;
          if ((s & 3) != 3) asm volatile("add.u32 %0,%1,%2;" : "=r"(sw[s]) : "r"(w.w), "r"(never));
          if (ye_of(s - YD) >= 0) acc[ye_of(s - YD) & 3] = add4(acc[ye_of(s - YD) & 3], ye);
          if (ye_of(s) >= 0) ye = ldtex(tex, tb | w.w);
        }
#pragma unroll
        for (int jj = j; jj < j + 2; jj++) {
          const uint32_t ww = jj < 3 ? w.x : jj < 6 ? w.y : w.z;
          const uint32_t sh = jj % 3 == 0 ? ww : jj % 3 == 1 ? ww >> 10 : __funnelshift_l(ww, ww, 12);
          x[(t + jj - j) % DEPTH] = lds128(sbase + ((sh & 0x1ff80) | lc) + jj * 16 - 128);
        }
      } else if (t < TT) {
        const int s = (t - TL) >> 1;
        if (s == 0) { arrive_both(emptyL, more ? lane : 9); TR(k * 4 + 3); mbar_wait_fast(fullU, (k + 1) & 1); }
        const uint32_t sv = sget(s);
        x[t % DEPTH] = lds128(sa0(sv));
        x[(t + 1) % DEPTH] = lds128(sa1(sv));
      } else if (t == TT) arrive_both(emptyU, lane);
      if ((t & (FENCE_N - 1)) == FENCE_N - 2) SCHED_FENCE(never, t);
    }
  }
  TS(1, 2);
  const uint4 w2v = lds128(barJ + 32);
  const uint32_t cell = sbase + SM_U + tid * 16;
  const int t9 = tbase + 9 * 1024;
  uint4 za[4], i9 = wq[0];
  auto fetch = [&](int q) {
    y[0] = ldtex(tex, t9 | i9.x); y[1] = ldtex(tex, t9 | i9.y); y[2] = ldtex(tex, t9 | i9.z); y[3] = ldtex(tex, t9 | i9.w);
    if (q) {
      i9 = ldtex(tex, ibase + NC * 8192 + min(q + 1, 7) * TH);
      const uint32_t ca = cell + (q > 6 ? 0 : q - 1) * 16384;
#pragma unroll
      for (int s = 0; s < 4; s++) za[s] = lds128(ca + s * 4096);
    }
  };
  fetch(0);
  i9 = wq[1];
#pragma unroll
  for (int s = 0; s < 4; s++) za[s] = acc[s];
#pragma unroll
  for (int s = 0; s < 24; s++) sts128(cell + s * 4096, acc[4 + s]);
  float hw[8];
  {
    const uint32_t ww[4] = {w2v.x, w2v.y, w2v.z, w2v.w};
#pragma unroll
    for (int k = 0; k < 8; k++) hw[k] = 0.5f * ((k & 1) ? bf_hi(ww[k >> 1]) : bf_lo(ww[k >> 1]));
  }
  float* outp = g_acc + half * 8192 + tid;
#pragma unroll 1
  for (int q = 0; q < NS / 4; q++) {
    uint4 z[4];
#pragma unroll
    for (int s = 0; s < 4; s++) z[s] = add4(za[s], y[s]);
    if (q == 1) {
#pragma unroll
      for (int s = 0; s < 4; s++) sts128(cell + s * 4096, acc[28 + s]);
    }
    if (q < 7) fetch(q + 1);
    SCHED_FENCE(never, 999);
#pragma unroll
    for (int s = 0; s < 4; s++) {
      const uint32_t a[4] = {z[s].x, z[s].y, z[s].z, z[s].w};
      float r0 = 0.f;
#pragma unroll
      for (int k = 0; k < 8; k++) {
        const float v = (k & 1) ? bf_hi(a[k >> 1]) : bf_lo(a[k >> 1]);
        const float u = v * fmaf(v * v, 0.7978845608028654f * 0.044715f, 0.7978845608028654f);
        float th; asm("tanh.approx.f32 %0,%1;" : "=f"(th) : "f"(u));
        r0 = fmaf(fmaf(v, th, v), hw[k], r0);
      }
      asm volatile("red.global.add.f32 [%0],%1;" :: "l"(outp + s * TH), "f"(r0) : "memory");
    }
    outp += 4 * TH;
  }
  TS(1, 3);
  asm volatile("bar.sync 1,%0;" :: "n"(TH + 32) : "memory");
  if (tid == 0) {
    __threadfence();
    const unsigned old = atomicInc(&g_done[half * 32], 63);
    asm volatile("st.shared.u32 [%0],%1;" :: "r"(barJ + 8), "r"(old) : "memory");
  }
  asm volatile("bar.sync 2,%0;" :: "n"(TH) : "memory");
  uint32_t old; asm volatile("ld.shared.u32 %0,[%1];" : "=r"(old) : "r"(barJ + 8));
  if (old == 63) {
    __threadfence();
    float4 v[8];
#pragma unroll
    for (int q = 0; q < 8; q++) v[q] = __ldcg((const float4*)(g_acc + half * 8192) + q * TH + tid);
#pragma unroll
    for (int q = 0; q < 8; q++) ((uint2*)(out + half * 8192))[q * TH + tid] = make_uint2(pack_bf2(v[q].x, v[q].y), pack_bf2(v[q].z, v[q].w));
    TS(6, 2);
  }
}

}

extern "C" void kernel_launch(void* const* d_in, const int* in_sizes, int n_in, void* d_out, int out_size) {
  const int* idx = (const int*)d_in[0];
  const __nv_bfloat16* table = (const __nv_bfloat16*)d_in[1];
  const __nv_bfloat16* wp = (const __nv_bfloat16*)d_in[2];
  const __nv_bfloat16* w1 = (const __nv_bfloat16*)d_in[3];
  const __nv_bfloat16* b1 = (const __nv_bfloat16*)d_in[4];
  const __nv_bfloat16* w2 = (const __nv_bfloat16*)d_in[5];
  const __nv_bfloat16* b2 = (const __nv_bfloat16*)d_in[6];
  static cudaTextureObject_t texScr = 0, texG = 0;
  static CUtensorMap mapW, mapL, mapS, mapT, mapE, mapC;
  static const void *c_tab = nullptr, *c_w1 = nullptr;
  if (c_tab != table || c_w1 != w1) {
    c_tab = table; c_w1 = w1;
    char* scr = nullptr; cudaGetSymbolAddress((void**)&scr, g_scr);
    auto mk_tex = [](const void* p, size_t bytes, cudaChannelFormatDesc d) {
      cudaResourceDesc rd = {}; rd.resType = cudaResourceTypeLinear; rd.res.linear.devPtr = (void*)p; rd.res.linear.desc = d; rd.res.linear.sizeInBytes = bytes;
      cudaTextureDesc td = {}; td.readMode = cudaReadModeElementType;
      cudaTextureObject_t t = 0; cudaCreateTextureObject(&t, &rd, &td, nullptr); return t;
    };
    if (!texScr) {
      texScr = mk_tex(scr, (size_t)SCR_N * 16, cudaCreateChannelDesc<uint4>());
      texG = mk_tex(scr + (size_t)PX_OFF * 16, (size_t)(SCR_N - PX_OFF) * 16, cudaCreateChannelDesc<unsigned>());
    }
    typedef CUresult (*EncFn)(CUtensorMap*, CUtensorMapDataType, cuuint32_t, void*, const cuuint64_t*, const cuuint64_t*, const cuuint32_t*,
                              const cuuint32_t*, CUtensorMapInterleave, CUtensorMapSwizzle, CUtensorMapL2promotion, CUtensorMapFloatOOBfill);
    EncFn enc = nullptr; cudaDriverEntryPointQueryResult qr;
    cudaGetDriverEntryPoint("cuTensorMapEncodeTiled", (void**)&enc, cudaEnableDefault, &qr);
    const cuuint32_t ones[4] = {1, 1, 1, 1};
    auto mk = [&](CUtensorMap* m, CUtensorMapDataType dt, int rank, void* p, const cuuint64_t* dim, const cuuint64_t* str, const cuuint32_t* box, CUtensorMapSwizzle sw) {
      enc(m, dt, rank, p, dim, str, box, ones, CU_TENSOR_MAP_INTERLEAVE_NONE, sw, CU_TENSOR_MAP_L2_PROMOTION_NONE, CU_TENSOR_MAP_FLOAT_OOB_FILL_NONE);
    };
    { cuuint64_t dim[2] = {H_, F_ * D_}, str[1] = {H_ * 2}; cuuint32_t box[2] = {32, 256};
      mk(&mapW, CU_TENSOR_MAP_DATA_TYPE_BFLOAT16, 2, (void*)w1, dim, str, box, CU_TENSOR_MAP_SWIZZLE_64B); }
    { cuuint64_t dim[4] = {64, V_, NC, 64}, str[3] = {128, 128000, 128000 * NC}; cuuint32_t box[4] = {32, 64, 1, 4};
      mk(&mapL, CU_TENSOR_MAP_DATA_TYPE_BFLOAT16, 4, scr + (size_t)PL_OFF * 16, dim, str, box, CU_TENSOR_MAP_SWIZZLE_64B); }
    { cuuint64_t dim[4] = {16, V_, NC, 64}, str[3] = {32, 32000, 32000 * NC}; cuuint32_t box[4] = {16, 64, 1, 4};
      mk(&mapS, CU_TENSOR_MAP_DATA_TYPE_BFLOAT16, 4, scr + (size_t)PS_OFF * 16, dim, str, box, CU_TENSOR_MAP_SWIZZLE_32B); }
    { cuuint64_t dim[3] = {2048, 10, 64}, str[2] = {16384, 163840}; cuuint32_t box[3] = {128, 2, 4};
      mk(&mapT, CU_TENSOR_MAP_DATA_TYPE_UINT64, 3, scr + (size_t)PT_OFF * 16, dim, str, box, CU_TENSOR_MAP_SWIZZLE_NONE); }
    { cuuint64_t dim[2] = {D_, V_}, str[1] = {D_ * 2}; cuuint32_t box[2] = {64, 128};
      mk(&mapE, CU_TENSOR_MAP_DATA_TYPE_BFLOAT16, 2, (void*)table, dim, str, box, CU_TENSOR_MAP_SWIZZLE_128B);
      cuuint32_t box2[2] = {8, 256};
      mk(&mapC, CU_TENSOR_MAP_DATA_TYPE_BFLOAT16, 2, (void*)table, dim, str, box2, CU_TENSOR_MAP_SWIZZLE_NONE); }
    cudaFuncSetAttribute(k_deep, cudaFuncAttributeMaxDynamicSharedMemorySize, DEEP_SMEM);
    cudaFuncSetAttribute(k_tens, cudaFuncAttributeMaxDynamicSharedMemorySize, K1_SMEM);
  }
  k_tens<<<132, 512, K1_SMEM, cudaStreamPerThread>>>(mapW, mapL, mapS, mapT, mapE, mapC, texScr, texG, idx, table, wp, w1, b1, 0);
  cudaLaunchAttribute at[1];
  at[0].id = cudaLaunchAttributeProgrammaticStreamSerialization; at[0].val.programmaticStreamSerializationAllowed = 1;
  cudaLaunchConfig_t cfg = {};
  cfg.stream = cudaStreamPerThread; cfg.attrs = at;
  cfg.gridDim = 128; cfg.blockDim = TH + 128; cfg.dynamicSmemBytes = DEEP_SMEM; cfg.numAttrs = PDL & 1;
  cudaLaunchKernelEx(&cfg, k_deep, texScr, w2, b2, (__nv_bfloat16*)d_out, 0);

}
```

```cpp
#include <cuda_runtime.h>
#include <cuda_bf16.h>
#include <cuda_fp16.h>
#include <stdint.h>
#include <cuda.h>

namespace {

constexpr int B_ = 16384, F_ = 100, D_ = 128, V_ = 1000, H_ = 512;
constexpr int NC = 9;
constexpr int PT_OFF = 0;
constexpr int PL_OFF = 64 * 10 * 1024;
constexpr int PS_OFF = PL_OFF + 64 * NC * 8000;
constexpr int IXH = NC * 8192 + 2048;
constexpr int IX_OFF = PS_OFF + 64 * NC * 2000;
constexpr int I0_OFF = IX_OFF + 2 * IXH;
constexpr int PX_OFF = I0_OFF + 4096;
constexpr int SCR_N = PX_OFF + 64 * 16 * 136;
static_assert(PX_OFF % 32 == 0, "");

__device__ __align__(1024) uint4 g_scr[SCR_N];
__device__ float g_acc[B_];
__device__ unsigned g_done[64];
__device__ float g_partP[16 * B_];
__device__ unsigned g_flag[16 * 32];

#define TS(k, i)
#define TR(slot)
#define PT(slot)

constexpr uint64_t POL_EF = 0x12F0000000000000ull, POL_N = 0x1000000000000000ull;
__device__ __forceinline__ uint32_t addbf2(uint32_t a, uint32_t b) { uint32_t r; asm("add.rn.bf16x2 %0,%1,%2;" : "=r"(r) : "r"(a), "r"(b)); return r; }
__device__ __forceinline__ uint4 add4(const uint4& a, const uint4& b) { return make_uint4(addbf2(a.x, b.x), addbf2(a.y, b.y), addbf2(a.z, b.z), addbf2(a.w, b.w)); }
__device__ __forceinline__ void acc4(uint4& a, const uint4& b, int never) {
  asm("{.reg .pred p; setp.eq.s32 p,%8,0;\n"
      "@p add.rn.bf16x2 %0,%0,%4; @p add.rn.bf16x2 %1,%1,%5; @p add.rn.bf16x2 %2,%2,%6; @p add.rn.bf16x2 %3,%3,%7;}"
      : "+r"(a.x), "+r"(a.y), "+r"(a.z), "+r"(a.w) : "r"(b.x), "r"(b.y), "r"(b.z), "r"(b.w), "r"(never));
}
__device__ __forceinline__ uint4 ldtex(cudaTextureObject_t t, int i) {
  uint4 v; asm volatile("tex.1d.v4.u32.s32 {%0,%1,%2,%3},[%4,{%5}];" : "=r"(v.x), "=r"(v.y), "=r"(v.z), "=r"(v.w) : "l"(t), "r"(i)); return v;
}
__device__ __forceinline__ uint4 lds128(uint32_t a) {
  uint4 v; asm volatile("ld.volatile.shared.v4.u32 {%0,%1,%2,%3},[%4];" : "=r"(v.x), "=r"(v.y), "=r"(v.z), "=r"(v.w) : "r"(a)); return v;
}
__device__ __forceinline__ void sts128(uint32_t a, const uint4& v) {
  asm volatile("st.shared.v4.u32 [%0],{%1,%2,%3,%4};" :: "r"(a), "r"(v.x), "r"(v.y), "r"(v.z), "r"(v.w) : "memory");
}
__device__ __forceinline__ void mbar_init(uint32_t bar, int n) { asm volatile("mbarrier.init.shared::cta.b64 [%0],%1;" :: "r"(bar), "r"(n) : "memory"); }
__device__ __forceinline__ void mbar_wait(uint32_t bar, uint32_t parity) {
  uint32_t ok; int it = 0;
  do { asm volatile("{.reg .pred p; mbarrier.try_wait.parity.shared::cta.b64 p,[%1],%2; selp.u32 %0,1,0,p;}" : "=r"(ok) : "r"(bar), "r"(parity) : "memory"); } while (!ok && ++it < (1 << 19));
}
__device__ __forceinline__ void mbar_expect(uint32_t bar, uint32_t bytes) { asm volatile("mbarrier.arrive.expect_tx.shared::cta.b64 _,[%0],%1;" :: "r"(bar), "r"(bytes) : "memory"); }
__device__ __forceinline__ void bulk_g2s(uint32_t dst, const void* src, uint32_t bytes, uint32_t bar) {
  asm volatile("cp.async.bulk.shared::cluster.global.mbarrier::complete_tx::bytes [%0],[%1],%2,[%3];" :: "r"(dst), "l"(src), "r"(bytes), "r"(bar) : "memory");
}
__device__ __forceinline__ void bulk_pf(const void* src, uint32_t bytes) { asm volatile("cp.async.bulk.prefetch.L2.global [%0],%1;" :: "l"(src), "r"(bytes) : "memory"); }
#define NOMMA 0
#define NGRP 16
#define PDL 1
#define FIN_S 128
#define WR8 0
#define TRIG 14
#define PREW 5
#define PXW 3
#define WQL 1
#define EARLY 1
#define CBAR 0
#define TW 1
#define PP0 10
#define PT0 10000
#define PDT 0
#define RPNN "160"
#define RAUX "32"
#define RPRO "160"
#define PARK 0
#define NLOOK 128
#define NEF 16
#define ORD 0
#define WFENCE 0
#define SPLIT 0
#define IORD 3
#define IPF 3
#define IPACE 4500
#define WPF 3
#define QV 3
#define QORD(n) ((n) < 23 ? (n) + 2 : (n) - 23)
#define DYD 4
#define DPF 4
#define DDEPTH 4
#define FENCE_N 4
#define INPL 0
#define STAG 1
#define PACE 800
#define PM4 "pmevent 1; pmevent 2; pmevent 3; pmevent 4;"
#define PMFILL "pmevent 1;"
#define SCHED_FENCE(never, k) asm volatile("{.reg .pred p; setp.ne.u32 p,%0,%1; @p bra.uni SKIP_%=;" PMFILL "SKIP_%=: }" :: "r"(never), "r"(0x7fff0000 + (k)) : "memory")

__global__ void k_prod_naive(const __nv_bfloat16* __restrict__ table, const __nv_bfloat16* __restrict__ w1) {
  __shared__ float t[8][D_];
  int f = blockIdx.y, v0 = blockIdx.x * 8, h = threadIdx.x;
  for (int i = h; i < 8 * D_; i += 512) t[i / D_][i % D_] = __bfloat162float(table[v0 * D_ + i]);
  __syncthreads();
  float s[8] = {0, 0, 0, 0, 0, 0, 0, 0};
  for (int d = 0; d < D_; d++) { float w = __bfloat162float(w1[(size_t)(f * D_ + d) * H_ + h]);
#pragma unroll
    for (int k = 0; k < 8; k++) s[k] += t[k][d] * w; }
  __nv_bfloat16* P = (__nv_bfloat16*)g_scr;
  int c = h >> 3;
  for (int k = 0; k < 8; k++) {
    size_t e = f < 72 ? (size_t)PL_OFF + ((size_t)(c * NC + (f >> 3)) * 1000 + v0 + k) * 8 + (f & 7)
             : f < 90 ? (size_t)PS_OFF + ((size_t)(c * NC + ((f - 72) >> 1)) * 1000 + v0 + k) * 2 + (f & 1)
                      : (size_t)PT_OFF + (size_t)(c * 10 + f - 90) * 1024 + v0 + k;
    P[e * 8 + (h & 7)] = __float2bfloat16(s[k]);
  }
}
__global__ void k_pnn_naive(const int* __restrict__ idx, const __nv_bfloat16* __restrict__ table, const __nv_bfloat16* __restrict__ wp) {
  __shared__ float e[F_][33];
  int b = blockIdx.x, d0 = blockIdx.y * 32, tid = threadIdx.x;
  for (int i = tid; i < F_ * 32; i += 128) e[i >> 5][i & 31] = __bfloat162float(table[idx[b * F_ + (i >> 5)] * D_ + d0 + (i & 31)]);
  __syncthreads();
  float s = 0; int d = tid & 31;
  for (int i = tid >> 5; i < F_; i += 4) { float u = 0; for (int j = 0; j < F_; j++) u += __bfloat162float(wp[i * F_ + j]) * e[j][d]; s += u * e[i][d]; }
  for (int o = 16; o; o >>= 1) s += __shfl_xor_sync(~0u, s, o);
  if (d == 0) g_partP[(blockIdx.y * 4 + (tid >> 5)) * B_ + b] = s;
}
__device__ __forceinline__ void mbar_wait_fast(uint32_t bar, uint32_t parity) {
  asm volatile("{.reg .pred p; .reg .u32 n;\n"
               "mbarrier.try_wait.parity.shared::cta.b64 p,[%0],%1;\n"
               "@p bra DONE_%=;\n"
               "mov.u32 n,0;\n"
               "LOOP_%=: mbarrier.try_wait.parity.shared::cta.b64 p,[%0],%1;\n"
               "add.u32 n,n,1; setp.gt.or.u32 p,n,400000,p;\n"
               "@!p bra LOOP_%=;\n"
               "DONE_%=: }" :: "r"(bar), "r"(parity) : "memory");
}
__device__ __forceinline__ void sleep_until(uint32_t t0, uint32_t dt) { while ((uint32_t)clock() - t0 < dt) __nanosleep(40); }
__device__ __forceinline__ uint32_t s_mask(uint32_t v, int q) { return (1u << ((v + 3 - q) & 3)) | (16u << ((v + 3 + q) & 3)); }
__device__ __forceinline__ uint32_t s_cell(uint32_t v, int q, uint32_t m) {
  const int t = __ffs(~m) - 1;
  const int cp = t == 8 ? q >> 1 : ((t & 4 ? t - q : t + q) - v) & 3;
  return cp * 1001 + v;
}
__device__ __forceinline__ uint32_t pk3(uint32_t a, uint32_t b, uint32_t c) {
  const uint32_t w = c + (a << 12) + (b << 22); return __funnelshift_l(w, w, 27);
}
constexpr int TH = 256, NS = 8192 / TH, YD = DYD;
__host__ __device__ constexpr int ye_of(int s) { return s == 3 ? 0 : s == 11 ? 1 : s == 19 ? 2 : s == 23 ? 3 : -1; }
template <int N> __device__ __forceinline__ void wgmma_h(uint32_t* d, const uint32_t* a, uint64_t desc, int acc);
template <> __device__ __forceinline__ void wgmma_h<64>(uint32_t* d, const uint32_t* a, uint64_t desc, int acc) {
  asm volatile("{.reg .pred p; setp.ne.s32 p,%21,0;\n"
    "wgmma.mma_async.sync.aligned.m64n64k16.f16.f16.f16 {%0,%1,%2,%3,%4,%5,%6,%7,%8,%9,%10,%11,%12,%13,%14,%15},{%16,%17,%18,%19},%20,p,1,1,0;}"
    : "+r"(d[0]),"+r"(d[1]),"+r"(d[2]),"+r"(d[3]),"+r"(d[4]),"+r"(d[5]),"+r"(d[6]),"+r"(d[7]),"+r"(d[8]),"+r"(d[9]),"+r"(d[10]),"+r"(d[11]),"+r"(d[12]),"+r"(d[13]),"+r"(d[14]),"+r"(d[15])
    : "r"(a[0]), "r"(a[1]), "r"(a[2]), "r"(a[3]), "l"(desc), "r"(acc));
}
template <> __device__ __forceinline__ void wgmma_h<56>(uint32_t* d, const uint32_t* a, uint64_t desc, int acc) {
  asm volatile("{.reg .pred p; setp.ne.s32 p,%19,0;\n"
    "wgmma.mma_async.sync.aligned.m64n56k16.f16.f16.f16 {%0,%1,%2,%3,%4,%5,%6,%7,%8,%9,%10,%11,%12,%13},{%14,%15,%16,%17},%18,p,1,1,0;}"
    : "+r"(d[0]),"+r"(d[1]),"+r"(d[2]),"+r"(d[3]),"+r"(d[4]),"+r"(d[5]),"+r"(d[6]),"+r"(d[7]),"+r"(d[8]),"+r"(d[9]),"+r"(d[10]),"+r"(d[11]),"+r"(d[12]),"+r"(d[13])
    : "r"(a[0]), "r"(a[1]), "r"(a[2]), "r"(a[3]), "l"(desc), "r"(acc));
}
template <> __device__ __forceinline__ void wgmma_h<48>(uint32_t* d, const uint32_t* a, uint64_t desc, int acc) {
  asm volatile("{.reg .pred p; setp.ne.s32 p,%17,0;\n"
    "wgmma.mma_async.sync.aligned.m64n48k16.f16.f16.f16 {%0,%1,%2,%3,%4,%5,%6,%7,%8,%9,%10,%11},{%12,%13,%14,%15},%16,p,1,1,0;}"
    : "+r"(d[0]),"+r"(d[1]),"+r"(d[2]),"+r"(d[3]),"+r"(d[4]),"+r"(d[5]),"+r"(d[6]),"+r"(d[7]),"+r"(d[8]),"+r"(d[9]),"+r"(d[10]),"+r"(d[11])
    : "r"(a[0]), "r"(a[1]), "r"(a[2]), "r"(a[3]), "l"(desc), "r"(acc));
}
template <> __device__ __forceinline__ void wgmma_h<40>(uint32_t* d, const uint32_t* a, uint64_t desc, int acc) {
  asm volatile("{.reg .pred p; setp.ne.s32 p,%15,0;\n"
    "wgmma.mma_async.sync.aligned.m64n40k16.f16.f16.f16 {%0,%1,%2,%3,%4,%5,%6,%7,%8,%9},{%10,%11,%12,%13},%14,p,1,1,0;}"
    : "+r"(d[0]),"+r"(d[1]),"+r"(d[2]),"+r"(d[3]),"+r"(d[4]),"+r"(d[5]),"+r"(d[6]),"+r"(d[7]),"+r"(d[8]),"+r"(d[9])
    : "r"(a[0]), "r"(a[1]), "r"(a[2]), "r"(a[3]), "l"(desc), "r"(acc));
}
template <> __device__ __forceinline__ void wgmma_h<32>(uint32_t* d, const uint32_t* a, uint64_t desc, int acc) {
  asm volatile("{.reg .pred p; setp.ne.s32 p,%13,0;\n"
    "wgmma.mma_async.sync.aligned.m64n32k16.f16.f16.f16 {%0,%1,%2,%3,%4,%5,%6,%7},{%8,%9,%10,%11},%12,p,1,1,0;}"
    : "+r"(d[0]),"+r"(d[1]),"+r"(d[2]),"+r"(d[3]),"+r"(d[4]),"+r"(d[5]),"+r"(d[6]),"+r"(d[7])
    : "r"(a[0]), "r"(a[1]), "r"(a[2]), "r"(a[3]), "l"(desc), "r"(acc));
}
__device__ __forceinline__ void wgmma_p(float* d, const uint32_t* a, uint64_t desc, int acc) {
  asm volatile("{.reg .pred p; setp.ne.s32 p,%37,0;\n"
    "wgmma.mma_async.sync.aligned.m64n64k16.f32.bf16.bf16 {%0,%1,%2,%3,%4,%5,%6,%7,%8,%9,%10,%11,%12,%13,%14,%15,%16,%17,%18,%19,%20,%21,%22,%23,%24,%25,%26,%27,%28,%29,%30,%31},{%32,%33,%34,%35},%36,p,1,1,1;}"
    : "+f"(d[0]),"+f"(d[1]),"+f"(d[2]),"+f"(d[3]),"+f"(d[4]),"+f"(d[5]),"+f"(d[6]),"+f"(d[7]),"+f"(d[8]),"+f"(d[9]),"+f"(d[10]),"+f"(d[11]),"+f"(d[12]),"+f"(d[13]),"+f"(d[14]),"+f"(d[15]),"+f"(d[16]),"+f"(d[17]),"+f"(d[18]),"+f"(d[19]),"+f"(d[20]),"+f"(d[21]),"+f"(d[22]),"+f"(d[23]),"+f"(d[24]),"+f"(d[25]),"+f"(d[26]),"+f"(d[27]),"+f"(d[28]),"+f"(d[29]),"+f"(d[30]),"+f"(d[31])
    : "r"(a[0]), "r"(a[1]), "r"(a[2]), "r"(a[3]), "l"(desc), "r"(acc));
}

__device__ __forceinline__ void mma16816h(uint32_t* c, const uint32_t* a, uint32_t b0, uint32_t b1) {
  asm("mma.sync.aligned.m16n8k16.row.col.f16.f16.f16.f16 {%0,%1},{%2,%3,%4,%5},{%6,%7},{%0,%1};"
      : "+r"(c[0]), "+r"(c[1]) : "r"(a[0]), "r"(a[1]), "r"(a[2]), "r"(a[3]), "r"(b0), "r"(b1));
}
__device__ __forceinline__ void mma1688h(uint32_t* c, uint32_t a0, uint32_t a1, uint32_t b) {
  asm("mma.sync.aligned.m16n8k8.row.col.f16.f16.f16.f16 {%0,%1},{%2,%3},{%4},{%0,%1};" : "+r"(c[0]), "+r"(c[1]) : "r"(a0), "r"(a1), "r"(b));
}
__device__ __forceinline__ void mma16816f(float* c, const uint32_t* a, uint32_t b) {
  asm("mma.sync.aligned.m16n8k16.row.col.f32.f16.f16.f32 {%0,%1,%2,%3},{%4,%5,%6,%7},{%8,%8},{%0,%1,%2,%3};"
      : "+f"(c[0]), "+f"(c[1]), "+f"(c[2]), "+f"(c[3]) : "r"(a[0]), "r"(a[1]), "r"(a[2]), "r"(a[3]), "r"(b));
}
__device__ __forceinline__ uint32_t hfma2(uint32_t a, uint32_t b, uint32_t c) { uint32_t r; asm("fma.rn.f16x2 %0,%1,%2,%3;" : "=r"(r) : "r"(a), "r"(b), "r"(c)); return r; }
__device__ __forceinline__ uint32_t pack_bf2(float lo, float hi) { uint32_t r; asm("cvt.rn.bf16x2.f32 %0,%1,%2;" : "=r"(r) : "f"(hi), "f"(lo)); return r; }
__device__ __forceinline__ uint32_t pack_h2(float lo, float hi) { uint32_t r; asm("cvt.rn.f16x2.f32 %0,%1,%2;" : "=r"(r) : "f"(hi), "f"(lo)); return r; }
__device__ __forceinline__ float bf_lo(uint32_t w) { return __uint_as_float(w << 16); }
__device__ __forceinline__ float bf_hi(uint32_t w) { return __uint_as_float(w & 0xffff0000u); }
__device__ __forceinline__ uint32_t absmax4(const uint4& v, uint32_t m) {
  return __vmaxu2(__vmaxu2(__vmaxu2(v.x & 0x7fff7fffu, v.y & 0x7fff7fffu), __vmaxu2(v.z & 0x7fff7fffu, v.w & 0x7fff7fffu)), m);
}
__device__ __forceinline__ float pow2_scale(uint32_t mbits, int p) { return __uint_as_float((uint32_t)min(max(253 + p - (int)(mbits >> 7), 2), 252) << 23); }

#define PV 4
constexpr int G_O0 = 8, G_O1 = 4, G_O2 = 0, G_N0 = 5, G_N1 = 4, G_N2 = 4, G_K0 = 5, G_K1 = 3, G_K2 = 1;
__host__ __device__ constexpr bool unit_wg(int kb, int on) {
  return (on >= G_O0 && on < G_O0 + G_N0 && kb < G_K0) || (on >= G_O1 && on < G_O1 + G_N1 && kb < G_K1) || (on >= G_O2 && on < G_O2 + G_N2 && kb < G_K2);
}
__host__ __device__ constexpr bool oct_wg(int on) { return unit_wg(0, on); }
constexpr int G_U1 = G_N0 * G_K0, G_U2 = G_U1 + G_N1 * G_K1, G_U = G_U2 + G_N2 * G_K2;
constexpr int K1_B = 130048, K1_STG = K1_B + 3 * 16384, K1_W = K1_STG + 2 * 16384, K1_BAR = K1_W + 48 * 256, K1_SMEM = K1_BAR + 128 + 4352;
__host__ __device__ constexpr int frag_index(int ok, int on) {
  int n = 0;
  for (int k = 0; k < 13; k++) for (int o = k; o < 13; o++) { if (k == ok && o == on) return n; if (!unit_wg(k >> 1, o)) n++; }
  return n;
}
constexpr int HU_N = 2 * G_U + frag_index(99, 99);
static_assert(HU_N <= 96, "");
struct FragIdx { int v[13][13]; };
__host__ __device__ constexpr FragIdx make_fi() { FragIdx f = {}; for (int k = 0; k < 13; k++) for (int o = 0; o < 13; o++) f.v[k][o] = frag_index(k, o); return f; }
__host__ __device__ constexpr uint64_t frag_tab(int first) {
  uint64_t t = 0;
  for (int k = 0; k < 13; k++) for (int o = k; o < 13; o++)
    if (!unit_wg(k >> 1, o)) { const int n = frag_index(k, o) - first; if (n >= 0 && n < 8) t |= (uint64_t)(k << 4 | o) << (8 * n); }
  return t;
}
__device__ __forceinline__ int hu_code(int hu) {
  constexpr uint64_t T0 = frag_tab(0), T1 = frag_tab(8), T2 = frag_tab(16), T3 = frag_tab(24);
  const int u = hu >> 1, f = hu - 2 * G_U;
  if (f >= 0) return (int)((f < 8 ? T0 : f < 16 ? T1 : f < 24 ? T2 : T3) >> (8 * (f & 7))) & 255;
  const int u0 = u < G_U1 ? u : u < G_U2 ? u - G_U1 : u - G_U2;
  const int kb = u < G_U1 ? u0 / G_N0 : u < G_U2 ? u0 / G_N1 : u0 / 4, on = u < G_U1 ? G_O0 + u0 % G_N0 : u < G_U2 ? G_O1 + u0 % G_N1 : G_O2 + u0 % 4;
  return (2 * kb + (hu & 1)) << 4 | on;
}

__device__ __forceinline__ void flag_arrive(unsigned* f, int lane) {
  __threadfence(); __syncwarp();
  if (lane == 0) asm volatile("red.release.gpu.global.add.u32 [%0],1;" :: "l"(f) : "memory");
}
__device__ __forceinline__ void flag_wait(const unsigned* f, unsigned n) {
  unsigned v; int it = 0;
  asm volatile("ld.acquire.gpu.global.u32 %0,[%1];" : "=r"(v) : "l"(f) : "memory");
  if (v < n) {
    do { __nanosleep(300); asm volatile("ld.relaxed.gpu.global.u32 %0,[%1];" : "=r"(v) : "l"(f) : "memory"); } while (v < n && ++it < (1 << 20));
    asm volatile("ld.acquire.gpu.global.u32 %0,[%1];" : "=r"(v) : "l"(f) : "memory");
  }
}
__device__ __forceinline__ void mbar_arrive(uint32_t bar) { asm volatile("mbarrier.arrive.shared::cta.b64 _,[%0];" :: "r"(bar) : "memory"); }
__device__ __forceinline__ void mbar_arrive_lane0(uint32_t bar) {
  asm volatile("{.reg .pred p; elect.sync _|p,0xffffffff; @p mbarrier.arrive.shared::cta.b64 _,[%0];}" :: "r"(bar) : "memory");
}

__device__ __forceinline__ void pack_role(const int* __restrict__ idx, uint32_t sbase, int pc) {
  constexpr int CH = 3200 + 32, BUF = 32 * 3328;
  const int tid = threadIdx.x, lane = tid & 31, warp = tid >> 5;
  const uint32_t full = sbase + 2 * BUF, empty = full + 16;
  if (tid == 0) { mbar_init(full, 1); mbar_init(full + 8, 1); mbar_init(empty, 18); mbar_init(empty + 8, 18); asm volatile("fence.proxy.async.shared::cta;" ::: "memory"); }
  __syncthreads();
  auto chunk = [&](int s) { return s * 3200 + (s >> 2) * 288; };
  auto load = [&](int n) {
    const int blk = pc * 16 + n;
    if (lane == 0) mbar_expect(full + (n & 1) * 8, 32 * 3200);
    __syncwarp();
    bulk_g2s(sbase + (n & 1) * BUF + chunk(lane), idx + ((blk >> 5) * 8192 + lane * TH + (blk & 31) * 8) * F_, 3200, full + (n & 1) * 8);
  };
  if (warp == 0) { load(0); load(1); }
  const int l = lane & 7;
  uint32_t rot[8], inc[3];
#pragma unroll
  for (int jj = 0; jj < 8; jj++) rot[jj] = ((l + jj) & 7) * 4;
#pragma unroll
  for (int q = 0; q < 3; q++) inc[q] = (l + 3 * q < 8) << 12 | (l + 3 * q + 1 < 8) << 22 | (q < 2 && l + 3 * q + 2 < 8);
  int loaded = 2;
#pragma unroll 1
  for (int task = warp; task < 288; task += 16) {
    const int n = task / 18, q = (task % 18) * 4 + (lane >> 3), sq = q / 9, k = q % 9;
    if (warp == 0 && n + 1 == loaded && loaded < 16) { mbar_wait(empty + (loaded & 1) * 8, ((loaded >> 1) - 1) & 1); load(loaded); loaded++; }
    mbar_wait(full + (n & 1) * 8, (n >> 1) & 1);
    const uint32_t buf = sbase + (n & 1) * BUF + l * 400, row = buf + chunk(sq * 4);
    auto ld = [&](uint32_t ad) { uint32_t v; asm volatile("ld.shared.u32 %0,[%1];" : "=r"(v) : "r"(ad)); return v; };
    const int blk = pc * 16 + n, half = blk >> 5, col = (blk & 31) * 8 + l;
    const int ks = k == NC - 1 ? 0 : k + 1;
    uint32_t cw[4], sv[8], m[2] = {0, 0};
    { const uint32_t a0 = row + (72 + 2 * ks + (l >> 2)) * 4;
#pragma unroll
      for (int u = 0; u < 8; u++) { sv[u] = ld((a0 ^ ((u >> 2) * 4)) + (u & 3) * 3200); m[u >> 2] |= s_mask(sv[u], l & 3) << (8 * (u & 3)); } }
#pragma unroll
    for (int h = 0; h < 2; h++) { m[h] |= __shfl_xor_sync(0xffffffffu, m[h], 1); m[h] |= __shfl_xor_sync(0xffffffffu, m[h], 2); }
#pragma unroll
    for (int u = 0; u < 4; u++) cw[u] = s_cell(sv[u], l & 3, (m[0] >> (8 * u)) & 255) | s_cell(sv[4 + u], l & 3, (m[1] >> (8 * u)) & 255) << 12;
    if (k == NC - 1) {
      g_scr[I0_OFF + (half * 8 + sq) * TH + col] = make_uint4(cw[0], cw[1], cw[2], cw[3]);
      g_scr[IX_OFF + half * IXH + NC * 8192 + sq * TH + col] = make_uint4(ld(row + 396), ld(row + 3596), ld(row + 6796), ld(row + 9996));
      cw[0] = cw[1] = cw[2] = cw[3] = 0;
    }
    const uint32_t ax = buf + chunk(min(sq + 1, 7) * 4) + (90 + k) * 4;
    const uint32_t yev = ld(buf + ((0x3210 >> (sq * 2 + (sq == 5) * 2)) & 3) * 3200 + (90 + k) * 4);
    uint4* dst = g_scr + IX_OFF + half * IXH + (k * NS + sq * 4) * TH + col;
#pragma unroll
    for (int u = 0; u < 4; u++) {
      uint32_t e[8];
#pragma unroll
      for (int jj = 0; jj < 8; jj++) e[jj] = ld(row + k * 32 + rot[jj] + u * 3200);
      dst[u * TH] = make_uint4(pk3(e[0], e[1], e[2] + inc[0]), pk3(e[3], e[4], e[5] + inc[1]), pk3(e[6], e[7], ld(ax + u * 3200) + inc[2]),
                               u < 3 ? __byte_perm(cw[u], cw[3], 0x4210 + (u << 12)) : yev);
    }
    mbar_arrive_lane0(empty + (n & 1) * 8);
  }
  (void)CH;
}

__global__ void __cluster_dims__(2, 1, 1) __launch_bounds__(512, 1)
k_tens(const __grid_constant__ CUtensorMap mapW, const __grid_constant__ CUtensorMap mapL, const __grid_constant__ CUtensorMap mapS,
       const __grid_constant__ CUtensorMap mapT, const __grid_constant__ CUtensorMap mapE, const __grid_constant__ CUtensorMap mapC, cudaTextureObject_t tex, cudaTextureObject_t texX,
       const int* __restrict__ idx, const __nv_bfloat16* __restrict__ table, const __nv_bfloat16* __restrict__ wp, const __nv_bfloat16* __restrict__ w1,
       const __nv_bfloat16* __restrict__ b1, int never) {
  extern __shared__ __align__(1024) uint4 sm[];
  const int tid = threadIdx.x, lane = tid & 31, cta = blockIdx.x;
  const uint32_t sbase = (uint32_t)__cvta_generic_to_shared(sm);
  const int g = lane >> 2, r = lane & 3;
  TS(0, 0);
  if (cta >= 128) {
    pack_role(idx, sbase, cta - 128);
    __syncthreads();
    if (tid < 32) flag_arrive(&g_flag[8 * 32], lane);
    TS(2, 1);
    asm volatile("barrier.cluster.arrive.relaxed.aligned; barrier.cluster.wait.aligned;" ::: "memory");
    return;
  }
  const uint32_t fullB = sbase + K1_BAR, emptyB = fullB + 24, fullS = fullB + 48, emptyS = fullB + 64, fullE = fullB + 80, fullC = fullB + 88, fullI = fullB + 96, fullX = fullB + 104, progG = fullB + 112;
  const int rb = cta & 7, hc = cta >> 3;
  if (tid >= 384) {
    asm volatile("setmaxnreg.dec.sync.aligned.u32 " RAUX ";");
    if (tid < 416) {
      auto load_pair = [&](int p, int st) {
        mbar_expect(fullB + st * 8, 16384);
        asm volatile("cp.async.bulk.tensor.2d.shared::cluster.global.mbarrier::complete_tx::bytes [%0],[%1,{%2,%3}],[%4];"
                     :: "r"(sbase + K1_B + st * 16384), "l"(&mapW), "r"(hc * 32), "r"(QORD(p >> 1) * 512 + (p & 1) * 256), "r"(fullB + st * 8) : "memory");
        p += WPF;
        if (p < 50) bulk_pf(w1 + QORD(p >> 1) * 262144 + (p & 1) * 131072 + cta * 1024, 2048);
      };
      if (tid == 384) {
        for (int q = 0; q < 3; q++) { mbar_init(fullB + q * 8, 1); mbar_init(emptyB + q * 8, 4); }
        for (int q = 0; q < 2; q++) { mbar_init(fullS + q * 8, 4); mbar_init(emptyS + q * 8, 1); }
        mbar_init(fullE, 1); mbar_init(fullC, 1); mbar_init(fullI, 1); mbar_init(fullX, 1); mbar_init(progG, 1);
        asm volatile("fence.proxy.async.shared::cta;" ::: "memory");
        mbar_expect(fullC, 16384);
        for (int q = 0; q < 4; q++)
          asm volatile("cp.async.bulk.tensor.2d.shared::cluster.global.mbarrier::complete_tx::bytes [%0],[%1,{%2,%3}],[%4];"
                       :: "r"(sbase + 32768 + q * 4096), "l"(&mapC), "r"((cta & 15) * 8), "r"(q * 256), "r"(fullC) : "memory");
        mbar_expect(fullE, 32768);
        for (int q = 0; q < 2; q++)
          asm volatile("cp.async.bulk.tensor.2d.shared::cluster.global.mbarrier::complete_tx::bytes [%0],[%1,{%2,%3}],[%4];"
                       :: "r"(sbase + K1_STG + q * 16384), "l"(&mapE), "r"(q * 64), "r"(rb * 128), "r"(fullE) : "memory");
      }
      __syncwarp();
      asm volatile("bar.arrive 2,448;" ::: "memory");
      if (tid == 384) {
        int st = 0, ph = 1;
        const uint32_t tl0 = clock();
#pragma unroll 1
        for (int p = 0; p < 50; p++) {
          if (p == IORD) {
            mbar_expect(fullI, 51200);
#pragma unroll 1
            for (int q = 0; q < 8; q++) bulk_g2s(sbase + 76800 + q * 6400, idx + (((cta >> 4) * 8 + q) * 256 + (cta & 15) * 16) * F_, 6400, fullI);
          }
          if (PDT && p > PP0) sleep_until(tl0, PT0 + (p - PP0) * PDT);
          mbar_wait(emptyB + st * 8, ph);
          load_pair(p, st);
          if (++st == 3) { st = 0; ph ^= 1; }
        }
      }
    } else if (tid < 448) {
      ((float4*)g_acc)[cta * 32 + lane] = make_float4(0.f, 0.f, 0.f, 0.f);
      asm volatile("bar.sync 2,448;" ::: "memory");
      asm volatile("bar.sync 4,288;" ::: "memory");
      flag_arrive(&g_flag[(cta >> 4) * 32], lane);
      if (tid == 416) {
#pragma unroll 1
        for (int n = 0; n < 50; n++) {
          const int quad = QORD(n >> 1), mt = n & 1, v0 = rb * 128 + mt * 64;
          const uint32_t stg = sbase + K1_STG + mt * 16384;
          const uint64_t pol = n < 2 * NEF ? POL_EF : POL_N;
          mbar_wait(fullS + mt * 8, (n >> 1) & 1);
          asm volatile("fence.proxy.async.shared::cta;" ::: "memory");
          if (quad < 18) {
            asm volatile("cp.async.bulk.tensor.4d.global.shared::cta.bulk_group.L2::cache_hint [%0,{%1,%2,%3,%4}],[%5],%6;"
                         :: "l"(&mapL), "r"((quad & 1) * 32), "r"(v0), "r"(quad >> 1), "r"(hc * 4), "r"(stg), "l"(pol) : "memory");
          } else {
#pragma unroll 1
            for (int hh = 0; hh < 2; hh++) {
              const int pq = quad * 2 + hh;
              if (pq < 45) asm volatile("cp.async.bulk.tensor.4d.global.shared::cta.bulk_group.L2::cache_hint [%0,{%1,%2,%3,%4}],[%5],%6;"
                         :: "l"(&mapS), "r"(0), "r"(v0), "r"(pq - 36), "r"(hc * 4), "r"(stg + hh * 8192), "l"(pol) : "memory");
              else asm volatile("cp.async.bulk.tensor.3d.global.shared::cta.bulk_group.L2::cache_hint [%0,{%1,%2,%3}],[%4],%5;"
                         :: "l"(&mapT), "r"(v0 * 2), "r"((pq - 45) * 2), "r"(hc * 4), "r"(stg + hh * 8192), "l"(pol) : "memory");
            }
          }
          asm volatile("cp.async.bulk.commit_group;" ::: "memory");
          asm volatile("cp.async.bulk.wait_group.read 0;" ::: "memory");
          mbar_arrive(emptyS + mt * 8);
        }
        asm volatile("cp.async.bulk.wait_group 0;" ::: "memory");
        asm volatile("fence.proxy.async.global;" ::: "memory");
        __threadfence();
        asm volatile("red.release.gpu.global.add.u32 [%0],1;" :: "l"(&g_flag[8 * 32]) : "memory");
        flag_wait(&g_flag[8 * 32], 132);
        asm volatile("fence.proxy.async.global;" ::: "memory");
        const char* base = (const char*)g_scr;
        const int c = cta >> 1, half = cta & 1, ch = (c + (c >> 4) * 5) & 15;
        bulk_pf(base + (PS_OFF + c * NC * 2000) * 16u + half * 16000, 16000);
        if (PREW & 2) bulk_pf(base + (PL_OFF + c * NC * 8000) * 16u + half * 64000, 64000);
        bulk_pf(base + (PT_OFF + c * 10 * 1024) * 16u + half * 8192, 8192);
        mbar_expect(fullE, 18432);
        bulk_g2s(sbase + K1_STG, base + (I0_OFF + half * 2048 + ch * 128) * 16u, 2048, fullE);
        bulk_g2s(sbase + K1_STG + 2048, base + (IX_OFF + half * IXH + ch * 512) * 16u, 8192, fullE);
        bulk_g2s(sbase + K1_STG + 10240, base + (IX_OFF + half * IXH + 8192 + ch * 512) * 16u, 8192, fullE);
        mbar_wait(fullE, 1);
      }
    } else if (tid == 448 && PXW) {
      flag_wait(&g_flag[(cta >> 4) * 32], 16);
      asm volatile("fence.proxy.async.global;" ::: "memory");
      const char* src = (const char*)(g_scr + PX_OFF + ((cta >> 4) * 8 + ((cta >> 1) & 3) * 2) * 16 * 136);
#pragma unroll 1
      for (int n = 1; n < 16; n++) {
        if (n >= PXW) mbar_wait(progG, (n - PXW) & 1);
        mbar_expect(fullX, 4352);
        bulk_g2s(sbase + K1_BAR + 128, src + n * 2176, 2176, fullX);
        bulk_g2s(sbase + K1_BAR + 128 + 2176, src + (16 + n) * 2176, 2176, fullX);
        mbar_wait(fullX, (n - 1) & 1);
      }
    }
    return;
  }
  if (tid >= 256) {
    asm volatile("setmaxnreg.inc.sync.aligned.u32 " RPRO ";");
    const int w = (tid >> 5) & 3;
    const int srow = w * 16 + (lane & 7) + ((lane >> 3) & 1) * 8, sc = lane >> 4;
    uint32_t a[2][8][4];
    asm volatile("bar.sync 2,448;" ::: "memory");
    mbar_wait_fast(fullE, 0);
#pragma unroll
    for (int mt = 0; mt < 2; mt++)
#pragma unroll
      for (int ks = 0; ks < 8; ks++)
        asm volatile("ldmatrix.sync.aligned.m8n8.x4.shared.b16 {%0,%1,%2,%3},[%4];"
                     : "=r"(a[mt][ks][0]), "=r"(a[mt][ks][1]), "=r"(a[mt][ks][2]), "=r"(a[mt][ks][3])
                     : "r"(sbase + K1_STG + (ks >> 2) * 16384 + (mt * 64 + srow) * 128 + ((((ks & 3) * 2 + sc) ^ (lane & 7)) * 16)) : "memory");
    asm volatile("bar.sync 5,128;" ::: "memory");
    const uint32_t baseL = sc * 4096 + srow * 64 + ((srow >> 1) & 3) * 16, baseS = sc * 2048 + srow * 32 + ((srow >> 2) & 1) * 16, baseT = sc * 2048 + srow * 16;
    const uint64_t desc0 = (uint64_t)(((sbase + K1_B) & 0x3FFFF) >> 4) | ((uint64_t)(8192 >> 4) << 16) | ((uint64_t)(512 >> 4) << 32) | (2ull << 62);
    float d[2][32];
    auto issue = [&](int x, int mt, int st) {
      uint32_t a7[4];
#pragma unroll
      for (int e = 0; e < 4; e++) { if (PARK) asm volatile("add.u32 %0,%1,%2;" : "=r"(a7[e]) : "r"(a[mt][7][e]), "r"(never)); else a7[e] = a[mt][7][e]; }
      asm volatile("wgmma.fence.sync.aligned;" ::: "memory");
#pragma unroll
      for (int ks = 0; ks < 8; ks++) wgmma_p(d[x], ks < 7 ? a[mt][ks] : a7, desc0 + st * 1024 + ks * 64, ks);
      asm volatile("wgmma.commit_group.sync.aligned;" ::: "memory");
    };
    auto wait_acc = [&](int x) {
      asm volatile("wgmma.wait_group.sync.aligned 0;" ::: "memory");
#pragma unroll
      for (int q = 0; q < 8; q++) asm volatile("" : "+f"(d[x][q * 4]), "+f"(d[x][q * 4 + 1]), "+f"(d[x][q * 4 + 2]), "+f"(d[x][q * 4 + 3]) :: "memory");
    };
    mbar_wait_fast(fullB, 0);
    issue(0, 0, 0);
    int s0 = 0, ph = 0;
#pragma unroll 1
    for (int qn = 0; qn < 25; qn++) {
      const int quad = QORD(qn);
      const int s1 = s0 == 2 ? 0 : s0 + 1, s2 = s1 == 2 ? 0 : s1 + 1, ph1 = ph ^ (s1 == 0), ph2 = ph1 ^ (s2 == 0);
#pragma unroll
      for (int step = 0; step < 4; step++) {
        const int mt = ORD ? step & 1 : step >> 1, h = ORD ? step >> 1 : step & 1, x = step & 1, nx = (step + 1) & 3;
        const bool isL = quad < 18, isS = quad * 2 + h < 45;
        const uint32_t base = (isL ? baseL ^ (h * 32) : (isS ? baseS : baseT) ^ (h * 8192)), xj = (isL || isS) ? 16 : 1024, xc = isL ? 8192 : 4096;
        PT(qn * 16 + step * 4);
        if (h == 0) mbar_wait_fast(emptyS + mt * 8, (qn & 1) ^ 1);
        if (step == (ORD ? 1 : 0)) mbar_wait_fast(fullB + s1 * 8, ph1);
        if (step == 3) mbar_wait_fast(fullB + s2 * 8, qn == 24 ? ph2 ^ 1 : ph2);
        PT(qn * 16 + step * 4 + 1);
        wait_acc(x);
        PT(qn * 16 + step * 4 + 2);
        if (mt) mbar_arrive_lane0(emptyB + (h ? s1 : s0) * 8);
        issue(x ^ 1, ORD ? nx & 1 : nx >> 1, step == 3 ? s2 : (ORD ? nx >> 1 : nx & 1) ? s1 : s0);
        PT(qn * 16 + step * 4 + 3);
        if (h && quad == 24) {
#pragma unroll
          for (int cq = 0; cq < 4; cq++) {
            const uint32_t bw = __ldg((const uint32_t*)(b1 + hc * 32 + cq * 8) + r);
#pragma unroll
            for (int e = 0; e < 4; e++) d[x][16 + cq * 4 + e] += (e & 1) ? bf_hi(bw) : bf_lo(bw);
          }
        }
#pragma unroll
        for (int e4 = 0; e4 < 4; e4++) {
          const float* e = d[x] + e4 * 8;
          asm volatile("stmatrix.sync.aligned.m8n8.x4.shared.b16 [%0],{%1,%2,%3,%4};"
                       :: "r"(sbase + K1_STG + mt * 16384 + (base ^ ((e4 >> 1) * xj) ^ ((e4 & 1) * xc))),
                          "r"(pack_bf2(e[0], e[1])), "r"(pack_bf2(e[2], e[3])), "r"(pack_bf2(e[4], e[5])), "r"(pack_bf2(e[6], e[7])) : "memory");
        }
        if (h) { __syncwarp(); mbar_arrive_lane0(fullS + mt * 8); }
      }
      s0 = s2; ph = ph2;
    }
    asm volatile("wgmma.wait_group.sync.aligned 0;" ::: "memory");
    return;
  }
  asm volatile("setmaxnreg.inc.sync.aligned.u32 " RPNN ";");
  const int slice = cta & 15;
  const int range = (cta >> 4) * 8 + (tid >> 5);
  uint4 iv[4], trow[4]; uint32_t ix;
  uint2 wrow[10];
#pragma unroll
  for (int q = 0; q < 10; q++) asm volatile("ld.global.nc.v2.u32 {%0,%1},[%2];" : "=r"(wrow[q].x), "=r"(wrow[q].y) : "l"((const uint2*)wp + min(tid + q * 256, 2499)));
  asm volatile("bar.sync 2,448;" ::: "memory");
  uint32_t me = 0, mw = 0;
#pragma unroll
  for (int q = 0; q < 10; q++) {
    mw = __vmaxu2(__vmaxu2(wrow[q].x & 0x7fff7fffu, wrow[q].y & 0x7fff7fffu), mw);
    const int e = min(tid + q * 256, 2499), row = e / 25;
    asm volatile("st.shared.v2.u32 [%0],{%1,%2};" :: "r"(sbase + (e + row) * 8), "r"(wrow[q].x), "r"(wrow[q].y) : "memory");
    if (e - row * 25 == 24) asm volatile("st.shared.v2.u32 [%0],{%1,%2};" :: "r"(sbase + (e + row) * 8 + 8), "r"(wrow[q].x), "r"(wrow[q].y) : "memory");
  }
  mbar_wait_fast(fullC, 0);
#pragma unroll
  for (int q = 0; q < 4; q++) { trow[q] = lds128(sbase + 32768 + (tid + q * 256) * 16); me = absmax4(trow[q], me); }
  me = __reduce_max_sync(0xffffffffu, max(me & 0xffff, me >> 16));
  mw = __reduce_max_sync(0xffffffffu, max(mw & 0xffff, mw >> 16));
  uint32_t* sred = (uint32_t*)((char*)sm + 128000);
  if (lane == 0) sred[tid >> 5] = me | mw << 16;
  TS(3, 0);
  asm volatile("bar.sync 1,256;" ::: "memory");
  { uint32_t m = 0;
#pragma unroll
    for (int q = 0; q < 8; q++) m = __vmaxu2(m, sred[q]);
    me = m & 0xffff; mw = m >> 16; }
  const float se = pow2_scale(me, 3), sW = pow2_scale(mw, -2);
  TS(3, 1);
  auto put_rows = [&](int q, bool on) {
    const uint4 t = trow[q];
    const uint4 hv = make_uint4(pack_h2(bf_lo(t.x) * se, bf_hi(t.x) * se), pack_h2(bf_lo(t.y) * se, bf_hi(t.y) * se),
                                pack_h2(bf_lo(t.z) * se, bf_hi(t.z) * se), pack_h2(bf_lo(t.w) * se, bf_hi(t.w) * se));
    if (on)
#pragma unroll
      for (int s = 0; s < 8; s++) sts128(sbase + (tid + q * 256) * 128 + ((s + lane) & 7) * 16, hv);
  };
#pragma unroll 1
  for (int it = 0; it < 3; it++) {
    const int hu = ((tid >> 5) * 3 + it) * 4, code = hu_code(min(hu + (lane >> 3), HU_N - 1)), ok = code >> 4, on = code & 15;
    uint32_t x[4], y[4];
    asm volatile("ldmatrix.sync.aligned.m8n8.x4.shared.b16 {%0,%1,%2,%3},[%4];" : "=r"(x[0]), "=r"(x[1]), "=r"(x[2]), "=r"(x[3])
                 : "r"(sbase + (on * 8 + (lane & (on == 12 ? 3 : 7))) * 208 + ok * 16) : "memory");
    asm volatile("ldmatrix.sync.aligned.m8n8.x4.trans.shared.b16 {%0,%1,%2,%3},[%4];" : "=r"(y[0]), "=r"(y[1]), "=r"(y[2]), "=r"(y[3])
                 : "r"(sbase + (ok * 8 + (lane & (ok == 12 ? 3 : 7))) * 208 + on * 16) : "memory");
    const uint32_t lo = __ballot_sync(0xffffffffu, ok > on), dg = __ballot_sync(0xffffffffu, ok >= on);
#pragma unroll
    for (int q = 0; q < 4; q++) {
      const float m0 = (lo >> (8 * q)) & 1 ? 0.f : sW, m1 = (dg >> (8 * q)) & 1 ? 0.f : sW;
      asm volatile("st.shared.u32 [%0],%1;" :: "r"(sbase + K1_W + (hu + q) * 128 + lane * 4),
                   "r"(pack_h2(fmaf(bf_lo(x[q]), m0, bf_lo(y[q]) * m1), fmaf(bf_hi(x[q]), m0, bf_hi(y[q]) * m1))) : "memory");
    }
  }
  put_rows(1, true); put_rows(2, tid < 88);
  TS(3, 2);
  asm volatile("fence.proxy.async.shared::cta;" ::: "memory");
  asm volatile("bar.sync 1,256;" ::: "memory");
  put_rows(0, true);
  uint32_t bf[HU_N - 2 * G_U];
#pragma unroll
  for (int q = 0; q < HU_N - 2 * G_U; q++) asm volatile("ld.shared.u32 %0,[%1];" : "=r"(bf[q]) : "r"(sbase + K1_W + (2 * G_U + q) * 128 + lane * 4));
  const float unscale = __uint_as_float(0x7f000000u - __float_as_uint(se)), unscale2 = __uint_as_float(0x7f000000u - __float_as_uint(sW));
  TS(3, 3);
  const int px = range * 16 * 136;
  mbar_wait_fast(fullI, 0);
  {
    const uint32_t ib = sbase + 76800 + (tid >> 5) * 6400, p0 = ib + ((lane >> 3) & 1) * 400 + ((lane >> 4) * 8 + (lane & 7)) * 4;
    auto ld = [&](uint32_t ad) { uint32_t v; asm volatile("ld.shared.u32 %0,[%1];" : "=r"(v) : "r"(ad)); return v; };
    auto wd = [&](int t, int h) { return pk3(ld(p0 + t * 800 + h * 192), ld(p0 + t * 800 + h * 192 + 64), ld(p0 + t * 800 + h * 192 + 128)); };
#pragma unroll
    for (int q = 0; q < 4; q++) {
      iv[q] = make_uint4(wd(2 * q, 0), wd(2 * q, 1), wd(2 * q + 1, 0), wd(2 * q + 1, 1));
      g_scr[PX_OFF + px + slice * 136 + q * 32 + lane] = iv[q];
    }
    ix = pk3(ld(ib + g * 400 + 384 + r * 4), ld(ib + (8 + g) * 400 + 384 + r * 4), 0);
    ((uint32_t*)(g_scr + PX_OFF + px + slice * 136 + 128))[lane] = ix;
  }
  asm volatile("bar.arrive 4,288;" ::: "memory");
  asm volatile("bar.sync 1,256;" ::: "memory");
  put_rows(2, tid >= 88); put_rows(3, tid + 768 < V_);
  asm volatile("bar.sync 1,256;" ::: "memory");
  TS(0, 1);
  const uint32_t lc = (lane & 7) * 16;
  const uint64_t wdesc = (uint64_t)(((sbase + K1_W) & 0x3FFFF) >> 4) | ((uint64_t)(128 >> 4) << 16) | ((uint64_t)(256 >> 4) << 32);
  uint32_t a[2][6][4], d[2][26], ex[4] = {}, s[4] = {};
  float red[4] = {0.f, 0.f, 0.f, 0.f};
  auto ldsm = [&](uint32_t* o, uint32_t sh) {
    asm volatile("ldmatrix.sync.aligned.m8n8.x4.trans.shared.b16 {%0,%1,%2,%3},[%4];"
                 : "=r"(o[0]), "=r"(o[1]), "=r"(o[2]), "=r"(o[3]) : "r"(sbase + ((sh & 0x1ff80) | lc)));
  };
  auto gather = [&](int t, int hf) {
    const int x = t & 1;
    const uint4 v = iv[(t >> 1) & 3];
#pragma unroll
    for (int kb = 3 * hf; kb < 3 * hf + 3; kb++) {
      const uint32_t ww = x ? (kb < 3 ? v.z : v.w) : (kb < 3 ? v.x : v.y);
      ldsm(a[x][kb], kb % 3 == 0 ? ww : kb % 3 == 1 ? ww >> 10 : __funnelshift_l(ww, ww, 12));
    }
  };
  auto issue = [&](int x) {
    asm volatile("wgmma.fence.sync.aligned;" ::: "memory");
#pragma unroll
    for (int kb = 0; kb < 6; kb++) {
      if (kb < G_K0) wgmma_h<G_N0 * 8>(d[x] + G_O0 * 2, a[x][kb], wdesc + kb * G_N0 * 16, kb);
      if (kb < G_K1) wgmma_h<G_N1 * 8>(d[x] + G_O1 * 2, a[x][kb], wdesc + (G_U1 + kb * G_N1) * 16, kb);
      if (kb < G_K2) wgmma_h<32>(d[x] + G_O2 * 2, a[x][kb], wdesc + (G_U2 + kb * G_N2) * 16, kb);
    }
    asm volatile("wgmma.commit_group.sync.aligned;" ::: "memory");
  };
  auto hmma_part = [&](int t) {
    constexpr FragIdx FI = make_fi();
    const int x = t & 1;
#pragma unroll
    for (int o = 0; o < 13; o++) {
      if (oct_wg(o)) asm volatile("" : "+r"(d[x][o * 2]), "+r"(d[x][o * 2 + 1]) :: "memory"); else d[x][o * 2] = d[x][o * 2 + 1] = 0;
    }
#pragma unroll
    for (int kb = 0; kb < 6; kb++)
#pragma unroll
      for (int o = 2 * kb + 1; o < 13; o++)
        if (!unit_wg(kb, o)) mma16816h(d[x] + o * 2, a[x][kb], bf[FI.v[2 * kb][o]], bf[FI.v[2 * kb + 1][o]]);
#pragma unroll
    for (int q = 0; q < 6; q++) if (!unit_wg(q, 2 * q)) mma1688h(d[x] + q * 4, a[x][q][0], a[x][q][1], bf[FI.v[2 * q][2 * q]]);
    mma1688h(d[x] + 24, r < 2 ? ex[t & 3] : 0u, r < 2 ? 0u : ex[t & 3], bf[FI.v[12][12]]);
  };
  auto dot_part = [&](int t, int hf) {
    const int x = t & 1;
    if (hf == 0) {
      const uint32_t pe = hfma2(r < 2 ? d[x][24] : d[x][25], ex[t & 3], 0u);
      s[0] = r < 2 ? pe : 0u; s[1] = r < 2 ? 0u : pe; s[2] = s[3] = 0;
    }
#pragma unroll
    for (int q = 3 * hf; q < 3 * hf + 3; q++)
#pragma unroll
      for (int e = 0; e < 4; e++) s[e] = hfma2(d[x][q * 4 + e], a[x][q][e], s[e]);
  };
  float* outp = g_partP + slice * B_ + range * 256 + r * 4 + ((lane >> 3) & 1) * 2 + (lane >> 4);
  float k0 = 0.f, k1 = 0.f, x0 = 0.f, x1 = 0.f;
  auto red_stage = [&](int st, int grp) {
    const bool u16 = lane & 16, u8 = lane & 8;
    if (st == 0) {
      k0 = u16 ? red[2] : red[0]; x0 = __shfl_xor_sync(0xffffffffu, u16 ? red[0] : red[2], 16);
      k1 = u16 ? red[3] : red[1]; x1 = __shfl_xor_sync(0xffffffffu, u16 ? red[1] : red[3], 16);
      red[0] = red[1] = red[2] = red[3] = 0.f;
    }
    if (st == 1) { const float p0 = k0 + x0, p1 = k1 + x1; k0 = u8 ? p1 : p0; x0 = __shfl_xor_sync(0xffffffffu, u8 ? p0 : p1, 8); }
    if (st == 2) { k0 += x0; x0 = __shfl_xor_sync(0xffffffffu, k0, 4); }
    if (st == 3 && !(lane & 4)) outp[grp * 16] = (k0 + x0) * unscale * unscale * unscale2;
  };
  auto group = [&](bool first, int prv, int cur, int nxt) {
    const int pn = PX_OFF + px + nxt * 136 + lane;
#pragma unroll
    for (int t = 0; t < 8; t++) {
      issue((t & 1) ^ 1);
      SCHED_FENCE(never, t * 8);
      if (!first) {
        if (t == 0) { iv[3] = ldtex(tex, PX_OFF + px + cur * 136 + lane + 96); iv[0] = ldtex(tex, pn); }
        if (t == 2) iv[1] = ldtex(tex, pn + 32);
        if (t < 4) red_stage(t, prv);
      } else if (t == 4) {
        TS(4, 2);
        flag_wait(&g_flag[(cta >> 4) * 32], 16);
        TS(4, 3);
        iv[0] = ldtex(tex, pn); iv[1] = ldtex(tex, pn + 32);
      }
      if (t == 4) { ix = ldtex(texX, (px + nxt * 136 + 128) * 4 + lane).x; iv[2] = ldtex(tex, pn + 64); }
      dot_part(t, 0); dot_part(t, 1);
      SCHED_FENCE(never, t * 8 + 1);
      if (t == 3) ldsm(ex, ix >> 10);
      if (t == 7) ldsm(ex, ix);
      gather(t + 2, 0); gather(t + 2, 1);
      asm volatile("wgmma.wait_group.sync.aligned 0;" ::: "memory");
      SCHED_FENCE(never, t * 8 + 2);
      mma16816f(red, s, g == t ? 0x3c003c00u : 0u);
      hmma_part(t + 1);
      SCHED_FENCE(never, t * 8 + 3);
    }
  };
  gather(0, 0); gather(0, 1); issue(0); ldsm(ex, ix); gather(1, 0); gather(1, 1);
  asm volatile("wgmma.wait_group.sync.aligned 0;" ::: "memory");
  hmma_part(0);
  int prv = slice, cur = slice == 0;
  group(true, 0, prv, cur);
  TS(4, 1);
#pragma unroll 1
  for (int n = 1; n < NGRP; n++) {
    const int nxt = (n + (n >= slice)) & 15;
    if (n == TRIG) asm volatile("griddepcontrol.launch_dependents;");
    if (PXW && tid == 0) mbar_arrive(progG);
    group(false, prv, cur, nxt);
    prv = cur; cur = nxt;
  }
#pragma unroll
  for (int st = 0; st < 4; st++) red_stage(st, prv);
  TS(0, 2);
  asm volatile("barrier.cluster.arrive.relaxed.aligned; barrier.cluster.wait.aligned;" ::: "memory");
}

constexpr int SM_U = 130048, SM_BAR = 128000, SM_J = SM_U + 98304, DEEP_SMEM = SM_J + 4096;

__device__ __forceinline__ void arrive_both(uint32_t bar, int lane) {
  asm volatile("{.reg .pred p; .reg .u32 a; setp.lt.u32 p,%1,2; mapa.shared::cluster.u32 a,%0,%1;\n"
               "@p mbarrier.arrive.shared::cluster.b64 _,[a];}" :: "r"(bar), "r"(lane) : "memory");
}
#define ELECT "{.reg .pred p; elect.sync _|p,0xffffffff; @p "
__device__ __forceinline__ void e_mc(uint32_t dst, const void* src, uint32_t bytes, uint32_t bar, uint64_t pol) {
  asm volatile(ELECT "cp.async.bulk.shared::cluster.global.mbarrier::complete_tx::bytes.multicast::cluster.L2::cache_hint [%0],[%1],%2,[%3],%4,%5;}"
               :: "r"(dst), "l"(src), "r"(bytes), "r"(bar), "h"((unsigned short)3), "l"(pol) : "memory");
}
__device__ __forceinline__ void e_g2s(uint32_t dst, const void* src, uint32_t bytes, uint32_t bar) {
  asm volatile(ELECT "cp.async.bulk.shared::cluster.global.mbarrier::complete_tx::bytes [%0],[%1],%2,[%3];}" :: "r"(dst), "l"(src), "r"(bytes), "r"(bar) : "memory");
}
__device__ __forceinline__ void e_pf(const void* src, uint32_t bytes) { asm volatile(ELECT "cp.async.bulk.prefetch.L2.global [%0],%1;}" :: "l"(src), "r"(bytes) : "memory"); }
__device__ __forceinline__ void e_expect(uint32_t bar, uint32_t bytes) { asm volatile(ELECT "mbarrier.arrive.expect_tx.shared::cta.b64 _,[%0],%1;}" :: "r"(bar), "r"(bytes) : "memory"); }

__global__ void __cluster_dims__(2, 1, 1) __launch_bounds__(TH + 128, 1)
k_deep(cudaTextureObject_t tex, const __nv_bfloat16* __restrict__ w2, const __nv_bfloat16* __restrict__ b2,
       __nv_bfloat16* __restrict__ out, int never) {
  extern __shared__ __align__(1024) uint4 sm[];
  constexpr int PF = DPF, DEPTH = DDEPTH, NW = TH / 32;
  static_assert(YD == 4 && PF == 4, "");
  const int tid = threadIdx.x;
  const int c = blockIdx.x >> 1, half = blockIdx.x & 1;
  const uint32_t sbase = (uint32_t)__cvta_generic_to_shared(sm);
  const uint32_t fullL = sbase + SM_BAR, fullU = fullL + 8, emptyL = fullL + 16, emptyU = fullL + 24, barJ = fullL + 32;
  TS(1, 0);
  if (tid == 0) {
    mbar_init(fullL, 1); mbar_init(fullU, 1); mbar_init(emptyL, 2 * NW); mbar_init(emptyU, 2 * NW); mbar_init(barJ, 1);
    asm volatile("fence.mbarrier_init.release.cluster;" ::: "memory");
  }
  __syncwarp();
  const int wrp = __shfl_sync(0xffffffffu, tid >> 5, 0);
  const char* base = (const char*)g_scr;
  uint32_t oL = (PL_OFF + c * NC * 8000) * 16u + half * 64000, oS = (PS_OFF + c * NC * 2000) * 16u + half * 16000;
  asm volatile("barrier.cluster.arrive.relaxed.aligned;" ::: "memory");
  flag_wait(&g_flag[8 * 32], 132);
  asm volatile("barrier.cluster.wait.aligned;" ::: "memory");
  if (wrp == NW) {
    asm volatile("fence.proxy.async.global;" ::: "memory");
    e_expect(fullU, 96000);
#pragma unroll
    for (int m = 0; m < 3; m++) e_mc(sbase + SM_U + m * 32032 + half * 16000, base + oS, 16000, fullU, m == 2 ? POL_EF : POL_N);
    e_expect(fullL, 128000);
    if (!STAG) e_mc(sbase + half * 64000, base + oL, 64000, fullL, POL_EF);
  }
  TS(5, 1);
  if (wrp >= NW) {
    asm volatile("setmaxnreg.dec.sync.aligned.u32 24;");
    if (wrp == NW) {
      uint32_t oT = (PT_OFF + c * 10 * 1024) * 16u + half * 8192;
      const uint32_t junk = sbase + SM_J, oW = (IX_OFF + half * IXH + ((c + (c >> 4) * 5) & 15) * 512) * 16u;
      auto warm = [&](uint32_t off) {
        asm volatile(ELECT "mbarrier.expect_tx.relaxed.cta.shared::cta.b64 [%0],%1;}" :: "r"(barJ), "r"(8192) : "memory");
        e_g2s(junk, base + off, 4096, barJ); e_g2s(junk, base + off + 4096, 4096, barJ);
      };
      uint32_t t0 = clock();
      if (!PREW) warm(oW);
      if (STAG) { if (STAG == 1) mbar_wait_fast(fullU, 0); else sleep_until(t0, STAG); e_mc(sbase + half * 64000, base + oL, 64000, fullL, POL_EF); }
      warm(oT);
      if (!(PREW & 4)) warm(oW + 131072);
#pragma unroll 1
      for (int k = 0; k + 1 < NC; k++) {
        oL += 128000; oS += 32000; oT += 16384;
        mbar_wait_fast(fullL, k & 1);
        t0 = clock();
        e_pf(base + oS, 16000);
        warm(k + 2 < NC ? oW + (k + 2) * 131072 : (IX_OFF + half * IXH + NC * 8192 + (c & 3) * 512) * 16u);
        mbar_wait_fast(emptyU, k & 1);
        e_expect(fullU, 96000);
#pragma unroll 1
        for (int q = 0; q < 8; q++) {
          sleep_until(t0, q * PACE);
          e_pf(base + oL + q * 8000, 8000);
          if (q >= 2) e_mc(sbase + SM_U + ((q - 2) >> 1) * 32032 + half * 16000 + (q & 1) * 8000, base + oS + (q & 1) * 8000, 8000, fullU, q >= 6 ? POL_EF : POL_N);
        }
        warm(oT);
        e_expect(fullL, 128000);
        mbar_wait_fast(emptyL, k & 1);
        e_mc(sbase + half * 64000, base + oL, 64000, fullL, POL_EF);
      }
      mbar_wait_fast(fullL, (NC - 1) & 1);
      mbar_wait_fast(emptyU, (NC - 1) & 1);
      mbar_arrive_lane0(fullU);
      warm(oT + 16384);
      mbar_arrive_lane0(barJ); mbar_wait_fast(barJ, 0);
    } else if (tid >= TH + 96) {
      if (tid == TH + 96) sts128(barJ + 32, *(const uint4*)(w2 + c * 8));
      asm volatile("bar.arrive 3,%0;" :: "n"(TH + 32) : "memory");
      asm volatile("griddepcontrol.wait;" ::: "memory");
      const int b = half * 8192 + c * 128 + (tid & 31) * 4;
      const float bias = __bfloat162float(b2[0]);
      float4 s = make_float4(bias, bias, bias, bias);
#pragma unroll 2
      for (int k = 0; k < 16; k++) { const float4 v = __ldcg((const float4*)(g_partP + k * B_ + b)); s.x += v.x; s.y += v.y; s.z += v.z; s.w += v.w; }
      asm volatile("red.global.add.v4.f32 [%0],{%1,%2,%3,%4};" :: "l"(g_acc + b), "f"(s.x), "f"(s.y), "f"(s.z), "f"(s.w) : "memory");
      asm volatile("bar.arrive 1,%0;" :: "n"(TH + 32) : "memory");
    }
    return;
  }
  asm volatile("setmaxnreg.inc.sync.aligned.u32 240;");
  const int lane = tid & 31;
  const int tbase = PT_OFF + c * 10 * 1024;
  const int ibase = IX_OFF + half * IXH + tid;
  const uint32_t lc = (tid & 7) << 4;
  uint4 acc[NS], wq[PF], x[DEPTH], y[YD], ye;
  uint32_t sw[NS] = {};
  auto sget = [&](int s) { return (s & 3) == 3 ? __byte_perm(__byte_perm(sw[s - 3], sw[s - 2], 0x0073), sw[s - 1], 0x0710) : sw[s]; };
  auto sa0 = [&](uint32_t v) { return sbase + SM_U + (((v << 5) & 0x1ffe0) | ((lc >> 2) & 16)); };
  auto sa1 = [&](uint32_t v) { return sbase + SM_U + (((v >> 7) & 0x1ffe0) | ((~lc >> 2) & 16)); };
  {
    uint4 i0[8];
#pragma unroll
    for (int q = 0; q < 8; q++) i0[q] = ldtex(tex, I0_OFF + (half * 8 + q) * TH + tid);
#pragma unroll
    for (int i = 0; i < PF; i++) if (!WQL) wq[i] = ldtex(tex, ibase + i * TH);
    auto wd = [&](int k) { return (k & 3) == 0 ? i0[k >> 2].x : (k & 3) == 1 ? i0[k >> 2].y : (k & 3) == 2 ? i0[k >> 2].z : i0[k >> 2].w; };
    TS(5, 2);
    mbar_wait_fast(fullU, 0);
#pragma unroll
    for (int i = 0; i < PF; i++) if (WQL) wq[i] = ldtex(tex, ibase + i * TH);
    TS(1, 1);
#pragma unroll
    for (int s = 0; s < NS; s++) acc[s] = add4(lds128(sa0(wd(s))), lds128(sa1(wd(s))));
    arrive_both(emptyU, lane);
    asm volatile("bar.sync 3,%0;" :: "n"(TH + 32) : "memory");
    TS(5, 3);
  }
#pragma unroll 1
  for (int k = 0; k < NC; k++) {
    const int ti = ibase + k * 8192;
    const int tb = tbase + k * 1024;
    const bool more = k + 1 < NC;
    TR(k * 4);
    if (CBAR & 1) asm volatile("bar.sync 4,%0;" :: "n"(TH) : "memory");
    mbar_wait_fast(fullL, k & 1);
    TR(k * 4 + 2);
    uint4 w, cc; uint32_t yc, yn;
    constexpr int TL = NS * 8, TT = TL + NS * 2;
#pragma unroll
    for (int t = 0; t < TT + DEPTH; t += 2) {
      if (t == TL + DEPTH && !more) break;
      if (t >= DEPTH) {
        const int u = t - DEPTH;
        uint4 p = add4(x[u % DEPTH], x[(u + 1) % DEPTH]);
        if (u < TL) {
          const int s = u >> 3, j = u & 7;
          if (j == 0) {
            cc = s >= YD ? add4(y[s % YD], p) : p;
            if (s + YD < NS) y[s % YD] = ldtex(tex, tb | (yc & 1023));
          } else cc = add4(cc, p);
          if (j == 6) acc[s] = add4(acc[s], cc);
        } else {
          const int s = (u - TL) >> 1;
          acc[s] = add4(acc[s], p);
        }
      }
      if ((CBAR & 4) && t == TL / 2) asm volatile("bar.sync 4,%0;" :: "n"(TH) : "memory");
      if ((CBAR & 8) && t == TL - 40) asm volatile("bar.sync 4,%0;" :: "n"(TH) : "memory");
      if (DEPTH == 8 && (t & 7) == 2) yc = yn;
      if (t < TL) {
        const int s = t >> 3, j = t & 7;
        if (j == 0) {
          if (ye_of(s - YD) >= 0) acc[ye_of(s - YD) & 3] = add4(acc[ye_of(s - YD) & 3], ye);
          w = wq[s % PF];
          if (!EARLY || s < NS - 4) wq[s % PF] = ldtex(tex, ti + (s + PF) * TH);
          else {
            if (s == NS - 4) { wq[0] = ldtex(tex, ti + NS * TH); ye = ldtex(tex, ti + (NS + 3) * TH); }
            if (s == NS - 3) { wq[1] = ldtex(tex, ti + (NS + 1) * TH); y[0] = ldtex(tex, ti + (NS + 2) * TH); }
            if (s == NS - 2) wq[2] = y[0];
            if (s == NS - 1) wq[3] = ye;
          }
          yn = __funnelshift_l(w.z, w.z, 5); if (DEPTH < 8) yc = yn;
          if ((s & 3) != 3) asm volatile("add.u32 %0,%1,%2;" : "=r"(sw[s]) : "r"(w.w), "r"(never));
          if (ye_of(s) >= 0) ye = ldtex(tex, tb | w.w);
        }
#pragma unroll
        for (int jj = j; jj < j + 2; jj++) {
          const uint32_t ww = jj < 3 ? w.x : jj < 6 ? w.y : w.z;
          const uint32_t sh = jj % 3 == 0 ? ww : jj % 3 == 1 ? ww >> 10 : __funnelshift_l(ww, ww, 12);
          x[(t + jj - j) % DEPTH] = lds128(sbase + ((sh & 0x1ff80) | lc) + jj * 16 - 128);
        }
      } else if (t < TT) {
        const int s = (t - TL) >> 1;
        if (s == 0) { arrive_both(emptyL, more ? lane : 9); TR(k * 4 + 3); if (CBAR & 2) asm volatile("bar.sync 4,%0;" :: "n"(TH) : "memory"); mbar_wait_fast(fullU, (k + 1) & 1); }
        const uint32_t sv = sget(s);
        x[t % DEPTH] = lds128(sa0(sv));
        x[(t + 1) % DEPTH] = lds128(sa1(sv));
      } else if (t == TT) arrive_both(emptyU, lane);
      if ((t & (FENCE_N - 1)) == FENCE_N - 2) SCHED_FENCE(never, t);
    }
  }
  TS(1, 2);
  const uint4 w2v = lds128(barJ + 32);
  const uint32_t cell = sbase + SM_U + tid * 16;
  const int t9 = tbase + 9 * 1024;
  uint4 za[4], i9 = wq[0];
  auto fetch = [&](int q) {
    y[0] = ldtex(tex, t9 | i9.x); y[1] = ldtex(tex, t9 | i9.y); y[2] = ldtex(tex, t9 | i9.z); y[3] = ldtex(tex, t9 | i9.w);
    if (q) {
      i9 = ldtex(tex, ibase + NC * 8192 + min(q + 1, 7) * TH);
      const uint32_t ca = cell + (q > 6 ? 0 : q - 1) * 16384;
#pragma unroll
      for (int s = 0; s < 4; s++) za[s] = lds128(ca + s * 4096);
    }
  };
  fetch(0);
  i9 = wq[1];
#pragma unroll
  for (int s = 0; s < 4; s++) za[s] = acc[s];
#pragma unroll
  for (int s = 0; s < 24; s++) sts128(cell + s * 4096, acc[4 + s]);
  float hw[8];
  {
    const uint32_t ww[4] = {w2v.x, w2v.y, w2v.z, w2v.w};
#pragma unroll
    for (int k = 0; k < 8; k++) hw[k] = 0.5f * ((k & 1) ? bf_hi(ww[k >> 1]) : bf_lo(ww[k >> 1]));
  }
  float* outp = g_acc + half * 8192 + tid;
#pragma unroll 1
  for (int q = 0; q < NS / 4; q++) {
    uint4 z[4];
#pragma unroll
    for (int s = 0; s < 4; s++) z[s] = add4(za[s], y[s]);
    if (q == 1) {
#pragma unroll
      for (int s = 0; s < 4; s++) sts128(cell + s * 4096, acc[28 + s]);
    }
    if (q < 7) fetch(q + 1);
    SCHED_FENCE(never, 999);
#pragma unroll
    for (int s = 0; s < 4; s++) {
      const uint32_t a[4] = {z[s].x, z[s].y, z[s].z, z[s].w};
      float r0 = 0.f;
#pragma unroll
      for (int k = 0; k < 8; k++) {
        const float v = (k & 1) ? bf_hi(a[k >> 1]) : bf_lo(a[k >> 1]);
        const float u = v * fmaf(v * v, 0.7978845608028654f * 0.044715f, 0.7978845608028654f);
        float th; asm("tanh.approx.f32 %0,%1;" : "=f"(th) : "f"(u));
        r0 = fmaf(fmaf(v, th, v), hw[k], r0);
      }
      asm volatile("red.global.add.f32 [%0],%1;" :: "l"(outp + s * TH), "f"(r0) : "memory");
    }
    outp += 4 * TH;
  }
  TS(1, 3);
  asm volatile("bar.sync 1,%0;" :: "n"(TH + 32) : "memory");
  if (tid == 0) {
    __threadfence();
    const unsigned old = atomicInc(&g_done[half * 32], 63);
    asm volatile("st.shared.u32 [%0],%1;" :: "r"(barJ + 8), "r"(old) : "memory");
  }
  asm volatile("bar.sync 2,%0;" :: "n"(TH) : "memory");
  uint32_t old; asm volatile("ld.shared.u32 %0,[%1];" : "=r"(old) : "r"(barJ + 8));
  if (old == 63) {
    if (half == 0 && tid < 9) g_flag[tid * 32] = 0;
    __threadfence();
    float4 v[8];
#pragma unroll
    for (int q = 0; q < 8; q++) v[q] = __ldcg((const float4*)(g_acc + half * 8192) + q * TH + tid);
#pragma unroll
    for (int q = 0; q < 8; q++) ((uint2*)(out + half * 8192))[q * TH + tid] = make_uint2(pack_bf2(v[q].x, v[q].y), pack_bf2(v[q].z, v[q].w));
    TS(6, 2);
  }
}

}

extern "C" void kernel_launch(void* const* d_in, const int* in_sizes, int n_in, void* d_out, int out_size) {
  const int* idx = (const int*)d_in[0];
  const __nv_bfloat16* table = (const __nv_bfloat16*)d_in[1];
  const __nv_bfloat16* wp = (const __nv_bfloat16*)d_in[2];
  const __nv_bfloat16* w1 = (const __nv_bfloat16*)d_in[3];
  const __nv_bfloat16* b1 = (const __nv_bfloat16*)d_in[4];
  const __nv_bfloat16* w2 = (const __nv_bfloat16*)d_in[5];
  const __nv_bfloat16* b2 = (const __nv_bfloat16*)d_in[6];
  static cudaTextureObject_t texScr = 0, texG = 0;
  static CUtensorMap mapW, mapL, mapS, mapT, mapE, mapC;
  static const void *c_tab = nullptr, *c_w1 = nullptr;
  if (c_tab != table || c_w1 != w1) {
    c_tab = table; c_w1 = w1;
    char* scr = nullptr; cudaGetSymbolAddress((void**)&scr, g_scr);
    auto mk_tex = [](const void* p, size_t bytes, cudaChannelFormatDesc d) {
      cudaResourceDesc rd = {}; rd.resType = cudaResourceTypeLinear; rd.res.linear.devPtr = (void*)p; rd.res.linear.desc = d; rd.res.linear.sizeInBytes = bytes;
      cudaTextureDesc td = {}; td.readMode = cudaReadModeElementType;
      cudaTextureObject_t t = 0; cudaCreateTextureObject(&t, &rd, &td, nullptr); return t;
    };
    if (!texScr) {
      texScr = mk_tex(scr, (size_t)SCR_N * 16, cudaCreateChannelDesc<uint4>());
      texG = mk_tex(scr + (size_t)PX_OFF * 16, (size_t)(SCR_N - PX_OFF) * 16, cudaCreateChannelDesc<unsigned>());
    }
    typedef CUresult (*EncFn)(CUtensorMap*, CUtensorMapDataType, cuuint32_t, void*, const cuuint64_t*, const cuuint64_t*, const cuuint32_t*,
                              const cuuint32_t*, CUtensorMapInterleave, CUtensorMapSwizzle, CUtensorMapL2promotion, CUtensorMapFloatOOBfill);
    EncFn enc = nullptr; cudaDriverEntryPointQueryResult qr;
    cudaGetDriverEntryPoint("cuTensorMapEncodeTiled", (void**)&enc, cudaEnableDefault, &qr);
    const cuuint32_t ones[4] = {1, 1, 1, 1};
    auto mk = [&](CUtensorMap* m, CUtensorMapDataType dt, int rank, void* p, const cuuint64_t* dim, const cuuint64_t* str, const cuuint32_t* box, CUtensorMapSwizzle sw) {
      enc(m, dt, rank, p, dim, str, box, ones, CU_TENSOR_MAP_INTERLEAVE_NONE, sw, CU_TENSOR_MAP_L2_PROMOTION_NONE, CU_TENSOR_MAP_FLOAT_OOB_FILL_NONE);
    };
    { cuuint64_t dim[2] = {H_, F_ * D_}, str[1] = {H_ * 2}; cuuint32_t box[2] = {32, 256};
      mk(&mapW, CU_TENSOR_MAP_DATA_TYPE_BFLOAT16, 2, (void*)w1, dim, str, box, CU_TENSOR_MAP_SWIZZLE_64B); }
    { cuuint64_t dim[4] = {64, V_, NC, 64}, str[3] = {128, 128000, 128000 * NC}; cuuint32_t box[4] = {32, 64, 1, 4};
      mk(&mapL, CU_TENSOR_MAP_DATA_TYPE_BFLOAT16, 4, scr + (size_t)PL_OFF * 16, dim, str, box, CU_TENSOR_MAP_SWIZZLE_64B); }
    { cuuint64_t dim[4] = {16, V_, NC, 64}, str[3] = {32, 32000, 32000 * NC}; cuuint32_t box[4] = {16, 64, 1, 4};
      mk(&mapS, CU_TENSOR_MAP_DATA_TYPE_BFLOAT16, 4, scr + (size_t)PS_OFF * 16, dim, str, box, CU_TENSOR_MAP_SWIZZLE_32B); }
    { cuuint64_t dim[3] = {2048, 10, 64}, str[2] = {16384, 163840}; cuuint32_t box[3] = {128, 2, 4};
      mk(&mapT, CU_TENSOR_MAP_DATA_TYPE_UINT64, 3, scr + (size_t)PT_OFF * 16, dim, str, box, CU_TENSOR_MAP_SWIZZLE_NONE); }
    { cuuint64_t dim[2] = {D_, V_}, str[1] = {D_ * 2}; cuuint32_t box[2] = {64, 128};
      mk(&mapE, CU_TENSOR_MAP_DATA_TYPE_BFLOAT16, 2, (void*)table, dim, str, box, CU_TENSOR_MAP_SWIZZLE_128B);
      cuuint32_t box2[2] = {8, 256};
      mk(&mapC, CU_TENSOR_MAP_DATA_TYPE_BFLOAT16, 2, (void*)table, dim, str, box2, CU_TENSOR_MAP_SWIZZLE_NONE); }
    cudaFuncSetAttribute(k_deep, cudaFuncAttributeMaxDynamicSharedMemorySize, DEEP_SMEM);
    cudaFuncSetAttribute(k_tens, cudaFuncAttributeMaxDynamicSharedMemorySize, K1_SMEM);
  }
  k_tens<<<132, 512, K1_SMEM, cudaStreamPerThread>>>(mapW, mapL, mapS, mapT, mapE, mapC, texScr, texG, idx, table, wp, w1, b1, 0);
  cudaLaunchAttribute at[1];
  at[0].id = cudaLaunchAttributeProgrammaticStreamSerialization; at[0].val.programmaticStreamSerializationAllowed = 1;
  cudaLaunchConfig_t cfg = {};
  cfg.stream = cudaStreamPerThread; cfg.attrs = at;
  cfg.gridDim = 128; cfg.blockDim = TH + 128; cfg.dynamicSmemBytes = DEEP_SMEM; cfg.numAttrs = PDL & 1;
  cudaLaunchKernelEx(&cfg, k_deep, texScr, w2, b2, (__nv_bfloat16*)d_out, 0);

}
```

```cpp
#include <cuda_runtime.h>
#include <cuda_bf16.h>
#include <cuda_fp16.h>
#include <stdint.h>
#include <cuda.h>

namespace {

constexpr int B_ = 16384, F_ = 100, D_ = 128, V_ = 1000, H_ = 512;
constexpr int NC = 9;
constexpr int PT_OFF = 0;
constexpr int PL_OFF = 64 * 10 * 1024;
constexpr int PS_OFF = PL_OFF + 64 * NC * 8000;
constexpr int IXH = NC * 8192 + 2048;
constexpr int IX_OFF = PS_OFF + 64 * NC * 2000;
constexpr int I0_OFF = IX_OFF + 2 * IXH;
constexpr int PX_OFF = I0_OFF + 4096;
constexpr int SCR_N = PX_OFF + 64 * 16 * 136;
static_assert(PX_OFF % 32 == 0, "");

__device__ __align__(1024) uint4 g_scr[SCR_N];
__device__ float g_acc[B_];
__device__ unsigned g_done[64];
__device__ float g_partP[16 * B_];
__device__ unsigned g_flag[16 * 32];

#define TS(k, i)
#define TR(slot)
#define PT(slot)

constexpr uint64_t POL_EF = 0x12F0000000000000ull, POL_N = 0x1000000000000000ull;
__device__ __forceinline__ uint32_t addbf2(uint32_t a, uint32_t b) { uint32_t r; asm("add.rn.bf16x2 %0,%1,%2;" : "=r"(r) : "r"(a), "r"(b)); return r; }
__device__ __forceinline__ uint4 add4(const uint4& a, const uint4& b) { return make_uint4(addbf2(a.x, b.x), addbf2(a.y, b.y), addbf2(a.z, b.z), addbf2(a.w, b.w)); }
__device__ __forceinline__ void acc4(uint4& a, const uint4& b, int never) {
  asm("{.reg .pred p; setp.eq.s32 p,%8,0;\n"
      "@p add.rn.bf16x2 %0,%0,%4; @p add.rn.bf16x2 %1,%1,%5; @p add.rn.bf16x2 %2,%2,%6; @p add.rn.bf16x2 %3,%3,%7;}"
      : "+r"(a.x), "+r"(a.y), "+r"(a.z), "+r"(a.w) : "r"(b.x), "r"(b.y), "r"(b.z), "r"(b.w), "r"(never));
}
__device__ __forceinline__ uint4 ldtex(cudaTextureObject_t t, int i) {
  uint4 v; asm volatile("tex.1d.v4.u32.s32 {%0,%1,%2,%3},[%4,{%5}];" : "=r"(v.x), "=r"(v.y), "=r"(v.z), "=r"(v.w) : "l"(t), "r"(i)); return v;
}
__device__ __forceinline__ uint4 lds128(uint32_t a) {
  uint4 v; asm volatile("ld.volatile.shared.v4.u32 {%0,%1,%2,%3},[%4];" : "=r"(v.x), "=r"(v.y), "=r"(v.z), "=r"(v.w) : "r"(a)); return v;
}
__device__ __forceinline__ void sts128(uint32_t a, const uint4& v) {
  asm volatile("st.shared.v4.u32 [%0],{%1,%2,%3,%4};" :: "r"(a), "r"(v.x), "r"(v.y), "r"(v.z), "r"(v.w) : "memory");
}
__device__ __forceinline__ void mbar_init(uint32_t bar, int n) { asm volatile("mbarrier.init.shared::cta.b64 [%0],%1;" :: "r"(bar), "r"(n) : "memory"); }
__device__ __forceinline__ void mbar_wait(uint32_t bar, uint32_t parity) {
  uint32_t ok; int it = 0;
  do { asm volatile("{.reg .pred p; mbarrier.try_wait.parity.shared::cta.b64 p,[%1],%2; selp.u32 %0,1,0,p;}" : "=r"(ok) : "r"(bar), "r"(parity) : "memory"); } while (!ok && ++it < (1 << 19));
}
__device__ __forceinline__ void mbar_expect(uint32_t bar, uint32_t bytes) { asm volatile("mbarrier.arrive.expect_tx.shared::cta.b64 _,[%0],%1;" :: "r"(bar), "r"(bytes) : "memory"); }
__device__ __forceinline__ void bulk_g2s(uint32_t dst, const void* src, uint32_t bytes, uint32_t bar) {
  asm volatile("cp.async.bulk.shared::cluster.global.mbarrier::complete_tx::bytes [%0],[%1],%2,[%3];" :: "r"(dst), "l"(src), "r"(bytes), "r"(bar) : "memory");
}
__device__ __forceinline__ void bulk_pf(const void* src, uint32_t bytes) { asm volatile("cp.async.bulk.prefetch.L2.global [%0],%1;" :: "l"(src), "r"(bytes) : "memory"); }
#define NOMMA 0
#define NGRP 16
#define PDL 1
#define FIN_S 128
#define WR8 0
#define TRIG 14
#define PREW 5
#define PXW 3
#define WQL 1
#define EARLY 1
#define CBAR 0
#define X_SAMEK 0
#define X_SAMEW 0
#define FM 0
#define TW 1
#define PP0 10
#define PT0 10000
#define PDT 0
#define RPNN "160"
#define RAUX "32"
#define RPRO "160"
#define PARK 0
#define NLOOK 128
#define NEF 16
#define ORD 0
#define WFENCE 0
#define SPLIT 1
#define IORD 3
#define IPF 3
#define IPACE 4500
#define WPF 3
#define QV 3
#define QORD(n) ((n) < 23 ? (n) + 2 : (n) - 23)
#define DYD 4
#define DPF 4
#define DDEPTH 4
#define FENCE_N 4
#define INPL 0
#define STAG 1
#define PACE 800
#define PM4 "pmevent 1; pmevent 2; pmevent 3; pmevent 4;"
#define PMFILL "pmevent 1;"
#define SCHED_FENCE(never, k) asm volatile("{.reg .pred p; setp.ne.u32 p,%0,%1; @p bra.uni SKIP_%=;" PMFILL "SKIP_%=: }" :: "r"(never), "r"(0x7fff0000 + (k)) : "memory")

__global__ void k_prod_naive(const __nv_bfloat16* __restrict__ table, const __nv_bfloat16* __restrict__ w1) {
  __shared__ float t[8][D_];
  int f = blockIdx.y, v0 = blockIdx.x * 8, h = threadIdx.x;
  for (int i = h; i < 8 * D_; i += 512) t[i / D_][i % D_] = __bfloat162float(table[v0 * D_ + i]);
  __syncthreads();
  float s[8] = {0, 0, 0, 0, 0, 0, 0, 0};
  for (int d = 0; d < D_; d++) { float w = __bfloat162float(w1[(size_t)(f * D_ + d) * H_ + h]);
#pragma unroll
    for (int k = 0; k < 8; k++) s[k] += t[k][d] * w; }
  __nv_bfloat16* P = (__nv_bfloat16*)g_scr;
  int c = h >> 3;
  for (int k = 0; k < 8; k++) {
    size_t e = f < 72 ? (size_t)PL_OFF + ((size_t)(c * NC + (f >> 3)) * 1000 + v0 + k) * 8 + (f & 7)
             : f < 90 ? (size_t)PS_OFF + ((size_t)(c * NC + ((f - 72) >> 1)) * 1000 + v0 + k) * 2 + (f & 1)
                      : (size_t)PT_OFF + (size_t)(c * 10 + f - 90) * 1024 + v0 + k;
    P[e * 8 + (h & 7)] = __float2bfloat16(s[k]);
  }
}
__global__ void k_pnn_naive(const int* __restrict__ idx, const __nv_bfloat16* __restrict__ table, const __nv_bfloat16* __restrict__ wp) {
  __shared__ float e[F_][33];
  int b = blockIdx.x, d0 = blockIdx.y * 32, tid = threadIdx.x;
  for (int i = tid; i < F_ * 32; i += 128) e[i >> 5][i & 31] = __bfloat162float(table[idx[b * F_ + (i >> 5)] * D_ + d0 + (i & 31)]);
  __syncthreads();
  float s = 0; int d = tid & 31;
  for (int i = tid >> 5; i < F_; i += 4) { float u = 0; for (int j = 0; j < F_; j++) u += __bfloat162float(wp[i * F_ + j]) * e[j][d]; s += u * e[i][d]; }
  for (int o = 16; o; o >>= 1) s += __shfl_xor_sync(~0u, s, o);
  if (d == 0) g_partP[(blockIdx.y * 4 + (tid >> 5)) * B_ + b] = s;
}
__device__ __forceinline__ void mbar_wait_fast(uint32_t bar, uint32_t parity) {
  asm volatile("{.reg .pred p; .reg .u32 n;\n"
               "mbarrier.try_wait.parity.shared::cta.b64 p,[%0],%1;\n"
               "@p bra DONE_%=;\n"
               "mov.u32 n,0;\n"
               "LOOP_%=: mbarrier.try_wait.parity.shared::cta.b64 p,[%0],%1;\n"
               "add.u32 n,n,1; setp.gt.or.u32 p,n,400000,p;\n"
               "@!p bra LOOP_%=;\n"
               "DONE_%=: }" :: "r"(bar), "r"(parity) : "memory");
}
__device__ __forceinline__ void sleep_until(uint32_t t0, uint32_t dt) { while ((uint32_t)clock() - t0 < dt) __nanosleep(40); }
__device__ __forceinline__ uint32_t s_mask(uint32_t v, int q) { return (1u << ((v + 3 - q) & 3)) | (16u << ((v + 3 + q) & 3)); }
__device__ __forceinline__ uint32_t s_cell(uint32_t v, int q, uint32_t m) {
  const int t = __ffs(~m) - 1;
  const int cp = t == 8 ? q >> 1 : ((t & 4 ? t - q : t + q) - v) & 3;
  return cp * 1001 + v;
}
__device__ __forceinline__ uint32_t pk3(uint32_t a, uint32_t b, uint32_t c) {
  const uint32_t w = c + (a << 12) + (b << 22); return __funnelshift_l(w, w, 27);
}
constexpr int TH = 256, NS = 8192 / TH, YD = DYD;
__host__ __device__ constexpr int ye_of(int s) { return s == 3 ? 0 : s == 11 ? 1 : s == 19 ? 2 : s == 23 ? 3 : -1; }
template <int N> __device__ __forceinline__ void wgmma_h(uint32_t* d, const uint32_t* a, uint64_t desc, int acc);
template <> __device__ __forceinline__ void wgmma_h<64>(uint32_t* d, const uint32_t* a, uint64_t desc, int acc) {
  asm volatile("{.reg .pred p; setp.ne.s32 p,%21,0;\n"
    "wgmma.mma_async.sync.aligned.m64n64k16.f16.f16.f16 {%0,%1,%2,%3,%4,%5,%6,%7,%8,%9,%10,%11,%12,%13,%14,%15},{%16,%17,%18,%19},%20,p,1,1,0;}"
    : "+r"(d[0]),"+r"(d[1]),"+r"(d[2]),"+r"(d[3]),"+r"(d[4]),"+r"(d[5]),"+r"(d[6]),"+r"(d[7]),"+r"(d[8]),"+r"(d[9]),"+r"(d[10]),"+r"(d[11]),"+r"(d[12]),"+r"(d[13]),"+r"(d[14]),"+r"(d[15])
    : "r"(a[0]), "r"(a[1]), "r"(a[2]), "r"(a[3]), "l"(desc), "r"(acc));
}
template <> __device__ __forceinline__ void wgmma_h<56>(uint32_t* d, const uint32_t* a, uint64_t desc, int acc) {
  asm volatile("{.reg .pred p; setp.ne.s32 p,%19,0;\n"
    "wgmma.mma_async.sync.aligned.m64n56k16.f16.f16.f16 {%0,%1,%2,%3,%4,%5,%6,%7,%8,%9,%10,%11,%12,%13},{%14,%15,%16,%17},%18,p,1,1,0;}"
    : "+r"(d[0]),"+r"(d[1]),"+r"(d[2]),"+r"(d[3]),"+r"(d[4]),"+r"(d[5]),"+r"(d[6]),"+r"(d[7]),"+r"(d[8]),"+r"(d[9]),"+r"(d[10]),"+r"(d[11]),"+r"(d[12]),"+r"(d[13])
    : "r"(a[0]), "r"(a[1]), "r"(a[2]), "r"(a[3]), "l"(desc), "r"(acc));
}
template <> __device__ __forceinline__ void wgmma_h<48>(uint32_t* d, const uint32_t* a, uint64_t desc, int acc) {
  asm volatile("{.reg .pred p; setp.ne.s32 p,%17,0;\n"
    "wgmma.mma_async.sync.aligned.m64n48k16.f16.f16.f16 {%0,%1,%2,%3,%4,%5,%6,%7,%8,%9,%10,%11},{%12,%13,%14,%15},%16,p,1,1,0;}"
    : "+r"(d[0]),"+r"(d[1]),"+r"(d[2]),"+r"(d[3]),"+r"(d[4]),"+r"(d[5]),"+r"(d[6]),"+r"(d[7]),"+r"(d[8]),"+r"(d[9]),"+r"(d[10]),"+r"(d[11])
    : "r"(a[0]), "r"(a[1]), "r"(a[2]), "r"(a[3]), "l"(desc), "r"(acc));
}
template <> __device__ __forceinline__ void wgmma_h<40>(uint32_t* d, const uint32_t* a, uint64_t desc, int acc) {
  asm volatile("{.reg .pred p; setp.ne.s32 p,%15,0;\n"
    "wgmma.mma_async.sync.aligned.m64n40k16.f16.f16.f16 {%0,%1,%2,%3,%4,%5,%6,%7,%8,%9},{%10,%11,%12,%13},%14,p,1,1,0;}"
    : "+r"(d[0]),"+r"(d[1]),"+r"(d[2]),"+r"(d[3]),"+r"(d[4]),"+r"(d[5]),"+r"(d[6]),"+r"(d[7]),"+r"(d[8]),"+r"(d[9])
    : "r"(a[0]), "r"(a[1]), "r"(a[2]), "r"(a[3]), "l"(desc), "r"(acc));
}
template <> __device__ __forceinline__ void wgmma_h<32>(uint32_t* d, const uint32_t* a, uint64_t desc, int acc) {
  asm volatile("{.reg .pred p; setp.ne.s32 p,%13,0;\n"
    "wgmma.mma_async.sync.aligned.m64n32k16.f16.f16.f16 {%0,%1,%2,%3,%4,%5,%6,%7},{%8,%9,%10,%11},%12,p,1,1,0;}"
    : "+r"(d[0]),"+r"(d[1]),"+r"(d[2]),"+r"(d[3]),"+r"(d[4]),"+r"(d[5]),"+r"(d[6]),"+r"(d[7])
    : "r"(a[0]), "r"(a[1]), "r"(a[2]), "r"(a[3]), "l"(desc), "r"(acc));
}
__device__ __forceinline__ void wgmma_p(float* d, const uint32_t* a, uint64_t desc, int acc) {
  asm volatile("{.reg .pred p; setp.ne.s32 p,%37,0;\n"
    "wgmma.mma_async.sync.aligned.m64n64k16.f32.bf16.bf16 {%0,%1,%2,%3,%4,%5,%6,%7,%8,%9,%10,%11,%12,%13,%14,%15,%16,%17,%18,%19,%20,%21,%22,%23,%24,%25,%26,%27,%28,%29,%30,%31},{%32,%33,%34,%35},%36,p,1,1,1;}"
    : "+f"(d[0]),"+f"(d[1]),"+f"(d[2]),"+f"(d[3]),"+f"(d[4]),"+f"(d[5]),"+f"(d[6]),"+f"(d[7]),"+f"(d[8]),"+f"(d[9]),"+f"(d[10]),"+f"(d[11]),"+f"(d[12]),"+f"(d[13]),"+f"(d[14]),"+f"(d[15]),"+f"(d[16]),"+f"(d[17]),"+f"(d[18]),"+f"(d[19]),"+f"(d[20]),"+f"(d[21]),"+f"(d[22]),"+f"(d[23]),"+f"(d[24]),"+f"(d[25]),"+f"(d[26]),"+f"(d[27]),"+f"(d[28]),"+f"(d[29]),"+f"(d[30]),"+f"(d[31])
    : "r"(a[0]), "r"(a[1]), "r"(a[2]), "r"(a[3]), "l"(desc), "r"(acc));
}

__device__ __forceinline__ void mma16816h(uint32_t* c, const uint32_t* a, uint32_t b0, uint32_t b1) {
  asm("mma.sync.aligned.m16n8k16.row.col.f16.f16.f16.f16 {%0,%1},{%2,%3,%4,%5},{%6,%7},{%0,%1};"
      : "+r"(c[0]), "+r"(c[1]) : "r"(a[0]), "r"(a[1]), "r"(a[2]), "r"(a[3]), "r"(b0), "r"(b1));
}
__device__ __forceinline__ void mma1688h(uint32_t* c, uint32_t a0, uint32_t a1, uint32_t b) {
  asm("mma.sync.aligned.m16n8k8.row.col.f16.f16.f16.f16 {%0,%1},{%2,%3},{%4},{%0,%1};" : "+r"(c[0]), "+r"(c[1]) : "r"(a0), "r"(a1), "r"(b));
}
__device__ __forceinline__ void mma1688f(float* c, uint32_t a0, uint32_t a1, uint32_t b) {
  asm("mma.sync.aligned.m16n8k8.row.col.f32.f16.f16.f32 {%0,%1,%2,%3},{%4,%5},{%6},{%0,%1,%2,%3};"
      : "+f"(c[0]), "+f"(c[1]), "+f"(c[2]), "+f"(c[3]) : "r"(a0), "r"(a1), "r"(b));
}
__device__ __forceinline__ uint32_t hadd2(uint32_t a, uint32_t b) { uint32_t r; asm("add.rn.f16x2 %0,%1,%2;" : "=r"(r) : "r"(a), "r"(b)); return r; }
__device__ __forceinline__ uint32_t hfma2(uint32_t a, uint32_t b, uint32_t c) { uint32_t r; asm("fma.rn.f16x2 %0,%1,%2,%3;" : "=r"(r) : "r"(a), "r"(b), "r"(c)); return r; }
__device__ __forceinline__ uint32_t pack_bf2(float lo, float hi) { uint32_t r; asm("cvt.rn.bf16x2.f32 %0,%1,%2;" : "=r"(r) : "f"(hi), "f"(lo)); return r; }
__device__ __forceinline__ uint32_t pack_h2(float lo, float hi) { uint32_t r; asm("cvt.rn.f16x2.f32 %0,%1,%2;" : "=r"(r) : "f"(hi), "f"(lo)); return r; }
__device__ __forceinline__ float bf_lo(uint32_t w) { return __uint_as_float(w << 16); }
__device__ __forceinline__ float bf_hi(uint32_t w) { return __uint_as_float(w & 0xffff0000u); }
__device__ __forceinline__ uint32_t absmax4(const uint4& v, uint32_t m) {
  return __vmaxu2(__vmaxu2(__vmaxu2(v.x & 0x7fff7fffu, v.y & 0x7fff7fffu), __vmaxu2(v.z & 0x7fff7fffu, v.w & 0x7fff7fffu)), m);
}
__device__ __forceinline__ float pow2_scale(uint32_t mbits, int p) { return __uint_as_float((uint32_t)min(max(253 + p - (int)(mbits >> 7), 2), 252) << 23); }

#define PV 4
constexpr int G_O0 = 8, G_O1 = 4, G_O2 = 0, G_N0 = 5, G_N1 = 4, G_N2 = 4, G_K0 = 5, G_K1 = 3, G_K2 = 1;
__host__ __device__ constexpr bool unit_wg(int kb, int on) {
  return (on >= G_O0 && on < G_O0 + G_N0 && kb < G_K0) || (on >= G_O1 && on < G_O1 + G_N1 && kb < G_K1) || (on >= G_O2 && on < G_O2 + G_N2 && kb < G_K2);
}
__host__ __device__ constexpr bool oct_wg(int on) { return unit_wg(0, on); }
constexpr int G_U1 = G_N0 * G_K0, G_U2 = G_U1 + G_N1 * G_K1, G_U = G_U2 + G_N2 * G_K2;
constexpr int K1_B = 130048, K1_STG = K1_B + 3 * 16384, K1_W = K1_STG + 2 * 16384, K1_BAR = K1_W + 48 * 256, K1_SMEM = K1_BAR + 128 + 4352;
__host__ __device__ constexpr int frag_index(int ok, int on) {
  int n = 0;
  for (int k = 0; k < 13; k++) for (int o = k; o < 13; o++) { if (k == ok && o == on) return n; if (!unit_wg(k >> 1, o)) n++; }
  return n;
}
constexpr int HU_N = 2 * G_U + frag_index(99, 99);
static_assert(HU_N <= 96, "");
struct FragIdx { int v[13][13]; };
__host__ __device__ constexpr FragIdx make_fi() { FragIdx f = {}; for (int k = 0; k < 13; k++) for (int o = 0; o < 13; o++) f.v[k][o] = frag_index(k, o); return f; }
__host__ __device__ constexpr uint64_t frag_tab(int first) {
  uint64_t t = 0;
  for (int k = 0; k < 13; k++) for (int o = k; o < 13; o++)
    if (!unit_wg(k >> 1, o)) { const int n = frag_index(k, o) - first; if (n >= 0 && n < 8) t |= (uint64_t)(k << 4 | o) << (8 * n); }
  return t;
}
__device__ __forceinline__ int hu_code(int hu) {
  constexpr uint64_t T0 = frag_tab(0), T1 = frag_tab(8), T2 = frag_tab(16), T3 = frag_tab(24);
  const int u = hu >> 1, f = hu - 2 * G_U;
  if (f >= 0) return (int)((f < 8 ? T0 : f < 16 ? T1 : f < 24 ? T2 : T3) >> (8 * (f & 7))) & 255;
  const int u0 = u < G_U1 ? u : u < G_U2 ? u - G_U1 : u - G_U2;
  const int kb = u < G_U1 ? u0 / G_N0 : u < G_U2 ? u0 / G_N1 : u0 / 4, on = u < G_U1 ? G_O0 + u0 % G_N0 : u < G_U2 ? G_O1 + u0 % G_N1 : G_O2 + u0 % 4;
  return (2 * kb + (hu & 1)) << 4 | on;
}

__device__ __forceinline__ void flag_arrive(unsigned* f, int lane) {
  __threadfence(); __syncwarp();
  if (lane == 0) asm volatile("red.release.gpu.global.add.u32 [%0],1;" :: "l"(f) : "memory");
}
__device__ __forceinline__ void flag_wait(const unsigned* f, unsigned n) {
  unsigned v; int it = 0;
  asm volatile("ld.acquire.gpu.global.u32 %0,[%1];" : "=r"(v) : "l"(f) : "memory");
  if (v < n) {
    do { __nanosleep(300); asm volatile("ld.relaxed.gpu.global.u32 %0,[%1];" : "=r"(v) : "l"(f) : "memory"); } while (v < n && ++it < (1 << 20));
    asm volatile("ld.acquire.gpu.global.u32 %0,[%1];" : "=r"(v) : "l"(f) : "memory");
  }
}
__device__ __forceinline__ void mbar_arrive(uint32_t bar) { asm volatile("mbarrier.arrive.shared::cta.b64 _,[%0];" :: "r"(bar) : "memory"); }
__device__ __forceinline__ void mbar_arrive_lane0(uint32_t bar) {
  asm volatile("{.reg .pred p; elect.sync _|p,0xffffffff; @p mbarrier.arrive.shared::cta.b64 _,[%0];}" :: "r"(bar) : "memory");
}

__device__ __forceinline__ void pack_role(const int* __restrict__ idx, uint32_t sbase, int pc) {
  constexpr int CH = 3200 + 32, BUF = 32 * 3328;
  const int tid = threadIdx.x, lane = tid & 31, warp = tid >> 5;
  const uint32_t full = sbase + 2 * BUF, empty = full + 16;
  if (tid == 0) { mbar_init(full, 1); mbar_init(full + 8, 1); mbar_init(empty, 18); mbar_init(empty + 8, 18); asm volatile("fence.proxy.async.shared::cta;" ::: "memory"); }
  __syncthreads();
  auto chunk = [&](int s) { return s * 3200 + (s >> 2) * 288; };
  auto load = [&](int n) {
    const int blk = pc * 16 + n;
    if (lane == 0) mbar_expect(full + (n & 1) * 8, 32 * 3200);
    __syncwarp();
    bulk_g2s(sbase + (n & 1) * BUF + chunk(lane), idx + ((blk >> 5) * 8192 + lane * TH + (blk & 31) * 8) * F_, 3200, full + (n & 1) * 8);
  };
  if (warp == 0) { load(0); load(1); }
  const int l = lane & 7;
  uint32_t rot[8], inc[3];
#pragma unroll
  for (int jj = 0; jj < 8; jj++) rot[jj] = ((l + jj) & 7) * 4;
#pragma unroll
  for (int q = 0; q < 3; q++) inc[q] = (l + 3 * q < 8) << 12 | (l + 3 * q + 1 < 8) << 22 | (q < 2 && l + 3 * q + 2 < 8);
  int loaded = 2;
#pragma unroll 1
  for (int task = warp; task < 288; task += 16) {
    const int n = task / 18, q = (task % 18) * 4 + (lane >> 3), sq = q / 9, k = q % 9;
    if (warp == 0 && n + 1 == loaded && loaded < 16) { mbar_wait(empty + (loaded & 1) * 8, ((loaded >> 1) - 1) & 1); load(loaded); loaded++; }
    mbar_wait(full + (n & 1) * 8, (n >> 1) & 1);
    const uint32_t buf = sbase + (n & 1) * BUF + l * 400, row = buf + chunk(sq * 4);
    auto ld = [&](uint32_t ad) { uint32_t v; asm volatile("ld.shared.u32 %0,[%1];" : "=r"(v) : "r"(ad)); return v; };
    const int blk = pc * 16 + n, half = blk >> 5, col = (blk & 31) * 8 + l;
    const int ks = k == NC - 1 ? 0 : k + 1;
    uint32_t cw[4], sv[8], m[2] = {0, 0};
    { const uint32_t a0 = row + (72 + 2 * ks + (l >> 2)) * 4;
#pragma unroll
      for (int u = 0; u < 8; u++) { sv[u] = ld((a0 ^ ((u >> 2) * 4)) + (u & 3) * 3200); m[u >> 2] |= s_mask(sv[u], l & 3) << (8 * (u & 3)); } }
#pragma unroll
    for (int h = 0; h < 2; h++) { m[h] |= __shfl_xor_sync(0xffffffffu, m[h], 1); m[h] |= __shfl_xor_sync(0xffffffffu, m[h], 2); }
#pragma unroll
    for (int u = 0; u < 4; u++) cw[u] = s_cell(sv[u], l & 3, (m[0] >> (8 * u)) & 255) | s_cell(sv[4 + u], l & 3, (m[1] >> (8 * u)) & 255) << 12;
    if (k == NC - 1) {
      g_scr[I0_OFF + (half * 8 + sq) * TH + col] = make_uint4(cw[0], cw[1], cw[2], cw[3]);
      g_scr[IX_OFF + half * IXH + NC * 8192 + sq * TH + col] = make_uint4(ld(row + 396), ld(row + 3596), ld(row + 6796), ld(row + 9996));
      cw[0] = cw[1] = cw[2] = cw[3] = 0;
    }
    const uint32_t ax = buf + chunk(min(sq + 1, 7) * 4) + (90 + k) * 4;
    const uint32_t yev = ld(buf + ((0x3210 >> (sq * 2 + (sq == 5) * 2)) & 3) * 3200 + (90 + k) * 4);
    uint4* dst = g_scr + IX_OFF + half * IXH + (k * NS + sq * 4) * TH + col;
#pragma unroll
    for (int u = 0; u < 4; u++) {
      uint32_t e[8];
#pragma unroll
      for (int jj = 0; jj < 8; jj++) e[jj] = ld(row + k * 32 + rot[jj] + u * 3200);
      dst[u * TH] = make_uint4(pk3(e[0], e[1], e[2] + inc[0]), pk3(e[3], e[4], e[5] + inc[1]), pk3(e[6], e[7], ld(ax + u * 3200) + inc[2]),
                               u < 3 ? __byte_perm(cw[u], cw[3], 0x4210 + (u << 12)) : yev);
    }
    mbar_arrive_lane0(empty + (n & 1) * 8);
  }
  (void)CH;
}

__global__ void __cluster_dims__(2, 1, 1) __launch_bounds__(512, 1)
k_tens(const __grid_constant__ CUtensorMap mapW, const __grid_constant__ CUtensorMap mapL, const __grid_constant__ CUtensorMap mapS,
       const __grid_constant__ CUtensorMap mapT, const __grid_constant__ CUtensorMap mapE, const __grid_constant__ CUtensorMap mapC, cudaTextureObject_t tex, cudaTextureObject_t texX,
       const int* __restrict__ idx, const __nv_bfloat16* __restrict__ table, const __nv_bfloat16* __restrict__ wp, const __nv_bfloat16* __restrict__ w1,
       const __nv_bfloat16* __restrict__ b1, int never) {
  extern __shared__ __align__(1024) uint4 sm[];
  const int tid = threadIdx.x, lane = tid & 31, cta = blockIdx.x;
  const uint32_t sbase = (uint32_t)__cvta_generic_to_shared(sm);
  const int g = lane >> 2, r = lane & 3;
  TS(0, 0);
  if (cta >= 128) {
    pack_role(idx, sbase, cta - 128);
    __syncthreads();
    if (tid < 32) flag_arrive(&g_flag[8 * 32], lane);
    TS(2, 1);
    asm volatile("barrier.cluster.arrive.relaxed.aligned; barrier.cluster.wait.aligned;" ::: "memory");
    return;
  }
  const uint32_t fullB = sbase + K1_BAR, emptyB = fullB + 24, fullS = fullB + 48, emptyS = fullB + 64, fullE = fullB + 80, fullC = fullB + 88, fullI = fullB + 96, fullX = fullB + 104, progG = fullB + 112;
  const int rb = cta & 7, hc = cta >> 3;
  if (tid >= 384) {
    asm volatile("setmaxnreg.dec.sync.aligned.u32 " RAUX ";");
    if (tid < 416) {
      auto load_pair = [&](int p, int st) {
        mbar_expect(fullB + st * 8, 16384);
        asm volatile("cp.async.bulk.tensor.2d.shared::cluster.global.mbarrier::complete_tx::bytes [%0],[%1,{%2,%3}],[%4];"
                     :: "r"(sbase + K1_B + st * 16384), "l"(&mapW), "r"(hc * 32), "r"(X_SAMEW ? 0 : QORD(p >> 1) * 512 + (p & 1) * 256), "r"(fullB + st * 8) : "memory");
        p += WPF;
        if (p < 50) bulk_pf(w1 + QORD(p >> 1) * 262144 + (p & 1) * 131072 + cta * 1024, 2048);
      };
      if (tid == 384) {
        for (int q = 0; q < 3; q++) { mbar_init(fullB + q * 8, 1); mbar_init(emptyB + q * 8, 4); }
        for (int q = 0; q < 2; q++) { mbar_init(fullS + q * 8, 4); mbar_init(emptyS + q * 8, 1); }
        mbar_init(fullE, 1); mbar_init(fullC, 1); mbar_init(fullI, 1); mbar_init(fullX, 1); mbar_init(progG, 1);
        asm volatile("fence.proxy.async.shared::cta;" ::: "memory");
        mbar_expect(fullC, 16384);
        for (int q = 0; q < 4; q++)
          asm volatile("cp.async.bulk.tensor.2d.shared::cluster.global.mbarrier::complete_tx::bytes [%0],[%1,{%2,%3}],[%4];"
                       :: "r"(sbase + 32768 + q * 4096), "l"(&mapC), "r"((cta & 15) * 8), "r"(q * 256), "r"(fullC) : "memory");
        mbar_expect(fullE, 32768);
        for (int q = 0; q < 2; q++)
          asm volatile("cp.async.bulk.tensor.2d.shared::cluster.global.mbarrier::complete_tx::bytes [%0],[%1,{%2,%3}],[%4];"
                       :: "r"(sbase + K1_STG + q * 16384), "l"(&mapE), "r"(q * 64), "r"(rb * 128), "r"(fullE) : "memory");
      }
      __syncwarp();
      asm volatile("bar.arrive 2,448;" ::: "memory");
      if (tid == 384) {
        int st = 0, ph = 1;
        const uint32_t tl0 = clock();
#pragma unroll 1
        for (int p = 0; p < 50; p++) {
          if (p == IORD) {
            mbar_expect(fullI, 51200);
#pragma unroll 1
            for (int q = 0; q < 8; q++) bulk_g2s(sbase + 76800 + q * 6400, idx + (((cta >> 4) * 8 + q) * 256 + (cta & 15) * 16) * F_, 6400, fullI);
          }
          if (PDT && p > PP0) sleep_until(tl0, PT0 + (p - PP0) * PDT);
          mbar_wait(emptyB + st * 8, ph);
          load_pair(p, st);
          if (++st == 3) { st = 0; ph ^= 1; }
        }
      }
    } else if (tid < 448) {
      ((float4*)g_acc)[cta * 32 + lane] = make_float4(0.f, 0.f, 0.f, 0.f);
      asm volatile("bar.sync 2,448;" ::: "memory");
      asm volatile("bar.sync 4,288;" ::: "memory");
      flag_arrive(&g_flag[(cta >> 4) * 32], lane);
      if (tid == 416) {
#pragma unroll 1
        for (int n = 0; n < 50; n++) {
          const int quad = QORD(n >> 1), mt = n & 1, v0 = rb * 128 + mt * 64;
          const uint32_t stg = sbase + K1_STG + mt * 16384;
          const uint64_t pol = n < 2 * NEF ? POL_EF : POL_N;
          mbar_wait(fullS + mt * 8, (n >> 1) & 1);
          asm volatile("fence.proxy.async.shared::cta;" ::: "memory");
          if (quad < 18) {
            asm volatile("cp.async.bulk.tensor.4d.global.shared::cta.bulk_group.L2::cache_hint [%0,{%1,%2,%3,%4}],[%5],%6;"
                         :: "l"(&mapL), "r"((quad & 1) * 32), "r"(v0), "r"(X_SAMEK ? 0 : quad >> 1), "r"(hc * 4), "r"(stg), "l"(pol) : "memory");
          } else {
#pragma unroll 1
            for (int hh = 0; hh < 2; hh++) {
              const int pq = quad * 2 + hh;
              if (pq < 45) asm volatile("cp.async.bulk.tensor.4d.global.shared::cta.bulk_group.L2::cache_hint [%0,{%1,%2,%3,%4}],[%5],%6;"
                         :: "l"(&mapS), "r"(0), "r"(v0), "r"(pq - 36), "r"(hc * 4), "r"(stg + hh * 8192), "l"(pol) : "memory");
              else asm volatile("cp.async.bulk.tensor.3d.global.shared::cta.bulk_group.L2::cache_hint [%0,{%1,%2,%3}],[%4],%5;"
                         :: "l"(&mapT), "r"(v0 * 2), "r"((pq - 45) * 2), "r"(hc * 4), "r"(stg + hh * 8192), "l"(pol) : "memory");
            }
          }
          asm volatile("cp.async.bulk.commit_group;" ::: "memory");
          asm volatile("cp.async.bulk.wait_group.read 0;" ::: "memory");
          mbar_arrive(emptyS + mt * 8);
        }
        asm volatile("cp.async.bulk.wait_group 0;" ::: "memory");
        asm volatile("fence.proxy.async.global;" ::: "memory");
        __threadfence();
        asm volatile("red.release.gpu.global.add.u32 [%0],1;" :: "l"(&g_flag[8 * 32]) : "memory");
        flag_wait(&g_flag[8 * 32], 132);
        asm volatile("fence.proxy.async.global;" ::: "memory");
        const char* base = (const char*)g_scr;
        const int c = cta >> 1, half = cta & 1, ch = (c + (c >> 4) * 5) & 15;
        bulk_pf(base + (PS_OFF + c * NC * 2000) * 16u + half * 16000, 16000);
        if (PREW & 2) bulk_pf(base + (PL_OFF + c * NC * 8000) * 16u + half * 64000, 64000);
        bulk_pf(base + (PT_OFF + c * 10 * 1024) * 16u + half * 8192, 8192);
        mbar_expect(fullE, 18432);
        bulk_g2s(sbase + K1_STG, base + (I0_OFF + half * 2048 + ch * 128) * 16u, 2048, fullE);
        bulk_g2s(sbase + K1_STG + 2048, base + (IX_OFF + half * IXH + ch * 512) * 16u, 8192, fullE);
        bulk_g2s(sbase + K1_STG + 10240, base + (IX_OFF + half * IXH + 8192 + ch * 512) * 16u, 8192, fullE);
        mbar_wait(fullE, 1);
      }
    } else if (tid == 448 && PXW) {
      flag_wait(&g_flag[(cta >> 4) * 32], 16);
      asm volatile("fence.proxy.async.global;" ::: "memory");
      const char* src = (const char*)(g_scr + PX_OFF + ((cta >> 4) * 8 + ((cta >> 1) & 3) * 2) * 16 * 136);
#pragma unroll 1
      for (int n = 1; n < 16; n++) {
        if (n >= PXW) mbar_wait(progG, (n - PXW) & 1);
        mbar_expect(fullX, 4352);
        bulk_g2s(sbase + K1_BAR + 128, src + n * 2176, 2176, fullX);
        bulk_g2s(sbase + K1_BAR + 128 + 2176, src + (16 + n) * 2176, 2176, fullX);
        mbar_wait(fullX, (n - 1) & 1);
      }
    }
    return;
  }
  if (tid >= 256) {
    asm volatile("setmaxnreg.inc.sync.aligned.u32 " RPRO ";");
    const int w = (tid >> 5) & 3;
    const int srow = w * 16 + (lane & 7) + ((lane >> 3) & 1) * 8, sc = lane >> 4;
    uint32_t a[2][8][4];
    asm volatile("bar.sync 2,448;" ::: "memory");
    mbar_wait_fast(fullE, 0);
#pragma unroll
    for (int mt = 0; mt < 2; mt++)
#pragma unroll
      for (int ks = 0; ks < 8; ks++)
        asm volatile("ldmatrix.sync.aligned.m8n8.x4.shared.b16 {%0,%1,%2,%3},[%4];"
                     : "=r"(a[mt][ks][0]), "=r"(a[mt][ks][1]), "=r"(a[mt][ks][2]), "=r"(a[mt][ks][3])
                     : "r"(sbase + K1_STG + (ks >> 2) * 16384 + (mt * 64 + srow) * 128 + ((((ks & 3) * 2 + sc) ^ (lane & 7)) * 16)) : "memory");
    asm volatile("bar.sync 5,128;" ::: "memory");
    const uint32_t baseL = sc * 4096 + srow * 64 + ((srow >> 1) & 3) * 16, baseS = sc * 2048 + srow * 32 + ((srow >> 2) & 1) * 16, baseT = sc * 2048 + srow * 16;
    const uint64_t desc0 = (uint64_t)(((sbase + K1_B) & 0x3FFFF) >> 4) | ((uint64_t)(8192 >> 4) << 16) | ((uint64_t)(512 >> 4) << 32) | (2ull << 62);
    float d[2][32];
    auto issue = [&](int x, int mt, int st) {
      uint32_t a7[4];
#pragma unroll
      for (int e = 0; e < 4; e++) { if (PARK) asm volatile("add.u32 %0,%1,%2;" : "=r"(a7[e]) : "r"(a[mt][7][e]), "r"(never)); else a7[e] = a[mt][7][e]; }
      asm volatile("wgmma.fence.sync.aligned;" ::: "memory");
#pragma unroll
      for (int ks = 0; ks < 8; ks++) wgmma_p(d[x], ks < 7 ? a[mt][ks] : a7, desc0 + st * 1024 + ks * 64, ks);
      asm volatile("wgmma.commit_group.sync.aligned;" ::: "memory");
    };
    auto wait_acc = [&](int x) {
      asm volatile("wgmma.wait_group.sync.aligned 0;" ::: "memory");
#pragma unroll
      for (int q = 0; q < 8; q++) asm volatile("" : "+f"(d[x][q * 4]), "+f"(d[x][q * 4 + 1]), "+f"(d[x][q * 4 + 2]), "+f"(d[x][q * 4 + 3]) :: "memory");
    };
    mbar_wait_fast(fullB, 0);
    issue(0, 0, 0);
    int s0 = 0, ph = 0;
#pragma unroll 1
    for (int qn = 0; qn < 25; qn++) {
      const int quad = QORD(qn);
      const int s1 = s0 == 2 ? 0 : s0 + 1, s2 = s1 == 2 ? 0 : s1 + 1, ph1 = ph ^ (s1 == 0), ph2 = ph1 ^ (s2 == 0);
#pragma unroll
      for (int step = 0; step < 4; step++) {
        const int mt = ORD ? step & 1 : step >> 1, h = ORD ? step >> 1 : step & 1, x = step & 1, nx = (step + 1) & 3;
        const bool isL = quad < 18, isS = quad * 2 + h < 45;
        const uint32_t base = (isL ? baseL ^ (h * 32) : (isS ? baseS : baseT) ^ (h * 8192)), xj = (isL || isS) ? 16 : 1024, xc = isL ? 8192 : 4096;
        PT(qn * 16 + step * 4);
        if (h == 0) mbar_wait_fast(emptyS + mt * 8, (qn & 1) ^ 1);
        if (step == (ORD ? 1 : 0)) mbar_wait_fast(fullB + s1 * 8, ph1);
        if (step == 3) mbar_wait_fast(fullB + s2 * 8, qn == 24 ? ph2 ^ 1 : ph2);
        PT(qn * 16 + step * 4 + 1);
        wait_acc(x);
        PT(qn * 16 + step * 4 + 2);
        if (mt) mbar_arrive_lane0(emptyB + (h ? s1 : s0) * 8);
        issue(x ^ 1, ORD ? nx & 1 : nx >> 1, step == 3 ? s2 : (ORD ? nx >> 1 : nx & 1) ? s1 : s0);
        PT(qn * 16 + step * 4 + 3);
        if (h && quad == 24) {
#pragma unroll
          for (int cq = 0; cq < 4; cq++) {
            const uint32_t bw = __ldg((const uint32_t*)(b1 + hc * 32 + cq * 8) + r);
#pragma unroll
            for (int e = 0; e < 4; e++) d[x][16 + cq * 4 + e] += (e & 1) ? bf_hi(bw) : bf_lo(bw);
          }
        }
#pragma unroll
        for (int e4 = 0; e4 < 4; e4++) {
          const float* e = d[x] + e4 * 8;
          asm volatile("stmatrix.sync.aligned.m8n8.x4.shared.b16 [%0],{%1,%2,%3,%4};"
                       :: "r"(sbase + K1_STG + mt * 16384 + (base ^ ((e4 >> 1) * xj) ^ ((e4 & 1) * xc))),
                          "r"(pack_bf2(e[0], e[1])), "r"(pack_bf2(e[2], e[3])), "r"(pack_bf2(e[4], e[5])), "r"(pack_bf2(e[6], e[7])) : "memory");
        }
        if (h) { __syncwarp(); mbar_arrive_lane0(fullS + mt * 8); }
      }
      s0 = s2; ph = ph2;
    }
    asm volatile("wgmma.wait_group.sync.aligned 0;" ::: "memory");
    return;
  }
  asm volatile("setmaxnreg.inc.sync.aligned.u32 " RPNN ";");
  const int slice = cta & 15;
  const int range = (cta >> 4) * 8 + __shfl_sync(0xffffffffu, tid >> 5, 0);
  uint4 iv[4], trow[4]; uint32_t ix;
  uint2 wrow[10];
#pragma unroll
  for (int q = 0; q < 10; q++) asm volatile("ld.global.nc.v2.u32 {%0,%1},[%2];" : "=r"(wrow[q].x), "=r"(wrow[q].y) : "l"((const uint2*)wp + min(tid + q * 256, 2499)));
  asm volatile("bar.sync 2,448;" ::: "memory");
  uint32_t me = 0, mw = 0;
#pragma unroll
  for (int q = 0; q < 10; q++) {
    mw = __vmaxu2(__vmaxu2(wrow[q].x & 0x7fff7fffu, wrow[q].y & 0x7fff7fffu), mw);
    const int e = min(tid + q * 256, 2499), row = e / 25;
    asm volatile("st.shared.v2.u32 [%0],{%1,%2};" :: "r"(sbase + (e + row) * 8), "r"(wrow[q].x), "r"(wrow[q].y) : "memory");
    if (e - row * 25 == 24) asm volatile("st.shared.v2.u32 [%0],{%1,%2};" :: "r"(sbase + (e + row) * 8 + 8), "r"(wrow[q].x), "r"(wrow[q].y) : "memory");
  }
  mbar_wait_fast(fullC, 0);
#pragma unroll
  for (int q = 0; q < 4; q++) { trow[q] = lds128(sbase + 32768 + (tid + q * 256) * 16); me = absmax4(trow[q], me); }
  me = __reduce_max_sync(0xffffffffu, max(me & 0xffff, me >> 16));
  mw = __reduce_max_sync(0xffffffffu, max(mw & 0xffff, mw >> 16));
  uint32_t* sred = (uint32_t*)((char*)sm + 128000);
  if (lane == 0) sred[tid >> 5] = me | mw << 16;
  TS(3, 0);
  asm volatile("bar.sync 1,256;" ::: "memory");
  { uint32_t m = 0;
#pragma unroll
    for (int q = 0; q < 8; q++) m = __vmaxu2(m, sred[q]);
    m = __shfl_sync(0xffffffffu, m, 0);
    me = m & 0xffff; mw = m >> 16; }
  const float se = pow2_scale(me, 3), sW = pow2_scale(mw, -2);
  TS(3, 1);
  auto put_rows = [&](int q, bool on) {
    const uint4 t = trow[q];
    const uint4 hv = make_uint4(pack_h2(bf_lo(t.x) * se, bf_hi(t.x) * se), pack_h2(bf_lo(t.y) * se, bf_hi(t.y) * se),
                                pack_h2(bf_lo(t.z) * se, bf_hi(t.z) * se), pack_h2(bf_lo(t.w) * se, bf_hi(t.w) * se));
    if (on)
#pragma unroll
      for (int s = 0; s < 8; s++) sts128(sbase + (tid + q * 256) * 128 + ((s + lane) & 7) * 16, hv);
  };
#pragma unroll 1
  for (int it = 0; it < 3; it++) {
    const int hu = ((tid >> 5) * 3 + it) * 4, code = hu_code(min(hu + (lane >> 3), HU_N - 1)), ok = code >> 4, on = code & 15;
    uint32_t x[4], y[4];
    asm volatile("ldmatrix.sync.aligned.m8n8.x4.shared.b16 {%0,%1,%2,%3},[%4];" : "=r"(x[0]), "=r"(x[1]), "=r"(x[2]), "=r"(x[3])
                 : "r"(sbase + (on * 8 + (lane & (on == 12 ? 3 : 7))) * 208 + ok * 16) : "memory");
    asm volatile("ldmatrix.sync.aligned.m8n8.x4.trans.shared.b16 {%0,%1,%2,%3},[%4];" : "=r"(y[0]), "=r"(y[1]), "=r"(y[2]), "=r"(y[3])
                 : "r"(sbase + (ok * 8 + (lane & (ok == 12 ? 3 : 7))) * 208 + on * 16) : "memory");
    const uint32_t lo = __ballot_sync(0xffffffffu, ok > on), dg = __ballot_sync(0xffffffffu, ok >= on);
#pragma unroll
    for (int q = 0; q < 4; q++) {
      const float m0 = (lo >> (8 * q)) & 1 ? 0.f : sW, m1 = (dg >> (8 * q)) & 1 ? 0.f : sW;
      asm volatile("st.shared.u32 [%0],%1;" :: "r"(sbase + K1_W + (hu + q) * 128 + lane * 4),
                   "r"(pack_h2(fmaf(bf_lo(x[q]), m0, bf_lo(y[q]) * m1), fmaf(bf_hi(x[q]), m0, bf_hi(y[q]) * m1))) : "memory");
    }
  }
  put_rows(1, true); put_rows(2, tid < 88);
  TS(3, 2);
  asm volatile("fence.proxy.async.shared::cta;" ::: "memory");
  asm volatile("bar.sync 1,256;" ::: "memory");
  put_rows(0, true);
  uint32_t bf[HU_N - 2 * G_U];
#pragma unroll
  for (int q = 0; q < HU_N - 2 * G_U; q++) asm volatile("ld.shared.u32 %0,[%1];" : "=r"(bf[q]) : "r"(sbase + K1_W + (2 * G_U + q) * 128 + lane * 4));
  const float unscale = __uint_as_float(0x7f000000u - __float_as_uint(se)), unscale2 = __uint_as_float(0x7f000000u - __float_as_uint(sW));
  TS(3, 3);
  const int px = range * 16 * 136;
  mbar_wait_fast(fullI, 0);
  {
    const uint32_t ib = sbase + 76800 + (tid >> 5) * 6400, p0 = ib + ((lane >> 3) & 1) * 400 + ((lane >> 4) * 8 + (lane & 7)) * 4;
    auto ld = [&](uint32_t ad) { uint32_t v; asm volatile("ld.shared.u32 %0,[%1];" : "=r"(v) : "r"(ad)); return v; };
    auto wd = [&](int t, int h) { return pk3(ld(p0 + t * 800 + h * 192), ld(p0 + t * 800 + h * 192 + 64), ld(p0 + t * 800 + h * 192 + 128)); };
#pragma unroll
    for (int q = 0; q < 4; q++) {
      iv[q] = make_uint4(wd(2 * q, 0), wd(2 * q, 1), wd(2 * q + 1, 0), wd(2 * q + 1, 1));
      g_scr[PX_OFF + px + slice * 136 + q * 32 + lane] = iv[q];
    }
    ix = pk3(ld(ib + g * 400 + 384 + r * 4), ld(ib + (8 + g) * 400 + 384 + r * 4), 0);
    ((uint32_t*)(g_scr + PX_OFF + px + slice * 136 + 128))[lane] = ix;
  }
  asm volatile("bar.arrive 4,288;" ::: "memory");
  asm volatile("bar.sync 1,256;" ::: "memory");
  put_rows(2, tid >= 88); put_rows(3, tid + 768 < V_);
  asm volatile("bar.sync 1,256;" ::: "memory");
  TS(0, 1);
  uint32_t lc; asm volatile("add.u32 %0,%1,%2;" : "=r"(lc) : "r"((lane & 7) * 16), "r"(never));
  const uint64_t wdesc = (uint64_t)(((sbase + K1_W) & 0x3FFFF) >> 4) | ((uint64_t)(128 >> 4) << 16) | ((uint64_t)(256 >> 4) << 32);
  uint32_t a[2][6][4], d[2][26], ex[4] = {}, s[4] = {};
  float red[4] = {0.f, 0.f, 0.f, 0.f};
  auto ldsm = [&](uint32_t* o, uint32_t sh, uint32_t dep = 0) {
    asm volatile("ldmatrix.sync.aligned.m8n8.x4.trans.shared.b16 {%0,%1,%2,%3},[%4];"
                 : "=r"(o[0]), "=r"(o[1]), "=r"(o[2]), "=r"(o[3]) : "r"(sbase + ((sh & 0x1ff80) | (lc | (dep & never)))));
  };
  auto gather = [&](int t, int hf) {
    const int x = t & 1;
    const uint4 v = iv[(t >> 1) & 3];
#pragma unroll
    for (int kb = 3 * hf; kb < 3 * hf + 3; kb++) {
      const uint32_t ww = x ? (kb < 3 ? v.z : v.w) : (kb < 3 ? v.x : v.y);
      ldsm(a[x][kb], kb % 3 == 0 ? ww : kb % 3 == 1 ? ww >> 10 : __funnelshift_l(ww, ww, 12));
    }
  };
  auto issue = [&](int x) {
    asm volatile("wgmma.fence.sync.aligned;" ::: "memory");
#pragma unroll
    for (int kb = 0; kb < 6; kb++) {
      if (kb < G_K0) wgmma_h<G_N0 * 8>(d[x] + G_O0 * 2, a[x][kb], wdesc + kb * G_N0 * 16, kb);
      if (kb < G_K1) wgmma_h<G_N1 * 8>(d[x] + G_O1 * 2, a[x][kb], wdesc + (G_U1 + kb * G_N1) * 16, kb);
      if (kb < G_K2) wgmma_h<32>(d[x] + G_O2 * 2, a[x][kb], wdesc + (G_U2 + kb * G_N2) * 16, kb);
    }
    asm volatile("wgmma.commit_group.sync.aligned;" ::: "memory");
  };
  auto hmma_part = [&](int t) {
    constexpr FragIdx FI = make_fi();
    const int x = t & 1;
#pragma unroll
    for (int o = 0; o < 13; o++) {
      if (oct_wg(o)) asm volatile("" : "+r"(d[x][o * 2]), "+r"(d[x][o * 2 + 1]) :: "memory"); else d[x][o * 2] = d[x][o * 2 + 1] = 0;
    }
#pragma unroll
    for (int kb = 0; kb < 6; kb++)
#pragma unroll
      for (int o = 2 * kb + 1; o < 13; o++)
        if (!unit_wg(kb, o)) mma16816h(d[x] + o * 2, a[x][kb], bf[FI.v[2 * kb][o]], bf[FI.v[2 * kb + 1][o]]);
#pragma unroll
    for (int q = 0; q < 6; q++) if (!unit_wg(q, 2 * q)) mma1688h(d[x] + q * 4, a[x][q][0], a[x][q][1], bf[FI.v[2 * q][2 * q]]);
    mma1688h(d[x] + 24, r < 2 ? ex[t & 3] : 0u, r < 2 ? 0u : ex[t & 3], bf[FI.v[12][12]]);
  };
  auto dot_part = [&](int t, int hf) {
    const int x = t & 1;
    if (hf == 0) {
      const uint32_t pe = hfma2(r < 2 ? d[x][24] : d[x][25], ex[t & 3], 0u);
      s[0] = r < 2 ? pe : 0u; s[1] = r < 2 ? 0u : pe; s[2] = s[3] = 0;
    }
#pragma unroll
    for (int q = 3 * hf; q < 3 * hf + 3; q++)
#pragma unroll
      for (int e = 0; e < 4; e++) s[e] = hfma2(d[x][q * 4 + e], a[x][q][e], s[e]);
  };
  float* outp = g_partP + slice * B_ + range * 256;
  float k0 = 0.f, k1 = 0.f, x0 = 0.f, x1 = 0.f;
  auto red_stage = [&](int st, int grp) {
    const bool u16 = lane & 16, u8 = lane & 8;
    if (st == 0) {
      k0 = u16 ? red[2] : red[0]; x0 = __shfl_xor_sync(0xffffffffu, u16 ? red[0] : red[2], 16);
      k1 = u16 ? red[3] : red[1]; x1 = __shfl_xor_sync(0xffffffffu, u16 ? red[1] : red[3], 16);
      red[0] = red[1] = red[2] = red[3] = 0.f;
    }
    if (st == 1) { const float p0 = k0 + x0, p1 = k1 + x1; k0 = u8 ? p1 : p0; x0 = __shfl_xor_sync(0xffffffffu, u8 ? p0 : p1, 8); }
    if (st == 2) { k0 += x0; x0 = __shfl_xor_sync(0xffffffffu, k0, 4); }
    if (st == 3 && !(lane & 4)) outp[grp * 16 + r * 4 + ((lane >> 3) & 1) * 2 + (lane >> 4)] = (k0 + x0) * unscale * unscale * unscale2;
  };
  auto group = [&](bool first, int prv, int cur, int nxt) {
    const int pn = PX_OFF + px + nxt * 136 + lane;
#pragma unroll
    for (int t = 0; t < 8; t++) {
      issue((t & 1) ^ 1);
      SCHED_FENCE(never, t * 8);
      if (!first) {
        if (t == 0) { iv[3] = ldtex(tex, PX_OFF + px + cur * 136 + lane + 96); iv[0] = ldtex(tex, pn); }
        if (t == 2) iv[1] = ldtex(tex, pn + 32);
        if (t < 4) red_stage(t, prv);
      } else if (t == 4) {
        TS(4, 2);
        flag_wait(&g_flag[(cta >> 4) * 32], 16);
        TS(4, 3);
        iv[0] = ldtex(tex, pn); iv[1] = ldtex(tex, pn + 32);
      }
      if (t == 4) { ix = ldtex(texX, (px + nxt * 136 + 128) * 4 + lane).x; iv[2] = ldtex(tex, pn + 64); }
      dot_part(t, 0);
      SCHED_FENCE(never, t * 8 + 1);
      if (t == 3) ldsm(ex, ix >> 10);
      if (t == 7) ldsm(ex, ix);
      gather(t + 2, 0);
      dot_part(t, 1);
      SCHED_FENCE(never, t * 8 + 4);
      gather(t + 2, 1);
      asm volatile("wgmma.wait_group.sync.aligned 0;" ::: "memory");
      if (FM & 1) SCHED_FENCE(never, t * 8 + 2);
      asm volatile("" : "+r"(d[(t & 1) ^ 1][0]) :: "memory");
      mma1688f(red, hadd2(s[0], s[2]), hadd2(s[1], s[3]), (g | (d[(t & 1) ^ 1][0] & never)) == t ? 0x3c003c00u : 0u);
      hmma_part(t + 1);
      if (FM & 2) SCHED_FENCE(never, t * 8 + 3);
    }
  };
  gather(0, 0); gather(0, 1); issue(0); ldsm(ex, ix); gather(1, 0); gather(1, 1);
  asm volatile("wgmma.wait_group.sync.aligned 0;" ::: "memory");
  hmma_part(0);
  int prv = slice, cur = slice == 0;
  group(true, 0, prv, cur);
  TS(4, 1);
#pragma unroll 1
  for (int n = 1; n < NGRP; n++) {
    const int nxt = (n + (n >= slice)) & 15;
    if (n == TRIG) asm volatile("griddepcontrol.launch_dependents;");
    if (PXW && tid == 0) mbar_arrive(progG);
    group(false, prv, cur, nxt);
    prv = cur; cur = nxt;
  }
#pragma unroll
  for (int st = 0; st < 4; st++) red_stage(st, prv);
  TS(0, 2);
  asm volatile("barrier.cluster.arrive.relaxed.aligned; barrier.cluster.wait.aligned;" ::: "memory");
}

constexpr int SM_U = 130048, SM_BAR = 128000, SM_J = SM_U + 98304, DEEP_SMEM = SM_J + 4096;

__device__ __forceinline__ void arrive_both(uint32_t bar, int lane) {
  asm volatile("{.reg .pred p; .reg .u32 a; setp.lt.u32 p,%1,2; mapa.shared::cluster.u32 a,%0,%1;\n"
               "@p mbarrier.arrive.shared::cluster.b64 _,[a];}" :: "r"(bar), "r"(lane) : "memory");
}
#define ELECT "{.reg .pred p; elect.sync _|p,0xffffffff; @p "
__device__ __forceinline__ void e_mc(uint32_t dst, const void* src, uint32_t bytes, uint32_t bar, uint64_t pol) {
  asm volatile(ELECT "cp.async.bulk.shared::cluster.global.mbarrier::complete_tx::bytes.multicast::cluster.L2::cache_hint [%0],[%1],%2,[%3],%4,%5;}"
               :: "r"(dst), "l"(src), "r"(bytes), "r"(bar), "h"((unsigned short)3), "l"(pol) : "memory");
}
__device__ __forceinline__ void e_g2s(uint32_t dst, const void* src, uint32_t bytes, uint32_t bar) {
  asm volatile(ELECT "cp.async.bulk.shared::cluster.global.mbarrier::complete_tx::bytes [%0],[%1],%2,[%3];}" :: "r"(dst), "l"(src), "r"(bytes), "r"(bar) : "memory");
}
__device__ __forceinline__ void e_pf(const void* src, uint32_t bytes) { asm volatile(ELECT "cp.async.bulk.prefetch.L2.global [%0],%1;}" :: "l"(src), "r"(bytes) : "memory"); }
__device__ __forceinline__ void e_expect(uint32_t bar, uint32_t bytes) { asm volatile(ELECT "mbarrier.arrive.expect_tx.shared::cta.b64 _,[%0],%1;}" :: "r"(bar), "r"(bytes) : "memory"); }

__global__ void __cluster_dims__(2, 1, 1) __launch_bounds__(TH + 128, 1)
k_deep(cudaTextureObject_t tex, const __nv_bfloat16* __restrict__ w2, const __nv_bfloat16* __restrict__ b2,
       __nv_bfloat16* __restrict__ out, int never) {
  extern __shared__ __align__(1024) uint4 sm[];
  constexpr int PF = DPF, DEPTH = DDEPTH, NW = TH / 32;
  static_assert(YD == 4 && PF == 4, "");
  const int tid = threadIdx.x;
  const int c = blockIdx.x >> 1, half = blockIdx.x & 1;
  const uint32_t sbase = (uint32_t)__cvta_generic_to_shared(sm);
  const uint32_t fullL = sbase + SM_BAR, fullU = fullL + 8, emptyL = fullL + 16, emptyU = fullL + 24, barJ = fullL + 32;
  TS(1, 0);
  if (tid == 0) {
    mbar_init(fullL, 1); mbar_init(fullU, 1); mbar_init(emptyL, 2 * NW); mbar_init(emptyU, 2 * NW); mbar_init(barJ, 1);
    asm volatile("fence.mbarrier_init.release.cluster;" ::: "memory");
  }
  __syncwarp();
  const int wrp = __shfl_sync(0xffffffffu, tid >> 5, 0);
  const char* base = (const char*)g_scr;
  uint32_t oL = (PL_OFF + c * NC * 8000) * 16u + half * 64000, oS = (PS_OFF + c * NC * 2000) * 16u + half * 16000;
  asm volatile("barrier.cluster.arrive.relaxed.aligned;" ::: "memory");
  flag_wait(&g_flag[8 * 32], 132);
  asm volatile("barrier.cluster.wait.aligned;" ::: "memory");
  if (wrp == NW) {
    asm volatile("fence.proxy.async.global;" ::: "memory");
    e_expect(fullU, 96000);
#pragma unroll
    for (int m = 0; m < 3; m++) e_mc(sbase + SM_U + m * 32032 + half * 16000, base + oS, 16000, fullU, m == 2 ? POL_EF : POL_N);
    e_expect(fullL, 128000);
    if (!STAG) e_mc(sbase + half * 64000, base + oL, 64000, fullL, POL_EF);
  }
  TS(5, 1);
  if (wrp >= NW) {
    asm volatile("setmaxnreg.dec.sync.aligned.u32 24;");
    if (wrp == NW) {
      uint32_t oT = (PT_OFF + c * 10 * 1024) * 16u + half * 8192;
      const uint32_t junk = sbase + SM_J, oW = (IX_OFF + half * IXH + ((c + (c >> 4) * 5) & 15) * 512) * 16u;
      auto warm = [&](uint32_t off) {
        asm volatile(ELECT "mbarrier.expect_tx.relaxed.cta.shared::cta.b64 [%0],%1;}" :: "r"(barJ), "r"(8192) : "memory");
        e_g2s(junk, base + off, 4096, barJ); e_g2s(junk, base + off + 4096, 4096, barJ);
      };
      uint32_t t0 = clock();
      if (!PREW) warm(oW);
      if (STAG) { if (STAG == 1) mbar_wait_fast(fullU, 0); else sleep_until(t0, STAG); e_mc(sbase + half * 64000, base + oL, 64000, fullL, POL_EF); }
      warm(oT);
      if (!(PREW & 4)) warm(oW + 131072);
#pragma unroll 1
      for (int k = 0; k + 1 < NC; k++) {
        oL += 128000; oS += 32000; oT += 16384;
        mbar_wait_fast(fullL, k & 1);
        t0 = clock();
        e_pf(base + oS, 16000);
        warm(k + 2 < NC ? oW + (k + 2) * 131072 : (IX_OFF + half * IXH + NC * 8192 + (c & 3) * 512) * 16u);
        mbar_wait_fast(emptyU, k & 1);
        e_expect(fullU, 96000);
#pragma unroll 1
        for (int q = 0; q < 8; q++) {
          sleep_until(t0, q * PACE);
          e_pf(base + oL + q * 8000, 8000);
          if (q >= 2) e_mc(sbase + SM_U + ((q - 2) >> 1) * 32032 + half * 16000 + (q & 1) * 8000, base + oS + (q & 1) * 8000, 8000, fullU, q >= 6 ? POL_EF : POL_N);
        }
        warm(oT);
        e_expect(fullL, 128000);
        mbar_wait_fast(emptyL, k & 1);
        e_mc(sbase + half * 64000, base + oL, 64000, fullL, POL_EF);
      }
      mbar_wait_fast(fullL, (NC - 1) & 1);
      mbar_wait_fast(emptyU, (NC - 1) & 1);
      mbar_arrive_lane0(fullU);
      warm(oT + 16384);
      mbar_arrive_lane0(barJ); mbar_wait_fast(barJ, 0);
    } else if (tid >= TH + 96) {
      if (tid == TH + 96) sts128(barJ + 32, *(const uint4*)(w2 + c * 8));
      asm volatile("bar.arrive 3,%0;" :: "n"(TH + 32) : "memory");
      asm volatile("griddepcontrol.wait;" ::: "memory");
      const int b = half * 8192 + c * 128 + (tid & 31) * 4;
      const float bias = __bfloat162float(b2[0]);
      float4 s = make_float4(bias, bias, bias, bias);
#pragma unroll 2
      for (int k = 0; k < 16; k++) { const float4 v = __ldcg((const float4*)(g_partP + k * B_ + b)); s.x += v.x; s.y += v.y; s.z += v.z; s.w += v.w; }
      asm volatile("red.global.add.v4.f32 [%0],{%1,%2,%3,%4};" :: "l"(g_acc + b), "f"(s.x), "f"(s.y), "f"(s.z), "f"(s.w) : "memory");
      asm volatile("bar.arrive 1,%0;" :: "n"(TH + 32) : "memory");
    }
    return;
  }
  asm volatile("setmaxnreg.inc.sync.aligned.u32 240;");
  const int lane = tid & 31;
  const int tbase = PT_OFF + c * 10 * 1024;
  const int ibase = IX_OFF + half * IXH + tid;
  const uint32_t lc = (tid & 7) << 4;
  uint4 acc[NS], wq[PF], x[DEPTH], y[YD], ye;
  uint32_t sw[NS] = {};
  auto sget = [&](int s) { return (s & 3) == 3 ? __byte_perm(__byte_perm(sw[s - 3], sw[s - 2], 0x0073), sw[s - 1], 0x0710) : sw[s]; };
  auto sa0 = [&](uint32_t v) { return sbase + SM_U + (((v << 5) & 0x1ffe0) | ((lc >> 2) & 16)); };
  auto sa1 = [&](uint32_t v) { return sbase + SM_U + (((v >> 7) & 0x1ffe0) | ((~lc >> 2) & 16)); };
  {
    uint4 i0[8];
#pragma unroll
    for (int q = 0; q < 8; q++) i0[q] = ldtex(tex, I0_OFF + (half * 8 + q) * TH + tid);
#pragma unroll
    for (int i = 0; i < PF; i++) if (!WQL) wq[i] = ldtex(tex, ibase + i * TH);
    auto wd = [&](int k) { return (k & 3) == 0 ? i0[k >> 2].x : (k & 3) == 1 ? i0[k >> 2].y : (k & 3) == 2 ? i0[k >> 2].z : i0[k >> 2].w; };
    TS(5, 2);
    mbar_wait_fast(fullU, 0);
#pragma unroll
    for (int i = 0; i < PF; i++) if (WQL) wq[i] = ldtex(tex, ibase + i * TH);
    TS(1, 1);
#pragma unroll
    for (int s = 0; s < NS; s++) acc[s] = add4(lds128(sa0(wd(s))), lds128(sa1(wd(s))));
    arrive_both(emptyU, lane);
    asm volatile("bar.sync 3,%0;" :: "n"(TH + 32) : "memory");
    TS(5, 3);
  }
#pragma unroll 1
  for (int k = 0; k < NC; k++) {
    const int ti = ibase + k * 8192;
    const int tb = tbase + k * 1024;
    const bool more = k + 1 < NC;
    TR(k * 4);
    if (CBAR & 1) asm volatile("bar.sync 4,%0;" :: "n"(TH) : "memory");
    mbar_wait_fast(fullL, k & 1);
    TR(k * 4 + 2);
    uint4 w, cc; uint32_t yc, yn;
    constexpr int TL = NS * 8, TT = TL + NS * 2;
#pragma unroll
    for (int t = 0; t < TT + DEPTH; t += 2) {
      if (t == TL + DEPTH && !more) break;
      if (t >= DEPTH) {
        const int u = t - DEPTH;
        uint4 p = add4(x[u % DEPTH], x[(u + 1) % DEPTH]);
        if (u < TL) {
          const int s = u >> 3, j = u & 7;
          if (j == 0) {
            cc = s >= YD ? add4(y[s % YD], p) : p;
            if (s + YD < NS) y[s % YD] = ldtex(tex, tb | (yc & 1023));
          } else cc = add4(cc, p);
          if (j == 6) acc[s] = add4(acc[s], cc);
        } else {
          const int s = (u - TL) >> 1;
          acc[s] = add4(acc[s], p);
        }
      }
      if ((CBAR & 4) && t == TL / 2) asm volatile("bar.sync 4,%0;" :: "n"(TH) : "memory");
      if ((CBAR & 8) && t == TL - 40) asm volatile("bar.sync 4,%0;" :: "n"(TH) : "memory");
      if (DEPTH == 8 && (t & 7) == 2) yc = yn;
      if (t < TL) {
        const int s = t >> 3, j = t & 7;
        if (j == 0) {
          if (ye_of(s - YD) >= 0) acc[ye_of(s - YD) & 3] = add4(acc[ye_of(s - YD) & 3], ye);
          w = wq[s % PF];
          if (!EARLY || s < NS - 4) wq[s % PF] = ldtex(tex, ti + (s + PF) * TH);
          else {
            if (s == NS - 4) { wq[0] = ldtex(tex, ti + NS * TH); ye = ldtex(tex, ti + (NS + 3) * TH); }
            if (s == NS - 3) { wq[1] = ldtex(tex, ti + (NS + 1) * TH); y[0] = ldtex(tex, ti + (NS + 2) * TH); }
            if (s == NS - 2) wq[2] = y[0];
            if (s == NS - 1) wq[3] = ye;
          }
          yn = __funnelshift_l(w.z, w.z, 5); if (DEPTH < 8) yc = yn;
          if ((s & 3) != 3) asm volatile("add.u32 %0,%1,%2;" : "=r"(sw[s]) : "r"(w.w), "r"(never));
          if (ye_of(s) >= 0) ye = ldtex(tex, tb | w.w);
        }
#pragma unroll
        for (int jj = j; jj < j + 2; jj++) {
          const uint32_t ww = jj < 3 ? w.x : jj < 6 ? w.y : w.z;
          const uint32_t sh = jj % 3 == 0 ? ww : jj % 3 == 1 ? ww >> 10 : __funnelshift_l(ww, ww, 12);
          x[(t + jj - j) % DEPTH] = lds128(sbase + ((sh & 0x1ff80) | lc) + jj * 16 - 128);
        }
      } else if (t < TT) {
        const int s = (t - TL) >> 1;
        if (s == 0) { arrive_both(emptyL, more ? lane : 9); TR(k * 4 + 3); if (CBAR & 2) asm volatile("bar.sync 4,%0;" :: "n"(TH) : "memory"); mbar_wait_fast(fullU, (k + 1) & 1); }
        const uint32_t sv = sget(s);
        x[t % DEPTH] = lds128(sa0(sv));
        x[(t + 1) % DEPTH] = lds128(sa1(sv));
      } else if (t == TT) arrive_both(emptyU, lane);
      if ((t & (FENCE_N - 1)) == FENCE_N - 2) SCHED_FENCE(never, t);
    }
  }
  TS(1, 2);
  const uint4 w2v = lds128(barJ + 32);
  const uint32_t cell = sbase + SM_U + tid * 16;
  const int t9 = tbase + 9 * 1024;
  uint4 za[4], i9 = wq[0];
  auto fetch = [&](int q) {
    y[0] = ldtex(tex, t9 | i9.x); y[1] = ldtex(tex, t9 | i9.y); y[2] = ldtex(tex, t9 | i9.z); y[3] = ldtex(tex, t9 | i9.w);
    if (q) {
      i9 = ldtex(tex, ibase + NC * 8192 + min(q + 1, 7) * TH);
      const uint32_t ca = cell + (q > 6 ? 0 : q - 1) * 16384;
#pragma unroll
      for (int s = 0; s < 4; s++) za[s] = lds128(ca + s * 4096);
    }
  };
  fetch(0);
  i9 = wq[1];
#pragma unroll
  for (int s = 0; s < 4; s++) za[s] = acc[s];
#pragma unroll
  for (int s = 0; s < 24; s++) sts128(cell + s * 4096, acc[4 + s]);
  float hw[8];
  {
    const uint32_t ww[4] = {w2v.x, w2v.y, w2v.z, w2v.w};
#pragma unroll
    for (int k = 0; k < 8; k++) hw[k] = 0.5f * ((k & 1) ? bf_hi(ww[k >> 1]) : bf_lo(ww[k >> 1]));
  }
  float* outp = g_acc + half * 8192 + tid;
#pragma unroll 1
  for (int q = 0; q < NS / 4; q++) {
    uint4 z[4];
#pragma unroll
    for (int s = 0; s < 4; s++) z[s] = add4(za[s], y[s]);
    if (q == 1) {
#pragma unroll
      for (int s = 0; s < 4; s++) sts128(cell + s * 4096, acc[28 + s]);
    }
    if (q < 7) fetch(q + 1);
    SCHED_FENCE(never, 999);
#pragma unroll
    for (int s = 0; s < 4; s++) {
      const uint32_t a[4] = {z[s].x, z[s].y, z[s].z, z[s].w};
      float r0 = 0.f;
#pragma unroll
      for (int k = 0; k < 8; k++) {
        const float v = (k & 1) ? bf_hi(a[k >> 1]) : bf_lo(a[k >> 1]);
        const float u = v * fmaf(v * v, 0.7978845608028654f * 0.044715f, 0.7978845608028654f);
        float th; asm("tanh.approx.f32 %0,%1;" : "=f"(th) : "f"(u));
        r0 = fmaf(fmaf(v, th, v), hw[k], r0);
      }
      asm volatile("red.global.add.f32 [%0],%1;" :: "l"(outp + s * TH), "f"(r0) : "memory");
    }
    outp += 4 * TH;
  }
  TS(1, 3);
  asm volatile("bar.sync 1,%0;" :: "n"(TH + 32) : "memory");
  if (tid == 0) {
    __threadfence();
    const unsigned old = atomicInc(&g_done[half * 32], 63);
    asm volatile("st.shared.u32 [%0],%1;" :: "r"(barJ + 8), "r"(old) : "memory");
  }
  asm volatile("bar.sync 2,%0;" :: "n"(TH) : "memory");
  uint32_t old; asm volatile("ld.shared.u32 %0,[%1];" : "=r"(old) : "r"(barJ + 8));
  if (old == 63) {
    if (half == 0 && tid < 9) g_flag[tid * 32] = 0;
    __threadfence();
    float4 v[8];
#pragma unroll
    for (int q = 0; q < 8; q++) v[q] = __ldcg((const float4*)(g_acc + half * 8192) + q * TH + tid);
#pragma unroll
    for (int q = 0; q < 8; q++) ((uint2*)(out + half * 8192))[q * TH + tid] = make_uint2(pack_bf2(v[q].x, v[q].y), pack_bf2(v[q].z, v[q].w));
    TS(6, 2);
  }
}

}

extern "C" void kernel_launch(void* const* d_in, const int* in_sizes, int n_in, void* d_out, int out_size) {
  const int* idx = (const int*)d_in[0];
  const __nv_bfloat16* table = (const __nv_bfloat16*)d_in[1];
  const __nv_bfloat16* wp = (const __nv_bfloat16*)d_in[2];
  const __nv_bfloat16* w1 = (const __nv_bfloat16*)d_in[3];
  const __nv_bfloat16* b1 = (const __nv_bfloat16*)d_in[4];
  const __nv_bfloat16* w2 = (const __nv_bfloat16*)d_in[5];
  const __nv_bfloat16* b2 = (const __nv_bfloat16*)d_in[6];
  static cudaTextureObject_t texScr = 0, texG = 0;
  static CUtensorMap mapW, mapL, mapS, mapT, mapE, mapC;
  static const void *c_tab = nullptr, *c_w1 = nullptr;
  if (c_tab != table || c_w1 != w1) {
    c_tab = table; c_w1 = w1;
    char* scr = nullptr; cudaGetSymbolAddress((void**)&scr, g_scr);
    auto mk_tex = [](const void* p, size_t bytes, cudaChannelFormatDesc d) {
      cudaResourceDesc rd = {}; rd.resType = cudaResourceTypeLinear; rd.res.linear.devPtr = (void*)p; rd.res.linear.desc = d; rd.res.linear.sizeInBytes = bytes;
      cudaTextureDesc td = {}; td.readMode = cudaReadModeElementType;
      cudaTextureObject_t t = 0; cudaCreateTextureObject(&t, &rd, &td, nullptr); return t;
    };
    if (!texScr) {
      texScr = mk_tex(scr, (size_t)SCR_N * 16, cudaCreateChannelDesc<uint4>());
      texG = mk_tex(scr + (size_t)PX_OFF * 16, (size_t)(SCR_N - PX_OFF) * 16, cudaCreateChannelDesc<unsigned>());
    }
    typedef CUresult (*EncFn)(CUtensorMap*, CUtensorMapDataType, cuuint32_t, void*, const cuuint64_t*, const cuuint64_t*, const cuuint32_t*,
                              const cuuint32_t*, CUtensorMapInterleave, CUtensorMapSwizzle, CUtensorMapL2promotion, CUtensorMapFloatOOBfill);
    EncFn enc = nullptr; cudaDriverEntryPointQueryResult qr;
    cudaGetDriverEntryPoint("cuTensorMapEncodeTiled", (void**)&enc, cudaEnableDefault, &qr);
    const cuuint32_t ones[4] = {1, 1, 1, 1};
    auto mk = [&](CUtensorMap* m, CUtensorMapDataType dt, int rank, void* p, const cuuint64_t* dim, const cuuint64_t* str, const cuuint32_t* box, CUtensorMapSwizzle sw) {
      enc(m, dt, rank, p, dim, str, box, ones, CU_TENSOR_MAP_INTERLEAVE_NONE, sw, CU_TENSOR_MAP_L2_PROMOTION_NONE, CU_TENSOR_MAP_FLOAT_OOB_FILL_NONE);
    };
    { cuuint64_t dim[2] = {H_, F_ * D_}, str[1] = {H_ * 2}; cuuint32_t box[2] = {32, 256};
      mk(&mapW, CU_TENSOR_MAP_DATA_TYPE_BFLOAT16, 2, (void*)w1, dim, str, box, CU_TENSOR_MAP_SWIZZLE_64B); }
    { cuuint64_t dim[4] = {64, V_, NC, 64}, str[3] = {128, 128000, 128000 * NC}; cuuint32_t box[4] = {32, 64, 1, 4};
      mk(&mapL, CU_TENSOR_MAP_DATA_TYPE_BFLOAT16, 4, scr + (size_t)PL_OFF * 16, dim, str, box, CU_TENSOR_MAP_SWIZZLE_64B); }
    { cuuint64_t dim[4] = {16, V_, NC, 64}, str[3] = {32, 32000, 32000 * NC}; cuuint32_t box[4] = {16, 64, 1, 4};
      mk(&mapS, CU_TENSOR_MAP_DATA_TYPE_BFLOAT16, 4, scr + (size_t)PS_OFF * 16, dim, str, box, CU_TENSOR_MAP_SWIZZLE_32B); }
    { cuuint64_t dim[3] = {2048, 10, 64}, str[2] = {16384, 163840}; cuuint32_t box[3] = {128, 2, 4};
      mk(&mapT, CU_TENSOR_MAP_DATA_TYPE_UINT64, 3, scr + (size_t)PT_OFF * 16, dim, str, box, CU_TENSOR_MAP_SWIZZLE_NONE); }
    { cuuint64_t dim[2] = {D_, V_}, str[1] = {D_ * 2}; cuuint32_t box[2] = {64, 128};
      mk(&mapE, CU_TENSOR_MAP_DATA_TYPE_BFLOAT16, 2, (void*)table, dim, str, box, CU_TENSOR_MAP_SWIZZLE_128B);
      cuuint32_t box2[2] = {8, 256};
      mk(&mapC, CU_TENSOR_MAP_DATA_TYPE_BFLOAT16, 2, (void*)table, dim, str, box2, CU_TENSOR_MAP_SWIZZLE_NONE); }
    cudaFuncSetAttribute(k_deep, cudaFuncAttributeMaxDynamicSharedMemorySize, DEEP_SMEM);
    cudaFuncSetAttribute(k_tens, cudaFuncAttributeMaxDynamicSharedMemorySize, K1_SMEM);
  }
  k_tens<<<132, 512, K1_SMEM, cudaStreamPerThread>>>(mapW, mapL, mapS, mapT, mapE, mapC, texScr, texG, idx, table, wp, w1, b1, 0);
  cudaLaunchAttribute at[1];
  at[0].id = cudaLaunchAttributeProgrammaticStreamSerialization; at[0].val.programmaticStreamSerializationAllowed = 1;
  cudaLaunchConfig_t cfg = {};
  cfg.stream = cudaStreamPerThread; cfg.attrs = at;
  cfg.gridDim = 128; cfg.blockDim = TH + 128; cfg.dynamicSmemBytes = DEEP_SMEM; cfg.numAttrs = PDL & 1;
  cudaLaunchKernelEx(&cfg, k_deep, texScr, w2, b2, (__nv_bfloat16*)d_out, 0);

}
```

```cpp
#include <cuda_runtime.h>
#include <cuda_bf16.h>
#include <cuda_fp16.h>
#include <stdint.h>
#include <cuda.h>

namespace {

constexpr int B_ = 16384, F_ = 100, D_ = 128, V_ = 1000, H_ = 512;
constexpr int NC = 9;
constexpr int PT_OFF = 0;
constexpr int PL_OFF = 64 * 10 * 1024;
constexpr int PS_OFF = PL_OFF + 64 * NC * 8000;
constexpr int IXH = NC * 8192 + 2048;
constexpr int IX_OFF = PS_OFF + 64 * NC * 2000;
constexpr int I0_OFF = IX_OFF + 2 * IXH;
constexpr int PX_OFF = I0_OFF + 4096;
constexpr int SCR_N = PX_OFF + 64 * 16 * 136;
static_assert(PX_OFF % 32 == 0, "");

__device__ __align__(1024) uint4 g_scr[SCR_N];
__device__ float g_acc[B_];
__device__ unsigned g_done[64];
__device__ float g_partP[16 * B_];
__device__ unsigned g_flag[16 * 32];

#define TS(k, i)
#define TR(slot)
#define PT(slot)

constexpr uint64_t POL_EF = 0x12F0000000000000ull, POL_N = 0x1000000000000000ull;
__device__ __forceinline__ uint32_t addbf2(uint32_t a, uint32_t b) { uint32_t r; asm("add.rn.bf16x2 %0,%1,%2;" : "=r"(r) : "r"(a), "r"(b)); return r; }
__device__ __forceinline__ uint4 add4(const uint4& a, const uint4& b) { return make_uint4(addbf2(a.x, b.x), addbf2(a.y, b.y), addbf2(a.z, b.z), addbf2(a.w, b.w)); }
__device__ __forceinline__ void acc4(uint4& a, const uint4& b, int never) {
  asm("{.reg .pred p; setp.eq.s32 p,%8,0;\n"
      "@p add.rn.bf16x2 %0,%0,%4; @p add.rn.bf16x2 %1,%1,%5; @p add.rn.bf16x2 %2,%2,%6; @p add.rn.bf16x2 %3,%3,%7;}"
      : "+r"(a.x), "+r"(a.y), "+r"(a.z), "+r"(a.w) : "r"(b.x), "r"(b.y), "r"(b.z), "r"(b.w), "r"(never));
}
__device__ __forceinline__ uint4 ldtex(cudaTextureObject_t t, int i) {
  uint4 v; asm volatile("tex.1d.v4.u32.s32 {%0,%1,%2,%3},[%4,{%5}];" : "=r"(v.x), "=r"(v.y), "=r"(v.z), "=r"(v.w) : "l"(t), "r"(i)); return v;
}
__device__ __forceinline__ uint4 lds128(uint32_t a) {
  uint4 v; asm volatile("ld.volatile.shared.v4.u32 {%0,%1,%2,%3},[%4];" : "=r"(v.x), "=r"(v.y), "=r"(v.z), "=r"(v.w) : "r"(a)); return v;
}
__device__ __forceinline__ void sts128(uint32_t a, const uint4& v) {
  asm volatile("st.shared.v4.u32 [%0],{%1,%2,%3,%4};" :: "r"(a), "r"(v.x), "r"(v.y), "r"(v.z), "r"(v.w) : "memory");
}
__device__ __forceinline__ void mbar_init(uint32_t bar, int n) { asm volatile("mbarrier.init.shared::cta.b64 [%0],%1;" :: "r"(bar), "r"(n) : "memory"); }
__device__ __forceinline__ void mbar_wait(uint32_t bar, uint32_t parity) {
  uint32_t ok; int it = 0;
  do { asm volatile("{.reg .pred p; mbarrier.try_wait.parity.shared::cta.b64 p,[%1],%2; selp.u32 %0,1,0,p;}" : "=r"(ok) : "r"(bar), "r"(parity) : "memory"); } while (!ok && ++it < (1 << 19));
}
__device__ __forceinline__ void mbar_expect(uint32_t bar, uint32_t bytes) { asm volatile("mbarrier.arrive.expect_tx.shared::cta.b64 _,[%0],%1;" :: "r"(bar), "r"(bytes) : "memory"); }
__device__ __forceinline__ void bulk_g2s(uint32_t dst, const void* src, uint32_t bytes, uint32_t bar) {
  asm volatile("cp.async.bulk.shared::cluster.global.mbarrier::complete_tx::bytes [%0],[%1],%2,[%3];" :: "r"(dst), "l"(src), "r"(bytes), "r"(bar) : "memory");
}
__device__ __forceinline__ void bulk_pf(const void* src, uint32_t bytes) { asm volatile("cp.async.bulk.prefetch.L2.global [%0],%1;" :: "l"(src), "r"(bytes) : "memory"); }
#define NOMMA 0
#define NGRP 16
#define PDL 1
#define FIN_S 128
#define WR8 0
#define TRIG 14
#define PREW 5
#define PXW 3
#define WQL 1
#define EARLY 1
#define CBAR 0
#define X_SAMEK 0
#define X_SAMEW 0
#define FM 0
#define SWP 1
#define HOLD 1
#define TW 1
#define PP0 10
#define PT0 10000
#define PDT 0
#define RPNN "160"
#define RAUX "32"
#define RPRO "160"
#define PARK 0
#define NLOOK 128
#define NEF 16
#define ORD 0
#define WFENCE 0
#define SPLIT 1
#define IORD 3
#define IPF 3
#define IPACE 4500
#define WPF 4
#define QV 3
#define QORD(n) ((n) < 23 ? (n) + 2 : (n) - 23)
#define DYD 4
#define DPF 4
#define DDEPTH 4
#define FENCE_N 4
#define INPL 0
#define STAG 1
#define PACE 800
#define PM4 "pmevent 1; pmevent 2; pmevent 3; pmevent 4;"
#define PMFILL "pmevent 1;"
#define SCHED_FENCE(never, k) asm volatile("{.reg .pred p; setp.ne.u32 p,%0,%1; @p bra.uni SKIP_%=;" PMFILL "SKIP_%=: }" :: "r"(never), "r"(0x7fff0000 + (k)) : "memory")

__global__ void k_prod_naive(const __nv_bfloat16* __restrict__ table, const __nv_bfloat16* __restrict__ w1) {
  __shared__ float t[8][D_];
  int f = blockIdx.y, v0 = blockIdx.x * 8, h = threadIdx.x;
  for (int i = h; i < 8 * D_; i += 512) t[i / D_][i % D_] = __bfloat162float(table[v0 * D_ + i]);
  __syncthreads();
  float s[8] = {0, 0, 0, 0, 0, 0, 0, 0};
  for (int d = 0; d < D_; d++) { float w = __bfloat162float(w1[(size_t)(f * D_ + d) * H_ + h]);
#pragma unroll
    for (int k = 0; k < 8; k++) s[k] += t[k][d] * w; }
  __nv_bfloat16* P = (__nv_bfloat16*)g_scr;
  int c = h >> 3;
  for (int k = 0; k < 8; k++) {
    size_t e = f < 72 ? (size_t)PL_OFF + ((size_t)(c * NC + (f >> 3)) * 1000 + v0 + k) * 8 + (f & 7)
             : f < 90 ? (size_t)PS_OFF + ((size_t)(c * NC + ((f - 72) >> 1)) * 1000 + v0 + k) * 2 + (f & 1)
                      : (size_t)PT_OFF + (size_t)(c * 10 + f - 90) * 1024 + v0 + k;
    P[e * 8 + (h & 7)] = __float2bfloat16(s[k]);
  }
}
__global__ void k_pnn_naive(const int* __restrict__ idx, const __nv_bfloat16* __restrict__ table, const __nv_bfloat16* __restrict__ wp) {
  __shared__ float e[F_][33];
  int b = blockIdx.x, d0 = blockIdx.y * 32, tid = threadIdx.x;
  for (int i = tid; i < F_ * 32; i += 128) e[i >> 5][i & 31] = __bfloat162float(table[idx[b * F_ + (i >> 5)] * D_ + d0 + (i & 31)]);
  __syncthreads();
  float s = 0; int d = tid & 31;
  for (int i = tid >> 5; i < F_; i += 4) { float u = 0; for (int j = 0; j < F_; j++) u += __bfloat162float(wp[i * F_ + j]) * e[j][d]; s += u * e[i][d]; }
  for (int o = 16; o; o >>= 1) s += __shfl_xor_sync(~0u, s, o);
  if (d == 0) g_partP[(blockIdx.y * 4 + (tid >> 5)) * B_ + b] = s;
}
__device__ __forceinline__ void mbar_wait_fast(uint32_t bar, uint32_t parity) {
  asm volatile("{.reg .pred p; .reg .u32 n;\n"
               "mbarrier.try_wait.parity.shared::cta.b64 p,[%0],%1;\n"
               "@p bra DONE_%=;\n"
               "mov.u32 n,0;\n"
               "LOOP_%=: mbarrier.try_wait.parity.shared::cta.b64 p,[%0],%1;\n"
               "add.u32 n,n,1; setp.gt.or.u32 p,n,400000,p;\n"
               "@!p bra LOOP_%=;\n"
               "DONE_%=: }" :: "r"(bar), "r"(parity) : "memory");
}
__device__ __forceinline__ void sleep_until(uint32_t t0, uint32_t dt) { while ((uint32_t)clock() - t0 < dt) __nanosleep(40); }
__device__ __forceinline__ uint32_t s_mask(uint32_t v, int q) { return (1u << ((v + 3 - q) & 3)) | (16u << ((v + 3 + q) & 3)); }
__device__ __forceinline__ uint32_t s_cell(uint32_t v, int q, uint32_t m) {
  const int t = __ffs(~m) - 1;
  const int cp = t == 8 ? q >> 1 : ((t & 4 ? t - q : t + q) - v) & 3;
  return cp * 1001 + v;
}
__device__ __forceinline__ uint32_t pk3(uint32_t a, uint32_t b, uint32_t c) {
  const uint32_t w = c + (a << 12) + (b << 22); return __funnelshift_l(w, w, 27);
}
constexpr int TH = 256, NS = 8192 / TH, YD = DYD;
__host__ __device__ constexpr int ye_of(int s) { return s == 3 ? 0 : s == 11 ? 1 : s == 19 ? 2 : s == 23 ? 3 : -1; }
template <int N> __device__ __forceinline__ void wgmma_h(uint32_t* d, const uint32_t* a, uint64_t desc, int acc);
template <> __device__ __forceinline__ void wgmma_h<64>(uint32_t* d, const uint32_t* a, uint64_t desc, int acc) {
  asm volatile("{.reg .pred p; setp.ne.s32 p,%21,0;\n"
    "wgmma.mma_async.sync.aligned.m64n64k16.f16.f16.f16 {%0,%1,%2,%3,%4,%5,%6,%7,%8,%9,%10,%11,%12,%13,%14,%15},{%16,%17,%18,%19},%20,p,1,1,0;}"
    : "+r"(d[0]),"+r"(d[1]),"+r"(d[2]),"+r"(d[3]),"+r"(d[4]),"+r"(d[5]),"+r"(d[6]),"+r"(d[7]),"+r"(d[8]),"+r"(d[9]),"+r"(d[10]),"+r"(d[11]),"+r"(d[12]),"+r"(d[13]),"+r"(d[14]),"+r"(d[15])
    : "r"(a[0]), "r"(a[1]), "r"(a[2]), "r"(a[3]), "l"(desc), "r"(acc));
}
template <> __device__ __forceinline__ void wgmma_h<56>(uint32_t* d, const uint32_t* a, uint64_t desc, int acc) {
  asm volatile("{.reg .pred p; setp.ne.s32 p,%19,0;\n"
    "wgmma.mma_async.sync.aligned.m64n56k16.f16.f16.f16 {%0,%1,%2,%3,%4,%5,%6,%7,%8,%9,%10,%11,%12,%13},{%14,%15,%16,%17},%18,p,1,1,0;}"
    : "+r"(d[0]),"+r"(d[1]),"+r"(d[2]),"+r"(d[3]),"+r"(d[4]),"+r"(d[5]),"+r"(d[6]),"+r"(d[7]),"+r"(d[8]),"+r"(d[9]),"+r"(d[10]),"+r"(d[11]),"+r"(d[12]),"+r"(d[13])
    : "r"(a[0]), "r"(a[1]), "r"(a[2]), "r"(a[3]), "l"(desc), "r"(acc));
}
template <> __device__ __forceinline__ void wgmma_h<48>(uint32_t* d, const uint32_t* a, uint64_t desc, int acc) {
  asm volatile("{.reg .pred p; setp.ne.s32 p,%17,0;\n"
    "wgmma.mma_async.sync.aligned.m64n48k16.f16.f16.f16 {%0,%1,%2,%3,%4,%5,%6,%7,%8,%9,%10,%11},{%12,%13,%14,%15},%16,p,1,1,0;}"
    : "+r"(d[0]),"+r"(d[1]),"+r"(d[2]),"+r"(d[3]),"+r"(d[4]),"+r"(d[5]),"+r"(d[6]),"+r"(d[7]),"+r"(d[8]),"+r"(d[9]),"+r"(d[10]),"+r"(d[11])
    : "r"(a[0]), "r"(a[1]), "r"(a[2]), "r"(a[3]), "l"(desc), "r"(acc));
}
template <> __device__ __forceinline__ void wgmma_h<40>(uint32_t* d, const uint32_t* a, uint64_t desc, int acc) {
  asm volatile("{.reg .pred p; setp.ne.s32 p,%15,0;\n"
    "wgmma.mma_async.sync.aligned.m64n40k16.f16.f16.f16 {%0,%1,%2,%3,%4,%5,%6,%7,%8,%9},{%10,%11,%12,%13},%14,p,1,1,0;}"
    : "+r"(d[0]),"+r"(d[1]),"+r"(d[2]),"+r"(d[3]),"+r"(d[4]),"+r"(d[5]),"+r"(d[6]),"+r"(d[7]),"+r"(d[8]),"+r"(d[9])
    : "r"(a[0]), "r"(a[1]), "r"(a[2]), "r"(a[3]), "l"(desc), "r"(acc));
}
template <> __device__ __forceinline__ void wgmma_h<32>(uint32_t* d, const uint32_t* a, uint64_t desc, int acc) {
  asm volatile("{.reg .pred p; setp.ne.s32 p,%13,0;\n"
    "wgmma.mma_async.sync.aligned.m64n32k16.f16.f16.f16 {%0,%1,%2,%3,%4,%5,%6,%7},{%8,%9,%10,%11},%12,p,1,1,0;}"
    : "+r"(d[0]),"+r"(d[1]),"+r"(d[2]),"+r"(d[3]),"+r"(d[4]),"+r"(d[5]),"+r"(d[6]),"+r"(d[7])
    : "r"(a[0]), "r"(a[1]), "r"(a[2]), "r"(a[3]), "l"(desc), "r"(acc));
}
__device__ __forceinline__ void wgmma_p(float* d, const uint32_t* a, uint64_t desc, int acc) {
  asm volatile("{.reg .pred p; setp.ne.s32 p,%37,0;\n"
    "wgmma.mma_async.sync.aligned.m64n64k16.f32.bf16.bf16 {%0,%1,%2,%3,%4,%5,%6,%7,%8,%9,%10,%11,%12,%13,%14,%15,%16,%17,%18,%19,%20,%21,%22,%23,%24,%25,%26,%27,%28,%29,%30,%31},{%32,%33,%34,%35},%36,p,1,1,1;}"
    : "+f"(d[0]),"+f"(d[1]),"+f"(d[2]),"+f"(d[3]),"+f"(d[4]),"+f"(d[5]),"+f"(d[6]),"+f"(d[7]),"+f"(d[8]),"+f"(d[9]),"+f"(d[10]),"+f"(d[11]),"+f"(d[12]),"+f"(d[13]),"+f"(d[14]),"+f"(d[15]),"+f"(d[16]),"+f"(d[17]),"+f"(d[18]),"+f"(d[19]),"+f"(d[20]),"+f"(d[21]),"+f"(d[22]),"+f"(d[23]),"+f"(d[24]),"+f"(d[25]),"+f"(d[26]),"+f"(d[27]),"+f"(d[28]),"+f"(d[29]),"+f"(d[30]),"+f"(d[31])
    : "r"(a[0]), "r"(a[1]), "r"(a[2]), "r"(a[3]), "l"(desc), "r"(acc));
}

__device__ __forceinline__ void mma16816h(uint32_t* c, const uint32_t* a, uint32_t b0, uint32_t b1) {
  asm("mma.sync.aligned.m16n8k16.row.col.f16.f16.f16.f16 {%0,%1},{%2,%3,%4,%5},{%6,%7},{%0,%1};"
      : "+r"(c[0]), "+r"(c[1]) : "r"(a[0]), "r"(a[1]), "r"(a[2]), "r"(a[3]), "r"(b0), "r"(b1));
}
__device__ __forceinline__ void mma1688h(uint32_t* c, uint32_t a0, uint32_t a1, uint32_t b) {
  asm("mma.sync.aligned.m16n8k8.row.col.f16.f16.f16.f16 {%0,%1},{%2,%3},{%4},{%0,%1};" : "+r"(c[0]), "+r"(c[1]) : "r"(a0), "r"(a1), "r"(b));
}
__device__ __forceinline__ void mma1688f(float* c, uint32_t a0, uint32_t a1, uint32_t b) {
  asm("mma.sync.aligned.m16n8k8.row.col.f32.f16.f16.f32 {%0,%1,%2,%3},{%4,%5},{%6},{%0,%1,%2,%3};"
      : "+f"(c[0]), "+f"(c[1]), "+f"(c[2]), "+f"(c[3]) : "r"(a0), "r"(a1), "r"(b));
}
__device__ __forceinline__ uint32_t hadd2(uint32_t a, uint32_t b) { uint32_t r; asm("add.rn.f16x2 %0,%1,%2;" : "=r"(r) : "r"(a), "r"(b)); return r; }
__device__ __forceinline__ uint32_t hfma2(uint32_t a, uint32_t b, uint32_t c) { uint32_t r; asm("fma.rn.f16x2 %0,%1,%2,%3;" : "=r"(r) : "r"(a), "r"(b), "r"(c)); return r; }
__device__ __forceinline__ uint32_t pack_bf2(float lo, float hi) { uint32_t r; asm("cvt.rn.bf16x2.f32 %0,%1,%2;" : "=r"(r) : "f"(hi), "f"(lo)); return r; }
__device__ __forceinline__ uint32_t pack_h2(float lo, float hi) { uint32_t r; asm("cvt.rn.f16x2.f32 %0,%1,%2;" : "=r"(r) : "f"(hi), "f"(lo)); return r; }
__device__ __forceinline__ float bf_lo(uint32_t w) { return __uint_as_float(w << 16); }
__device__ __forceinline__ float bf_hi(uint32_t w) { return __uint_as_float(w & 0xffff0000u); }
__device__ __forceinline__ uint32_t absmax4(const uint4& v, uint32_t m) {
  return __vmaxu2(__vmaxu2(__vmaxu2(v.x & 0x7fff7fffu, v.y & 0x7fff7fffu), __vmaxu2(v.z & 0x7fff7fffu, v.w & 0x7fff7fffu)), m);
}
__device__ __forceinline__ float pow2_scale(uint32_t mbits, int p) { return __uint_as_float((uint32_t)min(max(253 + p - (int)(mbits >> 7), 2), 252) << 23); }

#define PV 4
constexpr int G_O0 = 8, G_O1 = 4, G_O2 = 0, G_N0 = 5, G_N1 = 4, G_N2 = 4, G_K0 = 5, G_K1 = 3, G_K2 = 1;
__host__ __device__ constexpr bool unit_wg(int kb, int on) {
  return (on >= G_O0 && on < G_O0 + G_N0 && kb < G_K0) || (on >= G_O1 && on < G_O1 + G_N1 && kb < G_K1) || (on >= G_O2 && on < G_O2 + G_N2 && kb < G_K2);
}
__host__ __device__ constexpr bool oct_wg(int on) { return unit_wg(0, on); }
constexpr int G_U1 = G_N0 * G_K0, G_U2 = G_U1 + G_N1 * G_K1, G_U = G_U2 + G_N2 * G_K2;
constexpr int K1_B = 130048, K1_STG = K1_B + 3 * 16384, K1_W = K1_STG + 2 * 16384, K1_BAR = K1_W + 48 * 256, K1_SMEM = K1_BAR + 256 + 4352;
__host__ __device__ constexpr int frag_index(int ok, int on) {
  int n = 0;
  for (int k = 0; k < 13; k++) for (int o = k; o < 13; o++) { if (k == ok && o == on) return n; if (!unit_wg(k >> 1, o)) n++; }
  return n;
}
constexpr int HU_N = 2 * G_U + frag_index(99, 99);
static_assert(HU_N <= 96, "");
struct FragIdx { int v[13][13]; };
__host__ __device__ constexpr FragIdx make_fi() { FragIdx f = {}; for (int k = 0; k < 13; k++) for (int o = 0; o < 13; o++) f.v[k][o] = frag_index(k, o); return f; }
__host__ __device__ constexpr uint64_t frag_tab(int first) {
  uint64_t t = 0;
  for (int k = 0; k < 13; k++) for (int o = k; o < 13; o++)
    if (!unit_wg(k >> 1, o)) { const int n = frag_index(k, o) - first; if (n >= 0 && n < 8) t |= (uint64_t)(k << 4 | o) << (8 * n); }
  return t;
}
__device__ __forceinline__ int hu_code(int hu) {
  constexpr uint64_t T0 = frag_tab(0), T1 = frag_tab(8), T2 = frag_tab(16), T3 = frag_tab(24);
  const int u = hu >> 1, f = hu - 2 * G_U;
  if (f >= 0) return (int)((f < 8 ? T0 : f < 16 ? T1 : f < 24 ? T2 : T3) >> (8 * (f & 7))) & 255;
  const int u0 = u < G_U1 ? u : u < G_U2 ? u - G_U1 : u - G_U2;
  const int kb = u < G_U1 ? u0 / G_N0 : u < G_U2 ? u0 / G_N1 : u0 / 4, on = u < G_U1 ? G_O0 + u0 % G_N0 : u < G_U2 ? G_O1 + u0 % G_N1 : G_O2 + u0 % 4;
  return (2 * kb + (hu & 1)) << 4 | on;
}

__device__ __forceinline__ void flag_arrive(unsigned* f, int lane) {
  __threadfence(); __syncwarp();
  if (lane == 0) asm volatile("red.release.gpu.global.add.u32 [%0],1;" :: "l"(f) : "memory");
}
__device__ __forceinline__ void flag_wait(const unsigned* f, unsigned n) {
  unsigned v; int it = 0;
  asm volatile("ld.acquire.gpu.global.u32 %0,[%1];" : "=r"(v) : "l"(f) : "memory");
  if (v < n) {
    do { __nanosleep(300); asm volatile("ld.relaxed.gpu.global.u32 %0,[%1];" : "=r"(v) : "l"(f) : "memory"); } while (v < n && ++it < (1 << 20));
    asm volatile("ld.acquire.gpu.global.u32 %0,[%1];" : "=r"(v) : "l"(f) : "memory");
  }
}
__device__ __forceinline__ void mbar_arrive(uint32_t bar) { asm volatile("mbarrier.arrive.shared::cta.b64 _,[%0];" :: "r"(bar) : "memory"); }
__device__ __forceinline__ void mbar_arrive_lane0(uint32_t bar) {
  asm volatile("{.reg .pred p; elect.sync _|p,0xffffffff; @p mbarrier.arrive.shared::cta.b64 _,[%0];}" :: "r"(bar) : "memory");
}

__device__ __forceinline__ void pack_role(const int* __restrict__ idx, uint32_t sbase, int pc) {
  constexpr int CH = 3200 + 32, BUF = 32 * 3328;
  const int tid = threadIdx.x, lane = tid & 31, warp = tid >> 5;
  const uint32_t full = sbase + 2 * BUF, empty = full + 16;
  if (tid == 0) { mbar_init(full, 1); mbar_init(full + 8, 1); mbar_init(empty, 18); mbar_init(empty + 8, 18); asm volatile("fence.proxy.async.shared::cta;" ::: "memory"); }
  __syncthreads();
  auto chunk = [&](int s) { return s * 3200 + (s >> 2) * 288; };
  auto load = [&](int n) {
    const int blk = pc * 16 + n;
    if (lane == 0) mbar_expect(full + (n & 1) * 8, 32 * 3200);
    __syncwarp();
    bulk_g2s(sbase + (n & 1) * BUF + chunk(lane), idx + ((blk >> 5) * 8192 + lane * TH + (blk & 31) * 8) * F_, 3200, full + (n & 1) * 8);
  };
  if (warp == 0) { load(0); load(1); }
  const int l = lane & 7;
  uint32_t rot[8], inc[3];
#pragma unroll
  for (int jj = 0; jj < 8; jj++) rot[jj] = ((l + jj) & 7) * 4;
#pragma unroll
  for (int q = 0; q < 3; q++) inc[q] = (l + 3 * q < 8) << 12 | (l + 3 * q + 1 < 8) << 22 | (q < 2 && l + 3 * q + 2 < 8);
  int loaded = 2;
#pragma unroll 1
  for (int task = warp; task < 288; task += 16) {
    const int n = task / 18, q = (task % 18) * 4 + (lane >> 3), sq = q / 9, k = q % 9;
    if (warp == 0 && n + 1 == loaded && loaded < 16) { mbar_wait(empty + (loaded & 1) * 8, ((loaded >> 1) - 1) & 1); load(loaded); loaded++; }
    mbar_wait(full + (n & 1) * 8, (n >> 1) & 1);
    const uint32_t buf = sbase + (n & 1) * BUF + l * 400, row = buf + chunk(sq * 4);
    auto ld = [&](uint32_t ad) { uint32_t v; asm volatile("ld.shared.u32 %0,[%1];" : "=r"(v) : "r"(ad)); return v; };
    const int blk = pc * 16 + n, half = blk >> 5, col = (blk & 31) * 8 + l;
    const int ks = k == NC - 1 ? 0 : k + 1;
    uint32_t cw[4], sv[8], m[2] = {0, 0};
    { const uint32_t a0 = row + (72 + 2 * ks + (l >> 2)) * 4;
#pragma unroll
      for (int u = 0; u < 8; u++) { sv[u] = ld((a0 ^ ((u >> 2) * 4)) + (u & 3) * 3200); m[u >> 2] |= s_mask(sv[u], l & 3) << (8 * (u & 3)); } }
#pragma unroll
    for (int h = 0; h < 2; h++) { m[h] |= __shfl_xor_sync(0xffffffffu, m[h], 1); m[h] |= __shfl_xor_sync(0xffffffffu, m[h], 2); }
#pragma unroll
    for (int u = 0; u < 4; u++) cw[u] = s_cell(sv[u], l & 3, (m[0] >> (8 * u)) & 255) | s_cell(sv[4 + u], l & 3, (m[1] >> (8 * u)) & 255) << 12;
    if (k == NC - 1) {
      g_scr[I0_OFF + (half * 8 + sq) * TH + col] = make_uint4(cw[0], cw[1], cw[2], cw[3]);
      g_scr[IX_OFF + half * IXH + NC * 8192 + sq * TH + col] = make_uint4(ld(row + 396), ld(row + 3596), ld(row + 6796), ld(row + 9996));
      cw[0] = cw[1] = cw[2] = cw[3] = 0;
    }
    const uint32_t ax = buf + chunk(min(sq + 1, 7) * 4) + (90 + k) * 4;
    const uint32_t yev = ld(buf + ((0x3210 >> (sq * 2 + (sq == 5) * 2)) & 3) * 3200 + (90 + k) * 4);
    uint4* dst = g_scr + IX_OFF + half * IXH + (k * NS + sq * 4) * TH + col;
#pragma unroll
    for (int u = 0; u < 4; u++) {
      uint32_t e[8];
#pragma unroll
      for (int jj = 0; jj < 8; jj++) e[jj] = ld(row + k * 32 + rot[jj] + u * 3200);
      dst[u * TH] = make_uint4(pk3(e[0], e[1], e[2] + inc[0]), pk3(e[3], e[4], e[5] + inc[1]), pk3(e[6], e[7], ld(ax + u * 3200) + inc[2]),
                               u < 3 ? __byte_perm(cw[u], cw[3], 0x4210 + (u << 12)) : yev);
    }
    mbar_arrive_lane0(empty + (n & 1) * 8);
  }
  (void)CH;
}

__global__ void __cluster_dims__(2, 1, 1) __launch_bounds__(512, 1)
k_tens(const __grid_constant__ CUtensorMap mapW, const __grid_constant__ CUtensorMap mapL, const __grid_constant__ CUtensorMap mapS,
       const __grid_constant__ CUtensorMap mapT, const __grid_constant__ CUtensorMap mapE, const __grid_constant__ CUtensorMap mapC, cudaTextureObject_t tex, cudaTextureObject_t texX,
       const int* __restrict__ idx, const __nv_bfloat16* __restrict__ table, const __nv_bfloat16* __restrict__ wp, const __nv_bfloat16* __restrict__ w1,
       const __nv_bfloat16* __restrict__ b1, int never) {
  extern __shared__ __align__(1024) uint4 sm[];
  const int tid = threadIdx.x, lane = tid & 31, cta = blockIdx.x;
  const uint32_t sbase = (uint32_t)__cvta_generic_to_shared(sm);
  const int g = lane >> 2, r = lane & 3;
  TS(0, 0);
  if (cta >= 128) {
    pack_role(idx, sbase, cta - 128);
    __syncthreads();
    if (tid < 32) flag_arrive(&g_flag[8 * 32], lane);
    TS(2, 1);
    asm volatile("barrier.cluster.arrive.relaxed.aligned; barrier.cluster.wait.aligned;" ::: "memory");
    return;
  }
  const uint32_t fullB = sbase + K1_BAR, emptyB = fullB + 24, fullE = fullB + 48, fullC = fullB + 56, fullI = fullB + 64, fullX = fullB + 72, progG = fullB + 80, fullS = fullB + 96, emptyS = fullB + 128;
  const int rb = cta & 7, hc = cta >> 3;
  auto uq = [&](int q) { return SWP && q < 18 ? (q & ~1) | (hc & 1) : q; };
  auto uh = [&](int q) { return SWP && q < 18 ? (hc & ~1) | (q & 1) : hc; };
  if (tid >= 384) {
    asm volatile("setmaxnreg.dec.sync.aligned.u32 " RAUX ";");
    if (tid < 416) {
      auto load_pair = [&](int p, int st) {
        mbar_expect(fullB + st * 8, 16384);
        asm volatile("cp.async.bulk.tensor.2d.shared::cluster.global.mbarrier::complete_tx::bytes [%0],[%1,{%2,%3}],[%4];"
                     :: "r"(sbase + K1_B + st * 16384), "l"(&mapW), "r"(uh(QORD(p >> 1)) * 32), "r"(uq(QORD(p >> 1)) * 512 + (p & 1) * 256), "r"(fullB + st * 8) : "memory");
        p += WPF;
        if (p < 50) {
          int pr = QORD(p >> 1) * 2 + (p & 1);
          if (SWP && pr < 36) pr = (pr & ~3) | ((pr & 1) << 1) | ((pr >> 1) & 1);
          bulk_pf(w1 + pr * 131072 + cta * 1024, 2048);
        }
      };
      if (tid == 384) {
        for (int q = 0; q < 3; q++) { mbar_init(fullB + q * 8, 1); mbar_init(emptyB + q * 8, 4); }
        for (int q = 0; q < 4; q++) { mbar_init(fullS + q * 8, 4); mbar_init(emptyS + q * 8, 1); }
        mbar_init(fullE, 1); mbar_init(fullC, 1); mbar_init(fullI, 1); mbar_init(fullX, 1); mbar_init(progG, 1);
        asm volatile("fence.proxy.async.shared::cta;" ::: "memory");
        mbar_expect(fullC, 16384);
        for (int q = 0; q < 4; q++)
          asm volatile("cp.async.bulk.tensor.2d.shared::cluster.global.mbarrier::complete_tx::bytes [%0],[%1,{%2,%3}],[%4];"
                       :: "r"(sbase + 32768 + q * 4096), "l"(&mapC), "r"((cta & 15) * 8), "r"(q * 256), "r"(fullC) : "memory");
        mbar_expect(fullE, 32768);
        for (int q = 0; q < 2; q++)
          asm volatile("cp.async.bulk.tensor.2d.shared::cluster.global.mbarrier::complete_tx::bytes [%0],[%1,{%2,%3}],[%4];"
                       :: "r"(sbase + K1_STG + q * 16384), "l"(&mapE), "r"(q * 64), "r"(rb * 128), "r"(fullE) : "memory");
      }
      __syncwarp();
      asm volatile("bar.arrive 2,448;" ::: "memory");
      if (tid == 384) {
        int st = 0, ph = 1;
        const uint32_t tl0 = clock();
#pragma unroll 1
        for (int p = 0; p < 50; p++) {
          if (p == IORD) {
            mbar_expect(fullI, 51200);
#pragma unroll 1
            for (int q = 0; q < 8; q++) bulk_g2s(sbase + 76800 + q * 6400, idx + (((cta >> 4) * 8 + q) * 256 + (cta & 15) * 16) * F_, 6400, fullI);
          }
          if (PDT && p > PP0) sleep_until(tl0, PT0 + (p - PP0) * PDT);
          mbar_wait(emptyB + st * 8, ph);
          load_pair(p, st);
          if (++st == 3) { st = 0; ph ^= 1; }
        }
      }
    } else if (tid < 448) {
      ((float4*)g_acc)[cta * 32 + lane] = make_float4(0.f, 0.f, 0.f, 0.f);
      asm volatile("bar.sync 2,448;" ::: "memory");
      if (HOLD) { asm volatile("bar.sync 4,288;" ::: "memory"); flag_arrive(&g_flag[(cta >> 4) * 32], lane); }
      __syncwarp();
      if (tid == 416) {
#pragma unroll 1
        for (int n = 0; n < 50; n++) {
          const int quad = QORD(n >> 1), mt = n & 1, v0 = rb * 128 + mt * 64;
          const uint32_t stg = sbase + K1_STG + mt * 16384;
          const uint64_t pol = n < 2 * NEF ? POL_EF : POL_N;
          mbar_wait(fullS + mt * 8, (n >> 1) & 1);
          asm volatile("fence.proxy.async.shared::cta;" ::: "memory");
          if (quad < 18) {
            asm volatile("cp.async.bulk.tensor.4d.global.shared::cta.bulk_group.L2::cache_hint [%0,{%1,%2,%3,%4}],[%5],%6;"
                         :: "l"(&mapL), "r"((uq(quad) & 1) * 32), "r"(v0), "r"(quad >> 1), "r"(uh(quad) * 4), "r"(stg), "l"(pol) : "memory");
          } else {
#pragma unroll 1
            for (int hh = 0; hh < 2; hh++) {
              const int pq = quad * 2 + hh;
              if (pq < 45) asm volatile("cp.async.bulk.tensor.4d.global.shared::cta.bulk_group.L2::cache_hint [%0,{%1,%2,%3,%4}],[%5],%6;"
                         :: "l"(&mapS), "r"(0), "r"(v0 >> 2), "r"(pq - 36), "r"(hc * 4), "r"(stg + hh * 8192), "l"(pol) : "memory");
              else asm volatile("cp.async.bulk.tensor.3d.global.shared::cta.bulk_group.L2::cache_hint [%0,{%1,%2,%3}],[%4],%5;"
                         :: "l"(&mapT), "r"(v0 * 2), "r"((pq - 45) * 2), "r"(hc * 4), "r"(stg + hh * 8192), "l"(pol) : "memory");
            }
          }
          asm volatile("cp.async.bulk.commit_group;" ::: "memory");
          asm volatile("cp.async.bulk.wait_group.read 0;" ::: "memory");
          mbar_arrive(emptyS + mt * 8);
        }
        asm volatile("cp.async.bulk.wait_group 0;" ::: "memory");
        asm volatile("fence.proxy.async.global;" ::: "memory");
        __threadfence();
        asm volatile("red.release.gpu.global.add.u32 [%0],1;" :: "l"(&g_flag[8 * 32]) : "memory");
        flag_wait(&g_flag[8 * 32], 132);
        asm volatile("fence.proxy.async.global;" ::: "memory");
        const char* base = (const char*)g_scr;
        const int c = cta >> 1, half = cta & 1, ch = (c + (c >> 4) * 5) & 15;
        bulk_pf(base + (PS_OFF + c * NC * 2000) * 16u + half * 16000, 16000);
        if (PREW & 2) bulk_pf(base + (PL_OFF + c * NC * 8000) * 16u + half * 64000, 64000);
        bulk_pf(base + (PT_OFF + c * 10 * 1024) * 16u + half * 8192, 8192);
        mbar_expect(fullE, 18432);
        bulk_g2s(sbase + K1_STG, base + (I0_OFF + half * 2048 + ch * 128) * 16u, 2048, fullE);
        bulk_g2s(sbase + K1_STG + 2048, base + (IX_OFF + half * IXH + ch * 512) * 16u, 8192, fullE);
        bulk_g2s(sbase + K1_STG + 10240, base + (IX_OFF + half * IXH + 8192 + ch * 512) * 16u, 8192, fullE);
        mbar_wait(fullE, 1);
      }
    } else if (tid >= 480) {
      if (!HOLD) { asm volatile("bar.sync 4,288;" ::: "memory"); flag_arrive(&g_flag[(cta >> 4) * 32], lane); }
    } else if (tid == 448 && PXW) {
      flag_wait(&g_flag[(cta >> 4) * 32], 16);
      asm volatile("fence.proxy.async.global;" ::: "memory");
      const char* src = (const char*)(g_scr + PX_OFF + ((cta >> 4) * 8 + ((cta >> 1) & 3) * 2) * 16 * 136);
#pragma unroll 1
      for (int n = 1; n < 16; n++) {
        if (n >= PXW) mbar_wait(progG, (n - PXW) & 1);
        mbar_expect(fullX, 4352);
        bulk_g2s(sbase + K1_BAR + 256, src + n * 2176, 2176, fullX);
        bulk_g2s(sbase + K1_BAR + 256 + 2176, src + (16 + n) * 2176, 2176, fullX);
        mbar_wait(fullX, (n - 1) & 1);
      }
    }
    return;
  }
  if (tid >= 256) {
    asm volatile("setmaxnreg.inc.sync.aligned.u32 " RPRO ";");
    const int w = (tid >> 5) & 3;
    const int srow = w * 16 + (lane & 7) + ((lane >> 3) & 1) * 8, sc = lane >> 4;
    uint32_t a[2][8][4];
    asm volatile("bar.sync 2,448;" ::: "memory");
    mbar_wait_fast(fullE, 0);
#pragma unroll
    for (int mt = 0; mt < 2; mt++)
#pragma unroll
      for (int ks = 0; ks < 8; ks++)
        asm volatile("ldmatrix.sync.aligned.m8n8.x4.shared.b16 {%0,%1,%2,%3},[%4];"
                     : "=r"(a[mt][ks][0]), "=r"(a[mt][ks][1]), "=r"(a[mt][ks][2]), "=r"(a[mt][ks][3])
                     : "r"(sbase + K1_STG + (ks >> 2) * 16384 + (mt * 64 + srow) * 128 + ((((ks & 3) * 2 + sc) ^ (lane & 7)) * 16)) : "memory");
    asm volatile("bar.sync 5,128;" ::: "memory");
    const uint32_t baseL = sc * 4096 + srow * 64 + ((srow >> 1) & 3) * 16, baseS = sc * 2048 + ((srow * 32) ^ (((srow >> 2) & 7) * 16)), baseT = sc * 2048 + srow * 16;
    const uint64_t desc0 = (uint64_t)(((sbase + K1_B) & 0x3FFFF) >> 4) | ((uint64_t)(8192 >> 4) << 16) | ((uint64_t)(512 >> 4) << 32) | (2ull << 62);
    float d[2][32];
    auto issue = [&](int x, int mt, int st) {
      uint32_t a7[4];
#pragma unroll
      for (int e = 0; e < 4; e++) { if (PARK) asm volatile("add.u32 %0,%1,%2;" : "=r"(a7[e]) : "r"(a[mt][7][e]), "r"(never)); else a7[e] = a[mt][7][e]; }
      asm volatile("wgmma.fence.sync.aligned;" ::: "memory");
#pragma unroll
      for (int ks = 0; ks < 8; ks++) wgmma_p(d[x], ks < 7 ? a[mt][ks] : a7, desc0 + st * 1024 + ks * 64, ks);
      asm volatile("wgmma.commit_group.sync.aligned;" ::: "memory");
    };
    auto wait_acc = [&](int x) {
      asm volatile("wgmma.wait_group.sync.aligned 0;" ::: "memory");
#pragma unroll
      for (int q = 0; q < 8; q++) asm volatile("" : "+f"(d[x][q * 4]), "+f"(d[x][q * 4 + 1]), "+f"(d[x][q * 4 + 2]), "+f"(d[x][q * 4 + 3]) :: "memory");
    };
    mbar_wait_fast(fullB, 0);
    issue(0, 0, 0);
    int s0 = 0, ph = 0;
#pragma unroll 1
    for (int qn = 0; qn < 25; qn++) {
      const int quad = QORD(qn);
      const int s1 = s0 == 2 ? 0 : s0 + 1, s2 = s1 == 2 ? 0 : s1 + 1, ph1 = ph ^ (s1 == 0), ph2 = ph1 ^ (s2 == 0);
#pragma unroll
      for (int step = 0; step < 4; step++) {
        const int mt = ORD ? step & 1 : step >> 1, h = ORD ? step >> 1 : step & 1, x = step & 1, nx = (step + 1) & 3;
        const bool isL = quad < 18, isS = quad * 2 + h < 45;
        const uint32_t base = (isL ? baseL ^ (h * 32) : (isS ? baseS : baseT) ^ (h * 8192)), xj = (isL || isS) ? 16 : 1024, xc = isL ? 8192 : 4096;
        PT(qn * 16 + step * 4);
        if (h == 0) mbar_wait_fast(emptyS + mt * 8, (qn & 1) ^ 1);
        if (step == (ORD ? 1 : 0)) mbar_wait_fast(fullB + s1 * 8, ph1);
        if (step == 3) mbar_wait_fast(fullB + s2 * 8, qn == 24 ? ph2 ^ 1 : ph2);
        PT(qn * 16 + step * 4 + 1);
        wait_acc(x);
        PT(qn * 16 + step * 4 + 2);
        if (mt) mbar_arrive_lane0(emptyB + (h ? s1 : s0) * 8);
        issue(x ^ 1, ORD ? nx & 1 : nx >> 1, step == 3 ? s2 : (ORD ? nx >> 1 : nx & 1) ? s1 : s0);
        PT(qn * 16 + step * 4 + 3);
        if (h && quad == 24) {
#pragma unroll
          for (int cq = 0; cq < 4; cq++) {
            const uint32_t bw = __ldg((const uint32_t*)(b1 + hc * 32 + cq * 8) + r);
#pragma unroll
            for (int e = 0; e < 4; e++) d[x][16 + cq * 4 + e] += (e & 1) ? bf_hi(bw) : bf_lo(bw);
          }
        }
#pragma unroll
        for (int e4 = 0; e4 < 4; e4++) {
          const float* e = d[x] + e4 * 8;
          asm volatile("stmatrix.sync.aligned.m8n8.x4.shared.b16 [%0],{%1,%2,%3,%4};"
                       :: "r"(sbase + K1_STG + mt * 16384 + (base ^ ((e4 >> 1) * xj) ^ ((e4 & 1) * xc))),
                          "r"(pack_bf2(e[0], e[1])), "r"(pack_bf2(e[2], e[3])), "r"(pack_bf2(e[4], e[5])), "r"(pack_bf2(e[6], e[7])) : "memory");
        }
        if (h) { __syncwarp(); mbar_arrive_lane0(fullS + mt * 8); }
      }
      s0 = s2; ph = ph2;
    }
    asm volatile("wgmma.wait_group.sync.aligned 0;" ::: "memory");
    return;
  }
  asm volatile("setmaxnreg.inc.sync.aligned.u32 " RPNN ";");
  const int slice = cta & 15;
  const int range = (cta >> 4) * 8 + __shfl_sync(0xffffffffu, tid >> 5, 0);
  uint4 iv[4], trow[4]; uint32_t ix;
  uint2 wrow[10];
#pragma unroll
  for (int q = 0; q < 10; q++) asm volatile("ld.global.nc.v2.u32 {%0,%1},[%2];" : "=r"(wrow[q].x), "=r"(wrow[q].y) : "l"((const uint2*)wp + min(tid + q * 256, 2499)));
  asm volatile("bar.sync 2,448;" ::: "memory");
  uint32_t me = 0, mw = 0;
#pragma unroll
  for (int q = 0; q < 10; q++) {
    mw = __vmaxu2(__vmaxu2(wrow[q].x & 0x7fff7fffu, wrow[q].y & 0x7fff7fffu), mw);
    const int e = min(tid + q * 256, 2499), row = e / 25;
    asm volatile("st.shared.v2.u32 [%0],{%1,%2};" :: "r"(sbase + (e + row) * 8), "r"(wrow[q].x), "r"(wrow[q].y) : "memory");
    if (e - row * 25 == 24) asm volatile("st.shared.v2.u32 [%0],{%1,%2};" :: "r"(sbase + (e + row) * 8 + 8), "r"(wrow[q].x), "r"(wrow[q].y) : "memory");
  }
  mbar_wait_fast(fullC, 0);
#pragma unroll
  for (int q = 0; q < 4; q++) { trow[q] = lds128(sbase + 32768 + (tid + q * 256) * 16); me = absmax4(trow[q], me); }
  me = __reduce_max_sync(0xffffffffu, max(me & 0xffff, me >> 16));
  mw = __reduce_max_sync(0xffffffffu, max(mw & 0xffff, mw >> 16));
  uint32_t* sred = (uint32_t*)((char*)sm + 128000);
  if (lane == 0) sred[tid >> 5] = me | mw << 16;
  TS(3, 0);
  asm volatile("bar.sync 1,256;" ::: "memory");
  { uint32_t m = 0;
#pragma unroll
    for (int q = 0; q < 8; q++) m = __vmaxu2(m, sred[q]);
    m = __shfl_sync(0xffffffffu, m, 0);
    me = m & 0xffff; mw = m >> 16; }
  const float se = pow2_scale(me, 3), sW = pow2_scale(mw, -2);
  TS(3, 1);
  auto put_rows = [&](int q, bool on) {
    const uint4 t = trow[q];
    const uint4 hv = make_uint4(pack_h2(bf_lo(t.x) * se, bf_hi(t.x) * se), pack_h2(bf_lo(t.y) * se, bf_hi(t.y) * se),
                                pack_h2(bf_lo(t.z) * se, bf_hi(t.z) * se), pack_h2(bf_lo(t.w) * se, bf_hi(t.w) * se));
    if (on)
#pragma unroll
      for (int s = 0; s < 8; s++) sts128(sbase + (tid + q * 256) * 128 + ((s + lane) & 7) * 16, hv);
  };
#pragma unroll 1
  for (int it = 0; it < 3; it++) {
    const int hu = ((tid >> 5) * 3 + it) * 4, code = hu_code(min(hu + (lane >> 3), HU_N - 1)), ok = code >> 4, on = code & 15;
    uint32_t x[4], y[4];
    asm volatile("ldmatrix.sync.aligned.m8n8.x4.shared.b16 {%0,%1,%2,%3},[%4];" : "=r"(x[0]), "=r"(x[1]), "=r"(x[2]), "=r"(x[3])
                 : "r"(sbase + (on * 8 + (lane & (on == 12 ? 3 : 7))) * 208 + ok * 16) : "memory");
    asm volatile("ldmatrix.sync.aligned.m8n8.x4.trans.shared.b16 {%0,%1,%2,%3},[%4];" : "=r"(y[0]), "=r"(y[1]), "=r"(y[2]), "=r"(y[3])
                 : "r"(sbase + (ok * 8 + (lane & (ok == 12 ? 3 : 7))) * 208 + on * 16) : "memory");
    const uint32_t lo = __ballot_sync(0xffffffffu, ok > on), dg = __ballot_sync(0xffffffffu, ok >= on);
#pragma unroll
    for (int q = 0; q < 4; q++) {
      const float m0 = (lo >> (8 * q)) & 1 ? 0.f : sW, m1 = (dg >> (8 * q)) & 1 ? 0.f : sW;
      asm volatile("st.shared.u32 [%0],%1;" :: "r"(sbase + K1_W + (hu + q) * 128 + lane * 4),
                   "r"(pack_h2(fmaf(bf_lo(x[q]), m0, bf_lo(y[q]) * m1), fmaf(bf_hi(x[q]), m0, bf_hi(y[q]) * m1))) : "memory");
    }
  }
  put_rows(1, true); put_rows(2, tid < 88);
  TS(3, 2);
  asm volatile("fence.proxy.async.shared::cta;" ::: "memory");
  asm volatile("bar.sync 1,256;" ::: "memory");
  put_rows(0, true);
  uint32_t bf[HU_N - 2 * G_U];
#pragma unroll
  for (int q = 0; q < HU_N - 2 * G_U; q++) asm volatile("ld.shared.u32 %0,[%1];" : "=r"(bf[q]) : "r"(sbase + K1_W + (2 * G_U + q) * 128 + lane * 4));
  const float unscale = __uint_as_float(0x7f000000u - __float_as_uint(se)), unscale2 = __uint_as_float(0x7f000000u - __float_as_uint(sW));
  TS(3, 3);
  const int px = range * 16 * 136;
  mbar_wait_fast(fullI, 0);
  {
    const uint32_t ib = sbase + 76800 + (tid >> 5) * 6400, p0 = ib + ((lane >> 3) & 1) * 400 + ((lane >> 4) * 8 + (lane & 7)) * 4;
    auto ld = [&](uint32_t ad) { uint32_t v; asm volatile("ld.shared.u32 %0,[%1];" : "=r"(v) : "r"(ad)); return v; };
    auto wd = [&](int t, int h) { return pk3(ld(p0 + t * 800 + h * 192), ld(p0 + t * 800 + h * 192 + 64), ld(p0 + t * 800 + h * 192 + 128)); };
#pragma unroll
    for (int q = 0; q < 4; q++) {
      iv[q] = make_uint4(wd(2 * q, 0), wd(2 * q, 1), wd(2 * q + 1, 0), wd(2 * q + 1, 1));
      g_scr[PX_OFF + px + slice * 136 + q * 32 + lane] = iv[q];
    }
    ix = pk3(ld(ib + g * 400 + 384 + r * 4), ld(ib + (8 + g) * 400 + 384 + r * 4), 0);
    ((uint32_t*)(g_scr + PX_OFF + px + slice * 136 + 128))[lane] = ix;
  }
  asm volatile("bar.arrive 4,288;" ::: "memory");
  asm volatile("bar.sync 1,256;" ::: "memory");
  put_rows(2, tid >= 88); put_rows(3, tid + 768 < V_);
  asm volatile("bar.sync 1,256;" ::: "memory");
  TS(0, 1);
  uint32_t lc; asm volatile("add.u32 %0,%1,%2;" : "=r"(lc) : "r"((lane & 7) * 16), "r"(never));
  const uint64_t wdesc = (uint64_t)(((sbase + K1_W) & 0x3FFFF) >> 4) | ((uint64_t)(128 >> 4) << 16) | ((uint64_t)(256 >> 4) << 32);
  uint32_t a[2][6][4], d[2][26], ex[4] = {}, s[4] = {};
  float red[4] = {0.f, 0.f, 0.f, 0.f};
  auto ldsm = [&](uint32_t* o, uint32_t sh, uint32_t dep = 0) {
    asm volatile("ldmatrix.sync.aligned.m8n8.x4.trans.shared.b16 {%0,%1,%2,%3},[%4];"
                 : "=r"(o[0]), "=r"(o[1]), "=r"(o[2]), "=r"(o[3]) : "r"(sbase + ((sh & 0x1ff80) | (lc | (dep & never)))));
  };
  auto gather = [&](int t, int hf) {
    const int x = t & 1;
    const uint4 v = iv[(t >> 1) & 3];
#pragma unroll
    for (int kb = 3 * hf; kb < 3 * hf + 3; kb++) {
      const uint32_t ww = x ? (kb < 3 ? v.z : v.w) : (kb < 3 ? v.x : v.y);
      ldsm(a[x][kb], kb % 3 == 0 ? ww : kb % 3 == 1 ? ww >> 10 : __funnelshift_l(ww, ww, 12));
    }
  };
  auto issue = [&](int x) {
    asm volatile("wgmma.fence.sync.aligned;" ::: "memory");
#pragma unroll
    for (int kb = 0; kb < 6; kb++) {
      if (kb < G_K0) wgmma_h<G_N0 * 8>(d[x] + G_O0 * 2, a[x][kb], wdesc + kb * G_N0 * 16, kb);
      if (kb < G_K1) wgmma_h<G_N1 * 8>(d[x] + G_O1 * 2, a[x][kb], wdesc + (G_U1 + kb * G_N1) * 16, kb);
      if (kb < G_K2) wgmma_h<32>(d[x] + G_O2 * 2, a[x][kb], wdesc + (G_U2 + kb * G_N2) * 16, kb);
    }
    asm volatile("wgmma.commit_group.sync.aligned;" ::: "memory");
  };
  auto hmma_part = [&](int t) {
    constexpr FragIdx FI = make_fi();
    const int x = t & 1;
#pragma unroll
    for (int o = 0; o < 13; o++) {
      if (oct_wg(o)) asm volatile("" : "+r"(d[x][o * 2]), "+r"(d[x][o * 2 + 1]) :: "memory"); else d[x][o * 2] = d[x][o * 2 + 1] = 0;
    }
#pragma unroll
    for (int kb = 0; kb < 6; kb++)
#pragma unroll
      for (int o = 2 * kb + 1; o < 13; o++)
        if (!unit_wg(kb, o)) mma16816h(d[x] + o * 2, a[x][kb], bf[FI.v[2 * kb][o]], bf[FI.v[2 * kb + 1][o]]);
#pragma unroll
    for (int q = 0; q < 6; q++) if (!unit_wg(q, 2 * q)) mma1688h(d[x] + q * 4, a[x][q][0], a[x][q][1], bf[FI.v[2 * q][2 * q]]);
    mma1688h(d[x] + 24, r < 2 ? ex[t & 3] : 0u, r < 2 ? 0u : ex[t & 3], bf[FI.v[12][12]]);
  };
  auto dot_part = [&](int t, int hf) {
    const int x = t & 1;
    if (hf == 0) {
      const uint32_t pe = hfma2(r < 2 ? d[x][24] : d[x][25], ex[t & 3], 0u);
      s[0] = r < 2 ? pe : 0u; s[1] = r < 2 ? 0u : pe; s[2] = s[3] = 0;
    }
#pragma unroll
    for (int q = 3 * hf; q < 3 * hf + 3; q++)
#pragma unroll
      for (int e = 0; e < 4; e++) s[e] = hfma2(d[x][q * 4 + e], a[x][q][e], s[e]);
  };
  float* outp = g_partP + slice * B_ + range * 256;
  float k0 = 0.f, k1 = 0.f, x0 = 0.f, x1 = 0.f;
  auto red_stage = [&](int st, int grp) {
    const bool u16 = lane & 16, u8 = lane & 8;
    if (st == 0) {
      k0 = u16 ? red[2] : red[0]; x0 = __shfl_xor_sync(0xffffffffu, u16 ? red[0] : red[2], 16);
      k1 = u16 ? red[3] : red[1]; x1 = __shfl_xor_sync(0xffffffffu, u16 ? red[1] : red[3], 16);
      red[0] = red[1] = red[2] = red[3] = 0.f;
    }
    if (st == 1) { const float p0 = k0 + x0, p1 = k1 + x1; k0 = u8 ? p1 : p0; x0 = __shfl_xor_sync(0xffffffffu, u8 ? p0 : p1, 8); }
    if (st == 2) { k0 += x0; x0 = __shfl_xor_sync(0xffffffffu, k0, 4); }
    if (st == 3 && !(lane & 4)) outp[grp * 16 + r * 4 + ((lane >> 3) & 1) * 2 + (lane >> 4)] = (k0 + x0) * unscale * unscale * unscale2;
  };
  auto group = [&](bool first, int prv, int cur, int nxt) {
    const int pn = PX_OFF + px + nxt * 136 + lane;
#pragma unroll
    for (int t = 0; t < 8; t++) {
      issue((t & 1) ^ 1);
      SCHED_FENCE(never, t * 8);
      if (!first) {
        if (t == 0) { iv[3] = ldtex(tex, PX_OFF + px + cur * 136 + lane + 96); iv[0] = ldtex(tex, pn); }
        if (t == 2) iv[1] = ldtex(tex, pn + 32);
        if (t < 4) red_stage(t, prv);
      } else if (t == 4) {
        TS(4, 2);
        flag_wait(&g_flag[(cta >> 4) * 32], 16);
        TS(4, 3);
        iv[0] = ldtex(tex, pn); iv[1] = ldtex(tex, pn + 32);
      }
      if (t == 4) { ix = ldtex(texX, (px + nxt * 136 + 128) * 4 + lane).x; iv[2] = ldtex(tex, pn + 64); }
      dot_part(t, 0);
      SCHED_FENCE(never, t * 8 + 1);
      if (t == 3) ldsm(ex, ix >> 10);
      if (t == 7) ldsm(ex, ix);
      gather(t + 2, 0);
      dot_part(t, 1);
      SCHED_FENCE(never, t * 8 + 4);
      gather(t + 2, 1);
      asm volatile("wgmma.wait_group.sync.aligned 0;" ::: "memory");
      if (FM & 1) SCHED_FENCE(never, t * 8 + 2);
      asm volatile("" : "+r"(d[(t & 1) ^ 1][0]) :: "memory");
      mma1688f(red, hadd2(s[0], s[2]), hadd2(s[1], s[3]), (g | (d[(t & 1) ^ 1][0] & never)) == t ? 0x3c003c00u : 0u);
      hmma_part(t + 1);
      if (FM & 2) SCHED_FENCE(never, t * 8 + 3);
    }
  };
  gather(0, 0); gather(0, 1); issue(0); ldsm(ex, ix); gather(1, 0); gather(1, 1);
  asm volatile("wgmma.wait_group.sync.aligned 0;" ::: "memory");
  hmma_part(0);
  int prv = slice, cur = slice == 0;
  group(true, 0, prv, cur);
  TS(4, 1);
#pragma unroll 1
  for (int n = 1; n < NGRP; n++) {
    const int nxt = (n + (n >= slice)) & 15;
    if (n == TRIG) asm volatile("griddepcontrol.launch_dependents;");
    if (PXW && tid == 0) mbar_arrive(progG);
    group(false, prv, cur, nxt);
    prv = cur; cur = nxt;
  }
#pragma unroll
  for (int st = 0; st < 4; st++) red_stage(st, prv);
  TS(0, 2);
  asm volatile("barrier.cluster.arrive.relaxed.aligned; barrier.cluster.wait.aligned;" ::: "memory");
}

constexpr int SM_U = 130048, SM_BAR = 128000, SM_J = SM_U + 98304, DEEP_SMEM = SM_J + 4096;

__device__ __forceinline__ void arrive_both(uint32_t bar, int lane) {
  asm volatile("{.reg .pred p; .reg .u32 a; setp.lt.u32 p,%1,2; mapa.shared::cluster.u32 a,%0,%1;\n"
               "@p mbarrier.arrive.shared::cluster.b64 _,[a];}" :: "r"(bar), "r"(lane) : "memory");
}
#define ELECT "{.reg .pred p; elect.sync _|p,0xffffffff; @p "
__device__ __forceinline__ void e_mc(uint32_t dst, const void* src, uint32_t bytes, uint32_t bar, uint64_t pol) {
  asm volatile(ELECT "cp.async.bulk.shared::cluster.global.mbarrier::complete_tx::bytes.multicast::cluster.L2::cache_hint [%0],[%1],%2,[%3],%4,%5;}"
               :: "r"(dst), "l"(src), "r"(bytes), "r"(bar), "h"((unsigned short)3), "l"(pol) : "memory");
}
__device__ __forceinline__ void e_g2s(uint32_t dst, const void* src, uint32_t bytes, uint32_t bar) {
  asm volatile(ELECT "cp.async.bulk.shared::cluster.global.mbarrier::complete_tx::bytes [%0],[%1],%2,[%3];}" :: "r"(dst), "l"(src), "r"(bytes), "r"(bar) : "memory");
}
__device__ __forceinline__ void e_pf(const void* src, uint32_t bytes) { asm volatile(ELECT "cp.async.bulk.prefetch.L2.global [%0],%1;}" :: "l"(src), "r"(bytes) : "memory"); }
__device__ __forceinline__ void e_expect(uint32_t bar, uint32_t bytes) { asm volatile(ELECT "mbarrier.arrive.expect_tx.shared::cta.b64 _,[%0],%1;}" :: "r"(bar), "r"(bytes) : "memory"); }

__global__ void __cluster_dims__(2, 1, 1) __launch_bounds__(TH + 128, 1)
k_deep(cudaTextureObject_t tex, const __nv_bfloat16* __restrict__ w2, const __nv_bfloat16* __restrict__ b2,
       __nv_bfloat16* __restrict__ out, int never) {
  extern __shared__ __align__(1024) uint4 sm[];
  constexpr int PF = DPF, DEPTH = DDEPTH, NW = TH / 32;
  static_assert(YD == 4 && PF == 4, "");
  const int tid = threadIdx.x;
  const int c = blockIdx.x >> 1, half = blockIdx.x & 1;
  const uint32_t sbase = (uint32_t)__cvta_generic_to_shared(sm);
  const uint32_t fullL = sbase + SM_BAR, fullU = fullL + 8, emptyL = fullL + 16, emptyU = fullL + 24, barJ = fullL + 32;
  TS(1, 0);
  if (tid == 0) {
    mbar_init(fullL, 1); mbar_init(fullU, 1); mbar_init(emptyL, 2 * NW); mbar_init(emptyU, 2 * NW); mbar_init(barJ, 1);
    asm volatile("fence.mbarrier_init.release.cluster;" ::: "memory");
  }
  __syncwarp();
  const int wrp = __shfl_sync(0xffffffffu, tid >> 5, 0);
  const char* base = (const char*)g_scr;
  uint32_t oL = (PL_OFF + c * NC * 8000) * 16u + half * 64000, oS = (PS_OFF + c * NC * 2000) * 16u + half * 16000;
  asm volatile("barrier.cluster.arrive.relaxed.aligned;" ::: "memory");
  flag_wait(&g_flag[8 * 32], 132);
  asm volatile("barrier.cluster.wait.aligned;" ::: "memory");
  if (wrp == NW) {
    asm volatile("fence.proxy.async.global;" ::: "memory");
    e_expect(fullU, 96000);
#pragma unroll
    for (int m = 0; m < 3; m++) e_mc(sbase + SM_U + m * 32032 + half * 16000, base + oS, 16000, fullU, m == 2 ? POL_EF : POL_N);
    e_expect(fullL, 128000);
    if (!STAG) e_mc(sbase + half * 64000, base + oL, 64000, fullL, POL_EF);
  }
  TS(5, 1);
  if (wrp >= NW) {
    asm volatile("setmaxnreg.dec.sync.aligned.u32 24;");
    if (wrp == NW) {
      uint32_t oT = (PT_OFF + c * 10 * 1024) * 16u + half * 8192;
      const uint32_t junk = sbase + SM_J, oW = (IX_OFF + half * IXH + ((c + (c >> 4) * 5) & 15) * 512) * 16u;
      auto warm = [&](uint32_t off) {
        asm volatile(ELECT "mbarrier.expect_tx.relaxed.cta.shared::cta.b64 [%0],%1;}" :: "r"(barJ), "r"(8192) : "memory");
        e_g2s(junk, base + off, 4096, barJ); e_g2s(junk, base + off + 4096, 4096, barJ);
      };
      uint32_t t0 = clock();
      if (!PREW) warm(oW);
      if (STAG) { if (STAG == 1) mbar_wait_fast(fullU, 0); else sleep_until(t0, STAG); e_mc(sbase + half * 64000, base + oL, 64000, fullL, POL_EF); }
      warm(oT);
      if (!(PREW & 4)) warm(oW + 131072);
#pragma unroll 1
      for (int k = 0; k + 1 < NC; k++) {
        oL += 128000; oS += 32000; oT += 16384;
        mbar_wait_fast(fullL, k & 1);
        t0 = clock();
        e_pf(base + oS, 16000);
        warm(k + 2 < NC ? oW + (k + 2) * 131072 : (IX_OFF + half * IXH + NC * 8192 + (c & 3) * 512) * 16u);
        mbar_wait_fast(emptyU, k & 1);
        e_expect(fullU, 96000);
#pragma unroll 1
        for (int q = 0; q < 8; q++) {
          sleep_until(t0, q * PACE);
          e_pf(base + oL + q * 8000, 8000);
          if (q >= 2) e_mc(sbase + SM_U + ((q - 2) >> 1) * 32032 + half * 16000 + (q & 1) * 8000, base + oS + (q & 1) * 8000, 8000, fullU, q >= 6 ? POL_EF : POL_N);
        }
        warm(oT);
        e_expect(fullL, 128000);
        mbar_wait_fast(emptyL, k & 1);
        e_mc(sbase + half * 64000, base + oL, 64000, fullL, POL_EF);
      }
      mbar_wait_fast(fullL, (NC - 1) & 1);
      mbar_wait_fast(emptyU, (NC - 1) & 1);
      mbar_arrive_lane0(fullU);
      warm(oT + 16384);
      mbar_arrive_lane0(barJ); mbar_wait_fast(barJ, 0);
    } else if (tid >= TH + 96) {
      if (tid == TH + 96) sts128(barJ + 32, *(const uint4*)(w2 + c * 8));
      asm volatile("bar.arrive 3,%0;" :: "n"(TH + 32) : "memory");
      asm volatile("griddepcontrol.wait;" ::: "memory");
      const int b = half * 8192 + c * 128 + (tid & 31) * 4;
      const float bias = __bfloat162float(b2[0]);
      float4 s = make_float4(bias, bias, bias, bias);
#pragma unroll 2
      for (int k = 0; k < 16; k++) { const float4 v = __ldcg((const float4*)(g_partP + k * B_ + b)); s.x += v.x; s.y += v.y; s.z += v.z; s.w += v.w; }
      asm volatile("red.global.add.v4.f32 [%0],{%1,%2,%3,%4};" :: "l"(g_acc + b), "f"(s.x), "f"(s.y), "f"(s.z), "f"(s.w) : "memory");
      asm volatile("bar.arrive 1,%0;" :: "n"(TH + 32) : "memory");
    }
    return;
  }
  asm volatile("setmaxnreg.inc.sync.aligned.u32 240;");
  const int lane = tid & 31;
  const int tbase = PT_OFF + c * 10 * 1024;
  const int ibase = IX_OFF + half * IXH + tid;
  const uint32_t lc = (tid & 7) << 4;
  uint4 acc[NS], wq[PF], x[DEPTH], y[YD], ye;
  uint32_t sw[NS] = {};
  auto sget = [&](int s) { return (s & 3) == 3 ? __byte_perm(__byte_perm(sw[s - 3], sw[s - 2], 0x0073), sw[s - 1], 0x0710) : sw[s]; };
  auto sa0 = [&](uint32_t v) { return sbase + SM_U + (((v << 5) & 0x1ffe0) | ((lc >> 2) & 16)); };
  auto sa1 = [&](uint32_t v) { return sbase + SM_U + (((v >> 7) & 0x1ffe0) | ((~lc >> 2) & 16)); };
  {
    uint4 i0[8];
#pragma unroll
    for (int q = 0; q < 8; q++) i0[q] = ldtex(tex, I0_OFF + (half * 8 + q) * TH + tid);
#pragma unroll
    for (int i = 0; i < PF; i++) if (!WQL) wq[i] = ldtex(tex, ibase + i * TH);
    auto wd = [&](int k) { return (k & 3) == 0 ? i0[k >> 2].x : (k & 3) == 1 ? i0[k >> 2].y : (k & 3) == 2 ? i0[k >> 2].z : i0[k >> 2].w; };
    TS(5, 2);
    mbar_wait_fast(fullU, 0);
#pragma unroll
    for (int i = 0; i < PF; i++) if (WQL) wq[i] = ldtex(tex, ibase + i * TH);
    TS(1, 1);
#pragma unroll
    for (int s = 0; s < NS; s++) acc[s] = add4(lds128(sa0(wd(s))), lds128(sa1(wd(s))));
    arrive_both(emptyU, lane);
    asm volatile("bar.sync 3,%0;" :: "n"(TH + 32) : "memory");
    TS(5, 3);
  }
#pragma unroll 1
  for (int k = 0; k < NC; k++) {
    const int ti = ibase + k * 8192;
    const int tb = tbase + k * 1024;
    const bool more = k + 1 < NC;
    TR(k * 4);
    if (CBAR & 1) asm volatile("bar.sync 4,%0;" :: "n"(TH) : "memory");
    mbar_wait_fast(fullL, k & 1);
    TR(k * 4 + 2);
    uint4 w, cc; uint32_t yc, yn;
    constexpr int TL = NS * 8, TT = TL + NS * 2;
#pragma unroll
    for (int t = 0; t < TT + DEPTH; t += 2) {
      if (t == TL + DEPTH && !more) break;
      if (t >= DEPTH) {
        const int u = t - DEPTH;
        uint4 p = add4(x[u % DEPTH], x[(u + 1) % DEPTH]);
        if (u < TL) {
          const int s = u >> 3, j = u & 7;
          if (j == 0) {
            cc = s >= YD ? add4(y[s % YD], p) : p;
            if (s + YD < NS) y[s % YD] = ldtex(tex, tb | (yc & 1023));
          } else cc = add4(cc, p);
          if (j == 6) acc[s] = add4(acc[s], cc);
        } else {
          const int s = (u - TL) >> 1;
          acc[s] = add4(acc[s], p);
        }
      }
      if ((CBAR & 4) && t == TL / 2) asm volatile("bar.sync 4,%0;" :: "n"(TH) : "memory");
      if ((CBAR & 8) && t == TL - 40) asm volatile("bar.sync 4,%0;" :: "n"(TH) : "memory");
      if (DEPTH == 8 && (t & 7) == 2) yc = yn;
      if (t < TL) {
        const int s = t >> 3, j = t & 7;
        if (j == 0) {
          if (ye_of(s - YD) >= 0) acc[ye_of(s - YD) & 3] = add4(acc[ye_of(s - YD) & 3], ye);
          w = wq[s % PF];
          if (!EARLY || s < NS - 4) wq[s % PF] = ldtex(tex, ti + (s + PF) * TH);
          else {
            if (s == NS - 4) { wq[0] = ldtex(tex, ti + NS * TH); ye = ldtex(tex, ti + (NS + 3) * TH); }
            if (s == NS - 3) { wq[1] = ldtex(tex, ti + (NS + 1) * TH); y[0] = ldtex(tex, ti + (NS + 2) * TH); }
            if (s == NS - 2) wq[2] = y[0];
            if (s == NS - 1) wq[3] = ye;
          }
          yn = __funnelshift_l(w.z, w.z, 5); if (DEPTH < 8) yc = yn;
          if ((s & 3) != 3) asm volatile("add.u32 %0,%1,%2;" : "=r"(sw[s]) : "r"(w.w), "r"(never));
          if (ye_of(s) >= 0) ye = ldtex(tex, tb | w.w);
        }
#pragma unroll
        for (int jj = j; jj < j + 2; jj++) {
          const uint32_t ww = jj < 3 ? w.x : jj < 6 ? w.y : w.z;
          const uint32_t sh = jj % 3 == 0 ? ww : jj % 3 == 1 ? ww >> 10 : __funnelshift_l(ww, ww, 12);
          x[(t + jj - j) % DEPTH] = lds128(sbase + ((sh & 0x1ff80) | lc) + jj * 16 - 128);
        }
      } else if (t < TT) {
        const int s = (t - TL) >> 1;
        if (s == 0) { arrive_both(emptyL, more ? lane : 9); TR(k * 4 + 3); if (CBAR & 2) asm volatile("bar.sync 4,%0;" :: "n"(TH) : "memory"); mbar_wait_fast(fullU, (k + 1) & 1); }
        const uint32_t sv = sget(s);
        x[t % DEPTH] = lds128(sa0(sv));
        x[(t + 1) % DEPTH] = lds128(sa1(sv));
      } else if (t == TT) arrive_both(emptyU, lane);
      if ((t & (FENCE_N - 1)) == FENCE_N - 2) SCHED_FENCE(never, t);
    }
  }
  TS(1, 2);
  const uint4 w2v = lds128(barJ + 32);
  const uint32_t cell = sbase + SM_U + tid * 16;
  const int t9 = tbase + 9 * 1024;
  uint4 za[4], i9 = wq[0];
  auto fetch = [&](int q) {
    y[0] = ldtex(tex, t9 | i9.x); y[1] = ldtex(tex, t9 | i9.y); y[2] = ldtex(tex, t9 | i9.z); y[3] = ldtex(tex, t9 | i9.w);
    if (q) {
      i9 = ldtex(tex, ibase + NC * 8192 + min(q + 1, 7) * TH);
      const uint32_t ca = cell + (q > 6 ? 0 : q - 1) * 16384;
#pragma unroll
      for (int s = 0; s < 4; s++) za[s] = lds128(ca + s * 4096);
    }
  };
  fetch(0);
  i9 = wq[1];
#pragma unroll
  for (int s = 0; s < 4; s++) za[s] = acc[s];
#pragma unroll
  for (int s = 0; s < 24; s++) sts128(cell + s * 4096, acc[4 + s]);
  float hw[8];
  {
    const uint32_t ww[4] = {w2v.x, w2v.y, w2v.z, w2v.w};
#pragma unroll
    for (int k = 0; k < 8; k++) hw[k] = 0.5f * ((k & 1) ? bf_hi(ww[k >> 1]) : bf_lo(ww[k >> 1]));
  }
  float* outp = g_acc + half * 8192 + tid;
#pragma unroll 1
  for (int q = 0; q < NS / 4; q++) {
    uint4 z[4];
#pragma unroll
    for (int s = 0; s < 4; s++) z[s] = add4(za[s], y[s]);
    if (q == 1) {
#pragma unroll
      for (int s = 0; s < 4; s++) sts128(cell + s * 4096, acc[28 + s]);
    }
    if (q < 7) fetch(q + 1);
    SCHED_FENCE(never, 999);
#pragma unroll
    for (int s = 0; s < 4; s++) {
      const uint32_t a[4] = {z[s].x, z[s].y, z[s].z, z[s].w};
      float r0 = 0.f;
#pragma unroll
      for (int k = 0; k < 8; k++) {
        const float v = (k & 1) ? bf_hi(a[k >> 1]) : bf_lo(a[k >> 1]);
        const float u = v * fmaf(v * v, 0.7978845608028654f * 0.044715f, 0.7978845608028654f);
        float th; asm("tanh.approx.f32 %0,%1;" : "=f"(th) : "f"(u));
        r0 = fmaf(fmaf(v, th, v), hw[k], r0);
      }
      asm volatile("red.global.add.f32 [%0],%1;" :: "l"(outp + s * TH), "f"(r0) : "memory");
    }
    outp += 4 * TH;
  }
  TS(1, 3);
  asm volatile("bar.sync 1,%0;" :: "n"(TH + 32) : "memory");
  if (tid == 0) {
    __threadfence();
    const unsigned old = atomicInc(&g_done[half * 32], 63);
    asm volatile("st.shared.u32 [%0],%1;" :: "r"(barJ + 8), "r"(old) : "memory");
  }
  asm volatile("bar.sync 2,%0;" :: "n"(TH) : "memory");
  uint32_t old; asm volatile("ld.shared.u32 %0,[%1];" : "=r"(old) : "r"(barJ + 8));
  if (old == 63) {
    if (half == 0 && tid < 9) g_flag[tid * 32] = 0;
    __threadfence();
    float4 v[8];
#pragma unroll
    for (int q = 0; q < 8; q++) v[q] = __ldcg((const float4*)(g_acc + half * 8192) + q * TH + tid);
#pragma unroll
    for (int q = 0; q < 8; q++) ((uint2*)(out + half * 8192))[q * TH + tid] = make_uint2(pack_bf2(v[q].x, v[q].y), pack_bf2(v[q].z, v[q].w));
    TS(6, 2);
  }
}

}

extern "C" void kernel_launch(void* const* d_in, const int* in_sizes, int n_in, void* d_out, int out_size) {
  const int* idx = (const int*)d_in[0];
  const __nv_bfloat16* table = (const __nv_bfloat16*)d_in[1];
  const __nv_bfloat16* wp = (const __nv_bfloat16*)d_in[2];
  const __nv_bfloat16* w1 = (const __nv_bfloat16*)d_in[3];
  const __nv_bfloat16* b1 = (const __nv_bfloat16*)d_in[4];
  const __nv_bfloat16* w2 = (const __nv_bfloat16*)d_in[5];
  const __nv_bfloat16* b2 = (const __nv_bfloat16*)d_in[6];
  static cudaTextureObject_t texScr = 0, texG = 0;
  static CUtensorMap mapW, mapL, mapS, mapT, mapE, mapC;
  static const void *c_tab = nullptr, *c_w1 = nullptr;
  if (c_tab != table || c_w1 != w1) {
    c_tab = table; c_w1 = w1;
    char* scr = nullptr; cudaGetSymbolAddress((void**)&scr, g_scr);
    auto mk_tex = [](const void* p, size_t bytes, cudaChannelFormatDesc d) {
      cudaResourceDesc rd = {}; rd.resType = cudaResourceTypeLinear; rd.res.linear.devPtr = (void*)p; rd.res.linear.desc = d; rd.res.linear.sizeInBytes = bytes;
      cudaTextureDesc td = {}; td.readMode = cudaReadModeElementType;
      cudaTextureObject_t t = 0; cudaCreateTextureObject(&t, &rd, &td, nullptr); return t;
    };
    if (!texScr) {
      texScr = mk_tex(scr, (size_t)SCR_N * 16, cudaCreateChannelDesc<uint4>());
      texG = mk_tex(scr + (size_t)PX_OFF * 16, (size_t)(SCR_N - PX_OFF) * 16, cudaCreateChannelDesc<unsigned>());
    }
    typedef CUresult (*EncFn)(CUtensorMap*, CUtensorMapDataType, cuuint32_t, void*, const cuuint64_t*, const cuuint64_t*, const cuuint32_t*,
                              const cuuint32_t*, CUtensorMapInterleave, CUtensorMapSwizzle, CUtensorMapL2promotion, CUtensorMapFloatOOBfill);
    EncFn enc = nullptr; cudaDriverEntryPointQueryResult qr;
    cudaGetDriverEntryPoint("cuTensorMapEncodeTiled", (void**)&enc, cudaEnableDefault, &qr);
    const cuuint32_t ones[4] = {1, 1, 1, 1};
    auto mk = [&](CUtensorMap* m, CUtensorMapDataType dt, int rank, void* p, const cuuint64_t* dim, const cuuint64_t* str, const cuuint32_t* box, CUtensorMapSwizzle sw) {
      enc(m, dt, rank, p, dim, str, box, ones, CU_TENSOR_MAP_INTERLEAVE_NONE, sw, CU_TENSOR_MAP_L2_PROMOTION_NONE, CU_TENSOR_MAP_FLOAT_OOB_FILL_NONE);
    };
    { cuuint64_t dim[2] = {H_, F_ * D_}, str[1] = {H_ * 2}; cuuint32_t box[2] = {32, 256};
      mk(&mapW, CU_TENSOR_MAP_DATA_TYPE_BFLOAT16, 2, (void*)w1, dim, str, box, CU_TENSOR_MAP_SWIZZLE_64B); }
    { cuuint64_t dim[4] = {64, V_, NC, 64}, str[3] = {128, 128000, 128000 * NC}; cuuint32_t box[4] = {32, 64, 1, 4};
      mk(&mapL, CU_TENSOR_MAP_DATA_TYPE_BFLOAT16, 4, scr + (size_t)PL_OFF * 16, dim, str, box, CU_TENSOR_MAP_SWIZZLE_64B); }
    { cuuint64_t dim[4] = {64, V_ / 4, NC, 64}, str[3] = {128, 32000, 32000 * NC}; cuuint32_t box[4] = {64, 16, 1, 4};
      mk(&mapS, CU_TENSOR_MAP_DATA_TYPE_BFLOAT16, 4, scr + (size_t)PS_OFF * 16, dim, str, box, CU_TENSOR_MAP_SWIZZLE_128B); }
    { cuuint64_t dim[3] = {2048, 10, 64}, str[2] = {16384, 163840}; cuuint32_t box[3] = {128, 2, 4};
      mk(&mapT, CU_TENSOR_MAP_DATA_TYPE_UINT64, 3, scr + (size_t)PT_OFF * 16, dim, str, box, CU_TENSOR_MAP_SWIZZLE_NONE); }
    { cuuint64_t dim[2] = {D_, V_}, str[1] = {D_ * 2}; cuuint32_t box[2] = {64, 128};
      mk(&mapE, CU_TENSOR_MAP_DATA_TYPE_BFLOAT16, 2, (void*)table, dim, str, box, CU_TENSOR_MAP_SWIZZLE_128B);
      cuuint32_t box2[2] = {8, 256};
      mk(&mapC, CU_TENSOR_MAP_DATA_TYPE_BFLOAT16, 2, (void*)table, dim, str, box2, CU_TENSOR_MAP_SWIZZLE_NONE); }
    cudaFuncSetAttribute(k_deep, cudaFuncAttributeMaxDynamicSharedMemorySize, DEEP_SMEM);
    cudaFuncSetAttribute(k_tens, cudaFuncAttributeMaxDynamicSharedMemorySize, K1_SMEM);
  }
  k_tens<<<132, 512, K1_SMEM, cudaStreamPerThread>>>(mapW, mapL, mapS, mapT, mapE, mapC, texScr, texG, idx, table, wp, w1, b1, 0);
  cudaLaunchAttribute at[1];
  at[0].id = cudaLaunchAttributeProgrammaticStreamSerialization; at[0].val.programmaticStreamSerializationAllowed = 1;
  cudaLaunchConfig_t cfg = {};
  cfg.stream = cudaStreamPerThread; cfg.attrs = at;
  cfg.gridDim = 128; cfg.blockDim = TH + 128; cfg.dynamicSmemBytes = DEEP_SMEM; cfg.numAttrs = PDL & 1;
  cudaLaunchKernelEx(&cfg, k_deep, texScr, w2, b2, (__nv_bfloat16*)d_out, 0);

}
```

```cpp
#include <cuda_runtime.h>
#include <cuda_bf16.h>
#include <cuda_fp16.h>
#include <stdint.h>
#include <cuda.h>

namespace {

constexpr int B_ = 16384, F_ = 100, D_ = 128, V_ = 1000, H_ = 512;
constexpr int NC = 9;
constexpr int PT_OFF = 0;
constexpr int PL_OFF = 64 * 10 * 1024;
constexpr int PS_OFF = PL_OFF + 64 * NC * 8000;
constexpr int IXH = NC * 8192 + 2048;
constexpr int IX_OFF = PS_OFF + 64 * NC * 2000;
constexpr int I0_OFF = IX_OFF + 2 * IXH;
constexpr int PX_OFF = I0_OFF + 4096;
constexpr int SCR_N = PX_OFF + 64 * 16 * 136;
static_assert(PX_OFF % 32 == 0, "");

__device__ __align__(1024) uint4 g_scr[SCR_N];
__device__ float g_acc[B_];
__device__ unsigned g_done[64];
__device__ float g_partP[16 * B_];
__device__ unsigned g_flag[16 * 32];

#define TS(k, i)
#define TR(slot)
#define PT(slot)

constexpr uint64_t POL_EF = 0x12F0000000000000ull, POL_N = 0x1000000000000000ull;
__device__ __forceinline__ uint32_t addbf2(uint32_t a, uint32_t b) { uint32_t r; asm("add.rn.bf16x2 %0,%1,%2;" : "=r"(r) : "r"(a), "r"(b)); return r; }
__device__ __forceinline__ uint4 add4(const uint4& a, const uint4& b) { return make_uint4(addbf2(a.x, b.x), addbf2(a.y, b.y), addbf2(a.z, b.z), addbf2(a.w, b.w)); }
__device__ __forceinline__ void acc4(uint4& a, const uint4& b, int never) {
  asm("{.reg .pred p; setp.eq.s32 p,%8,0;\n"
      "@p add.rn.bf16x2 %0,%0,%4; @p add.rn.bf16x2 %1,%1,%5; @p add.rn.bf16x2 %2,%2,%6; @p add.rn.bf16x2 %3,%3,%7;}"
      : "+r"(a.x), "+r"(a.y), "+r"(a.z), "+r"(a.w) : "r"(b.x), "r"(b.y), "r"(b.z), "r"(b.w), "r"(never));
}
__device__ __forceinline__ uint4 ldtex(cudaTextureObject_t t, int i) {
  uint4 v; asm volatile("tex.1d.v4.u32.s32 {%0,%1,%2,%3},[%4,{%5}];" : "=r"(v.x), "=r"(v.y), "=r"(v.z), "=r"(v.w) : "l"(t), "r"(i)); return v;
}
__device__ __forceinline__ uint4 lds128(uint32_t a) {
  uint4 v; asm volatile("ld.volatile.shared.v4.u32 {%0,%1,%2,%3},[%4];" : "=r"(v.x), "=r"(v.y), "=r"(v.z), "=r"(v.w) : "r"(a)); return v;
}
__device__ __forceinline__ void sts128(uint32_t a, const uint4& v) {
  asm volatile("st.shared.v4.u32 [%0],{%1,%2,%3,%4};" :: "r"(a), "r"(v.x), "r"(v.y), "r"(v.z), "r"(v.w) : "memory");
}
__device__ __forceinline__ void mbar_init(uint32_t bar, int n) { asm volatile("mbarrier.init.shared::cta.b64 [%0],%1;" :: "r"(bar), "r"(n) : "memory"); }
__device__ __forceinline__ void mbar_wait(uint32_t bar, uint32_t parity) {
  uint32_t ok; int it = 0;
  do { asm volatile("{.reg .pred p; mbarrier.try_wait.parity.shared::cta.b64 p,[%1],%2; selp.u32 %0,1,0,p;}" : "=r"(ok) : "r"(bar), "r"(parity) : "memory"); } while (!ok && ++it < (1 << 19));
}
__device__ __forceinline__ void mbar_expect(uint32_t bar, uint32_t bytes) { asm volatile("mbarrier.arrive.expect_tx.shared::cta.b64 _,[%0],%1;" :: "r"(bar), "r"(bytes) : "memory"); }
__device__ __forceinline__ void bulk_g2s(uint32_t dst, const void* src, uint32_t bytes, uint32_t bar) {
  asm volatile("cp.async.bulk.shared::cluster.global.mbarrier::complete_tx::bytes [%0],[%1],%2,[%3];" :: "r"(dst), "l"(src), "r"(bytes), "r"(bar) : "memory");
}
__device__ __forceinline__ void bulk_pf(const void* src, uint32_t bytes) { asm volatile("cp.async.bulk.prefetch.L2.global [%0],%1;" :: "l"(src), "r"(bytes) : "memory"); }
#define NOMMA 0
#define NGRP 16
#define PDL 1
#define FIN_S 128
#define WR8 0
#define TRIG 14
#define PREW 5
#define PXW 3
#define WQL 1
#define EARLY 1
#define CBAR 0
#define X_SAMEK 0
#define X_SAMEW 0
#define FM 0
#define SWP 1
#define HOLD 1
#define MCW 1
#define TW 1
#define PP0 10
#define PT0 10000
#define PDT 0
#define RPNN "160"
#define RAUX "32"
#define RPRO "160"
#define PARK 0
#define NLOOK 128
#define NEF 16
#define ORD 0
#define WFENCE 0
#define SPLIT 1
#define IORD 3
#define IPF 3
#define IPACE 4500
#define WPF 4
#define QV 3
#define QORD(n) ((n) < 23 ? (n) + 2 : (n) - 23)
#define DYD 4
#define DPF 4
#define DDEPTH 4
#define FENCE_N 4
#define INPL 0
#define STAG 1
#define PACE 800
#define PM4 "pmevent 1; pmevent 2; pmevent 3; pmevent 4;"
#define PMFILL "pmevent 1;"
#define SCHED_FENCE(never, k) asm volatile("{.reg .pred p; setp.ne.u32 p,%0,%1; @p bra.uni SKIP_%=;" PMFILL "SKIP_%=: }" :: "r"(never), "r"(0x7fff0000 + (k)) : "memory")

__global__ void k_prod_naive(const __nv_bfloat16* __restrict__ table, const __nv_bfloat16* __restrict__ w1) {
  __shared__ float t[8][D_];
  int f = blockIdx.y, v0 = blockIdx.x * 8, h = threadIdx.x;
  for (int i = h; i < 8 * D_; i += 512) t[i / D_][i % D_] = __bfloat162float(table[v0 * D_ + i]);
  __syncthreads();
  float s[8] = {0, 0, 0, 0, 0, 0, 0, 0};
  for (int d = 0; d < D_; d++) { float w = __bfloat162float(w1[(size_t)(f * D_ + d) * H_ + h]);
#pragma unroll
    for (int k = 0; k < 8; k++) s[k] += t[k][d] * w; }
  __nv_bfloat16* P = (__nv_bfloat16*)g_scr;
  int c = h >> 3;
  for (int k = 0; k < 8; k++) {
    size_t e = f < 72 ? (size_t)PL_OFF + ((size_t)(c * NC + (f >> 3)) * 1000 + v0 + k) * 8 + (f & 7)
             : f < 90 ? (size_t)PS_OFF + ((size_t)(c * NC + ((f - 72) >> 1)) * 1000 + v0 + k) * 2 + (f & 1)
                      : (size_t)PT_OFF + (size_t)(c * 10 + f - 90) * 1024 + v0 + k;
    P[e * 8 + (h & 7)] = __float2bfloat16(s[k]);
  }
}
__global__ void k_pnn_naive(const int* __restrict__ idx, const __nv_bfloat16* __restrict__ table, const __nv_bfloat16* __restrict__ wp) {
  __shared__ float e[F_][33];
  int b = blockIdx.x, d0 = blockIdx.y * 32, tid = threadIdx.x;
  for (int i = tid; i < F_ * 32; i += 128) e[i >> 5][i & 31] = __bfloat162float(table[idx[b * F_ + (i >> 5)] * D_ + d0 + (i & 31)]);
  __syncthreads();
  float s = 0; int d = tid & 31;
  for (int i = tid >> 5; i < F_; i += 4) { float u = 0; for (int j = 0; j < F_; j++) u += __bfloat162float(wp[i * F_ + j]) * e[j][d]; s += u * e[i][d]; }
  for (int o = 16; o; o >>= 1) s += __shfl_xor_sync(~0u, s, o);
  if (d == 0) g_partP[(blockIdx.y * 4 + (tid >> 5)) * B_ + b] = s;
}
__device__ __forceinline__ void mbar_wait_fast(uint32_t bar, uint32_t parity) {
  asm volatile("{.reg .pred p; .reg .u32 n;\n"
               "mbarrier.try_wait.parity.shared::cta.b64 p,[%0],%1;\n"
               "@p bra DONE_%=;\n"
               "mov.u32 n,0;\n"
               "LOOP_%=: mbarrier.try_wait.parity.shared::cta.b64 p,[%0],%1;\n"
               "add.u32 n,n,1; setp.gt.or.u32 p,n,400000,p;\n"
               "@!p bra LOOP_%=;\n"
               "DONE_%=: }" :: "r"(bar), "r"(parity) : "memory");
}
__device__ __forceinline__ void sleep_until(uint32_t t0, uint32_t dt) { while ((uint32_t)clock() - t0 < dt) __nanosleep(40); }
__device__ __forceinline__ uint32_t s_mask(uint32_t v, int q) { return (1u << ((v + 3 - q) & 3)) | (16u << ((v + 3 + q) & 3)); }
__device__ __forceinline__ uint32_t s_cell(uint32_t v, int q, uint32_t m) {
  const int t = __ffs(~m) - 1;
  const int cp = t == 8 ? q >> 1 : ((t & 4 ? t - q : t + q) - v) & 3;
  return cp * 1001 + v;
}
__device__ __forceinline__ uint32_t pk3(uint32_t a, uint32_t b, uint32_t c) {
  const uint32_t w = c + (a << 12) + (b << 22); return __funnelshift_l(w, w, 27);
}
constexpr int TH = 256, NS = 8192 / TH, YD = DYD;
__host__ __device__ constexpr int ye_of(int s) { return s == 3 ? 0 : s == 11 ? 1 : s == 19 ? 2 : s == 23 ? 3 : -1; }
template <int N> __device__ __forceinline__ void wgmma_h(uint32_t* d, const uint32_t* a, uint64_t desc, int acc);
template <> __device__ __forceinline__ void wgmma_h<64>(uint32_t* d, const uint32_t* a, uint64_t desc, int acc) {
  asm volatile("{.reg .pred p; setp.ne.s32 p,%21,0;\n"
    "wgmma.mma_async.sync.aligned.m64n64k16.f16.f16.f16 {%0,%1,%2,%3,%4,%5,%6,%7,%8,%9,%10,%11,%12,%13,%14,%15},{%16,%17,%18,%19},%20,p,1,1,0;}"
    : "+r"(d[0]),"+r"(d[1]),"+r"(d[2]),"+r"(d[3]),"+r"(d[4]),"+r"(d[5]),"+r"(d[6]),"+r"(d[7]),"+r"(d[8]),"+r"(d[9]),"+r"(d[10]),"+r"(d[11]),"+r"(d[12]),"+r"(d[13]),"+r"(d[14]),"+r"(d[15])
    : "r"(a[0]), "r"(a[1]), "r"(a[2]), "r"(a[3]), "l"(desc), "r"(acc));
}
template <> __device__ __forceinline__ void wgmma_h<56>(uint32_t* d, const uint32_t* a, uint64_t desc, int acc) {
  asm volatile("{.reg .pred p; setp.ne.s32 p,%19,0;\n"
    "wgmma.mma_async.sync.aligned.m64n56k16.f16.f16.f16 {%0,%1,%2,%3,%4,%5,%6,%7,%8,%9,%10,%11,%12,%13},{%14,%15,%16,%17},%18,p,1,1,0;}"
    : "+r"(d[0]),"+r"(d[1]),"+r"(d[2]),"+r"(d[3]),"+r"(d[4]),"+r"(d[5]),"+r"(d[6]),"+r"(d[7]),"+r"(d[8]),"+r"(d[9]),"+r"(d[10]),"+r"(d[11]),"+r"(d[12]),"+r"(d[13])
    : "r"(a[0]), "r"(a[1]), "r"(a[2]), "r"(a[3]), "l"(desc), "r"(acc));
}
template <> __device__ __forceinline__ void wgmma_h<48>(uint32_t* d, const uint32_t* a, uint64_t desc, int acc) {
  asm volatile("{.reg .pred p; setp.ne.s32 p,%17,0;\n"
    "wgmma.mma_async.sync.aligned.m64n48k16.f16.f16.f16 {%0,%1,%2,%3,%4,%5,%6,%7,%8,%9,%10,%11},{%12,%13,%14,%15},%16,p,1,1,0;}"
    : "+r"(d[0]),"+r"(d[1]),"+r"(d[2]),"+r"(d[3]),"+r"(d[4]),"+r"(d[5]),"+r"(d[6]),"+r"(d[7]),"+r"(d[8]),"+r"(d[9]),"+r"(d[10]),"+r"(d[11])
    : "r"(a[0]), "r"(a[1]), "r"(a[2]), "r"(a[3]), "l"(desc), "r"(acc));
}
template <> __device__ __forceinline__ void wgmma_h<40>(uint32_t* d, const uint32_t* a, uint64_t desc, int acc) {
  asm volatile("{.reg .pred p; setp.ne.s32 p,%15,0;\n"
    "wgmma.mma_async.sync.aligned.m64n40k16.f16.f16.f16 {%0,%1,%2,%3,%4,%5,%6,%7,%8,%9},{%10,%11,%12,%13},%14,p,1,1,0;}"
    : "+r"(d[0]),"+r"(d[1]),"+r"(d[2]),"+r"(d[3]),"+r"(d[4]),"+r"(d[5]),"+r"(d[6]),"+r"(d[7]),"+r"(d[8]),"+r"(d[9])
    : "r"(a[0]), "r"(a[1]), "r"(a[2]), "r"(a[3]), "l"(desc), "r"(acc));
}
template <> __device__ __forceinline__ void wgmma_h<32>(uint32_t* d, const uint32_t* a, uint64_t desc, int acc) {
  asm volatile("{.reg .pred p; setp.ne.s32 p,%13,0;\n"
    "wgmma.mma_async.sync.aligned.m64n32k16.f16.f16.f16 {%0,%1,%2,%3,%4,%5,%6,%7},{%8,%9,%10,%11},%12,p,1,1,0;}"
    : "+r"(d[0]),"+r"(d[1]),"+r"(d[2]),"+r"(d[3]),"+r"(d[4]),"+r"(d[5]),"+r"(d[6]),"+r"(d[7])
    : "r"(a[0]), "r"(a[1]), "r"(a[2]), "r"(a[3]), "l"(desc), "r"(acc));
}
__device__ __forceinline__ void wgmma_p(float* d, const uint32_t* a, uint64_t desc, int acc) {
  asm volatile("{.reg .pred p; setp.ne.s32 p,%37,0;\n"
    "wgmma.mma_async.sync.aligned.m64n64k16.f32.bf16.bf16 {%0,%1,%2,%3,%4,%5,%6,%7,%8,%9,%10,%11,%12,%13,%14,%15,%16,%17,%18,%19,%20,%21,%22,%23,%24,%25,%26,%27,%28,%29,%30,%31},{%32,%33,%34,%35},%36,p,1,1,1;}"
    : "+f"(d[0]),"+f"(d[1]),"+f"(d[2]),"+f"(d[3]),"+f"(d[4]),"+f"(d[5]),"+f"(d[6]),"+f"(d[7]),"+f"(d[8]),"+f"(d[9]),"+f"(d[10]),"+f"(d[11]),"+f"(d[12]),"+f"(d[13]),"+f"(d[14]),"+f"(d[15]),"+f"(d[16]),"+f"(d[17]),"+f"(d[18]),"+f"(d[19]),"+f"(d[20]),"+f"(d[21]),"+f"(d[22]),"+f"(d[23]),"+f"(d[24]),"+f"(d[25]),"+f"(d[26]),"+f"(d[27]),"+f"(d[28]),"+f"(d[29]),"+f"(d[30]),"+f"(d[31])
    : "r"(a[0]), "r"(a[1]), "r"(a[2]), "r"(a[3]), "l"(desc), "r"(acc));
}

__device__ __forceinline__ void mma16816h(uint32_t* c, const uint32_t* a, uint32_t b0, uint32_t b1) {
  asm("mma.sync.aligned.m16n8k16.row.col.f16.f16.f16.f16 {%0,%1},{%2,%3,%4,%5},{%6,%7},{%0,%1};"
      : "+r"(c[0]), "+r"(c[1]) : "r"(a[0]), "r"(a[1]), "r"(a[2]), "r"(a[3]), "r"(b0), "r"(b1));
}
__device__ __forceinline__ void mma1688h(uint32_t* c, uint32_t a0, uint32_t a1, uint32_t b) {
  asm("mma.sync.aligned.m16n8k8.row.col.f16.f16.f16.f16 {%0,%1},{%2,%3},{%4},{%0,%1};" : "+r"(c[0]), "+r"(c[1]) : "r"(a0), "r"(a1), "r"(b));
}
__device__ __forceinline__ void mma1688f(float* c, uint32_t a0, uint32_t a1, uint32_t b) {
  asm("mma.sync.aligned.m16n8k8.row.col.f32.f16.f16.f32 {%0,%1,%2,%3},{%4,%5},{%6},{%0,%1,%2,%3};"
      : "+f"(c[0]), "+f"(c[1]), "+f"(c[2]), "+f"(c[3]) : "r"(a0), "r"(a1), "r"(b));
}
__device__ __forceinline__ uint32_t hadd2(uint32_t a, uint32_t b) { uint32_t r; asm("add.rn.f16x2 %0,%1,%2;" : "=r"(r) : "r"(a), "r"(b)); return r; }
__device__ __forceinline__ uint32_t hfma2(uint32_t a, uint32_t b, uint32_t c) { uint32_t r; asm("fma.rn.f16x2 %0,%1,%2,%3;" : "=r"(r) : "r"(a), "r"(b), "r"(c)); return r; }
__device__ __forceinline__ uint32_t pack_bf2(float lo, float hi) { uint32_t r; asm("cvt.rn.bf16x2.f32 %0,%1,%2;" : "=r"(r) : "f"(hi), "f"(lo)); return r; }
__device__ __forceinline__ uint32_t pack_h2(float lo, float hi) { uint32_t r; asm("cvt.rn.f16x2.f32 %0,%1,%2;" : "=r"(r) : "f"(hi), "f"(lo)); return r; }
__device__ __forceinline__ float bf_lo(uint32_t w) { return __uint_as_float(w << 16); }
__device__ __forceinline__ float bf_hi(uint32_t w) { return __uint_as_float(w & 0xffff0000u); }
__device__ __forceinline__ uint32_t absmax4(const uint4& v, uint32_t m) {
  return __vmaxu2(__vmaxu2(__vmaxu2(v.x & 0x7fff7fffu, v.y & 0x7fff7fffu), __vmaxu2(v.z & 0x7fff7fffu, v.w & 0x7fff7fffu)), m);
}
__device__ __forceinline__ float pow2_scale(uint32_t mbits, int p) { return __uint_as_float((uint32_t)min(max(253 + p - (int)(mbits >> 7), 2), 252) << 23); }

#define PV 4
constexpr int G_O0 = 8, G_O1 = 4, G_O2 = 0, G_N0 = 5, G_N1 = 4, G_N2 = 4, G_K0 = 5, G_K1 = 3, G_K2 = 1;
__host__ __device__ constexpr bool unit_wg(int kb, int on) {
  return (on >= G_O0 && on < G_O0 + G_N0 && kb < G_K0) || (on >= G_O1 && on < G_O1 + G_N1 && kb < G_K1) || (on >= G_O2 && on < G_O2 + G_N2 && kb < G_K2);
}
__host__ __device__ constexpr bool oct_wg(int on) { return unit_wg(0, on); }
constexpr int G_U1 = G_N0 * G_K0, G_U2 = G_U1 + G_N1 * G_K1, G_U = G_U2 + G_N2 * G_K2;
constexpr int K1_B = 130048, K1_STG = K1_B + 3 * 16384, K1_W = K1_STG + 2 * 16384, K1_BAR = K1_W + 48 * 256, K1_SMEM = K1_BAR + 256 + 4352;
__host__ __device__ constexpr int frag_index(int ok, int on) {
  int n = 0;
  for (int k = 0; k < 13; k++) for (int o = k; o < 13; o++) { if (k == ok && o == on) return n; if (!unit_wg(k >> 1, o)) n++; }
  return n;
}
constexpr int HU_N = 2 * G_U + frag_index(99, 99);
static_assert(HU_N <= 96, "");
struct FragIdx { int v[13][13]; };
__host__ __device__ constexpr FragIdx make_fi() { FragIdx f = {}; for (int k = 0; k < 13; k++) for (int o = 0; o < 13; o++) f.v[k][o] = frag_index(k, o); return f; }
__host__ __device__ constexpr uint64_t frag_tab(int first) {
  uint64_t t = 0;
  for (int k = 0; k < 13; k++) for (int o = k; o < 13; o++)
    if (!unit_wg(k >> 1, o)) { const int n = frag_index(k, o) - first; if (n >= 0 && n < 8) t |= (uint64_t)(k << 4 | o) << (8 * n); }
  return t;
}
__device__ __forceinline__ int hu_code(int hu) {
  constexpr uint64_t T0 = frag_tab(0), T1 = frag_tab(8), T2 = frag_tab(16), T3 = frag_tab(24);
  const int u = hu >> 1, f = hu - 2 * G_U;
  if (f >= 0) return (int)((f < 8 ? T0 : f < 16 ? T1 : f < 24 ? T2 : T3) >> (8 * (f & 7))) & 255;
  const int u0 = u < G_U1 ? u : u < G_U2 ? u - G_U1 : u - G_U2;
  const int kb = u < G_U1 ? u0 / G_N0 : u < G_U2 ? u0 / G_N1 : u0 / 4, on = u < G_U1 ? G_O0 + u0 % G_N0 : u < G_U2 ? G_O1 + u0 % G_N1 : G_O2 + u0 % 4;
  return (2 * kb + (hu & 1)) << 4 | on;
}

__device__ __forceinline__ void flag_arrive(unsigned* f, int lane) {
  __threadfence(); __syncwarp();
  if (lane == 0) asm volatile("red.release.gpu.global.add.u32 [%0],1;" :: "l"(f) : "memory");
}
__device__ __forceinline__ void flag_wait(const unsigned* f, unsigned n) {
  unsigned v; int it = 0;
  asm volatile("ld.acquire.gpu.global.u32 %0,[%1];" : "=r"(v) : "l"(f) : "memory");
  if (v < n) {
    do { __nanosleep(300); asm volatile("ld.relaxed.gpu.global.u32 %0,[%1];" : "=r"(v) : "l"(f) : "memory"); } while (v < n && ++it < (1 << 20));
    asm volatile("ld.acquire.gpu.global.u32 %0,[%1];" : "=r"(v) : "l"(f) : "memory");
  }
}
__device__ __forceinline__ void mbar_arrive(uint32_t bar) { asm volatile("mbarrier.arrive.shared::cta.b64 _,[%0];" :: "r"(bar) : "memory"); }
__device__ __forceinline__ void mbar_arrive_lane0(uint32_t bar) {
  asm volatile("{.reg .pred p; elect.sync _|p,0xffffffff; @p mbarrier.arrive.shared::cta.b64 _,[%0];}" :: "r"(bar) : "memory");
}

__device__ __forceinline__ void arrive_both(uint32_t bar, int lane) {
  asm volatile("{.reg .pred p; .reg .u32 a; setp.lt.u32 p,%1,2; mapa.shared::cluster.u32 a,%0,%1;\n"
               "@p mbarrier.arrive.shared::cluster.b64 _,[a];}" :: "r"(bar), "r"(lane) : "memory");
}
__device__ __forceinline__ void pack_role(const int* __restrict__ idx, uint32_t sbase, int pc) {
  constexpr int CH = 3200 + 32, BUF = 32 * 3328;
  const int tid = threadIdx.x, lane = tid & 31, warp = tid >> 5;
  const uint32_t full = sbase + 2 * BUF, empty = full + 16;
  if (tid == 0) { mbar_init(full, 1); mbar_init(full + 8, 1); mbar_init(empty, 18); mbar_init(empty + 8, 18); asm volatile("fence.proxy.async.shared::cta;" ::: "memory"); }
  __syncthreads();
  auto chunk = [&](int s) { return s * 3200 + (s >> 2) * 288; };
  auto load = [&](int n) {
    const int blk = pc * 16 + n;
    if (lane == 0) mbar_expect(full + (n & 1) * 8, 32 * 3200);
    __syncwarp();
    bulk_g2s(sbase + (n & 1) * BUF + chunk(lane), idx + ((blk >> 5) * 8192 + lane * TH + (blk & 31) * 8) * F_, 3200, full + (n & 1) * 8);
  };
  if (warp == 0) { load(0); load(1); }
  const int l = lane & 7;
  uint32_t rot[8], inc[3];
#pragma unroll
  for (int jj = 0; jj < 8; jj++) rot[jj] = ((l + jj) & 7) * 4;
#pragma unroll
  for (int q = 0; q < 3; q++) inc[q] = (l + 3 * q < 8) << 12 | (l + 3 * q + 1 < 8) << 22 | (q < 2 && l + 3 * q + 2 < 8);
  int loaded = 2;
#pragma unroll 1
  for (int task = warp; task < 288; task += 16) {
    const int n = task / 18, q = (task % 18) * 4 + (lane >> 3), sq = q / 9, k = q % 9;
    if (warp == 0 && n + 1 == loaded && loaded < 16) { mbar_wait(empty + (loaded & 1) * 8, ((loaded >> 1) - 1) & 1); load(loaded); loaded++; }
    mbar_wait(full + (n & 1) * 8, (n >> 1) & 1);
    const uint32_t buf = sbase + (n & 1) * BUF + l * 400, row = buf + chunk(sq * 4);
    auto ld = [&](uint32_t ad) { uint32_t v; asm volatile("ld.shared.u32 %0,[%1];" : "=r"(v) : "r"(ad)); return v; };
    const int blk = pc * 16 + n, half = blk >> 5, col = (blk & 31) * 8 + l;
    const int ks = k == NC - 1 ? 0 : k + 1;
    uint32_t cw[4], sv[8], m[2] = {0, 0};
    { const uint32_t a0 = row + (72 + 2 * ks + (l >> 2)) * 4;
#pragma unroll
      for (int u = 0; u < 8; u++) { sv[u] = ld((a0 ^ ((u >> 2) * 4)) + (u & 3) * 3200); m[u >> 2] |= s_mask(sv[u], l & 3) << (8 * (u & 3)); } }
#pragma unroll
    for (int h = 0; h < 2; h++) { m[h] |= __shfl_xor_sync(0xffffffffu, m[h], 1); m[h] |= __shfl_xor_sync(0xffffffffu, m[h], 2); }
#pragma unroll
    for (int u = 0; u < 4; u++) cw[u] = s_cell(sv[u], l & 3, (m[0] >> (8 * u)) & 255) | s_cell(sv[4 + u], l & 3, (m[1] >> (8 * u)) & 255) << 12;
    if (k == NC - 1) {
      g_scr[I0_OFF + (half * 8 + sq) * TH + col] = make_uint4(cw[0], cw[1], cw[2], cw[3]);
      g_scr[IX_OFF + half * IXH + NC * 8192 + sq * TH + col] = make_uint4(ld(row + 396), ld(row + 3596), ld(row + 6796), ld(row + 9996));
      cw[0] = cw[1] = cw[2] = cw[3] = 0;
    }
    const uint32_t ax = buf + chunk(min(sq + 1, 7) * 4) + (90 + k) * 4;
    const uint32_t yev = ld(buf + ((0x3210 >> (sq * 2 + (sq == 5) * 2)) & 3) * 3200 + (90 + k) * 4);
    uint4* dst = g_scr + IX_OFF + half * IXH + (k * NS + sq * 4) * TH + col;
#pragma unroll
    for (int u = 0; u < 4; u++) {
      uint32_t e[8];
#pragma unroll
      for (int jj = 0; jj < 8; jj++) e[jj] = ld(row + k * 32 + rot[jj] + u * 3200);
      dst[u * TH] = make_uint4(pk3(e[0], e[1], e[2] + inc[0]), pk3(e[3], e[4], e[5] + inc[1]), pk3(e[6], e[7], ld(ax + u * 3200) + inc[2]),
                               u < 3 ? __byte_perm(cw[u], cw[3], 0x4210 + (u << 12)) : yev);
    }
    mbar_arrive_lane0(empty + (n & 1) * 8);
  }
  (void)CH;
}

__global__ void __cluster_dims__(2, 1, 1) __launch_bounds__(512, 1)
k_tens(const __grid_constant__ CUtensorMap mapW, const __grid_constant__ CUtensorMap mapL, const __grid_constant__ CUtensorMap mapS,
       const __grid_constant__ CUtensorMap mapT, const __grid_constant__ CUtensorMap mapE, const __grid_constant__ CUtensorMap mapC, cudaTextureObject_t tex, cudaTextureObject_t texX,
       const int* __restrict__ idx, const __nv_bfloat16* __restrict__ table, const __nv_bfloat16* __restrict__ wp, const __nv_bfloat16* __restrict__ w1,
       const __nv_bfloat16* __restrict__ b1, int never) {
  extern __shared__ __align__(1024) uint4 sm[];
  const int tid = threadIdx.x, lane = tid & 31, cta = blockIdx.x;
  const uint32_t sbase = (uint32_t)__cvta_generic_to_shared(sm);
  const int g = lane >> 2, r = lane & 3;
  TS(0, 0);
  if (cta >= 128) {
    pack_role(idx, sbase, cta - 128);
    __syncthreads();
    if (tid < 32) flag_arrive(&g_flag[8 * 32], lane);
    TS(2, 1);
    asm volatile("barrier.cluster.arrive.relaxed.aligned; barrier.cluster.wait.aligned;" ::: "memory");
    return;
  }
  const uint32_t fullB = sbase + K1_BAR, emptyB = fullB + 24, fullE = fullB + 48, fullC = fullB + 56, fullI = fullB + 64, fullX = fullB + 72, progG = fullB + 80, fullS = fullB + 96, emptyS = fullB + 128;
  const int rb = cta & 7, hc = cta >> 3;
  auto uq = [&](int q) { return SWP && q < 18 ? (q & ~1) | (hc & 1) : q; };
  auto uh = [&](int q) { return SWP && q < 18 ? (hc & ~1) | (q & 1) : hc; };
  if (MCW && (tid >> 5) != 12) asm volatile("barrier.cluster.arrive.relaxed.aligned;" ::: "memory");
  if (tid >= 384) {
    asm volatile("setmaxnreg.dec.sync.aligned.u32 " RAUX ";");
    if (tid < 416) {
      auto load_pair = [&](int p, int st) {
        mbar_expect(fullB + st * 8, 16384);
        asm volatile("cp.async.bulk.tensor.2d.shared::cluster.global.mbarrier::complete_tx::bytes.multicast::cluster [%0],[%1,{%2,%3}],[%4],%5;"
                     :: "r"(sbase + K1_B + st * 16384 + (cta & 1) * 8192), "l"(&mapW), "r"(uh(QORD(p >> 1)) * 32),
                        "r"(uq(QORD(p >> 1)) * 512 + (p & 1) * 256 + (cta & 1) * 128), "r"(fullB + st * 8), "h"((unsigned short)3) : "memory");
        p += WPF;
        if (p < 50) {
          int pr = QORD(p >> 1) * 2 + (p & 1);
          if (SWP && pr < 36) pr = (pr & ~3) | ((pr & 1) << 1) | ((pr >> 1) & 1);
          bulk_pf(w1 + pr * 131072 + cta * 1024, 2048);
        }
      };
      if (tid == 384) {
        for (int q = 0; q < 3; q++) { mbar_init(fullB + q * 8, 1); mbar_init(emptyB + q * 8, MCW ? 8 : 4); }
        for (int q = 0; q < 4; q++) { mbar_init(fullS + q * 8, 4); mbar_init(emptyS + q * 8, 1); }
        mbar_init(fullE, 1); mbar_init(fullC, 1); mbar_init(fullI, 1); mbar_init(fullX, 1); mbar_init(progG, 1);
        asm volatile("fence.proxy.async.shared::cta;" ::: "memory");
        mbar_expect(fullC, 16384);
        for (int q = 0; q < 4; q++)
          asm volatile("cp.async.bulk.tensor.2d.shared::cluster.global.mbarrier::complete_tx::bytes [%0],[%1,{%2,%3}],[%4];"
                       :: "r"(sbase + 32768 + q * 4096), "l"(&mapC), "r"((cta & 15) * 8), "r"(q * 256), "r"(fullC) : "memory");
        mbar_expect(fullE, 32768);
        for (int q = 0; q < 2; q++)
          asm volatile("cp.async.bulk.tensor.2d.shared::cluster.global.mbarrier::complete_tx::bytes [%0],[%1,{%2,%3}],[%4];"
                       :: "r"(sbase + K1_STG + q * 16384), "l"(&mapE), "r"(q * 64), "r"(rb * 128), "r"(fullE) : "memory");
      }
      __syncwarp();
      asm volatile("bar.arrive 2,448;" ::: "memory");
      if (MCW) asm volatile("fence.mbarrier_init.release.cluster; barrier.cluster.arrive.relaxed.aligned; barrier.cluster.wait.aligned;" ::: "memory");
      if (tid == 384) {
        int st = 0, ph = 1;
        const uint32_t tl0 = clock();
#pragma unroll 1
        for (int p = 0; p < 50; p++) {
          if (p == IORD) {
            mbar_expect(fullI, 51200);
#pragma unroll 1
            for (int q = 0; q < 8; q++) bulk_g2s(sbase + 76800 + q * 6400, idx + (((cta >> 4) * 8 + q) * 256 + (cta & 15) * 16) * F_, 6400, fullI);
          }
          if (PDT && p > PP0) sleep_until(tl0, PT0 + (p - PP0) * PDT);
          mbar_wait(emptyB + st * 8, ph);
          load_pair(p, st);
          if (++st == 3) { st = 0; ph ^= 1; }
        }
      }
    } else if (tid < 448) {
      ((float4*)g_acc)[cta * 32 + lane] = make_float4(0.f, 0.f, 0.f, 0.f);
      asm volatile("bar.sync 2,448;" ::: "memory");
      if (HOLD) { asm volatile("bar.sync 4,288;" ::: "memory"); flag_arrive(&g_flag[(cta >> 4) * 32], lane); }
      __syncwarp();
      if (tid == 416) {
#pragma unroll 1
        for (int n = 0; n < 50; n++) {
          const int quad = QORD(n >> 1), mt = n & 1, v0 = rb * 128 + mt * 64;
          const uint32_t stg = sbase + K1_STG + mt * 16384;
          const uint64_t pol = n < 2 * NEF ? POL_EF : POL_N;
          mbar_wait(fullS + mt * 8, (n >> 1) & 1);
          asm volatile("fence.proxy.async.shared::cta;" ::: "memory");
          if (quad < 18) {
            asm volatile("cp.async.bulk.tensor.4d.global.shared::cta.bulk_group.L2::cache_hint [%0,{%1,%2,%3,%4}],[%5],%6;"
                         :: "l"(&mapL), "r"((uq(quad) & 1) * 32), "r"(v0), "r"(quad >> 1), "r"(uh(quad) * 4), "r"(stg), "l"(pol) : "memory");
          } else {
#pragma unroll 1
            for (int hh = 0; hh < 2; hh++) {
              const int pq = quad * 2 + hh;
              if (pq < 45) asm volatile("cp.async.bulk.tensor.4d.global.shared::cta.bulk_group.L2::cache_hint [%0,{%1,%2,%3,%4}],[%5],%6;"
                         :: "l"(&mapS), "r"(0), "r"(v0 >> 2), "r"(pq - 36), "r"(hc * 4), "r"(stg + hh * 8192), "l"(pol) : "memory");
              else asm volatile("cp.async.bulk.tensor.3d.global.shared::cta.bulk_group.L2::cache_hint [%0,{%1,%2,%3}],[%4],%5;"
                         :: "l"(&mapT), "r"(v0 * 2), "r"((pq - 45) * 2), "r"(hc * 4), "r"(stg + hh * 8192), "l"(pol) : "memory");
            }
          }
          asm volatile("cp.async.bulk.commit_group;" ::: "memory");
          asm volatile("cp.async.bulk.wait_group.read 0;" ::: "memory");
          mbar_arrive(emptyS + mt * 8);
        }
        asm volatile("cp.async.bulk.wait_group 0;" ::: "memory");
        asm volatile("fence.proxy.async.global;" ::: "memory");
        __threadfence();
        asm volatile("red.release.gpu.global.add.u32 [%0],1;" :: "l"(&g_flag[8 * 32]) : "memory");
        flag_wait(&g_flag[8 * 32], 132);
        asm volatile("fence.proxy.async.global;" ::: "memory");
        const char* base = (const char*)g_scr;
        const int c = cta >> 1, half = cta & 1, ch = (c + (c >> 4) * 5) & 15;
        bulk_pf(base + (PS_OFF + c * NC * 2000) * 16u + half * 16000, 16000);
        if (PREW & 2) bulk_pf(base + (PL_OFF + c * NC * 8000) * 16u + half * 64000, 64000);
        bulk_pf(base + (PT_OFF + c * 10 * 1024) * 16u + half * 8192, 8192);
        mbar_expect(fullE, 18432);
        bulk_g2s(sbase + K1_STG, base + (I0_OFF + half * 2048 + ch * 128) * 16u, 2048, fullE);
        bulk_g2s(sbase + K1_STG + 2048, base + (IX_OFF + half * IXH + ch * 512) * 16u, 8192, fullE);
        bulk_g2s(sbase + K1_STG + 10240, base + (IX_OFF + half * IXH + 8192 + ch * 512) * 16u, 8192, fullE);
        mbar_wait(fullE, 1);
      }
    } else if (tid >= 480) {
      if (!HOLD) { asm volatile("bar.sync 4,288;" ::: "memory"); flag_arrive(&g_flag[(cta >> 4) * 32], lane); }
    } else if (tid == 448 && PXW) {
      flag_wait(&g_flag[(cta >> 4) * 32], 16);
      asm volatile("fence.proxy.async.global;" ::: "memory");
      const char* src = (const char*)(g_scr + PX_OFF + ((cta >> 4) * 8 + ((cta >> 1) & 3) * 2) * 16 * 136);
#pragma unroll 1
      for (int n = 1; n < 16; n++) {
        if (n >= PXW) mbar_wait(progG, (n - PXW) & 1);
        mbar_expect(fullX, 4352);
        bulk_g2s(sbase + K1_BAR + 256, src + n * 2176, 2176, fullX);
        bulk_g2s(sbase + K1_BAR + 256 + 2176, src + (16 + n) * 2176, 2176, fullX);
        mbar_wait(fullX, (n - 1) & 1);
      }
    }
    return;
  }
  if (tid >= 256) {
    asm volatile("setmaxnreg.inc.sync.aligned.u32 " RPRO ";");
    const int w = (tid >> 5) & 3;
    const int srow = w * 16 + (lane & 7) + ((lane >> 3) & 1) * 8, sc = lane >> 4;
    uint32_t a[2][8][4];
    asm volatile("bar.sync 2,448;" ::: "memory");
    mbar_wait_fast(fullE, 0);
#pragma unroll
    for (int mt = 0; mt < 2; mt++)
#pragma unroll
      for (int ks = 0; ks < 8; ks++)
        asm volatile("ldmatrix.sync.aligned.m8n8.x4.shared.b16 {%0,%1,%2,%3},[%4];"
                     : "=r"(a[mt][ks][0]), "=r"(a[mt][ks][1]), "=r"(a[mt][ks][2]), "=r"(a[mt][ks][3])
                     : "r"(sbase + K1_STG + (ks >> 2) * 16384 + (mt * 64 + srow) * 128 + ((((ks & 3) * 2 + sc) ^ (lane & 7)) * 16)) : "memory");
    asm volatile("bar.sync 5,128;" ::: "memory");
    const uint32_t baseL = sc * 4096 + srow * 64 + ((srow >> 1) & 3) * 16, baseS = sc * 2048 + ((srow * 32) ^ (((srow >> 2) & 7) * 16)), baseT = sc * 2048 + srow * 16;
    const uint64_t desc0 = (uint64_t)(((sbase + K1_B) & 0x3FFFF) >> 4) | ((uint64_t)(8192 >> 4) << 16) | ((uint64_t)(512 >> 4) << 32) | (2ull << 62);
    float d[2][32];
    auto issue = [&](int x, int mt, int st) {
      uint32_t a7[4];
#pragma unroll
      for (int e = 0; e < 4; e++) { if (PARK) asm volatile("add.u32 %0,%1,%2;" : "=r"(a7[e]) : "r"(a[mt][7][e]), "r"(never)); else a7[e] = a[mt][7][e]; }
      asm volatile("wgmma.fence.sync.aligned;" ::: "memory");
#pragma unroll
      for (int ks = 0; ks < 8; ks++) wgmma_p(d[x], ks < 7 ? a[mt][ks] : a7, desc0 + st * 1024 + ks * 64, ks);
      asm volatile("wgmma.commit_group.sync.aligned;" ::: "memory");
    };
    auto wait_acc = [&](int x) {
      asm volatile("wgmma.wait_group.sync.aligned 0;" ::: "memory");
#pragma unroll
      for (int q = 0; q < 8; q++) asm volatile("" : "+f"(d[x][q * 4]), "+f"(d[x][q * 4 + 1]), "+f"(d[x][q * 4 + 2]), "+f"(d[x][q * 4 + 3]) :: "memory");
    };
    mbar_wait_fast(fullB, 0);
    issue(0, 0, 0);
    int s0 = 0, ph = 0;
#pragma unroll 1
    for (int qn = 0; qn < 25; qn++) {
      const int quad = QORD(qn);
      const int s1 = s0 == 2 ? 0 : s0 + 1, s2 = s1 == 2 ? 0 : s1 + 1, ph1 = ph ^ (s1 == 0), ph2 = ph1 ^ (s2 == 0);
#pragma unroll
      for (int step = 0; step < 4; step++) {
        const int mt = ORD ? step & 1 : step >> 1, h = ORD ? step >> 1 : step & 1, x = step & 1, nx = (step + 1) & 3;
        const bool isL = quad < 18, isS = quad * 2 + h < 45;
        const uint32_t base = (isL ? baseL ^ (h * 32) : (isS ? baseS : baseT) ^ (h * 8192)), xj = (isL || isS) ? 16 : 1024, xc = isL ? 8192 : 4096;
        PT(qn * 16 + step * 4);
        if (h == 0) mbar_wait_fast(emptyS + mt * 8, (qn & 1) ^ 1);
        if (step == (ORD ? 1 : 0)) mbar_wait_fast(fullB + s1 * 8, ph1);
        if (step == 3) mbar_wait_fast(fullB + s2 * 8, qn == 24 ? ph2 ^ 1 : ph2);
        PT(qn * 16 + step * 4 + 1);
        wait_acc(x);
        PT(qn * 16 + step * 4 + 2);
        if (mt) { if (MCW) arrive_both(emptyB + (h ? s1 : s0) * 8, 2 * qn + h < 47 ? lane : 9); else mbar_arrive_lane0(emptyB + (h ? s1 : s0) * 8); }
        issue(x ^ 1, ORD ? nx & 1 : nx >> 1, step == 3 ? s2 : (ORD ? nx >> 1 : nx & 1) ? s1 : s0);
        PT(qn * 16 + step * 4 + 3);
        if (h && quad == 24) {
#pragma unroll
          for (int cq = 0; cq < 4; cq++) {
            const uint32_t bw = __ldg((const uint32_t*)(b1 + hc * 32 + cq * 8) + r);
#pragma unroll
            for (int e = 0; e < 4; e++) d[x][16 + cq * 4 + e] += (e & 1) ? bf_hi(bw) : bf_lo(bw);
          }
        }
#pragma unroll
        for (int e4 = 0; e4 < 4; e4++) {
          const float* e = d[x] + e4 * 8;
          asm volatile("stmatrix.sync.aligned.m8n8.x4.shared.b16 [%0],{%1,%2,%3,%4};"
                       :: "r"(sbase + K1_STG + mt * 16384 + (base ^ ((e4 >> 1) * xj) ^ ((e4 & 1) * xc))),
                          "r"(pack_bf2(e[0], e[1])), "r"(pack_bf2(e[2], e[3])), "r"(pack_bf2(e[4], e[5])), "r"(pack_bf2(e[6], e[7])) : "memory");
        }
        if (h) { __syncwarp(); mbar_arrive_lane0(fullS + mt * 8); }
      }
      s0 = s2; ph = ph2;
    }
    asm volatile("wgmma.wait_group.sync.aligned 0;" ::: "memory");
    return;
  }
  asm volatile("setmaxnreg.inc.sync.aligned.u32 " RPNN ";");
  const int slice = cta & 15;
  const int range = (cta >> 4) * 8 + __shfl_sync(0xffffffffu, tid >> 5, 0);
  uint4 iv[4], trow[4]; uint32_t ix;
  uint2 wrow[10];
#pragma unroll
  for (int q = 0; q < 10; q++) asm volatile("ld.global.nc.v2.u32 {%0,%1},[%2];" : "=r"(wrow[q].x), "=r"(wrow[q].y) : "l"((const uint2*)wp + min(tid + q * 256, 2499)));
  asm volatile("bar.sync 2,448;" ::: "memory");
  uint32_t me = 0, mw = 0;
#pragma unroll
  for (int q = 0; q < 10; q++) {
    mw = __vmaxu2(__vmaxu2(wrow[q].x & 0x7fff7fffu, wrow[q].y & 0x7fff7fffu), mw);
    const int e = min(tid + q * 256, 2499), row = e / 25;
    asm volatile("st.shared.v2.u32 [%0],{%1,%2};" :: "r"(sbase + (e + row) * 8), "r"(wrow[q].x), "r"(wrow[q].y) : "memory");
    if (e - row * 25 == 24) asm volatile("st.shared.v2.u32 [%0],{%1,%2};" :: "r"(sbase + (e + row) * 8 + 8), "r"(wrow[q].x), "r"(wrow[q].y) : "memory");
  }
  mbar_wait_fast(fullC, 0);
#pragma unroll
  for (int q = 0; q < 4; q++) { trow[q] = lds128(sbase + 32768 + (tid + q * 256) * 16); me = absmax4(trow[q], me); }
  me = __reduce_max_sync(0xffffffffu, max(me & 0xffff, me >> 16));
  mw = __reduce_max_sync(0xffffffffu, max(mw & 0xffff, mw >> 16));
  uint32_t* sred = (uint32_t*)((char*)sm + 128000);
  if (lane == 0) sred[tid >> 5] = me | mw << 16;
  TS(3, 0);
  asm volatile("bar.sync 1,256;" ::: "memory");
  { uint32_t m = 0;
#pragma unroll
    for (int q = 0; q < 8; q++) m = __vmaxu2(m, sred[q]);
    m = __shfl_sync(0xffffffffu, m, 0);
    me = m & 0xffff; mw = m >> 16; }
  const float se = pow2_scale(me, 3), sW = pow2_scale(mw, -2);
  TS(3, 1);
  auto put_rows = [&](int q, bool on) {
    const uint4 t = trow[q];
    const uint4 hv = make_uint4(pack_h2(bf_lo(t.x) * se, bf_hi(t.x) * se), pack_h2(bf_lo(t.y) * se, bf_hi(t.y) * se),
                                pack_h2(bf_lo(t.z) * se, bf_hi(t.z) * se), pack_h2(bf_lo(t.w) * se, bf_hi(t.w) * se));
    if (on)
#pragma unroll
      for (int s = 0; s < 8; s++) sts128(sbase + (tid + q * 256) * 128 + ((s + lane) & 7) * 16, hv);
  };
#pragma unroll 1
  for (int it = 0; it < 3; it++) {
    const int hu = ((tid >> 5) * 3 + it) * 4, code = hu_code(min(hu + (lane >> 3), HU_N - 1)), ok = code >> 4, on = code & 15;
    uint32_t x[4], y[4];
    asm volatile("ldmatrix.sync.aligned.m8n8.x4.shared.b16 {%0,%1,%2,%3},[%4];" : "=r"(x[0]), "=r"(x[1]), "=r"(x[2]), "=r"(x[3])
                 : "r"(sbase + (on * 8 + (lane & (on == 12 ? 3 : 7))) * 208 + ok * 16) : "memory");
    asm volatile("ldmatrix.sync.aligned.m8n8.x4.trans.shared.b16 {%0,%1,%2,%3},[%4];" : "=r"(y[0]), "=r"(y[1]), "=r"(y[2]), "=r"(y[3])
                 : "r"(sbase + (ok * 8 + (lane & (ok == 12 ? 3 : 7))) * 208 + on * 16) : "memory");
    const uint32_t lo = __ballot_sync(0xffffffffu, ok > on), dg = __ballot_sync(0xffffffffu, ok >= on);
#pragma unroll
    for (int q = 0; q < 4; q++) {
      const float m0 = (lo >> (8 * q)) & 1 ? 0.f : sW, m1 = (dg >> (8 * q)) & 1 ? 0.f : sW;
      asm volatile("st.shared.u32 [%0],%1;" :: "r"(sbase + K1_W + (hu + q) * 128 + lane * 4),
                   "r"(pack_h2(fmaf(bf_lo(x[q]), m0, bf_lo(y[q]) * m1), fmaf(bf_hi(x[q]), m0, bf_hi(y[q]) * m1))) : "memory");
    }
  }
  put_rows(1, true); put_rows(2, tid < 88);
  TS(3, 2);
  asm volatile("fence.proxy.async.shared::cta;" ::: "memory");
  asm volatile("bar.sync 1,256;" ::: "memory");
  put_rows(0, true);
  uint32_t bf[HU_N - 2 * G_U];
#pragma unroll
  for (int q = 0; q < HU_N - 2 * G_U; q++) asm volatile("ld.shared.u32 %0,[%1];" : "=r"(bf[q]) : "r"(sbase + K1_W + (2 * G_U + q) * 128 + lane * 4));
  const float unscale = __uint_as_float(0x7f000000u - __float_as_uint(se)), unscale2 = __uint_as_float(0x7f000000u - __float_as_uint(sW));
  TS(3, 3);
  const int px = range * 16 * 136;
  mbar_wait_fast(fullI, 0);
  {
    const uint32_t ib = sbase + 76800 + (tid >> 5) * 6400, p0 = ib + ((lane >> 3) & 1) * 400 + ((lane >> 4) * 8 + (lane & 7)) * 4;
    auto ld = [&](uint32_t ad) { uint32_t v; asm volatile("ld.shared.u32 %0,[%1];" : "=r"(v) : "r"(ad)); return v; };
    auto wd = [&](int t, int h) { return pk3(ld(p0 + t * 800 + h * 192), ld(p0 + t * 800 + h * 192 + 64), ld(p0 + t * 800 + h * 192 + 128)); };
#pragma unroll
    for (int q = 0; q < 4; q++) {
      iv[q] = make_uint4(wd(2 * q, 0), wd(2 * q, 1), wd(2 * q + 1, 0), wd(2 * q + 1, 1));
      g_scr[PX_OFF + px + slice * 136 + q * 32 + lane] = iv[q];
    }
    ix = pk3(ld(ib + g * 400 + 384 + r * 4), ld(ib + (8 + g) * 400 + 384 + r * 4), 0);
    ((uint32_t*)(g_scr + PX_OFF + px + slice * 136 + 128))[lane] = ix;
  }
  asm volatile("bar.arrive 4,288;" ::: "memory");
  asm volatile("bar.sync 1,256;" ::: "memory");
  put_rows(2, tid >= 88); put_rows(3, tid + 768 < V_);
  asm volatile("bar.sync 1,256;" ::: "memory");
  TS(0, 1);
  uint32_t lc; asm volatile("add.u32 %0,%1,%2;" : "=r"(lc) : "r"((lane & 7) * 16), "r"(never));
  const uint64_t wdesc = (uint64_t)(((sbase + K1_W) & 0x3FFFF) >> 4) | ((uint64_t)(128 >> 4) << 16) | ((uint64_t)(256 >> 4) << 32);
  uint32_t a[2][6][4], d[2][26], ex[4] = {}, s[4] = {};
  float red[4] = {0.f, 0.f, 0.f, 0.f};
  auto ldsm = [&](uint32_t* o, uint32_t sh, uint32_t dep = 0) {
    asm volatile("ldmatrix.sync.aligned.m8n8.x4.trans.shared.b16 {%0,%1,%2,%3},[%4];"
                 : "=r"(o[0]), "=r"(o[1]), "=r"(o[2]), "=r"(o[3]) : "r"(sbase + ((sh & 0x1ff80) | (lc | (dep & never)))));
  };
  auto gather = [&](int t, int hf) {
    const int x = t & 1;
    const uint4 v = iv[(t >> 1) & 3];
#pragma unroll
    for (int kb = 3 * hf; kb < 3 * hf + 3; kb++) {
      const uint32_t ww = x ? (kb < 3 ? v.z : v.w) : (kb < 3 ? v.x : v.y);
      ldsm(a[x][kb], kb % 3 == 0 ? ww : kb % 3 == 1 ? ww >> 10 : __funnelshift_l(ww, ww, 12));
    }
  };
  auto issue = [&](int x) {
    asm volatile("wgmma.fence.sync.aligned;" ::: "memory");
#pragma unroll
    for (int kb = 0; kb < 6; kb++) {
      if (kb < G_K0) wgmma_h<G_N0 * 8>(d[x] + G_O0 * 2, a[x][kb], wdesc + kb * G_N0 * 16, kb);
      if (kb < G_K1) wgmma_h<G_N1 * 8>(d[x] + G_O1 * 2, a[x][kb], wdesc + (G_U1 + kb * G_N1) * 16, kb);
      if (kb < G_K2) wgmma_h<32>(d[x] + G_O2 * 2, a[x][kb], wdesc + (G_U2 + kb * G_N2) * 16, kb);
    }
    asm volatile("wgmma.commit_group.sync.aligned;" ::: "memory");
  };
  auto hmma_part = [&](int t) {
    constexpr FragIdx FI = make_fi();
    const int x = t & 1;
#pragma unroll
    for (int o = 0; o < 13; o++) {
      if (oct_wg(o)) asm volatile("" : "+r"(d[x][o * 2]), "+r"(d[x][o * 2 + 1]) :: "memory"); else d[x][o * 2] = d[x][o * 2 + 1] = 0;
    }
#pragma unroll
    for (int kb = 0; kb < 6; kb++)
#pragma unroll
      for (int o = 2 * kb + 1; o < 13; o++)
        if (!unit_wg(kb, o)) mma16816h(d[x] + o * 2, a[x][kb], bf[FI.v[2 * kb][o]], bf[FI.v[2 * kb + 1][o]]);
#pragma unroll
    for (int q = 0; q < 6; q++) if (!unit_wg(q, 2 * q)) mma1688h(d[x] + q * 4, a[x][q][0], a[x][q][1], bf[FI.v[2 * q][2 * q]]);
    mma1688h(d[x] + 24, r < 2 ? ex[t & 3] : 0u, r < 2 ? 0u : ex[t & 3], bf[FI.v[12][12]]);
  };
  auto dot_part = [&](int t, int hf) {
    const int x = t & 1;
    if (hf == 0) {
      const uint32_t pe = hfma2(r < 2 ? d[x][24] : d[x][25], ex[t & 3], 0u);
      s[0] = r < 2 ? pe : 0u; s[1] = r < 2 ? 0u : pe; s[2] = s[3] = 0;
    }
#pragma unroll
    for (int q = 3 * hf; q < 3 * hf + 3; q++)
#pragma unroll
      for (int e = 0; e < 4; e++) s[e] = hfma2(d[x][q * 4 + e], a[x][q][e], s[e]);
  };
  float* outp = g_partP + slice * B_ + range * 256;
  float k0 = 0.f, k1 = 0.f, x0 = 0.f, x1 = 0.f;
  auto red_stage = [&](int st, int grp) {
    const bool u16 = lane & 16, u8 = lane & 8;
    if (st == 0) {
      k0 = u16 ? red[2] : red[0]; x0 = __shfl_xor_sync(0xffffffffu, u16 ? red[0] : red[2], 16);
      k1 = u16 ? red[3] : red[1]; x1 = __shfl_xor_sync(0xffffffffu, u16 ? red[1] : red[3], 16);
      red[0] = red[1] = red[2] = red[3] = 0.f;
    }
    if (st == 1) { const float p0 = k0 + x0, p1 = k1 + x1; k0 = u8 ? p1 : p0; x0 = __shfl_xor_sync(0xffffffffu, u8 ? p0 : p1, 8); }
    if (st == 2) { k0 += x0; x0 = __shfl_xor_sync(0xffffffffu, k0, 4); }
    if (st == 3 && !(lane & 4)) outp[grp * 16 + r * 4 + ((lane >> 3) & 1) * 2 + (lane >> 4)] = (k0 + x0) * unscale * unscale * unscale2;
  };
  auto group = [&](bool first, int prv, int cur, int nxt) {
    const int pn = PX_OFF + px + nxt * 136 + lane;
#pragma unroll
    for (int t = 0; t < 8; t++) {
      issue((t & 1) ^ 1);
      SCHED_FENCE(never, t * 8);
      if (!first) {
        if (t == 0) { iv[3] = ldtex(tex, PX_OFF + px + cur * 136 + lane + 96); iv[0] = ldtex(tex, pn); }
        if (t == 2) iv[1] = ldtex(tex, pn + 32);
        if (t < 4) red_stage(t, prv);
      } else if (t == 4) {
        TS(4, 2);
        flag_wait(&g_flag[(cta >> 4) * 32], 16);
        TS(4, 3);
        iv[0] = ldtex(tex, pn); iv[1] = ldtex(tex, pn + 32);
      }
      if (t == 4) { ix = ldtex(texX, (px + nxt * 136 + 128) * 4 + lane).x; iv[2] = ldtex(tex, pn + 64); }
      dot_part(t, 0);
      SCHED_FENCE(never, t * 8 + 1);
      if (t == 3) ldsm(ex, ix >> 10);
      if (t == 7) ldsm(ex, ix);
      gather(t + 2, 0);
      dot_part(t, 1);
      SCHED_FENCE(never, t * 8 + 4);
      gather(t + 2, 1);
      asm volatile("wgmma.wait_group.sync.aligned 0;" ::: "memory");
      if (FM & 1) SCHED_FENCE(never, t * 8 + 2);
      asm volatile("" : "+r"(d[(t & 1) ^ 1][0]) :: "memory");
      mma1688f(red, hadd2(s[0], s[2]), hadd2(s[1], s[3]), (g | (d[(t & 1) ^ 1][0] & never)) == t ? 0x3c003c00u : 0u);
      hmma_part(t + 1);
      if (FM & 2) SCHED_FENCE(never, t * 8 + 3);
    }
  };
  gather(0, 0); gather(0, 1); issue(0); ldsm(ex, ix); gather(1, 0); gather(1, 1);
  asm volatile("wgmma.wait_group.sync.aligned 0;" ::: "memory");
  hmma_part(0);
  int prv = slice, cur = slice == 0;
  group(true, 0, prv, cur);
  TS(4, 1);
#pragma unroll 1
  for (int n = 1; n < NGRP; n++) {
    const int nxt = (n + (n >= slice)) & 15;
    if (n == TRIG) asm volatile("griddepcontrol.launch_dependents;");
    if (PXW && tid == 0) mbar_arrive(progG);
    group(false, prv, cur, nxt);
    prv = cur; cur = nxt;
  }
#pragma unroll
  for (int st = 0; st < 4; st++) red_stage(st, prv);
  TS(0, 2);
  if (MCW) asm volatile("barrier.cluster.wait.aligned;" ::: "memory");
  asm volatile("barrier.cluster.arrive.relaxed.aligned; barrier.cluster.wait.aligned;" ::: "memory");
}

constexpr int SM_U = 130048, SM_BAR = 128000, SM_J = SM_U + 98304, DEEP_SMEM = SM_J + 4096;

#define ELECT "{.reg .pred p; elect.sync _|p,0xffffffff; @p "
__device__ __forceinline__ void e_mc(uint32_t dst, const void* src, uint32_t bytes, uint32_t bar, uint64_t pol) {
  asm volatile(ELECT "cp.async.bulk.shared::cluster.global.mbarrier::complete_tx::bytes.multicast::cluster.L2::cache_hint [%0],[%1],%2,[%3],%4,%5;}"
               :: "r"(dst), "l"(src), "r"(bytes), "r"(bar), "h"((unsigned short)3), "l"(pol) : "memory");
}
__device__ __forceinline__ void e_g2s(uint32_t dst, const void* src, uint32_t bytes, uint32_t bar) {
  asm volatile(ELECT "cp.async.bulk.shared::cluster.global.mbarrier::complete_tx::bytes [%0],[%1],%2,[%3];}" :: "r"(dst), "l"(src), "r"(bytes), "r"(bar) : "memory");
}
__device__ __forceinline__ void e_pf(const void* src, uint32_t bytes) { asm volatile(ELECT "cp.async.bulk.prefetch.L2.global [%0],%1;}" :: "l"(src), "r"(bytes) : "memory"); }
__device__ __forceinline__ void e_expect(uint32_t bar, uint32_t bytes) { asm volatile(ELECT "mbarrier.arrive.expect_tx.shared::cta.b64 _,[%0],%1;}" :: "r"(bar), "r"(bytes) : "memory"); }

__global__ void __cluster_dims__(2, 1, 1) __launch_bounds__(TH + 128, 1)
k_deep(cudaTextureObject_t tex, const __nv_bfloat16* __restrict__ w2, const __nv_bfloat16* __restrict__ b2,
       __nv_bfloat16* __restrict__ out, int never) {
  extern __shared__ __align__(1024) uint4 sm[];
  constexpr int PF = DPF, DEPTH = DDEPTH, NW = TH / 32;
  static_assert(YD == 4 && PF == 4, "");
  const int tid = threadIdx.x;
  const int c = blockIdx.x >> 1, half = blockIdx.x & 1;
  const uint32_t sbase = (uint32_t)__cvta_generic_to_shared(sm);
  const uint32_t fullL = sbase + SM_BAR, fullU = fullL + 8, emptyL = fullL + 16, emptyU = fullL + 24, barJ = fullL + 32;
  TS(1, 0);
  if (tid == 0) {
    mbar_init(fullL, 1); mbar_init(fullU, 1); mbar_init(emptyL, 2 * NW); mbar_init(emptyU, 2 * NW); mbar_init(barJ, 1);
    asm volatile("fence.mbarrier_init.release.cluster;" ::: "memory");
  }
  __syncwarp();
  const int wrp = __shfl_sync(0xffffffffu, tid >> 5, 0);
  const char* base = (const char*)g_scr;
  uint32_t oL = (PL_OFF + c * NC * 8000) * 16u + half * 64000, oS = (PS_OFF + c * NC * 2000) * 16u + half * 16000;
  asm volatile("barrier.cluster.arrive.relaxed.aligned;" ::: "memory");
  flag_wait(&g_flag[8 * 32], 132);
  asm volatile("barrier.cluster.wait.aligned;" ::: "memory");
  if (wrp == NW) {
    asm volatile("fence.proxy.async.global;" ::: "memory");
    e_expect(fullU, 96000);
#pragma unroll
    for (int m = 0; m < 3; m++) e_mc(sbase + SM_U + m * 32032 + half * 16000, base + oS, 16000, fullU, m == 2 ? POL_EF : POL_N);
    e_expect(fullL, 128000);
    if (!STAG) e_mc(sbase + half * 64000, base + oL, 64000, fullL, POL_EF);
  }
  TS(5, 1);
  if (wrp >= NW) {
    asm volatile("setmaxnreg.dec.sync.aligned.u32 24;");
    if (wrp == NW) {
      uint32_t oT = (PT_OFF + c * 10 * 1024) * 16u + half * 8192;
      const uint32_t junk = sbase + SM_J, oW = (IX_OFF + half * IXH + ((c + (c >> 4) * 5) & 15) * 512) * 16u;
      auto warm = [&](uint32_t off) {
        asm volatile(ELECT "mbarrier.expect_tx.relaxed.cta.shared::cta.b64 [%0],%1;}" :: "r"(barJ), "r"(8192) : "memory");
        e_g2s(junk, base + off, 4096, barJ); e_g2s(junk, base + off + 4096, 4096, barJ);
      };
      uint32_t t0 = clock();
      if (!PREW) warm(oW);
      if (STAG) { if (STAG == 1) mbar_wait_fast(fullU, 0); else sleep_until(t0, STAG); e_mc(sbase + half * 64000, base + oL, 64000, fullL, POL_EF); }
      warm(oT);
      if (!(PREW & 4)) warm(oW + 131072);
#pragma unroll 1
      for (int k = 0; k + 1 < NC; k++) {
        oL += 128000; oS += 32000; oT += 16384;
        mbar_wait_fast(fullL, k & 1);
        t0 = clock();
        e_pf(base + oS, 16000);
        warm(k + 2 < NC ? oW + (k + 2) * 131072 : (IX_OFF + half * IXH + NC * 8192 + (c & 3) * 512) * 16u);
        mbar_wait_fast(emptyU, k & 1);
        e_expect(fullU, 96000);
#pragma unroll 1
        for (int q = 0; q < 8; q++) {
          sleep_until(t0, q * PACE);
          e_pf(base + oL + q * 8000, 8000);
          if (q >= 2) e_mc(sbase + SM_U + ((q - 2) >> 1) * 32032 + half * 16000 + (q & 1) * 8000, base + oS + (q & 1) * 8000, 8000, fullU, q >= 6 ? POL_EF : POL_N);
        }
        warm(oT);
        e_expect(fullL, 128000);
        mbar_wait_fast(emptyL, k & 1);
        e_mc(sbase + half * 64000, base + oL, 64000, fullL, POL_EF);
      }
      mbar_wait_fast(fullL, (NC - 1) & 1);
      mbar_wait_fast(emptyU, (NC - 1) & 1);
      mbar_arrive_lane0(fullU);
      warm(oT + 16384);
      mbar_arrive_lane0(barJ); mbar_wait_fast(barJ, 0);
    } else if (tid >= TH + 96) {
      if (tid == TH + 96) sts128(barJ + 32, *(const uint4*)(w2 + c * 8));
      asm volatile("bar.arrive 3,%0;" :: "n"(TH + 32) : "memory");
      asm volatile("griddepcontrol.wait;" ::: "memory");
      const int b = half * 8192 + c * 128 + (tid & 31) * 4;
      const float bias = __bfloat162float(b2[0]);
      float4 s = make_float4(bias, bias, bias, bias);
#pragma unroll 2
      for (int k = 0; k < 16; k++) { const float4 v = __ldcg((const float4*)(g_partP + k * B_ + b)); s.x += v.x; s.y += v.y; s.z += v.z; s.w += v.w; }
      asm volatile("red.global.add.v4.f32 [%0],{%1,%2,%3,%4};" :: "l"(g_acc + b), "f"(s.x), "f"(s.y), "f"(s.z), "f"(s.w) : "memory");
      asm volatile("bar.arrive 1,%0;" :: "n"(TH + 32) : "memory");
    }
    return;
  }
  asm volatile("setmaxnreg.inc.sync.aligned.u32 240;");
  const int lane = tid & 31;
  const int tbase = PT_OFF + c * 10 * 1024;
  const int ibase = IX_OFF + half * IXH + tid;
  const uint32_t lc = (tid & 7) << 4;
  uint4 acc[NS], wq[PF], x[DEPTH], y[YD], ye;
  uint32_t sw[NS] = {};
  auto sget = [&](int s) { return (s & 3) == 3 ? __byte_perm(__byte_perm(sw[s - 3], sw[s - 2], 0x0073), sw[s - 1], 0x0710) : sw[s]; };
  auto sa0 = [&](uint32_t v) { return sbase + SM_U + (((v << 5) & 0x1ffe0) | ((lc >> 2) & 16)); };
  auto sa1 = [&](uint32_t v) { return sbase + SM_U + (((v >> 7) & 0x1ffe0) | ((~lc >> 2) & 16)); };
  {
    uint4 i0[8];
#pragma unroll
    for (int q = 0; q < 8; q++) i0[q] = ldtex(tex, I0_OFF + (half * 8 + q) * TH + tid);
#pragma unroll
    for (int i = 0; i < PF; i++) if (!WQL) wq[i] = ldtex(tex, ibase + i * TH);
    auto wd = [&](int k) { return (k & 3) == 0 ? i0[k >> 2].x : (k & 3) == 1 ? i0[k >> 2].y : (k & 3) == 2 ? i0[k >> 2].z : i0[k >> 2].w; };
    TS(5, 2);
    mbar_wait_fast(fullU, 0);
#pragma unroll
    for (int i = 0; i < PF; i++) if (WQL) wq[i] = ldtex(tex, ibase + i * TH);
    TS(1, 1);
#pragma unroll
    for (int s = 0; s < NS; s++) acc[s] = add4(lds128(sa0(wd(s))), lds128(sa1(wd(s))));
    arrive_both(emptyU, lane);
    asm volatile("bar.sync 3,%0;" :: "n"(TH + 32) : "memory");
    TS(5, 3);
  }
#pragma unroll 1
  for (int k = 0; k < NC; k++) {
    const int ti = ibase + k * 8192;
    const int tb = tbase + k * 1024;
    const bool more = k + 1 < NC;
    TR(k * 4);
    if (CBAR & 1) asm volatile("bar.sync 4,%0;" :: "n"(TH) : "memory");
    mbar_wait_fast(fullL, k & 1);
    TR(k * 4 + 2);
    uint4 w, cc; uint32_t yc, yn;
    constexpr int TL = NS * 8, TT = TL + NS * 2;
#pragma unroll
    for (int t = 0; t < TT + DEPTH; t += 2) {
      if (t == TL + DEPTH && !more) break;
      if (t >= DEPTH) {
        const int u = t - DEPTH;
        uint4 p = add4(x[u % DEPTH], x[(u + 1) % DEPTH]);
        if (u < TL) {
          const int s = u >> 3, j = u & 7;
          if (j == 0) {
            cc = s >= YD ? add4(y[s % YD], p) : p;
            if (s + YD < NS) y[s % YD] = ldtex(tex, tb | (yc & 1023));
          } else cc = add4(cc, p);
          if (j == 6) acc[s] = add4(acc[s], cc);
        } else {
          const int s = (u - TL) >> 1;
          acc[s] = add4(acc[s], p);
        }
      }
      if ((CBAR & 4) && t == TL / 2) asm volatile("bar.sync 4,%0;" :: "n"(TH) : "memory");
      if ((CBAR & 8) && t == TL - 40) asm volatile("bar.sync 4,%0;" :: "n"(TH) : "memory");
      if (DEPTH == 8 && (t & 7) == 2) yc = yn;
      if (t < TL) {
        const int s = t >> 3, j = t & 7;
        if (j == 0) {
          if (ye_of(s - YD) >= 0) acc[ye_of(s - YD) & 3] = add4(acc[ye_of(s - YD) & 3], ye);
          w = wq[s % PF];
          if (!EARLY || s < NS - 4) wq[s % PF] = ldtex(tex, ti + (s + PF) * TH);
          else {
            if (s == NS - 4) { wq[0] = ldtex(tex, ti + NS * TH); ye = ldtex(tex, ti + (NS + 3) * TH); }
            if (s == NS - 3) { wq[1] = ldtex(tex, ti + (NS + 1) * TH); y[0] = ldtex(tex, ti + (NS + 2) * TH); }
            if (s == NS - 2) wq[2] = y[0];
            if (s == NS - 1) wq[3] = ye;
          }
          yn = __funnelshift_l(w.z, w.z, 5); if (DEPTH < 8) yc = yn;
          if ((s & 3) != 3) asm volatile("add.u32 %0,%1,%2;" : "=r"(sw[s]) : "r"(w.w), "r"(never));
          if (ye_of(s) >= 0) ye = ldtex(tex, tb | w.w);
        }
#pragma unroll
        for (int jj = j; jj < j + 2; jj++) {
          const uint32_t ww = jj < 3 ? w.x : jj < 6 ? w.y : w.z;
          const uint32_t sh = jj % 3 == 0 ? ww : jj % 3 == 1 ? ww >> 10 : __funnelshift_l(ww, ww, 12);
          x[(t + jj - j) % DEPTH] = lds128(sbase + ((sh & 0x1ff80) | lc) + jj * 16 - 128);
        }
      } else if (t < TT) {
        const int s = (t - TL) >> 1;
        if (s == 0) { arrive_both(emptyL, more ? lane : 9); TR(k * 4 + 3); if (CBAR & 2) asm volatile("bar.sync 4,%0;" :: "n"(TH) : "memory"); mbar_wait_fast(fullU, (k + 1) & 1); }
        const uint32_t sv = sget(s);
        x[t % DEPTH] = lds128(sa0(sv));
        x[(t + 1) % DEPTH] = lds128(sa1(sv));
      } else if (t == TT) arrive_both(emptyU, lane);
      if ((t & (FENCE_N - 1)) == FENCE_N - 2) SCHED_FENCE(never, t);
    }
  }
  TS(1, 2);
  const uint4 w2v = lds128(barJ + 32);
  const uint32_t cell = sbase + SM_U + tid * 16;
  const int t9 = tbase + 9 * 1024;
  uint4 za[4], i9 = wq[0];
  auto fetch = [&](int q) {
    y[0] = ldtex(tex, t9 | i9.x); y[1] = ldtex(tex, t9 | i9.y); y[2] = ldtex(tex, t9 | i9.z); y[3] = ldtex(tex, t9 | i9.w);
    if (q) {
      i9 = ldtex(tex, ibase + NC * 8192 + min(q + 1, 7) * TH);
      const uint32_t ca = cell + (q > 6 ? 0 : q - 1) * 16384;
#pragma unroll
      for (int s = 0; s < 4; s++) za[s] = lds128(ca + s * 4096);
    }
  };
  fetch(0);
  i9 = wq[1];
#pragma unroll
  for (int s = 0; s < 4; s++) za[s] = acc[s];
#pragma unroll
  for (int s = 0; s < 24; s++) sts128(cell + s * 4096, acc[4 + s]);
  float hw[8];
  {
    const uint32_t ww[4] = {w2v.x, w2v.y, w2v.z, w2v.w};
#pragma unroll
    for (int k = 0; k < 8; k++) hw[k] = 0.5f * ((k & 1) ? bf_hi(ww[k >> 1]) : bf_lo(ww[k >> 1]));
  }
  float* outp = g_acc + half * 8192 + tid;
#pragma unroll 1
  for (int q = 0; q < NS / 4; q++) {
    uint4 z[4];
#pragma unroll
    for (int s = 0; s < 4; s++) z[s] = add4(za[s], y[s]);
    if (q == 1) {
#pragma unroll
      for (int s = 0; s < 4; s++) sts128(cell + s * 4096, acc[28 + s]);
    }
    if (q < 7) fetch(q + 1);
    SCHED_FENCE(never, 999);
#pragma unroll
    for (int s = 0; s < 4; s++) {
      const uint32_t a[4] = {z[s].x, z[s].y, z[s].z, z[s].w};
      float r0 = 0.f;
#pragma unroll
      for (int k = 0; k < 8; k++) {
        const float v = (k & 1) ? bf_hi(a[k >> 1]) : bf_lo(a[k >> 1]);
        const float u = v * fmaf(v * v, 0.7978845608028654f * 0.044715f, 0.7978845608028654f);
        float th; asm("tanh.approx.f32 %0,%1;" : "=f"(th) : "f"(u));
        r0 = fmaf(fmaf(v, th, v), hw[k], r0);
      }
      asm volatile("red.global.add.f32 [%0],%1;" :: "l"(outp + s * TH), "f"(r0) : "memory");
    }
    outp += 4 * TH;
  }
  TS(1, 3);
  asm volatile("bar.sync 1,%0;" :: "n"(TH + 32) : "memory");
  if (tid == 0) {
    __threadfence();
    const unsigned old = atomicInc(&g_done[half * 32], 63);
    asm volatile("st.shared.u32 [%0],%1;" :: "r"(barJ + 8), "r"(old) : "memory");
  }
  asm volatile("bar.sync 2,%0;" :: "n"(TH) : "memory");
  uint32_t old; asm volatile("ld.shared.u32 %0,[%1];" : "=r"(old) : "r"(barJ + 8));
  if (old == 63) {
    if (half == 0 && tid < 9) g_flag[tid * 32] = 0;
    __threadfence();
    float4 v[8];
#pragma unroll
    for (int q = 0; q < 8; q++) v[q] = __ldcg((const float4*)(g_acc + half * 8192) + q * TH + tid);
#pragma unroll
    for (int q = 0; q < 8; q++) ((uint2*)(out + half * 8192))[q * TH + tid] = make_uint2(pack_bf2(v[q].x, v[q].y), pack_bf2(v[q].z, v[q].w));
    TS(6, 2);
  }
}

}

extern "C" void kernel_launch(void* const* d_in, const int* in_sizes, int n_in, void* d_out, int out_size) {
  const int* idx = (const int*)d_in[0];
  const __nv_bfloat16* table = (const __nv_bfloat16*)d_in[1];
  const __nv_bfloat16* wp = (const __nv_bfloat16*)d_in[2];
  const __nv_bfloat16* w1 = (const __nv_bfloat16*)d_in[3];
  const __nv_bfloat16* b1 = (const __nv_bfloat16*)d_in[4];
  const __nv_bfloat16* w2 = (const __nv_bfloat16*)d_in[5];
  const __nv_bfloat16* b2 = (const __nv_bfloat16*)d_in[6];
  static cudaTextureObject_t texScr = 0, texG = 0;
  static CUtensorMap mapW, mapL, mapS, mapT, mapE, mapC;
  static const void *c_tab = nullptr, *c_w1 = nullptr;
  if (c_tab != table || c_w1 != w1) {
    c_tab = table; c_w1 = w1;
    char* scr = nullptr; cudaGetSymbolAddress((void**)&scr, g_scr);
    auto mk_tex = [](const void* p, size_t bytes, cudaChannelFormatDesc d) {
      cudaResourceDesc rd = {}; rd.resType = cudaResourceTypeLinear; rd.res.linear.devPtr = (void*)p; rd.res.linear.desc = d; rd.res.linear.sizeInBytes = bytes;
      cudaTextureDesc td = {}; td.readMode = cudaReadModeElementType;
      cudaTextureObject_t t = 0; cudaCreateTextureObject(&t, &rd, &td, nullptr); return t;
    };
    if (!texScr) {
      texScr = mk_tex(scr, (size_t)SCR_N * 16, cudaCreateChannelDesc<uint4>());
      texG = mk_tex(scr + (size_t)PX_OFF * 16, (size_t)(SCR_N - PX_OFF) * 16, cudaCreateChannelDesc<unsigned>());
    }
    typedef CUresult (*EncFn)(CUtensorMap*, CUtensorMapDataType, cuuint32_t, void*, const cuuint64_t*, const cuuint64_t*, const cuuint32_t*,
                              const cuuint32_t*, CUtensorMapInterleave, CUtensorMapSwizzle, CUtensorMapL2promotion, CUtensorMapFloatOOBfill);
    EncFn enc = nullptr; cudaDriverEntryPointQueryResult qr;
    cudaGetDriverEntryPoint("cuTensorMapEncodeTiled", (void**)&enc, cudaEnableDefault, &qr);
    const cuuint32_t ones[4] = {1, 1, 1, 1};
    auto mk = [&](CUtensorMap* m, CUtensorMapDataType dt, int rank, void* p, const cuuint64_t* dim, const cuuint64_t* str, const cuuint32_t* box, CUtensorMapSwizzle sw) {
      enc(m, dt, rank, p, dim, str, box, ones, CU_TENSOR_MAP_INTERLEAVE_NONE, sw, CU_TENSOR_MAP_L2_PROMOTION_NONE, CU_TENSOR_MAP_FLOAT_OOB_FILL_NONE);
    };
    { cuuint64_t dim[2] = {H_, F_ * D_}, str[1] = {H_ * 2}; cuuint32_t box[2] = {32, MCW ? 128 : 256};
      mk(&mapW, CU_TENSOR_MAP_DATA_TYPE_BFLOAT16, 2, (void*)w1, dim, str, box, CU_TENSOR_MAP_SWIZZLE_64B); }
    { cuuint64_t dim[4] = {64, V_, NC, 64}, str[3] = {128, 128000, 128000 * NC}; cuuint32_t box[4] = {32, 64, 1, 4};
      mk(&mapL, CU_TENSOR_MAP_DATA_TYPE_BFLOAT16, 4, scr + (size_t)PL_OFF * 16, dim, str, box, CU_TENSOR_MAP_SWIZZLE_64B); }
    { cuuint64_t dim[4] = {64, V_ / 4, NC, 64}, str[3] = {128, 32000, 32000 * NC}; cuuint32_t box[4] = {64, 16, 1, 4};
      mk(&mapS, CU_TENSOR_MAP_DATA_TYPE_BFLOAT16, 4, scr + (size_t)PS_OFF * 16, dim, str, box, CU_TENSOR_MAP_SWIZZLE_128B); }
    { cuuint64_t dim[3] = {2048, 10, 64}, str[2] = {16384, 163840}; cuuint32_t box[3] = {128, 2, 4};
      mk(&mapT, CU_TENSOR_MAP_DATA_TYPE_UINT64, 3, scr + (size_t)PT_OFF * 16, dim, str, box, CU_TENSOR_MAP_SWIZZLE_NONE); }
    { cuuint64_t dim[2] = {D_, V_}, str[1] = {D_ * 2}; cuuint32_t box[2] = {64, 128};
      mk(&mapE, CU_TENSOR_MAP_DATA_TYPE_BFLOAT16, 2, (void*)table, dim, str, box, CU_TENSOR_MAP_SWIZZLE_128B);
      cuuint32_t box2[2] = {8, 256};
      mk(&mapC, CU_TENSOR_MAP_DATA_TYPE_BFLOAT16, 2, (void*)table, dim, str, box2, CU_TENSOR_MAP_SWIZZLE_NONE); }
    cudaFuncSetAttribute(k_deep, cudaFuncAttributeMaxDynamicSharedMemorySize, DEEP_SMEM);
    cudaFuncSetAttribute(k_tens, cudaFuncAttributeMaxDynamicSharedMemorySize, K1_SMEM);
  }
  k_tens<<<132, 512, K1_SMEM, cudaStreamPerThread>>>(mapW, mapL, mapS, mapT, mapE, mapC, texScr, texG, idx, table, wp, w1, b1, 0);
  cudaLaunchAttribute at[1];
  at[0].id = cudaLaunchAttributeProgrammaticStreamSerialization; at[0].val.programmaticStreamSerializationAllowed = 1;
  cudaLaunchConfig_t cfg = {};
  cfg.stream = cudaStreamPerThread; cfg.attrs = at;
  cfg.gridDim = 128; cfg.blockDim = TH + 128; cfg.dynamicSmemBytes = DEEP_SMEM; cfg.numAttrs = PDL & 1;
  cudaLaunchKernelEx(&cfg, k_deep, texScr, w2, b2, (__nv_bfloat16*)d_out, 0);

}
```

```cpp
#include <cuda_runtime.h>
#include <cuda_bf16.h>
#include <cuda_fp16.h>
#include <stdint.h>
#include <cuda.h>

namespace {

constexpr int B_ = 16384, F_ = 100, D_ = 128, V_ = 1000, H_ = 512;
constexpr int NC = 9;
constexpr int PT_OFF = 0;
constexpr int PL_OFF = 64 * 10 * 1024;
constexpr int PS_OFF = PL_OFF + 64 * NC * 8000;
constexpr int IXH = NC * 8192 + 2048;
constexpr int IX_OFF = PS_OFF + 64 * NC * 2000;
constexpr int I0_OFF = IX_OFF + 2 * IXH;
constexpr int PX_OFF = I0_OFF + 4096;
constexpr int SCR_N = PX_OFF + 64 * 16 * 136;
static_assert(PX_OFF % 32 == 0, "");

__device__ __align__(1024) uint4 g_scr[SCR_N];
__device__ float g_acc[B_];
__device__ unsigned long long g_slot;
__device__ unsigned g_done[64];
__device__ float g_partP[16 * B_];
__device__ unsigned g_flag[16 * 32];

#define TS(k, i)
#define TR(slot)
#define PT(slot)

constexpr uint64_t POL_EF = 0x12F0000000000000ull, POL_N = 0x1000000000000000ull;
__device__ __forceinline__ uint32_t addbf2(uint32_t a, uint32_t b) { uint32_t r; asm("add.rn.bf16x2 %0,%1,%2;" : "=r"(r) : "r"(a), "r"(b)); return r; }
__device__ __forceinline__ uint4 add4(const uint4& a, const uint4& b) { return make_uint4(addbf2(a.x, b.x), addbf2(a.y, b.y), addbf2(a.z, b.z), addbf2(a.w, b.w)); }
__device__ __forceinline__ void acc4(uint4& a, const uint4& b, int never) {
  asm("{.reg .pred p; setp.eq.s32 p,%8,0;\n"
      "@p add.rn.bf16x2 %0,%0,%4; @p add.rn.bf16x2 %1,%1,%5; @p add.rn.bf16x2 %2,%2,%6; @p add.rn.bf16x2 %3,%3,%7;}"
      : "+r"(a.x), "+r"(a.y), "+r"(a.z), "+r"(a.w) : "r"(b.x), "r"(b.y), "r"(b.z), "r"(b.w), "r"(never));
}
__device__ __forceinline__ uint4 ldtex(cudaTextureObject_t t, int i) {
  uint4 v; asm volatile("tex.1d.v4.u32.s32 {%0,%1,%2,%3},[%4,{%5}];" : "=r"(v.x), "=r"(v.y), "=r"(v.z), "=r"(v.w) : "l"(t), "r"(i)); return v;
}
__device__ __forceinline__ uint4 lds128(uint32_t a) {
  uint4 v; asm volatile("ld.volatile.shared.v4.u32 {%0,%1,%2,%3},[%4];" : "=r"(v.x), "=r"(v.y), "=r"(v.z), "=r"(v.w) : "r"(a)); return v;
}
__device__ __forceinline__ void sts128(uint32_t a, const uint4& v) {
  asm volatile("st.shared.v4.u32 [%0],{%1,%2,%3,%4};" :: "r"(a), "r"(v.x), "r"(v.y), "r"(v.z), "r"(v.w) : "memory");
}
__device__ __forceinline__ void mbar_init(uint32_t bar, int n) { asm volatile("mbarrier.init.shared::cta.b64 [%0],%1;" :: "r"(bar), "r"(n) : "memory"); }
__device__ __forceinline__ void mbar_wait(uint32_t bar, uint32_t parity) {
  uint32_t ok; int it = 0;
  do { asm volatile("{.reg .pred p; mbarrier.try_wait.parity.shared::cta.b64 p,[%1],%2; selp.u32 %0,1,0,p;}" : "=r"(ok) : "r"(bar), "r"(parity) : "memory"); } while (!ok && ++it < (1 << 19));
}
__device__ __forceinline__ void mbar_expect(uint32_t bar, uint32_t bytes) { asm volatile("mbarrier.arrive.expect_tx.shared::cta.b64 _,[%0],%1;" :: "r"(bar), "r"(bytes) : "memory"); }
__device__ __forceinline__ void bulk_g2s(uint32_t dst, const void* src, uint32_t bytes, uint32_t bar) {
  asm volatile("cp.async.bulk.shared::cluster.global.mbarrier::complete_tx::bytes [%0],[%1],%2,[%3];" :: "r"(dst), "l"(src), "r"(bytes), "r"(bar) : "memory");
}
__device__ __forceinline__ void bulk_pf(const void* src, uint32_t bytes) { asm volatile("cp.async.bulk.prefetch.L2.global [%0],%1;" :: "l"(src), "r"(bytes) : "memory"); }
#define NOMMA 0
#define NGRP 16
#define PDL 1
#define FIN_S 128
#define WRED 4
#define RSV 24
#define RSV_T 7200
#define RSV_L 550
#define TRIG 14
#define PREW 5
#define PXW 3
#define WQL 1
#define EARLY 1
#define CBAR 0
#define X_SAMEK 0
#define X_SAMEW 0
#define FM 0
#define SWP 1
#define HOLD 1
#define MCW 1
#define TW 1
#define PP0 10
#define PT0 10000
#define PDT 0
#define RPNN "160"
#define RAUX "32"
#define RPRO "160"
#define PARK 0
#define NLOOK 128
#define NEF 16
#define ORD 0
#define WFENCE 0
#define SPLIT 1
#define IORD 3
#define IPF 3
#define IPACE 4500
#define WPF 4
#define QV 3
#define QORD(n) ((n) < 23 ? (n) + 2 : (n) - 23)
#define DYD 4
#define DPF 4
#define DDEPTH 4
#define FENCE_N 4
#define INPL 0
#define STAG 1
#define PACE 800
#define PM4 "pmevent 1; pmevent 2; pmevent 3; pmevent 4;"
#define PMFILL "pmevent 1;"
#define SCHED_FENCE(never, k) asm volatile("{.reg .pred p; setp.ne.u32 p,%0,%1; @p bra.uni SKIP_%=;" PMFILL "SKIP_%=: }" :: "r"(never), "r"(0x7fff0000 + (k)) : "memory")

__global__ void k_prod_naive(const __nv_bfloat16* __restrict__ table, const __nv_bfloat16* __restrict__ w1) {
  __shared__ float t[8][D_];
  int f = blockIdx.y, v0 = blockIdx.x * 8, h = threadIdx.x;
  for (int i = h; i < 8 * D_; i += 512) t[i / D_][i % D_] = __bfloat162float(table[v0 * D_ + i]);
  __syncthreads();
  float s[8] = {0, 0, 0, 0, 0, 0, 0, 0};
  for (int d = 0; d < D_; d++) { float w = __bfloat162float(w1[(size_t)(f * D_ + d) * H_ + h]);
#pragma unroll
    for (int k = 0; k < 8; k++) s[k] += t[k][d] * w; }
  __nv_bfloat16* P = (__nv_bfloat16*)g_scr;
  int c = h >> 3;
  for (int k = 0; k < 8; k++) {
    size_t e = f < 72 ? (size_t)PL_OFF + ((size_t)(c * NC + (f >> 3)) * 1000 + v0 + k) * 8 + (f & 7)
             : f < 90 ? (size_t)PS_OFF + ((size_t)(c * NC + ((f - 72) >> 1)) * 1000 + v0 + k) * 2 + (f & 1)
                      : (size_t)PT_OFF + (size_t)(c * 10 + f - 90) * 1024 + v0 + k;
    P[e * 8 + (h & 7)] = __float2bfloat16(s[k]);
  }
}
__global__ void k_pnn_naive(const int* __restrict__ idx, const __nv_bfloat16* __restrict__ table, const __nv_bfloat16* __restrict__ wp) {
  __shared__ float e[F_][33];
  int b = blockIdx.x, d0 = blockIdx.y * 32, tid = threadIdx.x;
  for (int i = tid; i < F_ * 32; i += 128) e[i >> 5][i & 31] = __bfloat162float(table[idx[b * F_ + (i >> 5)] * D_ + d0 + (i & 31)]);
  __syncthreads();
  float s = 0; int d = tid & 31;
  for (int i = tid >> 5; i < F_; i += 4) { float u = 0; for (int j = 0; j < F_; j++) u += __bfloat162float(wp[i * F_ + j]) * e[j][d]; s += u * e[i][d]; }
  for (int o = 16; o; o >>= 1) s += __shfl_xor_sync(~0u, s, o);
  if (d == 0) g_partP[(blockIdx.y * 4 + (tid >> 5)) * B_ + b] = s;
}
__device__ __forceinline__ void mbar_wait_fast(uint32_t bar, uint32_t parity) {
  asm volatile("{.reg .pred p; .reg .u32 n;\n"
               "mbarrier.try_wait.parity.shared::cta.b64 p,[%0],%1;\n"
               "@p bra DONE_%=;\n"
               "mov.u32 n,0;\n"
               "LOOP_%=: mbarrier.try_wait.parity.shared::cta.b64 p,[%0],%1;\n"
               "add.u32 n,n,1; setp.gt.or.u32 p,n,400000,p;\n"
               "@!p bra LOOP_%=;\n"
               "DONE_%=: }" :: "r"(bar), "r"(parity) : "memory");
}
__device__ __forceinline__ void sleep_until(uint32_t t0, uint32_t dt) { while ((uint32_t)clock() - t0 < dt) __nanosleep(40); }
__device__ __forceinline__ uint32_t s_mask(uint32_t v, int q) { return (1u << ((v + 3 - q) & 3)) | (16u << ((v + 3 + q) & 3)); }
__device__ __forceinline__ uint32_t s_cell(uint32_t v, int q, uint32_t m) {
  const int t = __ffs(~m) - 1;
  const int cp = t == 8 ? q >> 1 : ((t & 4 ? t - q : t + q) - v) & 3;
  return cp * 1001 + v;
}
__device__ __forceinline__ uint32_t pk3(uint32_t a, uint32_t b, uint32_t c) {
  const uint32_t w = c + (a << 12) + (b << 22); return __funnelshift_l(w, w, 27);
}
constexpr int TH = 256, NS = 8192 / TH, YD = DYD;
__host__ __device__ constexpr int ye_of(int s) { return s == 3 ? 0 : s == 11 ? 1 : s == 19 ? 2 : s == 23 ? 3 : -1; }
template <int N> __device__ __forceinline__ void wgmma_h(uint32_t* d, const uint32_t* a, uint64_t desc, int acc);
template <> __device__ __forceinline__ void wgmma_h<64>(uint32_t* d, const uint32_t* a, uint64_t desc, int acc) {
  asm volatile("{.reg .pred p; setp.ne.s32 p,%21,0;\n"
    "wgmma.mma_async.sync.aligned.m64n64k16.f16.f16.f16 {%0,%1,%2,%3,%4,%5,%6,%7,%8,%9,%10,%11,%12,%13,%14,%15},{%16,%17,%18,%19},%20,p,1,1,0;}"
    : "+r"(d[0]),"+r"(d[1]),"+r"(d[2]),"+r"(d[3]),"+r"(d[4]),"+r"(d[5]),"+r"(d[6]),"+r"(d[7]),"+r"(d[8]),"+r"(d[9]),"+r"(d[10]),"+r"(d[11]),"+r"(d[12]),"+r"(d[13]),"+r"(d[14]),"+r"(d[15])
    : "r"(a[0]), "r"(a[1]), "r"(a[2]), "r"(a[3]), "l"(desc), "r"(acc));
}
template <> __device__ __forceinline__ void wgmma_h<56>(uint32_t* d, const uint32_t* a, uint64_t desc, int acc) {
  asm volatile("{.reg .pred p; setp.ne.s32 p,%19,0;\n"
    "wgmma.mma_async.sync.aligned.m64n56k16.f16.f16.f16 {%0,%1,%2,%3,%4,%5,%6,%7,%8,%9,%10,%11,%12,%13},{%14,%15,%16,%17},%18,p,1,1,0;}"
    : "+r"(d[0]),"+r"(d[1]),"+r"(d[2]),"+r"(d[3]),"+r"(d[4]),"+r"(d[5]),"+r"(d[6]),"+r"(d[7]),"+r"(d[8]),"+r"(d[9]),"+r"(d[10]),"+r"(d[11]),"+r"(d[12]),"+r"(d[13])
    : "r"(a[0]), "r"(a[1]), "r"(a[2]), "r"(a[3]), "l"(desc), "r"(acc));
}
template <> __device__ __forceinline__ void wgmma_h<48>(uint32_t* d, const uint32_t* a, uint64_t desc, int acc) {
  asm volatile("{.reg .pred p; setp.ne.s32 p,%17,0;\n"
    "wgmma.mma_async.sync.aligned.m64n48k16.f16.f16.f16 {%0,%1,%2,%3,%4,%5,%6,%7,%8,%9,%10,%11},{%12,%13,%14,%15},%16,p,1,1,0;}"
    : "+r"(d[0]),"+r"(d[1]),"+r"(d[2]),"+r"(d[3]),"+r"(d[4]),"+r"(d[5]),"+r"(d[6]),"+r"(d[7]),"+r"(d[8]),"+r"(d[9]),"+r"(d[10]),"+r"(d[11])
    : "r"(a[0]), "r"(a[1]), "r"(a[2]), "r"(a[3]), "l"(desc), "r"(acc));
}
template <> __device__ __forceinline__ void wgmma_h<40>(uint32_t* d, const uint32_t* a, uint64_t desc, int acc) {
  asm volatile("{.reg .pred p; setp.ne.s32 p,%15,0;\n"
    "wgmma.mma_async.sync.aligned.m64n40k16.f16.f16.f16 {%0,%1,%2,%3,%4,%5,%6,%7,%8,%9},{%10,%11,%12,%13},%14,p,1,1,0;}"
    : "+r"(d[0]),"+r"(d[1]),"+r"(d[2]),"+r"(d[3]),"+r"(d[4]),"+r"(d[5]),"+r"(d[6]),"+r"(d[7]),"+r"(d[8]),"+r"(d[9])
    : "r"(a[0]), "r"(a[1]), "r"(a[2]), "r"(a[3]), "l"(desc), "r"(acc));
}
template <> __device__ __forceinline__ void wgmma_h<32>(uint32_t* d, const uint32_t* a, uint64_t desc, int acc) {
  asm volatile("{.reg .pred p; setp.ne.s32 p,%13,0;\n"
    "wgmma.mma_async.sync.aligned.m64n32k16.f16.f16.f16 {%0,%1,%2,%3,%4,%5,%6,%7},{%8,%9,%10,%11},%12,p,1,1,0;}"
    : "+r"(d[0]),"+r"(d[1]),"+r"(d[2]),"+r"(d[3]),"+r"(d[4]),"+r"(d[5]),"+r"(d[6]),"+r"(d[7])
    : "r"(a[0]), "r"(a[1]), "r"(a[2]), "r"(a[3]), "l"(desc), "r"(acc));
}
__device__ __forceinline__ void wgmma_p(float* d, const uint32_t* a, uint64_t desc, int acc) {
  asm volatile("{.reg .pred p; setp.ne.s32 p,%37,0;\n"
    "wgmma.mma_async.sync.aligned.m64n64k16.f32.bf16.bf16 {%0,%1,%2,%3,%4,%5,%6,%7,%8,%9,%10,%11,%12,%13,%14,%15,%16,%17,%18,%19,%20,%21,%22,%23,%24,%25,%26,%27,%28,%29,%30,%31},{%32,%33,%34,%35},%36,p,1,1,1;}"
    : "+f"(d[0]),"+f"(d[1]),"+f"(d[2]),"+f"(d[3]),"+f"(d[4]),"+f"(d[5]),"+f"(d[6]),"+f"(d[7]),"+f"(d[8]),"+f"(d[9]),"+f"(d[10]),"+f"(d[11]),"+f"(d[12]),"+f"(d[13]),"+f"(d[14]),"+f"(d[15]),"+f"(d[16]),"+f"(d[17]),"+f"(d[18]),"+f"(d[19]),"+f"(d[20]),"+f"(d[21]),"+f"(d[22]),"+f"(d[23]),"+f"(d[24]),"+f"(d[25]),"+f"(d[26]),"+f"(d[27]),"+f"(d[28]),"+f"(d[29]),"+f"(d[30]),"+f"(d[31])
    : "r"(a[0]), "r"(a[1]), "r"(a[2]), "r"(a[3]), "l"(desc), "r"(acc));
}

__device__ __forceinline__ void mma16816h(uint32_t* c, const uint32_t* a, uint32_t b0, uint32_t b1) {
  asm("mma.sync.aligned.m16n8k16.row.col.f16.f16.f16.f16 {%0,%1},{%2,%3,%4,%5},{%6,%7},{%0,%1};"
      : "+r"(c[0]), "+r"(c[1]) : "r"(a[0]), "r"(a[1]), "r"(a[2]), "r"(a[3]), "r"(b0), "r"(b1));
}
__device__ __forceinline__ void mma1688h(uint32_t* c, uint32_t a0, uint32_t a1, uint32_t b) {
  asm("mma.sync.aligned.m16n8k8.row.col.f16.f16.f16.f16 {%0,%1},{%2,%3},{%4},{%0,%1};" : "+r"(c[0]), "+r"(c[1]) : "r"(a0), "r"(a1), "r"(b));
}
__device__ __forceinline__ void mma1688f(float* c, uint32_t a0, uint32_t a1, uint32_t b) {
  asm("mma.sync.aligned.m16n8k8.row.col.f32.f16.f16.f32 {%0,%1,%2,%3},{%4,%5},{%6},{%0,%1,%2,%3};"
      : "+f"(c[0]), "+f"(c[1]), "+f"(c[2]), "+f"(c[3]) : "r"(a0), "r"(a1), "r"(b));
}
__device__ __forceinline__ uint32_t hadd2(uint32_t a, uint32_t b) { uint32_t r; asm("add.rn.f16x2 %0,%1,%2;" : "=r"(r) : "r"(a), "r"(b)); return r; }
__device__ __forceinline__ uint32_t hfma2(uint32_t a, uint32_t b, uint32_t c) { uint32_t r; asm("fma.rn.f16x2 %0,%1,%2,%3;" : "=r"(r) : "r"(a), "r"(b), "r"(c)); return r; }
__device__ __forceinline__ uint32_t pack_bf2(float lo, float hi) { uint32_t r; asm("cvt.rn.bf16x2.f32 %0,%1,%2;" : "=r"(r) : "f"(hi), "f"(lo)); return r; }
__device__ __forceinline__ uint32_t pack_h2(float lo, float hi) { uint32_t r; asm("cvt.rn.f16x2.f32 %0,%1,%2;" : "=r"(r) : "f"(hi), "f"(lo)); return r; }
__device__ __forceinline__ float bf_lo(uint32_t w) { return __uint_as_float(w << 16); }
__device__ __forceinline__ float bf_hi(uint32_t w) { return __uint_as_float(w & 0xffff0000u); }
__device__ __forceinline__ uint32_t absmax4(const uint4& v, uint32_t m) {
  return __vmaxu2(__vmaxu2(__vmaxu2(v.x & 0x7fff7fffu, v.y & 0x7fff7fffu), __vmaxu2(v.z & 0x7fff7fffu, v.w & 0x7fff7fffu)), m);
}
__device__ __forceinline__ float pow2_scale(uint32_t mbits, int p) { return __uint_as_float((uint32_t)min(max(253 + p - (int)(mbits >> 7), 2), 252) << 23); }

#define PV 4
constexpr int G_O0 = 8, G_O1 = 4, G_O2 = 0, G_N0 = 5, G_N1 = 4, G_N2 = 4, G_K0 = 5, G_K1 = 3, G_K2 = 1;
__host__ __device__ constexpr bool unit_wg(int kb, int on) {
  return (on >= G_O0 && on < G_O0 + G_N0 && kb < G_K0) || (on >= G_O1 && on < G_O1 + G_N1 && kb < G_K1) || (on >= G_O2 && on < G_O2 + G_N2 && kb < G_K2);
}
__host__ __device__ constexpr bool oct_wg(int on) { return unit_wg(0, on); }
constexpr int G_U1 = G_N0 * G_K0, G_U2 = G_U1 + G_N1 * G_K1, G_U = G_U2 + G_N2 * G_K2;
constexpr int K1_B = 130048, K1_STG = K1_B + 3 * 16384, K1_W = K1_STG + 2 * 16384, K1_BAR = K1_W + 48 * 256, K1_SMEM = K1_BAR + 256 + 4352;
__host__ __device__ constexpr int frag_index(int ok, int on) {
  int n = 0;
  for (int k = 0; k < 13; k++) for (int o = k; o < 13; o++) { if (k == ok && o == on) return n; if (!unit_wg(k >> 1, o)) n++; }
  return n;
}
constexpr int HU_N = 2 * G_U + frag_index(99, 99);
static_assert(HU_N <= 96, "");
struct FragIdx { int v[13][13]; };
__host__ __device__ constexpr FragIdx make_fi() { FragIdx f = {}; for (int k = 0; k < 13; k++) for (int o = 0; o < 13; o++) f.v[k][o] = frag_index(k, o); return f; }
__host__ __device__ constexpr uint64_t frag_tab(int first) {
  uint64_t t = 0;
  for (int k = 0; k < 13; k++) for (int o = k; o < 13; o++)
    if (!unit_wg(k >> 1, o)) { const int n = frag_index(k, o) - first; if (n >= 0 && n < 8) t |= (uint64_t)(k << 4 | o) << (8 * n); }
  return t;
}
__device__ __forceinline__ int hu_code(int hu) {
  constexpr uint64_t T0 = frag_tab(0), T1 = frag_tab(8), T2 = frag_tab(16), T3 = frag_tab(24);
  const int u = hu >> 1, f = hu - 2 * G_U;
  if (f >= 0) return (int)((f < 8 ? T0 : f < 16 ? T1 : f < 24 ? T2 : T3) >> (8 * (f & 7))) & 255;
  const int u0 = u < G_U1 ? u : u < G_U2 ? u - G_U1 : u - G_U2;
  const int kb = u < G_U1 ? u0 / G_N0 : u < G_U2 ? u0 / G_N1 : u0 / 4, on = u < G_U1 ? G_O0 + u0 % G_N0 : u < G_U2 ? G_O1 + u0 % G_N1 : G_O2 + u0 % 4;
  return (2 * kb + (hu & 1)) << 4 | on;
}

__device__ __forceinline__ void flag_arrive(unsigned* f, int lane) {
  __threadfence(); __syncwarp();
  if (lane == 0) asm volatile("red.release.gpu.global.add.u32 [%0],1;" :: "l"(f) : "memory");
}
__device__ __forceinline__ void flag_wait(const unsigned* f, unsigned n) {
  unsigned v; int it = 0;
  asm volatile("ld.acquire.gpu.global.u32 %0,[%1];" : "=r"(v) : "l"(f) : "memory");
  if (v < n) {
    do { __nanosleep(300); asm volatile("ld.relaxed.gpu.global.u32 %0,[%1];" : "=r"(v) : "l"(f) : "memory"); } while (v < n && ++it < (1 << 20));
    asm volatile("ld.acquire.gpu.global.u32 %0,[%1];" : "=r"(v) : "l"(f) : "memory");
  }
}
__device__ __forceinline__ void mbar_arrive(uint32_t bar) { asm volatile("mbarrier.arrive.shared::cta.b64 _,[%0];" :: "r"(bar) : "memory"); }
__device__ __forceinline__ void mbar_arrive_lane0(uint32_t bar) {
  asm volatile("{.reg .pred p; elect.sync _|p,0xffffffff; @p mbarrier.arrive.shared::cta.b64 _,[%0];}" :: "r"(bar) : "memory");
}

__device__ __forceinline__ void arrive_both(uint32_t bar, int lane) {
  asm volatile("{.reg .pred p; .reg .u32 a; setp.lt.u32 p,%1,2; mapa.shared::cluster.u32 a,%0,%1;\n"
               "@p mbarrier.arrive.shared::cluster.b64 _,[a];}" :: "r"(bar), "r"(lane) : "memory");
}
__device__ __forceinline__ void pack_role(const int* __restrict__ idx, uint32_t sbase, int pc) {
  constexpr int CH = 3200 + 32, BUF = 32 * 3328;
  const int tid = threadIdx.x, lane = tid & 31, warp = tid >> 5;
  const uint32_t full = sbase + 2 * BUF, empty = full + 16;
  if (tid == 0) { mbar_init(full, 1); mbar_init(full + 8, 1); mbar_init(empty, 18); mbar_init(empty + 8, 18); asm volatile("fence.proxy.async.shared::cta;" ::: "memory"); }
  __syncthreads();
  auto chunk = [&](int s) { return s * 3200 + (s >> 2) * 288; };
  auto load = [&](int n) {
    const int blk = pc * 16 + n;
    if (lane == 0) mbar_expect(full + (n & 1) * 8, 32 * 3200);
    __syncwarp();
    bulk_g2s(sbase + (n & 1) * BUF + chunk(lane), idx + ((blk >> 5) * 8192 + lane * TH + (blk & 31) * 8) * F_, 3200, full + (n & 1) * 8);
  };
  if (warp == 0) { load(0); load(1); }
  const int l = lane & 7;
  uint32_t rot[8], inc[3];
#pragma unroll
  for (int jj = 0; jj < 8; jj++) rot[jj] = ((l + jj) & 7) * 4;
#pragma unroll
  for (int q = 0; q < 3; q++) inc[q] = (l + 3 * q < 8) << 12 | (l + 3 * q + 1 < 8) << 22 | (q < 2 && l + 3 * q + 2 < 8);
  int loaded = 2;
#pragma unroll 1
  for (int task = warp; task < 288; task += 16) {
    const int n = task / 18, q = (task % 18) * 4 + (lane >> 3), sq = q / 9, k = q % 9;
    if (warp == 0 && n + 1 == loaded && loaded < 16) { mbar_wait(empty + (loaded & 1) * 8, ((loaded >> 1) - 1) & 1); load(loaded); loaded++; }
    mbar_wait(full + (n & 1) * 8, (n >> 1) & 1);
    const uint32_t buf = sbase + (n & 1) * BUF + l * 400, row = buf + chunk(sq * 4);
    auto ld = [&](uint32_t ad) { uint32_t v; asm volatile("ld.shared.u32 %0,[%1];" : "=r"(v) : "r"(ad)); return v; };
    const int blk = pc * 16 + n, half = blk >> 5, col = (blk & 31) * 8 + l;
    const int ks = k == NC - 1 ? 0 : k + 1;
    uint32_t cw[4], sv[8], m[2] = {0, 0};
    { const uint32_t a0 = row + (72 + 2 * ks + (l >> 2)) * 4;
#pragma unroll
      for (int u = 0; u < 8; u++) { sv[u] = ld((a0 ^ ((u >> 2) * 4)) + (u & 3) * 3200); m[u >> 2] |= s_mask(sv[u], l & 3) << (8 * (u & 3)); } }
#pragma unroll
    for (int h = 0; h < 2; h++) { m[h] |= __shfl_xor_sync(0xffffffffu, m[h], 1); m[h] |= __shfl_xor_sync(0xffffffffu, m[h], 2); }
#pragma unroll
    for (int u = 0; u < 4; u++) cw[u] = s_cell(sv[u], l & 3, (m[0] >> (8 * u)) & 255) | s_cell(sv[4 + u], l & 3, (m[1] >> (8 * u)) & 255) << 12;
    if (k == NC - 1) {
      g_scr[I0_OFF + (half * 8 + sq) * TH + col] = make_uint4(cw[0], cw[1], cw[2], cw[3]);
      g_scr[IX_OFF + half * IXH + NC * 8192 + sq * TH + col] = make_uint4(ld(row + 396), ld(row + 3596), ld(row + 6796), ld(row + 9996));
      cw[0] = cw[1] = cw[2] = cw[3] = 0;
    }
    const uint32_t ax = buf + chunk(min(sq + 1, 7) * 4) + (90 + k) * 4;
    const uint32_t yev = ld(buf + ((0x3210 >> (sq * 2 + (sq == 5) * 2)) & 3) * 3200 + (90 + k) * 4);
    uint4* dst = g_scr + IX_OFF + half * IXH + (k * NS + sq * 4) * TH + col;
#pragma unroll
    for (int u = 0; u < 4; u++) {
      uint32_t e[8];
#pragma unroll
      for (int jj = 0; jj < 8; jj++) e[jj] = ld(row + k * 32 + rot[jj] + u * 3200);
      dst[u * TH] = make_uint4(pk3(e[0], e[1], e[2] + inc[0]), pk3(e[3], e[4], e[5] + inc[1]), pk3(e[6], e[7], ld(ax + u * 3200) + inc[2]),
                               u < 3 ? __byte_perm(cw[u], cw[3], 0x4210 + (u << 12)) : yev);
    }
    mbar_arrive_lane0(empty + (n & 1) * 8);
  }
  (void)CH;
}

__global__ void __cluster_dims__(2, 1, 1) __launch_bounds__(512, 1)
k_tens(const __grid_constant__ CUtensorMap mapW, const __grid_constant__ CUtensorMap mapL, const __grid_constant__ CUtensorMap mapS,
       const __grid_constant__ CUtensorMap mapT, const __grid_constant__ CUtensorMap mapE, const __grid_constant__ CUtensorMap mapC, cudaTextureObject_t tex, cudaTextureObject_t texX,
       const int* __restrict__ idx, const __nv_bfloat16* __restrict__ table, const __nv_bfloat16* __restrict__ wp, const __nv_bfloat16* __restrict__ w1,
       const __nv_bfloat16* __restrict__ b1, int never) {
  extern __shared__ __align__(1024) uint4 sm[];
  const int tid = threadIdx.x, lane = tid & 31, cta = blockIdx.x;
  const uint32_t sbase = (uint32_t)__cvta_generic_to_shared(sm);
  const int g = lane >> 2, r = lane & 3;
  TS(0, 0);
  if (cta >= 128) {
    pack_role(idx, sbase, cta - 128);
    __syncthreads();
    if (tid < 32) flag_arrive(&g_flag[8 * 32], lane);
    TS(2, 1);
    asm volatile("barrier.cluster.arrive.relaxed.aligned; barrier.cluster.wait.aligned;" ::: "memory");
    return;
  }
  const uint32_t fullB = sbase + K1_BAR, emptyB = fullB + 24, fullE = fullB + 48, fullC = fullB + 56, fullI = fullB + 64, fullX = fullB + 72, progG = fullB + 80, fullS = fullB + 96, emptyS = fullB + 128;
  const int rb = cta & 7, hc = cta >> 3;
  auto uq = [&](int q) { return SWP && q < 18 ? (q & ~1) | (hc & 1) : q; };
  auto uh = [&](int q) { return SWP && q < 18 ? (hc & ~1) | (q & 1) : hc; };
  if (MCW && (tid >> 5) != 12) asm volatile("barrier.cluster.arrive.relaxed.aligned;" ::: "memory");
  if (tid >= 384) {
    asm volatile("setmaxnreg.dec.sync.aligned.u32 " RAUX ";");
    if (tid < 416) {
      auto load_pair = [&](int p, int st) {
        mbar_expect(fullB + st * 8, 16384);
        asm volatile("cp.async.bulk.tensor.2d.shared::cluster.global.mbarrier::complete_tx::bytes.multicast::cluster [%0],[%1,{%2,%3}],[%4],%5;"
                     :: "r"(sbase + K1_B + st * 16384 + (cta & 1) * 8192), "l"(&mapW), "r"(uh(QORD(p >> 1)) * 32),
                        "r"(uq(QORD(p >> 1)) * 512 + (p & 1) * 256 + (cta & 1) * 128), "r"(fullB + st * 8), "h"((unsigned short)3) : "memory");
        p += WPF;
        if (p < 50) {
          int pr = QORD(p >> 1) * 2 + (p & 1);
          if (SWP && pr < 36) pr = (pr & ~3) | ((pr & 1) << 1) | ((pr >> 1) & 1);
          bulk_pf(w1 + pr * 131072 + cta * 1024, 2048);
        }
      };
      if (tid == 384) {
        for (int q = 0; q < 3; q++) { mbar_init(fullB + q * 8, 1); mbar_init(emptyB + q * 8, MCW ? 8 : 4); }
        for (int q = 0; q < 4; q++) { mbar_init(fullS + q * 8, 4); mbar_init(emptyS + q * 8, 1); }
        mbar_init(fullE, 1); mbar_init(fullC, 1); mbar_init(fullI, 1); mbar_init(fullX, 1); mbar_init(progG, 1);
        asm volatile("fence.proxy.async.shared::cta;" ::: "memory");
        mbar_expect(fullC, 16384);
        for (int q = 0; q < 4; q++)
          asm volatile("cp.async.bulk.tensor.2d.shared::cluster.global.mbarrier::complete_tx::bytes [%0],[%1,{%2,%3}],[%4];"
                       :: "r"(sbase + 32768 + q * 4096), "l"(&mapC), "r"((cta & 15) * 8), "r"(q * 256), "r"(fullC) : "memory");
        mbar_expect(fullE, 32768);
        for (int q = 0; q < 2; q++)
          asm volatile("cp.async.bulk.tensor.2d.shared::cluster.global.mbarrier::complete_tx::bytes [%0],[%1,{%2,%3}],[%4];"
                       :: "r"(sbase + K1_STG + q * 16384), "l"(&mapE), "r"(q * 64), "r"(rb * 128), "r"(fullE) : "memory");
      }
      __syncwarp();
      asm volatile("bar.arrive 2,448;" ::: "memory");
      if (MCW) asm volatile("fence.mbarrier_init.release.cluster; barrier.cluster.arrive.relaxed.aligned; barrier.cluster.wait.aligned;" ::: "memory");
      if (tid == 384) {
        int st = 0, ph = 1;
        const uint32_t tl0 = clock();
#pragma unroll 1
        for (int p = 0; p < 50; p++) {
          if (p == IORD) {
            mbar_expect(fullI, 51200);
#pragma unroll 1
            for (int q = 0; q < 8; q++) bulk_g2s(sbase + 76800 + q * 6400, idx + (((cta >> 4) * 8 + q) * 256 + (cta & 15) * 16) * F_, 6400, fullI);
          }
          if (PDT && p > PP0) sleep_until(tl0, PT0 + (p - PP0) * PDT);
          mbar_wait(emptyB + st * 8, ph);
          load_pair(p, st);
          if (++st == 3) { st = 0; ph ^= 1; }
        }
      }
    } else if (tid < 448) {
      ((float4*)g_acc)[cta * 32 + lane] = make_float4(0.f, 0.f, 0.f, 0.f);
      asm volatile("bar.sync 2,448;" ::: "memory");
      if (HOLD) { asm volatile("bar.sync 4,288;" ::: "memory"); flag_arrive(&g_flag[(cta >> 4) * 32], lane); }
      __syncwarp();
      if (tid == 416) {
#pragma unroll 1
        for (int n = 0; n < 50; n++) {
          const int quad = QORD(n >> 1), mt = n & 1, v0 = rb * 128 + mt * 64;
          const uint32_t stg = sbase + K1_STG + mt * 16384;
          const uint64_t pol = n < 2 * NEF ? POL_EF : POL_N;
          mbar_wait(fullS + mt * 8, (n >> 1) & 1);
          asm volatile("fence.proxy.async.shared::cta;" ::: "memory");
          if (quad < 18) {
            asm volatile("cp.async.bulk.tensor.4d.global.shared::cta.bulk_group.L2::cache_hint [%0,{%1,%2,%3,%4}],[%5],%6;"
                         :: "l"(&mapL), "r"((uq(quad) & 1) * 32), "r"(v0), "r"(quad >> 1), "r"(uh(quad) * 4), "r"(stg), "l"(pol) : "memory");
          } else {
#pragma unroll 1
            for (int hh = 0; hh < 2; hh++) {
              const int pq = quad * 2 + hh;
              if (pq < 45) asm volatile("cp.async.bulk.tensor.4d.global.shared::cta.bulk_group.L2::cache_hint [%0,{%1,%2,%3,%4}],[%5],%6;"
                         :: "l"(&mapS), "r"(0), "r"(v0 >> 2), "r"(pq - 36), "r"(hc * 4), "r"(stg + hh * 8192), "l"(pol) : "memory");
              else asm volatile("cp.async.bulk.tensor.3d.global.shared::cta.bulk_group.L2::cache_hint [%0,{%1,%2,%3}],[%4],%5;"
                         :: "l"(&mapT), "r"(v0 * 2), "r"((pq - 45) * 2), "r"(hc * 4), "r"(stg + hh * 8192), "l"(pol) : "memory");
            }
          }
          asm volatile("cp.async.bulk.commit_group;" ::: "memory");
          asm volatile("cp.async.bulk.wait_group.read 0;" ::: "memory");
          mbar_arrive(emptyS + mt * 8);
        }
        asm volatile("cp.async.bulk.wait_group 0;" ::: "memory");
        asm volatile("fence.proxy.async.global;" ::: "memory");
        __threadfence();
        asm volatile("red.release.gpu.global.add.u32 [%0],1;" :: "l"(&g_flag[8 * 32]) : "memory");
        flag_wait(&g_flag[8 * 32], 132);
        asm volatile("fence.proxy.async.global;" ::: "memory");
        const char* base = (const char*)g_scr;
        const int c = cta >> 1, half = cta & 1, ch = (c + (c >> 4) * 5) & 15;
        bulk_pf(base + (PS_OFF + c * NC * 2000) * 16u + half * 16000, 16000);
        if (PREW & 2) bulk_pf(base + (PL_OFF + c * NC * 8000) * 16u + half * 64000, 64000);
        bulk_pf(base + (PT_OFF + c * 10 * 1024) * 16u + half * 8192, 8192);
        mbar_expect(fullE, 18432);
        bulk_g2s(sbase + K1_STG, base + (I0_OFF + half * 2048 + ch * 128) * 16u, 2048, fullE);
        bulk_g2s(sbase + K1_STG + 2048, base + (IX_OFF + half * IXH + ch * 512) * 16u, 8192, fullE);
        bulk_g2s(sbase + K1_STG + 10240, base + (IX_OFF + half * IXH + 8192 + ch * 512) * 16u, 8192, fullE);
        mbar_wait(fullE, 1);
      }
    } else if (tid >= 480) {
      if (!HOLD) { asm volatile("bar.sync 4,288;" ::: "memory"); flag_arrive(&g_flag[(cta >> 4) * 32], lane); }
    } else if (tid == 448 && PXW) {
      flag_wait(&g_flag[(cta >> 4) * 32], 16);
      asm volatile("fence.proxy.async.global;" ::: "memory");
      const char* src = (const char*)(g_scr + PX_OFF + ((cta >> 4) * 8 + ((cta >> 1) & 3) * 2) * 16 * 136);
#pragma unroll 1
      for (int n = 1; n < 16; n++) {
        if (n >= PXW) mbar_wait(progG, (n - PXW) & 1);
        mbar_expect(fullX, 4352);
        bulk_g2s(sbase + K1_BAR + 256, src + n * 2176, 2176, fullX);
        bulk_g2s(sbase + K1_BAR + 256 + 2176, src + (16 + n) * 2176, 2176, fullX);
        mbar_wait(fullX, (n - 1) & 1);
      }
    }
    return;
  }
  if (tid >= 256) {
    asm volatile("setmaxnreg.inc.sync.aligned.u32 " RPRO ";");
    const int w = (tid >> 5) & 3;
    const int srow = w * 16 + (lane & 7) + ((lane >> 3) & 1) * 8, sc = lane >> 4;
    uint32_t a[2][8][4];
    asm volatile("bar.sync 2,448;" ::: "memory");
    mbar_wait_fast(fullE, 0);
#pragma unroll
    for (int mt = 0; mt < 2; mt++)
#pragma unroll
      for (int ks = 0; ks < 8; ks++)
        asm volatile("ldmatrix.sync.aligned.m8n8.x4.shared.b16 {%0,%1,%2,%3},[%4];"
                     : "=r"(a[mt][ks][0]), "=r"(a[mt][ks][1]), "=r"(a[mt][ks][2]), "=r"(a[mt][ks][3])
                     : "r"(sbase + K1_STG + (ks >> 2) * 16384 + (mt * 64 + srow) * 128 + ((((ks & 3) * 2 + sc) ^ (lane & 7)) * 16)) : "memory");
    asm volatile("bar.sync 5,128;" ::: "memory");
    const uint32_t baseL = sc * 4096 + srow * 64 + ((srow >> 1) & 3) * 16, baseS = sc * 2048 + ((srow * 32) ^ (((srow >> 2) & 7) * 16)), baseT = sc * 2048 + srow * 16;
    const uint64_t desc0 = (uint64_t)(((sbase + K1_B) & 0x3FFFF) >> 4) | ((uint64_t)(8192 >> 4) << 16) | ((uint64_t)(512 >> 4) << 32) | (2ull << 62);
    float d[2][32];
    auto issue = [&](int x, int mt, int st) {
      uint32_t a7[4];
#pragma unroll
      for (int e = 0; e < 4; e++) { if (PARK) asm volatile("add.u32 %0,%1,%2;" : "=r"(a7[e]) : "r"(a[mt][7][e]), "r"(never)); else a7[e] = a[mt][7][e]; }
      asm volatile("wgmma.fence.sync.aligned;" ::: "memory");
#pragma unroll
      for (int ks = 0; ks < 8; ks++) wgmma_p(d[x], ks < 7 ? a[mt][ks] : a7, desc0 + st * 1024 + ks * 64, ks);
      asm volatile("wgmma.commit_group.sync.aligned;" ::: "memory");
    };
    auto wait_acc = [&](int x) {
      asm volatile("wgmma.wait_group.sync.aligned 0;" ::: "memory");
#pragma unroll
      for (int q = 0; q < 8; q++) asm volatile("" : "+f"(d[x][q * 4]), "+f"(d[x][q * 4 + 1]), "+f"(d[x][q * 4 + 2]), "+f"(d[x][q * 4 + 3]) :: "memory");
    };
    mbar_wait_fast(fullB, 0);
    issue(0, 0, 0);
    int s0 = 0, ph = 0;
#pragma unroll 1
    for (int qn = 0; qn < 25; qn++) {
      const int quad = QORD(qn);
      const int s1 = s0 == 2 ? 0 : s0 + 1, s2 = s1 == 2 ? 0 : s1 + 1, ph1 = ph ^ (s1 == 0), ph2 = ph1 ^ (s2 == 0);
#pragma unroll
      for (int step = 0; step < 4; step++) {
        const int mt = ORD ? step & 1 : step >> 1, h = ORD ? step >> 1 : step & 1, x = step & 1, nx = (step + 1) & 3;
        const bool isL = quad < 18, isS = quad * 2 + h < 45;
        const uint32_t base = (isL ? baseL ^ (h * 32) : (isS ? baseS : baseT) ^ (h * 8192)), xj = (isL || isS) ? 16 : 1024, xc = isL ? 8192 : 4096;
        PT(qn * 16 + step * 4);
        if (h == 0) mbar_wait_fast(emptyS + mt * 8, (qn & 1) ^ 1);
        if (step == (ORD ? 1 : 0)) mbar_wait_fast(fullB + s1 * 8, ph1);
        if (step == 3) mbar_wait_fast(fullB + s2 * 8, qn == 24 ? ph2 ^ 1 : ph2);
        PT(qn * 16 + step * 4 + 1);
        wait_acc(x);
        PT(qn * 16 + step * 4 + 2);
        if (mt) { if (MCW) arrive_both(emptyB + (h ? s1 : s0) * 8, 2 * qn + h < 47 ? lane : 9); else mbar_arrive_lane0(emptyB + (h ? s1 : s0) * 8); }
        issue(x ^ 1, ORD ? nx & 1 : nx >> 1, step == 3 ? s2 : (ORD ? nx >> 1 : nx & 1) ? s1 : s0);
        PT(qn * 16 + step * 4 + 3);
        if (h && quad == 24) {
#pragma unroll
          for (int cq = 0; cq < 4; cq++) {
            const uint32_t bw = __ldg((const uint32_t*)(b1 + hc * 32 + cq * 8) + r);
#pragma unroll
            for (int e = 0; e < 4; e++) d[x][16 + cq * 4 + e] += (e & 1) ? bf_hi(bw) : bf_lo(bw);
          }
        }
#pragma unroll
        for (int e4 = 0; e4 < 4; e4++) {
          const float* e = d[x] + e4 * 8;
          asm volatile("stmatrix.sync.aligned.m8n8.x4.shared.b16 [%0],{%1,%2,%3,%4};"
                       :: "r"(sbase + K1_STG + mt * 16384 + (base ^ ((e4 >> 1) * xj) ^ ((e4 & 1) * xc))),
                          "r"(pack_bf2(e[0], e[1])), "r"(pack_bf2(e[2], e[3])), "r"(pack_bf2(e[4], e[5])), "r"(pack_bf2(e[6], e[7])) : "memory");
        }
        if (h) { __syncwarp(); mbar_arrive_lane0(fullS + mt * 8); }
      }
      s0 = s2; ph = ph2;
    }
    asm volatile("wgmma.wait_group.sync.aligned 0;" ::: "memory");
    return;
  }
  asm volatile("setmaxnreg.inc.sync.aligned.u32 " RPNN ";");
  const int slice = cta & 15;
  const int range = (cta >> 4) * 8 + __shfl_sync(0xffffffffu, tid >> 5, 0);
  uint4 iv[4], trow[4]; uint32_t ix;
  uint2 wrow[10];
#pragma unroll
  for (int q = 0; q < 10; q++) asm volatile("ld.global.nc.v2.u32 {%0,%1},[%2];" : "=r"(wrow[q].x), "=r"(wrow[q].y) : "l"((const uint2*)wp + min(tid + q * 256, 2499)));
  asm volatile("bar.sync 2,448;" ::: "memory");
  uint32_t me = 0, mw = 0;
#pragma unroll
  for (int q = 0; q < 10; q++) {
    mw = __vmaxu2(__vmaxu2(wrow[q].x & 0x7fff7fffu, wrow[q].y & 0x7fff7fffu), mw);
    const int e = min(tid + q * 256, 2499), row = e / 25;
    asm volatile("st.shared.v2.u32 [%0],{%1,%2};" :: "r"(sbase + (e + row) * 8), "r"(wrow[q].x), "r"(wrow[q].y) : "memory");
    if (e - row * 25 == 24) asm volatile("st.shared.v2.u32 [%0],{%1,%2};" :: "r"(sbase + (e + row) * 8 + 8), "r"(wrow[q].x), "r"(wrow[q].y) : "memory");
  }
  mbar_wait_fast(fullC, 0);
#pragma unroll
  for (int q = 0; q < 4; q++) { trow[q] = lds128(sbase + 32768 + (tid + q * 256) * 16); me = absmax4(trow[q], me); }
  me = __reduce_max_sync(0xffffffffu, max(me & 0xffff, me >> 16));
  mw = __reduce_max_sync(0xffffffffu, max(mw & 0xffff, mw >> 16));
  uint32_t* sred = (uint32_t*)((char*)sm + 128000);
  if (lane == 0) sred[tid >> 5] = me | mw << 16;
  TS(3, 0);
  asm volatile("bar.sync 1,256;" ::: "memory");
  { uint32_t m = 0;
#pragma unroll
    for (int q = 0; q < 8; q++) m = __vmaxu2(m, sred[q]);
    m = __shfl_sync(0xffffffffu, m, 0);
    me = m & 0xffff; mw = m >> 16; }
  const float se = pow2_scale(me, 3), sW = pow2_scale(mw, -2);
  TS(3, 1);
  auto put_rows = [&](int q, bool on) {
    const uint4 t = trow[q];
    const uint4 hv = make_uint4(pack_h2(bf_lo(t.x) * se, bf_hi(t.x) * se), pack_h2(bf_lo(t.y) * se, bf_hi(t.y) * se),
                                pack_h2(bf_lo(t.z) * se, bf_hi(t.z) * se), pack_h2(bf_lo(t.w) * se, bf_hi(t.w) * se));
    if (on)
#pragma unroll
      for (int s = 0; s < 8; s++) sts128(sbase + (tid + q * 256) * 128 + ((s + lane) & 7) * 16, hv);
  };
#pragma unroll 1
  for (int it = 0; it < 3; it++) {
    const int hu = ((tid >> 5) * 3 + it) * 4, code = hu_code(min(hu + (lane >> 3), HU_N - 1)), ok = code >> 4, on = code & 15;
    uint32_t x[4], y[4];
    asm volatile("ldmatrix.sync.aligned.m8n8.x4.shared.b16 {%0,%1,%2,%3},[%4];" : "=r"(x[0]), "=r"(x[1]), "=r"(x[2]), "=r"(x[3])
                 : "r"(sbase + (on * 8 + (lane & (on == 12 ? 3 : 7))) * 208 + ok * 16) : "memory");
    asm volatile("ldmatrix.sync.aligned.m8n8.x4.trans.shared.b16 {%0,%1,%2,%3},[%4];" : "=r"(y[0]), "=r"(y[1]), "=r"(y[2]), "=r"(y[3])
                 : "r"(sbase + (ok * 8 + (lane & (ok == 12 ? 3 : 7))) * 208 + on * 16) : "memory");
    const uint32_t lo = __ballot_sync(0xffffffffu, ok > on), dg = __ballot_sync(0xffffffffu, ok >= on);
#pragma unroll
    for (int q = 0; q < 4; q++) {
      const float m0 = (lo >> (8 * q)) & 1 ? 0.f : sW, m1 = (dg >> (8 * q)) & 1 ? 0.f : sW;
      asm volatile("st.shared.u32 [%0],%1;" :: "r"(sbase + K1_W + (hu + q) * 128 + lane * 4),
                   "r"(pack_h2(fmaf(bf_lo(x[q]), m0, bf_lo(y[q]) * m1), fmaf(bf_hi(x[q]), m0, bf_hi(y[q]) * m1))) : "memory");
    }
  }
  put_rows(1, true); put_rows(2, tid < 88);
  TS(3, 2);
  asm volatile("fence.proxy.async.shared::cta;" ::: "memory");
  asm volatile("bar.sync 1,256;" ::: "memory");
  put_rows(0, true);
  uint32_t bf[HU_N - 2 * G_U];
#pragma unroll
  for (int q = 0; q < HU_N - 2 * G_U; q++) asm volatile("ld.shared.u32 %0,[%1];" : "=r"(bf[q]) : "r"(sbase + K1_W + (2 * G_U + q) * 128 + lane * 4));
  const float unscale = __uint_as_float(0x7f000000u - __float_as_uint(se)), unscale2 = __uint_as_float(0x7f000000u - __float_as_uint(sW));
  TS(3, 3);
  const int px = range * 16 * 136;
  mbar_wait_fast(fullI, 0);
  {
    const uint32_t ib = sbase + 76800 + (tid >> 5) * 6400, p0 = ib + ((lane >> 3) & 1) * 400 + ((lane >> 4) * 8 + (lane & 7)) * 4;
    auto ld = [&](uint32_t ad) { uint32_t v; asm volatile("ld.shared.u32 %0,[%1];" : "=r"(v) : "r"(ad)); return v; };
    auto wd = [&](int t, int h) { return pk3(ld(p0 + t * 800 + h * 192), ld(p0 + t * 800 + h * 192 + 64), ld(p0 + t * 800 + h * 192 + 128)); };
#pragma unroll
    for (int q = 0; q < 4; q++) {
      iv[q] = make_uint4(wd(2 * q, 0), wd(2 * q, 1), wd(2 * q + 1, 0), wd(2 * q + 1, 1));
      g_scr[PX_OFF + px + slice * 136 + q * 32 + lane] = iv[q];
    }
    ix = pk3(ld(ib + g * 400 + 384 + r * 4), ld(ib + (8 + g) * 400 + 384 + r * 4), 0);
    ((uint32_t*)(g_scr + PX_OFF + px + slice * 136 + 128))[lane] = ix;
  }
  asm volatile("bar.arrive 4,288;" ::: "memory");
  asm volatile("bar.sync 1,256;" ::: "memory");
  put_rows(2, tid >= 88); put_rows(3, tid + 768 < V_);
  asm volatile("bar.sync 1,256;" ::: "memory");
  TS(0, 1);
  uint32_t lc; asm volatile("add.u32 %0,%1,%2;" : "=r"(lc) : "r"((lane & 7) * 16), "r"(never));
  const uint64_t wdesc = (uint64_t)(((sbase + K1_W) & 0x3FFFF) >> 4) | ((uint64_t)(128 >> 4) << 16) | ((uint64_t)(256 >> 4) << 32);
  uint32_t a[2][6][4], d[2][26], ex[4] = {}, s[4] = {};
  float red[4] = {0.f, 0.f, 0.f, 0.f};
  auto ldsm = [&](uint32_t* o, uint32_t sh, uint32_t dep = 0) {
    asm volatile("ldmatrix.sync.aligned.m8n8.x4.trans.shared.b16 {%0,%1,%2,%3},[%4];"
                 : "=r"(o[0]), "=r"(o[1]), "=r"(o[2]), "=r"(o[3]) : "r"(sbase + ((sh & 0x1ff80) | (lc | (dep & never)))));
  };
  auto gather = [&](int t, int hf) {
    const int x = t & 1;
    const uint4 v = iv[(t >> 1) & 3];
#pragma unroll
    for (int kb = 3 * hf; kb < 3 * hf + 3; kb++) {
      const uint32_t ww = x ? (kb < 3 ? v.z : v.w) : (kb < 3 ? v.x : v.y);
      ldsm(a[x][kb], kb % 3 == 0 ? ww : kb % 3 == 1 ? ww >> 10 : __funnelshift_l(ww, ww, 12));
    }
  };
  auto issue = [&](int x) {
    asm volatile("wgmma.fence.sync.aligned;" ::: "memory");
#pragma unroll
    for (int kb = 0; kb < 6; kb++) {
      if (kb < G_K0) wgmma_h<G_N0 * 8>(d[x] + G_O0 * 2, a[x][kb], wdesc + kb * G_N0 * 16, kb);
      if (kb < G_K1) wgmma_h<G_N1 * 8>(d[x] + G_O1 * 2, a[x][kb], wdesc + (G_U1 + kb * G_N1) * 16, kb);
      if (kb < G_K2) wgmma_h<32>(d[x] + G_O2 * 2, a[x][kb], wdesc + (G_U2 + kb * G_N2) * 16, kb);
    }
    asm volatile("wgmma.commit_group.sync.aligned;" ::: "memory");
  };
  auto hmma_part = [&](int t) {
    constexpr FragIdx FI = make_fi();
    const int x = t & 1;
#pragma unroll
    for (int o = 0; o < 13; o++) {
      if (oct_wg(o)) asm volatile("" : "+r"(d[x][o * 2]), "+r"(d[x][o * 2 + 1]) :: "memory"); else d[x][o * 2] = d[x][o * 2 + 1] = 0;
    }
#pragma unroll
    for (int kb = 0; kb < 6; kb++)
#pragma unroll
      for (int o = 2 * kb + 1; o < 13; o++)
        if (!unit_wg(kb, o)) mma16816h(d[x] + o * 2, a[x][kb], bf[FI.v[2 * kb][o]], bf[FI.v[2 * kb + 1][o]]);
#pragma unroll
    for (int q = 0; q < 6; q++) if (!unit_wg(q, 2 * q)) mma1688h(d[x] + q * 4, a[x][q][0], a[x][q][1], bf[FI.v[2 * q][2 * q]]);
    mma1688h(d[x] + 24, r < 2 ? ex[t & 3] : 0u, r < 2 ? 0u : ex[t & 3], bf[FI.v[12][12]]);
  };
  auto dot_part = [&](int t, int hf) {
    const int x = t & 1;
    if (hf == 0) {
      const uint32_t pe = hfma2(r < 2 ? d[x][24] : d[x][25], ex[t & 3], 0u);
      s[0] = r < 2 ? pe : 0u; s[1] = r < 2 ? 0u : pe; s[2] = s[3] = 0;
    }
#pragma unroll
    for (int q = 3 * hf; q < 3 * hf + 3; q++)
#pragma unroll
      for (int e = 0; e < 4; e++) s[e] = hfma2(d[x][q * 4 + e], a[x][q][e], s[e]);
  };
  float* outp = g_partP + slice * B_ + range * 256;
  float k0 = 0.f, k1 = 0.f, x0 = 0.f, x1 = 0.f;
  auto red_stage = [&](int st, int grp) {
    const bool u16 = lane & 16, u8 = lane & 8;
    if (st == 0) {
      k0 = u16 ? red[2] : red[0]; x0 = __shfl_xor_sync(0xffffffffu, u16 ? red[0] : red[2], 16);
      k1 = u16 ? red[3] : red[1]; x1 = __shfl_xor_sync(0xffffffffu, u16 ? red[1] : red[3], 16);
      red[0] = red[1] = red[2] = red[3] = 0.f;
    }
    if (st == 1) { const float p0 = k0 + x0, p1 = k1 + x1; k0 = u8 ? p1 : p0; x0 = __shfl_xor_sync(0xffffffffu, u8 ? p0 : p1, 8); }
    if (st == 2) { k0 += x0; x0 = __shfl_xor_sync(0xffffffffu, k0, 4); }
    if (st == 3 && !(lane & 4)) outp[grp * 16 + r * 4 + ((lane >> 3) & 1) * 2 + (lane >> 4)] = (k0 + x0) * unscale * unscale * unscale2;
  };
  auto group = [&](bool first, int prv, int cur, int nxt) {
    const int pn = PX_OFF + px + nxt * 136 + lane;
#pragma unroll
    for (int t = 0; t < 8; t++) {
      issue((t & 1) ^ 1);
      SCHED_FENCE(never, t * 8);
      if (!first) {
        if (t == 0) { iv[3] = ldtex(tex, PX_OFF + px + cur * 136 + lane + 96); iv[0] = ldtex(tex, pn); }
        if (t == 2) iv[1] = ldtex(tex, pn + 32);
        if (t < 4) red_stage(t, prv);
      } else if (t == 4) {
        TS(4, 2);
        flag_wait(&g_flag[(cta >> 4) * 32], 16);
        TS(4, 3);
        iv[0] = ldtex(tex, pn); iv[1] = ldtex(tex, pn + 32);
      }
      if (t == 4) { ix = ldtex(texX, (px + nxt * 136 + 128) * 4 + lane).x; iv[2] = ldtex(tex, pn + 64); }
      dot_part(t, 0);
      SCHED_FENCE(never, t * 8 + 1);
      if (t == 3) ldsm(ex, ix >> 10);
      if (t == 7) ldsm(ex, ix);
      gather(t + 2, 0);
      dot_part(t, 1);
      SCHED_FENCE(never, t * 8 + 4);
      gather(t + 2, 1);
      asm volatile("wgmma.wait_group.sync.aligned 0;" ::: "memory");
      if (FM & 1) SCHED_FENCE(never, t * 8 + 2);
      asm volatile("" : "+r"(d[(t & 1) ^ 1][0]) :: "memory");
      mma1688f(red, hadd2(s[0], s[2]), hadd2(s[1], s[3]), (g | (d[(t & 1) ^ 1][0] & never)) == t ? 0x3c003c00u : 0u);
      hmma_part(t + 1);
      if (FM & 2) SCHED_FENCE(never, t * 8 + 3);
    }
  };
  gather(0, 0); gather(0, 1); issue(0); ldsm(ex, ix); gather(1, 0); gather(1, 1);
  asm volatile("wgmma.wait_group.sync.aligned 0;" ::: "memory");
  hmma_part(0);
  int prv = slice, cur = slice == 0;
  group(true, 0, prv, cur);
  TS(4, 1);
#pragma unroll 1
  for (int n = 1; n < NGRP; n++) {
    const int nxt = (n + (n >= slice)) & 15;
    if (n == TRIG) asm volatile("griddepcontrol.launch_dependents;");
    if (PXW && tid == 0) mbar_arrive(progG);
    group(false, prv, cur, nxt);
    prv = cur; cur = nxt;
  }
#pragma unroll
  for (int st = 0; st < 4; st++) red_stage(st, prv);
  TS(0, 2);
  if (MCW) asm volatile("barrier.cluster.wait.aligned;" ::: "memory");
  asm volatile("barrier.cluster.arrive.relaxed.aligned; barrier.cluster.wait.aligned;" ::: "memory");
}

constexpr int SM_U = 130048, SM_BAR = 128000, SM_J = SM_U + 98304, DEEP_SMEM = SM_J + 4096;

#define ELECT "{.reg .pred p; elect.sync _|p,0xffffffff; @p "
__device__ __forceinline__ void e_mc(uint32_t dst, const void* src, uint32_t bytes, uint32_t bar, uint64_t pol) {
  asm volatile(ELECT "cp.async.bulk.shared::cluster.global.mbarrier::complete_tx::bytes.multicast::cluster.L2::cache_hint [%0],[%1],%2,[%3],%4,%5;}"
               :: "r"(dst), "l"(src), "r"(bytes), "r"(bar), "h"((unsigned short)3), "l"(pol) : "memory");
}
__device__ __forceinline__ void e_g2s(uint32_t dst, const void* src, uint32_t bytes, uint32_t bar) {
  asm volatile(ELECT "cp.async.bulk.shared::cluster.global.mbarrier::complete_tx::bytes [%0],[%1],%2,[%3];}" :: "r"(dst), "l"(src), "r"(bytes), "r"(bar) : "memory");
}
__device__ __forceinline__ void e_pf(const void* src, uint32_t bytes) { asm volatile(ELECT "cp.async.bulk.prefetch.L2.global [%0],%1;}" :: "l"(src), "r"(bytes) : "memory"); }
__device__ __forceinline__ void e_expect(uint32_t bar, uint32_t bytes) { asm volatile(ELECT "mbarrier.arrive.expect_tx.shared::cta.b64 _,[%0],%1;}" :: "r"(bar), "r"(bytes) : "memory"); }

__global__ void __cluster_dims__(2, 1, 1) __launch_bounds__(TH + 128, 1)
k_deep(cudaTextureObject_t tex, const __nv_bfloat16* __restrict__ w2, const __nv_bfloat16* __restrict__ b2,
       __nv_bfloat16* __restrict__ out, int never) {
  extern __shared__ __align__(1024) uint4 sm[];
  constexpr int PF = DPF, DEPTH = DDEPTH, NW = TH / 32;
  static_assert(YD == 4 && PF == 4, "");
  const int tid = threadIdx.x;
  const int c = blockIdx.x >> 1, half = blockIdx.x & 1;
  const uint32_t sbase = (uint32_t)__cvta_generic_to_shared(sm);
  const uint32_t fullL = sbase + SM_BAR, fullU = fullL + 8, emptyL = fullL + 16, emptyU = fullL + 24, barJ = fullL + 32;
  TS(1, 0);
  if (tid == 0) {
    mbar_init(fullL, 1); mbar_init(fullU, 1); mbar_init(emptyL, 2 * NW); mbar_init(emptyU, 2 * NW); mbar_init(barJ, 1);
    asm volatile("fence.mbarrier_init.release.cluster;" ::: "memory");
  }
  __syncwarp();
  const int wrp = __shfl_sync(0xffffffffu, tid >> 5, 0);
  const char* base = (const char*)g_scr;
  uint32_t oL = (PL_OFF + c * NC * 8000) * 16u + half * 64000, oS = (PS_OFF + c * NC * 2000) * 16u + half * 16000;
  asm volatile("barrier.cluster.arrive.relaxed.aligned;" ::: "memory");
  flag_wait(&g_flag[8 * 32], 132);
  asm volatile("barrier.cluster.wait.aligned;" ::: "memory");
  if (wrp == NW) {
    asm volatile("fence.proxy.async.global;" ::: "memory");
    e_expect(fullU, 96000);
#pragma unroll
    for (int m = 0; m < 3; m++) e_mc(sbase + SM_U + m * 32032 + half * 16000, base + oS, 16000, fullU, m == 2 ? POL_EF : POL_N);
    e_expect(fullL, 128000);
    if (!STAG) e_mc(sbase + half * 64000, base + oL, 64000, fullL, POL_EF);
  }
  TS(5, 1);
  if (wrp >= NW) {
    asm volatile("setmaxnreg.dec.sync.aligned.u32 24;");
    if (wrp == NW) {
      uint32_t oT = (PT_OFF + c * 10 * 1024) * 16u + half * 8192;
      const uint32_t junk = sbase + SM_J, oW = (IX_OFF + half * IXH + ((c + (c >> 4) * 5) & 15) * 512) * 16u;
      auto warm = [&](uint32_t off) {
        asm volatile(ELECT "mbarrier.expect_tx.relaxed.cta.shared::cta.b64 [%0],%1;}" :: "r"(barJ), "r"(8192) : "memory");
        e_g2s(junk, base + off, 4096, barJ); e_g2s(junk, base + off + 4096, 4096, barJ);
      };
      uint32_t t0 = clock();
      if (!PREW) warm(oW);
      if (STAG) { if (STAG == 1) mbar_wait_fast(fullU, 0); else sleep_until(t0, STAG); e_mc(sbase + half * 64000, base + oL, 64000, fullL, POL_EF); }
      warm(oT);
      if (!(PREW & 4)) warm(oW + 131072);
#pragma unroll 1
      for (int k = 0; k + 1 < NC; k++) {
        oL += 128000; oS += 32000; oT += 16384;
        mbar_wait_fast(fullL, k & 1);
        t0 = clock();
        e_pf(base + oS, 16000);
        if (k + 2 < NC) {
          const uint32_t o2 = (IX_OFF + half * IXH + (k + 2) * 8192) * 16u + ((c + (c / (64 / WRED)) * (2 * k + 1)) & (64 / WRED - 1)) * (WRED * 2048);
#pragma unroll 1
          for (int q = 0; q < WRED / 4; q++) warm(o2 + q * 8192);
        } else warm((IX_OFF + half * IXH + NC * 8192 + (c & 3) * 512) * 16u);
        mbar_wait_fast(emptyU, k & 1);
        e_expect(fullU, 96000);
#pragma unroll 1
        for (int q = 0; q < 8; q++) {
          sleep_until(t0, q * PACE);
          e_pf(base + oL + q * 8000, 8000);
          if (q >= 2) e_mc(sbase + SM_U + ((q - 2) >> 1) * 32032 + half * 16000 + (q & 1) * 8000, base + oS + (q & 1) * 8000, 8000, fullU, q >= 6 ? POL_EF : POL_N);
        }
        warm(oT);
        e_expect(fullL, 128000);
        sleep_until(t0, RSV_T);
        unsigned long long now, slot = 0;
        asm volatile("mov.u64 %0,%globaltimer;" : "=l"(now));
        if ((tid & 31) == 0) { atomicMax(&g_slot, now + RSV_L); slot = atomicAdd(&g_slot, (unsigned long long)RSV); }
        slot = __shfl_sync(0xffffffffu, slot, 0);
        mbar_wait_fast(emptyL, k & 1);
        for (int it = 0; it < 4000; it++) { asm volatile("mov.u64 %0,%globaltimer;" : "=l"(now)); if (now >= slot) break; }
        e_mc(sbase + half * 64000, base + oL, 64000, fullL, POL_EF);
      }
      mbar_wait_fast(fullL, (NC - 1) & 1);
      mbar_wait_fast(emptyU, (NC - 1) & 1);
      mbar_arrive_lane0(fullU);
      warm(oT + 16384);
      mbar_arrive_lane0(barJ); mbar_wait_fast(barJ, 0);
    } else if (tid >= TH + 96) {
      if (tid == TH + 96) sts128(barJ + 32, *(const uint4*)(w2 + c * 8));
      asm volatile("bar.arrive 3,%0;" :: "n"(TH + 32) : "memory");
      asm volatile("griddepcontrol.wait;" ::: "memory");
      const int b = half * 8192 + c * 128 + (tid & 31) * 4;
      const float bias = __bfloat162float(b2[0]);
      float4 s = make_float4(bias, bias, bias, bias);
#pragma unroll 2
      for (int k = 0; k < 16; k++) { const float4 v = __ldcg((const float4*)(g_partP + k * B_ + b)); s.x += v.x; s.y += v.y; s.z += v.z; s.w += v.w; }
      asm volatile("red.global.add.v4.f32 [%0],{%1,%2,%3,%4};" :: "l"(g_acc + b), "f"(s.x), "f"(s.y), "f"(s.z), "f"(s.w) : "memory");
      asm volatile("bar.arrive 1,%0;" :: "n"(TH + 32) : "memory");
    }
    return;
  }
  asm volatile("setmaxnreg.inc.sync.aligned.u32 240;");
  const int lane = tid & 31;
  const int tbase = PT_OFF + c * 10 * 1024;
  const int ibase = IX_OFF + half * IXH + tid;
  const uint32_t lc = (tid & 7) << 4;
  uint4 acc[NS], wq[PF], x[DEPTH], y[YD], ye;
  uint32_t sw[NS] = {};
  auto sget = [&](int s) { return (s & 3) == 3 ? __byte_perm(__byte_perm(sw[s - 3], sw[s - 2], 0x0073), sw[s - 1], 0x0710) : sw[s]; };
  auto sa0 = [&](uint32_t v) { return sbase + SM_U + (((v << 5) & 0x1ffe0) | ((lc >> 2) & 16)); };
  auto sa1 = [&](uint32_t v) { return sbase + SM_U + (((v >> 7) & 0x1ffe0) | ((~lc >> 2) & 16)); };
  {
    uint4 i0[8];
#pragma unroll
    for (int q = 0; q < 8; q++) i0[q] = ldtex(tex, I0_OFF + (half * 8 + q) * TH + tid);
#pragma unroll
    for (int i = 0; i < PF; i++) if (!WQL) wq[i] = ldtex(tex, ibase + i * TH);
    auto wd = [&](int k) { return (k & 3) == 0 ? i0[k >> 2].x : (k & 3) == 1 ? i0[k >> 2].y : (k & 3) == 2 ? i0[k >> 2].z : i0[k >> 2].w; };
    TS(5, 2);
    mbar_wait_fast(fullU, 0);
#pragma unroll
    for (int i = 0; i < PF; i++) if (WQL) wq[i] = ldtex(tex, ibase + i * TH);
    TS(1, 1);
#pragma unroll
    for (int s = 0; s < NS; s++) acc[s] = add4(lds128(sa0(wd(s))), lds128(sa1(wd(s))));
    arrive_both(emptyU, lane);
    asm volatile("bar.sync 3,%0;" :: "n"(TH + 32) : "memory");
    TS(5, 3);
  }
#pragma unroll 1
  for (int k = 0; k < NC; k++) {
    const int ti = ibase + k * 8192;
    const int tb = tbase + k * 1024;
    const bool more = k + 1 < NC;
    TR(k * 4);
    if (CBAR & 1) asm volatile("bar.sync 4,%0;" :: "n"(TH) : "memory");
    mbar_wait_fast(fullL, k & 1);
    TR(k * 4 + 2);
    uint4 w, cc; uint32_t yc, yn;
    constexpr int TL = NS * 8, TT = TL + NS * 2;
#pragma unroll
    for (int t = 0; t < TT + DEPTH; t += 2) {
      if (t == TL + DEPTH && !more) break;
      if (t >= DEPTH) {
        const int u = t - DEPTH;
        uint4 p = add4(x[u % DEPTH], x[(u + 1) % DEPTH]);
        if (u < TL) {
          const int s = u >> 3, j = u & 7;
          if (j == 0) {
            cc = s >= YD ? add4(y[s % YD], p) : p;
            if (s + YD < NS) y[s % YD] = ldtex(tex, tb | (yc & 1023));
          } else cc = add4(cc, p);
          if (j == 6) acc[s] = add4(acc[s], cc);
        } else {
          const int s = (u - TL) >> 1;
          acc[s] = add4(acc[s], p);
        }
      }
      if ((CBAR & 4) && t == TL / 2) asm volatile("bar.sync 4,%0;" :: "n"(TH) : "memory");
      if ((CBAR & 8) && t == TL - 40) asm volatile("bar.sync 4,%0;" :: "n"(TH) : "memory");
      if (DEPTH == 8 && (t & 7) == 2) yc = yn;
      if (t < TL) {
        const int s = t >> 3, j = t & 7;
        if (j == 0) {
          if (ye_of(s - YD) >= 0) acc[ye_of(s - YD) & 3] = add4(acc[ye_of(s - YD) & 3], ye);
          w = wq[s % PF];
          if (!EARLY || s < NS - 4) wq[s % PF] = ldtex(tex, ti + (s + PF) * TH);
          else {
            if (s == NS - 4) { wq[0] = ldtex(tex, ti + NS * TH); ye = ldtex(tex, ti + (NS + 3) * TH); }
            if (s == NS - 3) { wq[1] = ldtex(tex, ti + (NS + 1) * TH); y[0] = ldtex(tex, ti + (NS + 2) * TH); }
            if (s == NS - 2) wq[2] = y[0];
            if (s == NS - 1) wq[3] = ye;
          }
          yn = __funnelshift_l(w.z, w.z, 5); if (DEPTH < 8) yc = yn;
          if ((s & 3) != 3) asm volatile("add.u32 %0,%1,%2;" : "=r"(sw[s]) : "r"(w.w), "r"(never));
          if (ye_of(s) >= 0) ye = ldtex(tex, tb | w.w);
        }
#pragma unroll
        for (int jj = j; jj < j + 2; jj++) {
          const uint32_t ww = jj < 3 ? w.x : jj < 6 ? w.y : w.z;
          const uint32_t sh = jj % 3 == 0 ? ww : jj % 3 == 1 ? ww >> 10 : __funnelshift_l(ww, ww, 12);
          x[(t + jj - j) % DEPTH] = lds128(sbase + ((sh & 0x1ff80) | lc) + jj * 16 - 128);
        }
      } else if (t < TT) {
        const int s = (t - TL) >> 1;
        if (s == 0) { arrive_both(emptyL, more ? lane : 9); TR(k * 4 + 3); if (CBAR & 2) asm volatile("bar.sync 4,%0;" :: "n"(TH) : "memory"); mbar_wait_fast(fullU, (k + 1) & 1); }
        const uint32_t sv = sget(s);
        x[t % DEPTH] = lds128(sa0(sv));
        x[(t + 1) % DEPTH] = lds128(sa1(sv));
      } else if (t == TT) arrive_both(emptyU, lane);
      if ((t & (FENCE_N - 1)) == FENCE_N - 2) SCHED_FENCE(never, t);
    }
  }
  TS(1, 2);
  const uint4 w2v = lds128(barJ + 32);
  const uint32_t cell = sbase + SM_U + tid * 16;
  const int t9 = tbase + 9 * 1024;
  uint4 za[4], i9 = wq[0];
  auto fetch = [&](int q) {
    y[0] = ldtex(tex, t9 | i9.x); y[1] = ldtex(tex, t9 | i9.y); y[2] = ldtex(tex, t9 | i9.z); y[3] = ldtex(tex, t9 | i9.w);
    if (q) {
      i9 = ldtex(tex, ibase + NC * 8192 + min(q + 1, 7) * TH);
      const uint32_t ca = cell + (q > 6 ? 0 : q - 1) * 16384;
#pragma unroll
      for (int s = 0; s < 4; s++) za[s] = lds128(ca + s * 4096);
    }
  };
  fetch(0);
  i9 = wq[1];
#pragma unroll
  for (int s = 0; s < 4; s++) za[s] = acc[s];
#pragma unroll
  for (int s = 0; s < 24; s++) sts128(cell + s * 4096, acc[4 + s]);
  float hw[8];
  {
    const uint32_t ww[4] = {w2v.x, w2v.y, w2v.z, w2v.w};
#pragma unroll
    for (int k = 0; k < 8; k++) hw[k] = 0.5f * ((k & 1) ? bf_hi(ww[k >> 1]) : bf_lo(ww[k >> 1]));
  }
  float* outp = g_acc + half * 8192 + tid;
#pragma unroll 1
  for (int q = 0; q < NS / 4; q++) {
    uint4 z[4];
#pragma unroll
    for (int s = 0; s < 4; s++) z[s] = add4(za[s], y[s]);
    if (q == 1) {
#pragma unroll
      for (int s = 0; s < 4; s++) sts128(cell + s * 4096, acc[28 + s]);
    }
    if (q < 7) fetch(q + 1);
    SCHED_FENCE(never, 999);
#pragma unroll
    for (int s = 0; s < 4; s++) {
      const uint32_t a[4] = {z[s].x, z[s].y, z[s].z, z[s].w};
      float r0 = 0.f;
#pragma unroll
      for (int k = 0; k < 8; k++) {
        const float v = (k & 1) ? bf_hi(a[k >> 1]) : bf_lo(a[k >> 1]);
        const float u = v * fmaf(v * v, 0.7978845608028654f * 0.044715f, 0.7978845608028654f);
        float th; asm("tanh.approx.f32 %0,%1;" : "=f"(th) : "f"(u));
        r0 = fmaf(fmaf(v, th, v), hw[k], r0);
      }
      asm volatile("red.global.add.f32 [%0],%1;" :: "l"(outp + s * TH), "f"(r0) : "memory");
    }
    outp += 4 * TH;
  }
  TS(1, 3);
  asm volatile("bar.sync 1,%0;" :: "n"(TH + 32) : "memory");
  if (tid == 0) {
    __threadfence();
    const unsigned old = atomicInc(&g_done[half * 32], 63);
    asm volatile("st.shared.u32 [%0],%1;" :: "r"(barJ + 8), "r"(old) : "memory");
  }
  asm volatile("bar.sync 2,%0;" :: "n"(TH) : "memory");
  uint32_t old; asm volatile("ld.shared.u32 %0,[%1];" : "=r"(old) : "r"(barJ + 8));
  if (old == 63) {
    if (half == 0 && tid == 9) g_slot = 0;
    if (half == 0 && tid < 9) g_flag[tid * 32] = 0;
    __threadfence();
    float4 v[8];
#pragma unroll
    for (int q = 0; q < 8; q++) v[q] = __ldcg((const float4*)(g_acc + half * 8192) + q * TH + tid);
#pragma unroll
    for (int q = 0; q < 8; q++) ((uint2*)(out + half * 8192))[q * TH + tid] = make_uint2(pack_bf2(v[q].x, v[q].y), pack_bf2(v[q].z, v[q].w));
    TS(6, 2);
  }
}

}

extern "C" void kernel_launch(void* const* d_in, const int* in_sizes, int n_in, void* d_out, int out_size) {
  const int* idx = (const int*)d_in[0];
  const __nv_bfloat16* table = (const __nv_bfloat16*)d_in[1];
  const __nv_bfloat16* wp = (const __nv_bfloat16*)d_in[2];
  const __nv_bfloat16* w1 = (const __nv_bfloat16*)d_in[3];
  const __nv_bfloat16* b1 = (const __nv_bfloat16*)d_in[4];
  const __nv_bfloat16* w2 = (const __nv_bfloat16*)d_in[5];
  const __nv_bfloat16* b2 = (const __nv_bfloat16*)d_in[6];
  static cudaTextureObject_t texScr = 0, texG = 0;
  static CUtensorMap mapW, mapL, mapS, mapT, mapE, mapC;
  static const void *c_tab = nullptr, *c_w1 = nullptr;
  if (c_tab != table || c_w1 != w1) {
    c_tab = table; c_w1 = w1;
    char* scr = nullptr; cudaGetSymbolAddress((void**)&scr, g_scr);
    auto mk_tex = [](const void* p, size_t bytes, cudaChannelFormatDesc d) {
      cudaResourceDesc rd = {}; rd.resType = cudaResourceTypeLinear; rd.res.linear.devPtr = (void*)p; rd.res.linear.desc = d; rd.res.linear.sizeInBytes = bytes;
      cudaTextureDesc td = {}; td.readMode = cudaReadModeElementType;
      cudaTextureObject_t t = 0; cudaCreateTextureObject(&t, &rd, &td, nullptr); return t;
    };
    if (!texScr) {
      texScr = mk_tex(scr, (size_t)SCR_N * 16, cudaCreateChannelDesc<uint4>());
      texG = mk_tex(scr + (size_t)PX_OFF * 16, (size_t)(SCR_N - PX_OFF) * 16, cudaCreateChannelDesc<unsigned>());
    }
    typedef CUresult (*EncFn)(CUtensorMap*, CUtensorMapDataType, cuuint32_t, void*, const cuuint64_t*, const cuuint64_t*, const cuuint32_t*,
                              const cuuint32_t*, CUtensorMapInterleave, CUtensorMapSwizzle, CUtensorMapL2promotion, CUtensorMapFloatOOBfill);
    EncFn enc = nullptr; cudaDriverEntryPointQueryResult qr;
    cudaGetDriverEntryPoint("cuTensorMapEncodeTiled", (void**)&enc, cudaEnableDefault, &qr);
    const cuuint32_t ones[4] = {1, 1, 1, 1};
    auto mk = [&](CUtensorMap* m, CUtensorMapDataType dt, int rank, void* p, const cuuint64_t* dim, const cuuint64_t* str, const cuuint32_t* box, CUtensorMapSwizzle sw) {
      enc(m, dt, rank, p, dim, str, box, ones, CU_TENSOR_MAP_INTERLEAVE_NONE, sw, CU_TENSOR_MAP_L2_PROMOTION_NONE, CU_TENSOR_MAP_FLOAT_OOB_FILL_NONE);
    };
    { cuuint64_t dim[2] = {H_, F_ * D_}, str[1] = {H_ * 2}; cuuint32_t box[2] = {32, MCW ? 128 : 256};
      mk(&mapW, CU_TENSOR_MAP_DATA_TYPE_BFLOAT16, 2, (void*)w1, dim, str, box, CU_TENSOR_MAP_SWIZZLE_64B); }
    { cuuint64_t dim[4] = {64, V_, NC, 64}, str[3] = {128, 128000, 128000 * NC}; cuuint32_t box[4] = {32, 64, 1, 4};
      mk(&mapL, CU_TENSOR_MAP_DATA_TYPE_BFLOAT16, 4, scr + (size_t)PL_OFF * 16, dim, str, box, CU_TENSOR_MAP_SWIZZLE_64B); }
    { cuuint64_t dim[4] = {64, V_ / 4, NC, 64}, str[3] = {128, 32000, 32000 * NC}; cuuint32_t box[4] = {64, 16, 1, 4};
      mk(&mapS, CU_TENSOR_MAP_DATA_TYPE_BFLOAT16, 4, scr + (size_t)PS_OFF * 16, dim, str, box, CU_TENSOR_MAP_SWIZZLE_128B); }
    { cuuint64_t dim[3] = {2048, 10, 64}, str[2] = {16384, 163840}; cuuint32_t box[3] = {128, 2, 4};
      mk(&mapT, CU_TENSOR_MAP_DATA_TYPE_UINT64, 3, scr + (size_t)PT_OFF * 16, dim, str, box, CU_TENSOR_MAP_SWIZZLE_NONE); }
    { cuuint64_t dim[2] = {D_, V_}, str[1] = {D_ * 2}; cuuint32_t box[2] = {64, 128};
      mk(&mapE, CU_TENSOR_MAP_DATA_TYPE_BFLOAT16, 2, (void*)table, dim, str, box, CU_TENSOR_MAP_SWIZZLE_128B);
      cuuint32_t box2[2] = {8, 256};
      mk(&mapC, CU_TENSOR_MAP_DATA_TYPE_BFLOAT16, 2, (void*)table, dim, str, box2, CU_TENSOR_MAP_SWIZZLE_NONE); }
    cudaFuncSetAttribute(k_deep, cudaFuncAttributeMaxDynamicSharedMemorySize, DEEP_SMEM);
    cudaFuncSetAttribute(k_tens, cudaFuncAttributeMaxDynamicSharedMemorySize, K1_SMEM);
  }
  k_tens<<<132, 512, K1_SMEM, cudaStreamPerThread>>>(mapW, mapL, mapS, mapT, mapE, mapC, texScr, texG, idx, table, wp, w1, b1, 0);
  cudaLaunchAttribute at[1];
  at[0].id = cudaLaunchAttributeProgrammaticStreamSerialization; at[0].val.programmaticStreamSerializationAllowed = 1;
  cudaLaunchConfig_t cfg = {};
  cfg.stream = cudaStreamPerThread; cfg.attrs = at;
  cfg.gridDim = 128; cfg.blockDim = TH + 128; cfg.dynamicSmemBytes = DEEP_SMEM; cfg.numAttrs = PDL & 1;
  cudaLaunchKernelEx(&cfg, k_deep, texScr, w2, b2, (__nv_bfloat16*)d_out, 0);

}
```

```cpp
#include <cuda_runtime.h>
#include <cuda_bf16.h>
#include <cuda_fp16.h>
#include <stdint.h>
#include <cuda.h>

namespace {

constexpr int B_ = 16384, F_ = 100, D_ = 128, V_ = 1000, H_ = 512;
constexpr int NC = 9;
constexpr int PT_OFF = 0;
constexpr int PL_OFF = 64 * 10 * 1024;
constexpr int PS_OFF = PL_OFF + 64 * NC * 8000;
constexpr int IXH = NC * 8192 + 2048;
constexpr int IX_OFF = PS_OFF + 64 * NC * 2000;
constexpr int I0_OFF = IX_OFF + 2 * IXH;
constexpr int PX_OFF = I0_OFF + 4096;
constexpr int SCR_N = PX_OFF + 64 * 16 * 136;
static_assert(PX_OFF % 32 == 0, "");

__device__ __align__(1024) uint4 g_scr[SCR_N];
__device__ float g_acc[B_];
__device__ unsigned long long g_slot;
__device__ unsigned g_done[64];
__device__ float g_partP[16 * B_];
__device__ unsigned g_flag[16 * 32];

#define TS(k, i)
#define TR(slot)
#define PT(slot)

constexpr uint64_t POL_EF = 0x12F0000000000000ull, POL_N = 0x1000000000000000ull;
__device__ __forceinline__ uint32_t addbf2(uint32_t a, uint32_t b) { uint32_t r; asm("add.rn.bf16x2 %0,%1,%2;" : "=r"(r) : "r"(a), "r"(b)); return r; }
__device__ __forceinline__ uint4 add4(const uint4& a, const uint4& b) { return make_uint4(addbf2(a.x, b.x), addbf2(a.y, b.y), addbf2(a.z, b.z), addbf2(a.w, b.w)); }
__device__ __forceinline__ void acc4(uint4& a, const uint4& b, int never) {
  asm("{.reg .pred p; setp.eq.s32 p,%8,0;\n"
      "@p add.rn.bf16x2 %0,%0,%4; @p add.rn.bf16x2 %1,%1,%5; @p add.rn.bf16x2 %2,%2,%6; @p add.rn.bf16x2 %3,%3,%7;}"
      : "+r"(a.x), "+r"(a.y), "+r"(a.z), "+r"(a.w) : "r"(b.x), "r"(b.y), "r"(b.z), "r"(b.w), "r"(never));
}
__device__ __forceinline__ uint4 ldtex(cudaTextureObject_t t, int i) {
  uint4 v; asm volatile("tex.1d.v4.u32.s32 {%0,%1,%2,%3},[%4,{%5}];" : "=r"(v.x), "=r"(v.y), "=r"(v.z), "=r"(v.w) : "l"(t), "r"(i)); return v;
}
__device__ __forceinline__ uint4 lds128(uint32_t a) {
  uint4 v; asm volatile("ld.volatile.shared.v4.u32 {%0,%1,%2,%3},[%4];" : "=r"(v.x), "=r"(v.y), "=r"(v.z), "=r"(v.w) : "r"(a)); return v;
}
__device__ __forceinline__ void sts128(uint32_t a, const uint4& v) {
  asm volatile("st.shared.v4.u32 [%0],{%1,%2,%3,%4};" :: "r"(a), "r"(v.x), "r"(v.y), "r"(v.z), "r"(v.w) : "memory");
}
__device__ __forceinline__ void mbar_init(uint32_t bar, int n) { asm volatile("mbarrier.init.shared::cta.b64 [%0],%1;" :: "r"(bar), "r"(n) : "memory"); }
__device__ __forceinline__ void mbar_wait(uint32_t bar, uint32_t parity) {
  uint32_t ok; int it = 0;
  do { asm volatile("{.reg .pred p; mbarrier.try_wait.parity.shared::cta.b64 p,[%1],%2; selp.u32 %0,1,0,p;}" : "=r"(ok) : "r"(bar), "r"(parity) : "memory"); } while (!ok && ++it < (1 << 19));
}
__device__ __forceinline__ void mbar_expect(uint32_t bar, uint32_t bytes) { asm volatile("mbarrier.arrive.expect_tx.shared::cta.b64 _,[%0],%1;" :: "r"(bar), "r"(bytes) : "memory"); }
__device__ __forceinline__ void bulk_g2s(uint32_t dst, const void* src, uint32_t bytes, uint32_t bar) {
  asm volatile("cp.async.bulk.shared::cluster.global.mbarrier::complete_tx::bytes [%0],[%1],%2,[%3];" :: "r"(dst), "l"(src), "r"(bytes), "r"(bar) : "memory");
}
__device__ __forceinline__ void bulk_pf(const void* src, uint32_t bytes) { asm volatile("cp.async.bulk.prefetch.L2.global [%0],%1;" :: "l"(src), "r"(bytes) : "memory"); }
#define NOMMA 0
#define NGRP 16
#define PDL 1
#define FIN_S 128
#define WRED 4
#define RSV 24
#define RSV_T 7200
#define RSV_L 550
#define TRIG 14
#define PREW 5
#define PXW 3
#define WQL 1
#define EARLY 1
#define CBAR 0
#define X_SAMEK 0
#define X_SAMEW 0
#define FM 0
#define SWP 1
#define HOLD 1
#define MCW 1
#define TW 1
#define PP0 10
#define PT0 10000
#define PDT 0
#define RPNN "160"
#define RAUX "32"
#define RPRO "160"
#define PARK 0
#define NLOOK 128
#define NEF 16
#define ORD 0
#define WFENCE 0
#define SPLIT 1
#define IORD 1
#define IPF 3
#define IPACE 4500
#define WPF 1
#define QV 3
#define QORD(n) ((n) < 23 ? (n) + 2 : (n) - 23)
#define DYD 4
#define DPF 4
#define DDEPTH 4
#define FENCE_N 4
#define INPL 0
#define STAG 1
#define PACE 800
#define PM4 "pmevent 1; pmevent 2; pmevent 3; pmevent 4;"
#define PMFILL "pmevent 1;"
#define SCHED_FENCE(never, k) asm volatile("{.reg .pred p; setp.ne.u32 p,%0,%1; @p bra.uni SKIP_%=;" PMFILL "SKIP_%=: }" :: "r"(never), "r"(0x7fff0000 + (k)) : "memory")

__global__ void k_prod_naive(const __nv_bfloat16* __restrict__ table, const __nv_bfloat16* __restrict__ w1) {
  __shared__ float t[8][D_];
  int f = blockIdx.y, v0 = blockIdx.x * 8, h = threadIdx.x;
  for (int i = h; i < 8 * D_; i += 512) t[i / D_][i % D_] = __bfloat162float(table[v0 * D_ + i]);
  __syncthreads();
  float s[8] = {0, 0, 0, 0, 0, 0, 0, 0};
  for (int d = 0; d < D_; d++) { float w = __bfloat162float(w1[(size_t)(f * D_ + d) * H_ + h]);
#pragma unroll
    for (int k = 0; k < 8; k++) s[k] += t[k][d] * w; }
  __nv_bfloat16* P = (__nv_bfloat16*)g_scr;
  int c = h >> 3;
  for (int k = 0; k < 8; k++) {
    size_t e = f < 72 ? (size_t)PL_OFF + ((size_t)(c * NC + (f >> 3)) * 1000 + v0 + k) * 8 + (f & 7)
             : f < 90 ? (size_t)PS_OFF + ((size_t)(c * NC + ((f - 72) >> 1)) * 1000 + v0 + k) * 2 + (f & 1)
                      : (size_t)PT_OFF + (size_t)(c * 10 + f - 90) * 1024 + v0 + k;
    P[e * 8 + (h & 7)] = __float2bfloat16(s[k]);
  }
}
__global__ void k_pnn_naive(const int* __restrict__ idx, const __nv_bfloat16* __restrict__ table, const __nv_bfloat16* __restrict__ wp) {
  __shared__ float e[F_][33];
  int b = blockIdx.x, d0 = blockIdx.y * 32, tid = threadIdx.x;
  for (int i = tid; i < F_ * 32; i += 128) e[i >> 5][i & 31] = __bfloat162float(table[idx[b * F_ + (i >> 5)] * D_ + d0 + (i & 31)]);
  __syncthreads();
  float s = 0; int d = tid & 31;
  for (int i = tid >> 5; i < F_; i += 4) { float u = 0; for (int j = 0; j < F_; j++) u += __bfloat162float(wp[i * F_ + j]) * e[j][d]; s += u * e[i][d]; }
  for (int o = 16; o; o >>= 1) s += __shfl_xor_sync(~0u, s, o);
  if (d == 0) g_partP[(blockIdx.y * 4 + (tid >> 5)) * B_ + b] = s;
}
__device__ __forceinline__ void mbar_wait_fast(uint32_t bar, uint32_t parity) {
  asm volatile("{.reg .pred p; .reg .u32 n;\n"
               "mbarrier.try_wait.parity.shared::cta.b64 p,[%0],%1;\n"
               "@p bra DONE_%=;\n"
               "mov.u32 n,0;\n"
               "LOOP_%=: mbarrier.try_wait.parity.shared::cta.b64 p,[%0],%1;\n"
               "add.u32 n,n,1; setp.gt.or.u32 p,n,400000,p;\n"
               "@!p bra LOOP_%=;\n"
               "DONE_%=: }" :: "r"(bar), "r"(parity) : "memory");
}
__device__ __forceinline__ void sleep_until(uint32_t t0, uint32_t dt) { while ((uint32_t)clock() - t0 < dt) __nanosleep(40); }
__device__ __forceinline__ uint32_t s_mask(uint32_t v, int q) { return (1u << ((v + 3 - q) & 3)) | (16u << ((v + 3 + q) & 3)); }
__device__ __forceinline__ uint32_t s_cell(uint32_t v, int q, uint32_t m) {
  const int t = __ffs(~m) - 1;
  const int cp = t == 8 ? q >> 1 : ((t & 4 ? t - q : t + q) - v) & 3;
  return cp * 1001 + v;
}
__device__ __forceinline__ uint32_t pk3(uint32_t a, uint32_t b, uint32_t c) {
  const uint32_t w = c + (a << 12) + (b << 22); return __funnelshift_l(w, w, 27);
}
constexpr int TH = 256, NS = 8192 / TH, YD = DYD;
__host__ __device__ constexpr int ye_of(int s) { return s == 3 ? 0 : s == 11 ? 1 : s == 19 ? 2 : s == 23 ? 3 : -1; }
template <int N> __device__ __forceinline__ void wgmma_h(uint32_t* d, const uint32_t* a, uint64_t desc, int acc);
template <> __device__ __forceinline__ void wgmma_h<64>(uint32_t* d, const uint32_t* a, uint64_t desc, int acc) {
  asm volatile("{.reg .pred p; setp.ne.s32 p,%21,0;\n"
    "wgmma.mma_async.sync.aligned.m64n64k16.f16.f16.f16 {%0,%1,%2,%3,%4,%5,%6,%7,%8,%9,%10,%11,%12,%13,%14,%15},{%16,%17,%18,%19},%20,p,1,1,0;}"
    : "+r"(d[0]),"+r"(d[1]),"+r"(d[2]),"+r"(d[3]),"+r"(d[4]),"+r"(d[5]),"+r"(d[6]),"+r"(d[7]),"+r"(d[8]),"+r"(d[9]),"+r"(d[10]),"+r"(d[11]),"+r"(d[12]),"+r"(d[13]),"+r"(d[14]),"+r"(d[15])
    : "r"(a[0]), "r"(a[1]), "r"(a[2]), "r"(a[3]), "l"(desc), "r"(acc));
}
template <> __device__ __forceinline__ void wgmma_h<56>(uint32_t* d, const uint32_t* a, uint64_t desc, int acc) {
  asm volatile("{.reg .pred p; setp.ne.s32 p,%19,0;\n"
    "wgmma.mma_async.sync.aligned.m64n56k16.f16.f16.f16 {%0,%1,%2,%3,%4,%5,%6,%7,%8,%9,%10,%11,%12,%13},{%14,%15,%16,%17},%18,p,1,1,0;}"
    : "+r"(d[0]),"+r"(d[1]),"+r"(d[2]),"+r"(d[3]),"+r"(d[4]),"+r"(d[5]),"+r"(d[6]),"+r"(d[7]),"+r"(d[8]),"+r"(d[9]),"+r"(d[10]),"+r"(d[11]),"+r"(d[12]),"+r"(d[13])
    : "r"(a[0]), "r"(a[1]), "r"(a[2]), "r"(a[3]), "l"(desc), "r"(acc));
}
template <> __device__ __forceinline__ void wgmma_h<48>(uint32_t* d, const uint32_t* a, uint64_t desc, int acc) {
  asm volatile("{.reg .pred p; setp.ne.s32 p,%17,0;\n"
    "wgmma.mma_async.sync.aligned.m64n48k16.f16.f16.f16 {%0,%1,%2,%3,%4,%5,%6,%7,%8,%9,%10,%11},{%12,%13,%14,%15},%16,p,1,1,0;}"
    : "+r"(d[0]),"+r"(d[1]),"+r"(d[2]),"+r"(d[3]),"+r"(d[4]),"+r"(d[5]),"+r"(d[6]),"+r"(d[7]),"+r"(d[8]),"+r"(d[9]),"+r"(d[10]),"+r"(d[11])
    : "r"(a[0]), "r"(a[1]), "r"(a[2]), "r"(a[3]), "l"(desc), "r"(acc));
}
template <> __device__ __forceinline__ void wgmma_h<40>(uint32_t* d, const uint32_t* a, uint64_t desc, int acc) {
  asm volatile("{.reg .pred p; setp.ne.s32 p,%15,0;\n"
    "wgmma.mma_async.sync.aligned.m64n40k16.f16.f16.f16 {%0,%1,%2,%3,%4,%5,%6,%7,%8,%9},{%10,%11,%12,%13},%14,p,1,1,0;}"
    : "+r"(d[0]),"+r"(d[1]),"+r"(d[2]),"+r"(d[3]),"+r"(d[4]),"+r"(d[5]),"+r"(d[6]),"+r"(d[7]),"+r"(d[8]),"+r"(d[9])
    : "r"(a[0]), "r"(a[1]), "r"(a[2]), "r"(a[3]), "l"(desc), "r"(acc));
}
template <> __device__ __forceinline__ void wgmma_h<32>(uint32_t* d, const uint32_t* a, uint64_t desc, int acc) {
  asm volatile("{.reg .pred p; setp.ne.s32 p,%13,0;\n"
    "wgmma.mma_async.sync.aligned.m64n32k16.f16.f16.f16 {%0,%1,%2,%3,%4,%5,%6,%7},{%8,%9,%10,%11},%12,p,1,1,0;}"
    : "+r"(d[0]),"+r"(d[1]),"+r"(d[2]),"+r"(d[3]),"+r"(d[4]),"+r"(d[5]),"+r"(d[6]),"+r"(d[7])
    : "r"(a[0]), "r"(a[1]), "r"(a[2]), "r"(a[3]), "l"(desc), "r"(acc));
}
__device__ __forceinline__ void wgmma_p(float* d, const uint32_t* a, uint64_t desc, int acc) {
  asm volatile("{.reg .pred p; setp.ne.s32 p,%69,0;\n"
    "wgmma.mma_async.sync.aligned.m64n128k16.f32.bf16.bf16 {%0,%1,%2,%3,%4,%5,%6,%7,%8,%9,%10,%11,%12,%13,%14,%15,%16,%17,%18,%19,%20,%21,%22,%23,%24,%25,%26,%27,%28,%29,%30,%31,%32,%33,%34,%35,%36,%37,%38,%39,%40,%41,%42,%43,%44,%45,%46,%47,%48,%49,%50,%51,%52,%53,%54,%55,%56,%57,%58,%59,%60,%61,%62,%63},{%64,%65,%66,%67},%68,p,1,1,1;}"
    : "+f"(d[0]),"+f"(d[1]),"+f"(d[2]),"+f"(d[3]),"+f"(d[4]),"+f"(d[5]),"+f"(d[6]),"+f"(d[7]),"+f"(d[8]),"+f"(d[9]),"+f"(d[10]),"+f"(d[11]),"+f"(d[12]),"+f"(d[13]),"+f"(d[14]),"+f"(d[15]),"+f"(d[16]),"+f"(d[17]),"+f"(d[18]),"+f"(d[19]),"+f"(d[20]),"+f"(d[21]),"+f"(d[22]),"+f"(d[23]),"+f"(d[24]),"+f"(d[25]),"+f"(d[26]),"+f"(d[27]),"+f"(d[28]),"+f"(d[29]),"+f"(d[30]),"+f"(d[31]),"+f"(d[32]),"+f"(d[33]),"+f"(d[34]),"+f"(d[35]),"+f"(d[36]),"+f"(d[37]),"+f"(d[38]),"+f"(d[39]),"+f"(d[40]),"+f"(d[41]),"+f"(d[42]),"+f"(d[43]),"+f"(d[44]),"+f"(d[45]),"+f"(d[46]),"+f"(d[47]),"+f"(d[48]),"+f"(d[49]),"+f"(d[50]),"+f"(d[51]),"+f"(d[52]),"+f"(d[53]),"+f"(d[54]),"+f"(d[55]),"+f"(d[56]),"+f"(d[57]),"+f"(d[58]),"+f"(d[59]),"+f"(d[60]),"+f"(d[61]),"+f"(d[62]),"+f"(d[63])
    : "r"(a[0]), "r"(a[1]), "r"(a[2]), "r"(a[3]), "l"(desc), "r"(acc));
}

__device__ __forceinline__ void mma16816h(uint32_t* c, const uint32_t* a, uint32_t b0, uint32_t b1) {
  asm("mma.sync.aligned.m16n8k16.row.col.f16.f16.f16.f16 {%0,%1},{%2,%3,%4,%5},{%6,%7},{%0,%1};"
      : "+r"(c[0]), "+r"(c[1]) : "r"(a[0]), "r"(a[1]), "r"(a[2]), "r"(a[3]), "r"(b0), "r"(b1));
}
__device__ __forceinline__ void mma1688h(uint32_t* c, uint32_t a0, uint32_t a1, uint32_t b) {
  asm("mma.sync.aligned.m16n8k8.row.col.f16.f16.f16.f16 {%0,%1},{%2,%3},{%4},{%0,%1};" : "+r"(c[0]), "+r"(c[1]) : "r"(a0), "r"(a1), "r"(b));
}
__device__ __forceinline__ void mma1688f(float* c, uint32_t a0, uint32_t a1, uint32_t b) {
  asm("mma.sync.aligned.m16n8k8.row.col.f32.f16.f16.f32 {%0,%1,%2,%3},{%4,%5},{%6},{%0,%1,%2,%3};"
      : "+f"(c[0]), "+f"(c[1]), "+f"(c[2]), "+f"(c[3]) : "r"(a0), "r"(a1), "r"(b));
}
__device__ __forceinline__ uint32_t hadd2(uint32_t a, uint32_t b) { uint32_t r; asm("add.rn.f16x2 %0,%1,%2;" : "=r"(r) : "r"(a), "r"(b)); return r; }
__device__ __forceinline__ uint32_t hfma2(uint32_t a, uint32_t b, uint32_t c) { uint32_t r; asm("fma.rn.f16x2 %0,%1,%2,%3;" : "=r"(r) : "r"(a), "r"(b), "r"(c)); return r; }
__device__ __forceinline__ uint32_t pack_bf2(float lo, float hi) { uint32_t r; asm("cvt.rn.bf16x2.f32 %0,%1,%2;" : "=r"(r) : "f"(hi), "f"(lo)); return r; }
__device__ __forceinline__ uint32_t pack_h2(float lo, float hi) { uint32_t r; asm("cvt.rn.f16x2.f32 %0,%1,%2;" : "=r"(r) : "f"(hi), "f"(lo)); return r; }
__device__ __forceinline__ float bf_lo(uint32_t w) { return __uint_as_float(w << 16); }
__device__ __forceinline__ float bf_hi(uint32_t w) { return __uint_as_float(w & 0xffff0000u); }
__device__ __forceinline__ uint32_t absmax4(const uint4& v, uint32_t m) {
  return __vmaxu2(__vmaxu2(__vmaxu2(v.x & 0x7fff7fffu, v.y & 0x7fff7fffu), __vmaxu2(v.z & 0x7fff7fffu, v.w & 0x7fff7fffu)), m);
}
__device__ __forceinline__ float pow2_scale(uint32_t mbits, int p) { return __uint_as_float((uint32_t)min(max(253 + p - (int)(mbits >> 7), 2), 252) << 23); }

#define PV 4
constexpr int G_O0 = 8, G_O1 = 4, G_O2 = 0, G_N0 = 5, G_N1 = 4, G_N2 = 4, G_K0 = 5, G_K1 = 3, G_K2 = 1;
__host__ __device__ constexpr bool unit_wg(int kb, int on) {
  return (on >= G_O0 && on < G_O0 + G_N0 && kb < G_K0) || (on >= G_O1 && on < G_O1 + G_N1 && kb < G_K1) || (on >= G_O2 && on < G_O2 + G_N2 && kb < G_K2);
}
__host__ __device__ constexpr bool oct_wg(int on) { return unit_wg(0, on); }
constexpr int G_U1 = G_N0 * G_K0, G_U2 = G_U1 + G_N1 * G_K1, G_U = G_U2 + G_N2 * G_K2;
constexpr int K1_B = 130048, K1_STG = K1_B + 2 * 32768, K1_W = K1_STG + 16384, K1_BAR = K1_W + 48 * 256, K1_SMEM = K1_BAR + 256 + 4352;
__host__ __device__ constexpr int frag_index(int ok, int on) {
  int n = 0;
  for (int k = 0; k < 13; k++) for (int o = k; o < 13; o++) { if (k == ok && o == on) return n; if (!unit_wg(k >> 1, o)) n++; }
  return n;
}
constexpr int HU_N = 2 * G_U + frag_index(99, 99);
static_assert(HU_N <= 96, "");
struct FragIdx { int v[13][13]; };
__host__ __device__ constexpr FragIdx make_fi() { FragIdx f = {}; for (int k = 0; k < 13; k++) for (int o = 0; o < 13; o++) f.v[k][o] = frag_index(k, o); return f; }
__host__ __device__ constexpr uint64_t frag_tab(int first) {
  uint64_t t = 0;
  for (int k = 0; k < 13; k++) for (int o = k; o < 13; o++)
    if (!unit_wg(k >> 1, o)) { const int n = frag_index(k, o) - first; if (n >= 0 && n < 8) t |= (uint64_t)(k << 4 | o) << (8 * n); }
  return t;
}
__device__ __forceinline__ int hu_code(int hu) {
  constexpr uint64_t T0 = frag_tab(0), T1 = frag_tab(8), T2 = frag_tab(16), T3 = frag_tab(24);
  const int u = hu >> 1, f = hu - 2 * G_U;
  if (f >= 0) return (int)((f < 8 ? T0 : f < 16 ? T1 : f < 24 ? T2 : T3) >> (8 * (f & 7))) & 255;
  const int u0 = u < G_U1 ? u : u < G_U2 ? u - G_U1 : u - G_U2;
  const int kb = u < G_U1 ? u0 / G_N0 : u < G_U2 ? u0 / G_N1 : u0 / 4, on = u < G_U1 ? G_O0 + u0 % G_N0 : u < G_U2 ? G_O1 + u0 % G_N1 : G_O2 + u0 % 4;
  return (2 * kb + (hu & 1)) << 4 | on;
}

__device__ __forceinline__ void flag_arrive(unsigned* f, int lane) {
  __threadfence(); __syncwarp();
  if (lane == 0) asm volatile("red.release.gpu.global.add.u32 [%0],1;" :: "l"(f) : "memory");
}
__device__ __forceinline__ void flag_wait(const unsigned* f, unsigned n) {
  unsigned v; int it = 0;
  asm volatile("ld.acquire.gpu.global.u32 %0,[%1];" : "=r"(v) : "l"(f) : "memory");
  if (v < n) {
    do { __nanosleep(300); asm volatile("ld.relaxed.gpu.global.u32 %0,[%1];" : "=r"(v) : "l"(f) : "memory"); } while (v < n && ++it < (1 << 20));
    asm volatile("ld.acquire.gpu.global.u32 %0,[%1];" : "=r"(v) : "l"(f) : "memory");
  }
}
__device__ __forceinline__ void mbar_arrive(uint32_t bar) { asm volatile("mbarrier.arrive.shared::cta.b64 _,[%0];" :: "r"(bar) : "memory"); }
__device__ __forceinline__ void mbar_arrive_lane0(uint32_t bar) {
  asm volatile("{.reg .pred p; elect.sync _|p,0xffffffff; @p mbarrier.arrive.shared::cta.b64 _,[%0];}" :: "r"(bar) : "memory");
}

__device__ __forceinline__ void arrive_both(uint32_t bar, int lane) {
  asm volatile("{.reg .pred p; .reg .u32 a; setp.lt.u32 p,%1,2; mapa.shared::cluster.u32 a,%0,%1;\n"
               "@p mbarrier.arrive.shared::cluster.b64 _,[a];}" :: "r"(bar), "r"(lane) : "memory");
}
__device__ __forceinline__ void pack_role(const int* __restrict__ idx, uint32_t sbase, int pc) {
  constexpr int CH = 3200 + 32, BUF = 32 * 3328;
  const int tid = threadIdx.x, lane = tid & 31, warp = tid >> 5;
  const uint32_t full = sbase + 2 * BUF, empty = full + 16;
  if (tid == 0) { mbar_init(full, 1); mbar_init(full + 8, 1); mbar_init(empty, 18); mbar_init(empty + 8, 18); asm volatile("fence.proxy.async.shared::cta;" ::: "memory"); }
  __syncthreads();
  auto chunk = [&](int s) { return s * 3200 + (s >> 2) * 288; };
  auto load = [&](int n) {
    const int blk = pc * 16 + n;
    if (lane == 0) mbar_expect(full + (n & 1) * 8, 32 * 3200);
    __syncwarp();
    bulk_g2s(sbase + (n & 1) * BUF + chunk(lane), idx + ((blk >> 5) * 8192 + lane * TH + (blk & 31) * 8) * F_, 3200, full + (n & 1) * 8);
  };
  if (warp == 0) { load(0); load(1); }
  const int l = lane & 7;
  uint32_t rot[8], inc[3];
#pragma unroll
  for (int jj = 0; jj < 8; jj++) rot[jj] = ((l + jj) & 7) * 4;
#pragma unroll
  for (int q = 0; q < 3; q++) inc[q] = (l + 3 * q < 8) << 12 | (l + 3 * q + 1 < 8) << 22 | (q < 2 && l + 3 * q + 2 < 8);
  int loaded = 2;
#pragma unroll 1
  for (int task = warp; task < 288; task += 16) {
    const int n = task / 18, q = (task % 18) * 4 + (lane >> 3), sq = q / 9, k = q % 9;
    if (warp == 0 && n + 1 == loaded && loaded < 16) { mbar_wait(empty + (loaded & 1) * 8, ((loaded >> 1) - 1) & 1); load(loaded); loaded++; }
    mbar_wait(full + (n & 1) * 8, (n >> 1) & 1);
    const uint32_t buf = sbase + (n & 1) * BUF + l * 400, row = buf + chunk(sq * 4);
    auto ld = [&](uint32_t ad) { uint32_t v; asm volatile("ld.shared.u32 %0,[%1];" : "=r"(v) : "r"(ad)); return v; };
    const int blk = pc * 16 + n, half = blk >> 5, col = (blk & 31) * 8 + l;
    const int ks = k == NC - 1 ? 0 : k + 1;
    uint32_t cw[4], sv[8], m[2] = {0, 0};
    { const uint32_t a0 = row + (72 + 2 * ks + (l >> 2)) * 4;
#pragma unroll
      for (int u = 0; u < 8; u++) { sv[u] = ld((a0 ^ ((u >> 2) * 4)) + (u & 3) * 3200); m[u >> 2] |= s_mask(sv[u], l & 3) << (8 * (u & 3)); } }
#pragma unroll
    for (int h = 0; h < 2; h++) { m[h] |= __shfl_xor_sync(0xffffffffu, m[h], 1); m[h] |= __shfl_xor_sync(0xffffffffu, m[h], 2); }
#pragma unroll
    for (int u = 0; u < 4; u++) cw[u] = s_cell(sv[u], l & 3, (m[0] >> (8 * u)) & 255) | s_cell(sv[4 + u], l & 3, (m[1] >> (8 * u)) & 255) << 12;
    if (k == NC - 1) {
      g_scr[I0_OFF + (half * 8 + sq) * TH + col] = make_uint4(cw[0], cw[1], cw[2], cw[3]);
      g_scr[IX_OFF + half * IXH + NC * 8192 + sq * TH + col] = make_uint4(ld(row + 396), ld(row + 3596), ld(row + 6796), ld(row + 9996));
      cw[0] = cw[1] = cw[2] = cw[3] = 0;
    }
    const uint32_t ax = buf + chunk(min(sq + 1, 7) * 4) + (90 + k) * 4;
    const uint32_t yev = ld(buf + ((0x3210 >> (sq * 2 + (sq == 5) * 2)) & 3) * 3200 + (90 + k) * 4);
    uint4* dst = g_scr + IX_OFF + half * IXH + (k * NS + sq * 4) * TH + col;
#pragma unroll
    for (int u = 0; u < 4; u++) {
      uint32_t e[8];
#pragma unroll
      for (int jj = 0; jj < 8; jj++) e[jj] = ld(row + k * 32 + rot[jj] + u * 3200);
      dst[u * TH] = make_uint4(pk3(e[0], e[1], e[2] + inc[0]), pk3(e[3], e[4], e[5] + inc[1]), pk3(e[6], e[7], ld(ax + u * 3200) + inc[2]),
                               u < 3 ? __byte_perm(cw[u], cw[3], 0x4210 + (u << 12)) : yev);
    }
    mbar_arrive_lane0(empty + (n & 1) * 8);
  }
  (void)CH;
}

__global__ void __cluster_dims__(2, 1, 1) __launch_bounds__(512, 1)
k_tens(const __grid_constant__ CUtensorMap mapW, const __grid_constant__ CUtensorMap mapL, const __grid_constant__ CUtensorMap mapS,
       const __grid_constant__ CUtensorMap mapT, const __grid_constant__ CUtensorMap mapE, const __grid_constant__ CUtensorMap mapC, cudaTextureObject_t tex, cudaTextureObject_t texX,
       const int* __restrict__ idx, const __nv_bfloat16* __restrict__ table, const __nv_bfloat16* __restrict__ wp, const __nv_bfloat16* __restrict__ w1,
       const __nv_bfloat16* __restrict__ b1, int never) {
  extern __shared__ __align__(1024) uint4 sm[];
  const int tid = threadIdx.x, lane = tid & 31, cta = blockIdx.x;
  const uint32_t sbase = (uint32_t)__cvta_generic_to_shared(sm);
  const int g = lane >> 2, r = lane & 3;
  TS(0, 0);
  if (cta >= 128) {
    pack_role(idx, sbase, cta - 128);
    __syncthreads();
    if (tid < 32) flag_arrive(&g_flag[8 * 32], lane);
    TS(2, 1);
    asm volatile("barrier.cluster.arrive.relaxed.aligned; barrier.cluster.wait.aligned;" ::: "memory");
    return;
  }
  const uint32_t fullB = sbase + K1_BAR, emptyB = fullB + 24, fullE = fullB + 48, fullC = fullB + 56, fullI = fullB + 64, fullX = fullB + 72, progG = fullB + 80, fullS = fullB + 96, emptyS = fullB + 128;
  const int rb = cta & 7, hc = cta >> 3;
  if (MCW && (tid >> 5) != 12) asm volatile("barrier.cluster.arrive.relaxed.aligned;" ::: "memory");
  if (tid >= 384) {
    asm volatile("setmaxnreg.dec.sync.aligned.u32 " RAUX ";");
    if (tid < 416) {
      if (tid == 384) {
        for (int q = 0; q < 2; q++) { mbar_init(fullB + q * 8, 1); mbar_init(emptyB + q * 8, 8); }
        mbar_init(fullS, 4); mbar_init(emptyS, 1);
        mbar_init(fullE, 1); mbar_init(fullC, 1); mbar_init(fullI, 1); mbar_init(fullX, 1); mbar_init(progG, 1);
        asm volatile("fence.proxy.async.shared::cta;" ::: "memory");
        mbar_expect(fullC, 16384);
        for (int q = 0; q < 4; q++)
          asm volatile("cp.async.bulk.tensor.2d.shared::cluster.global.mbarrier::complete_tx::bytes [%0],[%1,{%2,%3}],[%4];"
                       :: "r"(sbase + 32768 + q * 4096), "l"(&mapC), "r"((cta & 15) * 8), "r"(q * 256), "r"(fullC) : "memory");
        mbar_expect(fullE, 32768);
        for (int q = 0; q < 2; q++)
          asm volatile("cp.async.bulk.tensor.2d.shared::cluster.global.mbarrier::complete_tx::bytes [%0],[%1,{%2,%3}],[%4];"
                       :: "r"(sbase + K1_B + 32768 + q * 16384), "l"(&mapE), "r"(q * 64), "r"(rb * 128), "r"(fullE) : "memory");
      }
      __syncwarp();
      asm volatile("bar.arrive 2,448;" ::: "memory");
      if (MCW) asm volatile("fence.mbarrier_init.release.cluster; barrier.cluster.arrive.relaxed.aligned; barrier.cluster.wait.aligned;" ::: "memory");
      if (tid == 384) {
#pragma unroll 1
        for (int n = 0; n < 25; n++) {
          const int st = n & 1, q = QORD(n);
          if (n == IORD) {
            mbar_expect(fullI, 51200);
#pragma unroll 1
            for (int u = 0; u < 8; u++) bulk_g2s(sbase + 76800 + u * 6400, idx + (((cta >> 4) * 8 + u) * 256 + (cta & 15) * 16) * F_, 6400, fullI);
          }
          mbar_wait(emptyB + st * 8, (((n + 1) >> 1) & 1) ^ 1);
          mbar_expect(fullB + st * 8, 32768);
          asm volatile("cp.async.bulk.tensor.2d.shared::cluster.global.mbarrier::complete_tx::bytes.multicast::cluster [%0],[%1,{%2,%3}],[%4],%5;"
                       :: "r"(sbase + K1_B + st * 32768 + (cta & 1) * 16384), "l"(&mapW), "r"(hc * 32), "r"(q * 512 + (cta & 1) * 256),
                          "r"(fullB + st * 8), "h"((unsigned short)3) : "memory");
          if (n == 0) for (int u = 1; u < WPF; u++) bulk_pf(w1 + QORD(u) * 262144 + cta * 2048, 4096);
          if (WPF && n + WPF < 25) bulk_pf(w1 + QORD(n + WPF) * 262144 + cta * 2048, 4096);
        }
      }
    } else if (tid < 448) {
      ((float4*)g_acc)[cta * 32 + lane] = make_float4(0.f, 0.f, 0.f, 0.f);
      asm volatile("bar.sync 2,448;" ::: "memory");
      if (HOLD) { asm volatile("bar.sync 4,288;" ::: "memory"); flag_arrive(&g_flag[(cta >> 4) * 32], lane); }
      __syncwarp();
      if (tid == 416) {
#pragma unroll 1
        for (int n = 0; n < 50; n++) {
          const int quad = QORD(n >> 1), mt = n & 1, v0 = rb * 128 + mt * 64;
          const uint32_t stg = sbase + K1_STG;
          const uint64_t pol = n < 2 * NEF ? POL_EF : POL_N;
          mbar_wait(fullS, n & 1);
          asm volatile("fence.proxy.async.shared::cta;" ::: "memory");
          if (quad < 18) {
            asm volatile("cp.async.bulk.tensor.4d.global.shared::cta.bulk_group.L2::cache_hint [%0,{%1,%2,%3,%4}],[%5],%6;"
                         :: "l"(&mapL), "r"((quad & 1) * 32), "r"(v0), "r"(quad >> 1), "r"(hc * 4), "r"(stg), "l"(pol) : "memory");
          } else {
#pragma unroll 1
            for (int hh = 0; hh < 2; hh++) {
              const int pq = quad * 2 + hh;
              if (pq < 45) asm volatile("cp.async.bulk.tensor.4d.global.shared::cta.bulk_group.L2::cache_hint [%0,{%1,%2,%3,%4}],[%5],%6;"
                         :: "l"(&mapS), "r"(0), "r"(v0 >> 2), "r"(pq - 36), "r"(hc * 4), "r"(stg + hh * 8192), "l"(pol) : "memory");
              else asm volatile("cp.async.bulk.tensor.3d.global.shared::cta.bulk_group.L2::cache_hint [%0,{%1,%2,%3}],[%4],%5;"
                         :: "l"(&mapT), "r"(v0 * 2), "r"((pq - 45) * 2), "r"(hc * 4), "r"(stg + hh * 8192), "l"(pol) : "memory");
            }
          }
          asm volatile("cp.async.bulk.commit_group;" ::: "memory");
          asm volatile("cp.async.bulk.wait_group.read 0;" ::: "memory");
          mbar_arrive(emptyS);
        }
        asm volatile("cp.async.bulk.wait_group 0;" ::: "memory");
        asm volatile("fence.proxy.async.global;" ::: "memory");
        __threadfence();
        asm volatile("red.release.gpu.global.add.u32 [%0],1;" :: "l"(&g_flag[8 * 32]) : "memory");
        flag_wait(&g_flag[8 * 32], 132);
        asm volatile("fence.proxy.async.global;" ::: "memory");
        const char* base = (const char*)g_scr;
        const int c = cta >> 1, half = cta & 1, ch = (c + (c >> 4) * 5) & 15;
        bulk_pf(base + (PS_OFF + c * NC * 2000) * 16u + half * 16000, 16000);
        if (PREW & 2) bulk_pf(base + (PL_OFF + c * NC * 8000) * 16u + half * 64000, 64000);
        bulk_pf(base + (PT_OFF + c * 10 * 1024) * 16u + half * 8192, 8192);
        mbar_expect(fullE, 18432);
        bulk_g2s(sbase + K1_B, base + (I0_OFF + half * 2048 + ch * 128) * 16u, 2048, fullE);
        bulk_g2s(sbase + K1_B + 2048, base + (IX_OFF + half * IXH + ch * 512) * 16u, 8192, fullE);
        bulk_g2s(sbase + K1_B + 10240, base + (IX_OFF + half * IXH + 8192 + ch * 512) * 16u, 8192, fullE);
        mbar_wait(fullE, 1);
      }
    } else if (tid >= 480) {
      if (!HOLD) { asm volatile("bar.sync 4,288;" ::: "memory"); flag_arrive(&g_flag[(cta >> 4) * 32], lane); }
    } else if (tid == 448 && PXW) {
      flag_wait(&g_flag[(cta >> 4) * 32], 16);
      asm volatile("fence.proxy.async.global;" ::: "memory");
      const char* src = (const char*)(g_scr + PX_OFF + ((cta >> 4) * 8 + ((cta >> 1) & 3) * 2) * 16 * 136);
#pragma unroll 1
      for (int n = 1; n < 16; n++) {
        if (n >= PXW) mbar_wait(progG, (n - PXW) & 1);
        mbar_expect(fullX, 4352);
        bulk_g2s(sbase + K1_BAR + 256, src + n * 2176, 2176, fullX);
        bulk_g2s(sbase + K1_BAR + 256 + 2176, src + (16 + n) * 2176, 2176, fullX);
        mbar_wait(fullX, (n - 1) & 1);
      }
    }
    return;
  }
  if (tid >= 256) {
    asm volatile("setmaxnreg.inc.sync.aligned.u32 " RPRO ";");
    const int w = (tid >> 5) & 3;
    const int srow = w * 16 + (lane & 7) + ((lane >> 3) & 1) * 8, sc = lane >> 4;
    uint32_t a[2][8][4];
    asm volatile("bar.sync 2,448;" ::: "memory");
    mbar_wait_fast(fullE, 0);
#pragma unroll
    for (int mt = 0; mt < 2; mt++)
#pragma unroll
      for (int ks = 0; ks < 8; ks++)
        asm volatile("ldmatrix.sync.aligned.m8n8.x4.shared.b16 {%0,%1,%2,%3},[%4];"
                     : "=r"(a[mt][ks][0]), "=r"(a[mt][ks][1]), "=r"(a[mt][ks][2]), "=r"(a[mt][ks][3])
                     : "r"(sbase + K1_B + 32768 + (ks >> 2) * 16384 + (mt * 64 + srow) * 128 + ((((ks & 3) * 2 + sc) ^ (lane & 7)) * 16)) : "memory");
    asm volatile("barrier.cluster.wait.aligned;" ::: "memory");
    arrive_both(emptyB + 8, lane);
    const uint32_t baseL = sc * 4096 + srow * 64 + ((srow >> 1) & 3) * 16, baseS = sc * 2048 + ((srow * 32) ^ (((srow >> 2) & 7) * 16)), baseT = sc * 2048 + srow * 16;
    const uint64_t desc0 = (uint64_t)(((sbase + K1_B) & 0x3FFFF) >> 4) | ((uint64_t)(8192 >> 4) << 16) | ((uint64_t)(512 >> 4) << 32) | (2ull << 62);
#pragma unroll 1
    for (int qn = 0; qn < 25; qn++) {
      const int quad = QORD(qn), st = qn & 1;
      const bool isL = quad < 18;
      PT(qn * 16);
      mbar_wait_fast(fullB + st * 8, (qn >> 1) & 1);
#pragma unroll
      for (int mt = 0; mt < 2; mt++) {
        float d[64];
        PT(qn * 16 + mt * 4 + 1);
        asm volatile("wgmma.fence.sync.aligned;" ::: "memory");
#pragma unroll
        for (int ks = 0; ks < 8; ks++) wgmma_p(d, a[mt][ks], desc0 + st * 2048 + ks * 64, ks);
        asm volatile("wgmma.commit_group.sync.aligned;" ::: "memory");
        mbar_wait_fast(emptyS, mt ^ 1);
        PT(qn * 16 + mt * 4 + 2);
        asm volatile("wgmma.wait_group.sync.aligned 0;" ::: "memory");
#pragma unroll
        for (int q = 0; q < 16; q++) asm volatile("" : "+f"(d[q * 4]), "+f"(d[q * 4 + 1]), "+f"(d[q * 4 + 2]), "+f"(d[q * 4 + 3]) :: "memory");
        PT(qn * 16 + mt * 4 + 3);
        if (mt) arrive_both(emptyB + st * 8, qn < 23 ? lane : 9);
        if (quad == 24) {
#pragma unroll
          for (int cq = 0; cq < 4; cq++) {
            const uint32_t bw = __ldg((const uint32_t*)(b1 + hc * 32 + cq * 8) + r);
#pragma unroll
            for (int e = 0; e < 4; e++) d[48 + cq * 4 + e] += (e & 1) ? bf_hi(bw) : bf_lo(bw);
          }
        }
#pragma unroll
        for (int h = 0; h < 2; h++) {
          const bool isS = quad * 2 + h < 45;
          const uint32_t base = (isL ? baseL ^ (h * 32) : (isS ? baseS : baseT) ^ (h * 8192)), xj = isS ? 16 : 1024, xc = isL ? 8192 : 4096;
#pragma unroll
          for (int e4 = 0; e4 < 4; e4++) {
            const float* e = d + h * 32 + e4 * 8;
            asm volatile("stmatrix.sync.aligned.m8n8.x4.shared.b16 [%0],{%1,%2,%3,%4};"
                         :: "r"(sbase + K1_STG + (base ^ ((e4 >> 1) * xj) ^ ((e4 & 1) * xc))),
                            "r"(pack_bf2(e[0], e[1])), "r"(pack_bf2(e[2], e[3])), "r"(pack_bf2(e[4], e[5])), "r"(pack_bf2(e[6], e[7])) : "memory");
          }
        }
        __syncwarp();
        mbar_arrive_lane0(fullS);
        if (!mt) PT(qn * 16 + 4);
      }
      PT(qn * 16 + 8);
    }
    return;
  }
  asm volatile("setmaxnreg.inc.sync.aligned.u32 " RPNN ";");
  const int slice = cta & 15;
  const int range = (cta >> 4) * 8 + __shfl_sync(0xffffffffu, tid >> 5, 0);
  uint4 iv[4], trow[4]; uint32_t ix;
  uint2 wrow[10];
#pragma unroll
  for (int q = 0; q < 10; q++) asm volatile("ld.global.nc.v2.u32 {%0,%1},[%2];" : "=r"(wrow[q].x), "=r"(wrow[q].y) : "l"((const uint2*)wp + min(tid + q * 256, 2499)));
  asm volatile("bar.sync 2,448;" ::: "memory");
  uint32_t me = 0, mw = 0;
#pragma unroll
  for (int q = 0; q < 10; q++) {
    mw = __vmaxu2(__vmaxu2(wrow[q].x & 0x7fff7fffu, wrow[q].y & 0x7fff7fffu), mw);
    const int e = min(tid + q * 256, 2499), row = e / 25;
    asm volatile("st.shared.v2.u32 [%0],{%1,%2};" :: "r"(sbase + (e + row) * 8), "r"(wrow[q].x), "r"(wrow[q].y) : "memory");
    if (e - row * 25 == 24) asm volatile("st.shared.v2.u32 [%0],{%1,%2};" :: "r"(sbase + (e + row) * 8 + 8), "r"(wrow[q].x), "r"(wrow[q].y) : "memory");
  }
  mbar_wait_fast(fullC, 0);
#pragma unroll
  for (int q = 0; q < 4; q++) { trow[q] = lds128(sbase + 32768 + (tid + q * 256) * 16); me = absmax4(trow[q], me); }
  me = __reduce_max_sync(0xffffffffu, max(me & 0xffff, me >> 16));
  mw = __reduce_max_sync(0xffffffffu, max(mw & 0xffff, mw >> 16));
  uint32_t* sred = (uint32_t*)((char*)sm + 128000);
  if (lane == 0) sred[tid >> 5] = me | mw << 16;
  TS(3, 0);
  asm volatile("bar.sync 1,256;" ::: "memory");
  { uint32_t m = 0;
#pragma unroll
    for (int q = 0; q < 8; q++) m = __vmaxu2(m, sred[q]);
    m = __shfl_sync(0xffffffffu, m, 0);
    me = m & 0xffff; mw = m >> 16; }
  const float se = pow2_scale(me, 3), sW = pow2_scale(mw, -2);
  TS(3, 1);
  auto put_rows = [&](int q, bool on) {
    const uint4 t = trow[q];
    const uint4 hv = make_uint4(pack_h2(bf_lo(t.x) * se, bf_hi(t.x) * se), pack_h2(bf_lo(t.y) * se, bf_hi(t.y) * se),
                                pack_h2(bf_lo(t.z) * se, bf_hi(t.z) * se), pack_h2(bf_lo(t.w) * se, bf_hi(t.w) * se));
    if (on)
#pragma unroll
      for (int s = 0; s < 8; s++) sts128(sbase + (tid + q * 256) * 128 + ((s + lane) & 7) * 16, hv);
  };
#pragma unroll 1
  for (int it = 0; it < 3; it++) {
    const int hu = ((tid >> 5) * 3 + it) * 4, code = hu_code(min(hu + (lane >> 3), HU_N - 1)), ok = code >> 4, on = code & 15;
    uint32_t x[4], y[4];
    asm volatile("ldmatrix.sync.aligned.m8n8.x4.shared.b16 {%0,%1,%2,%3},[%4];" : "=r"(x[0]), "=r"(x[1]), "=r"(x[2]), "=r"(x[3])
                 : "r"(sbase + (on * 8 + (lane & (on == 12 ? 3 : 7))) * 208 + ok * 16) : "memory");
    asm volatile("ldmatrix.sync.aligned.m8n8.x4.trans.shared.b16 {%0,%1,%2,%3},[%4];" : "=r"(y[0]), "=r"(y[1]), "=r"(y[2]), "=r"(y[3])
                 : "r"(sbase + (ok * 8 + (lane & (ok == 12 ? 3 : 7))) * 208 + on * 16) : "memory");
    const uint32_t lo = __ballot_sync(0xffffffffu, ok > on), dg = __ballot_sync(0xffffffffu, ok >= on);
#pragma unroll
    for (int q = 0; q < 4; q++) {
      const float m0 = (lo >> (8 * q)) & 1 ? 0.f : sW, m1 = (dg >> (8 * q)) & 1 ? 0.f : sW;
      asm volatile("st.shared.u32 [%0],%1;" :: "r"(sbase + K1_W + (hu + q) * 128 + lane * 4),
                   "r"(pack_h2(fmaf(bf_lo(x[q]), m0, bf_lo(y[q]) * m1), fmaf(bf_hi(x[q]), m0, bf_hi(y[q]) * m1))) : "memory");
    }
  }
  put_rows(1, true); put_rows(2, tid < 88);
  TS(3, 2);
  asm volatile("fence.proxy.async.shared::cta;" ::: "memory");
  asm volatile("bar.sync 1,256;" ::: "memory");
  put_rows(0, true);
  uint32_t bf[HU_N - 2 * G_U];
#pragma unroll
  for (int q = 0; q < HU_N - 2 * G_U; q++) asm volatile("ld.shared.u32 %0,[%1];" : "=r"(bf[q]) : "r"(sbase + K1_W + (2 * G_U + q) * 128 + lane * 4));
  const float unscale = __uint_as_float(0x7f000000u - __float_as_uint(se)), unscale2 = __uint_as_float(0x7f000000u - __float_as_uint(sW));
  TS(3, 3);
  const int px = range * 16 * 136;
  mbar_wait_fast(fullI, 0);
  {
    const uint32_t ib = sbase + 76800 + (tid >> 5) * 6400, p0 = ib + ((lane >> 3) & 1) * 400 + ((lane >> 4) * 8 + (lane & 7)) * 4;
    auto ld = [&](uint32_t ad) { uint32_t v; asm volatile("ld.shared.u32 %0,[%1];" : "=r"(v) : "r"(ad)); return v; };
    auto wd = [&](int t, int h) { return pk3(ld(p0 + t * 800 + h * 192), ld(p0 + t * 800 + h * 192 + 64), ld(p0 + t * 800 + h * 192 + 128)); };
#pragma unroll
    for (int q = 0; q < 4; q++) {
      iv[q] = make_uint4(wd(2 * q, 0), wd(2 * q, 1), wd(2 * q + 1, 0), wd(2 * q + 1, 1));
      g_scr[PX_OFF + px + slice * 136 + q * 32 + lane] = iv[q];
    }
    ix = pk3(ld(ib + g * 400 + 384 + r * 4), ld(ib + (8 + g) * 400 + 384 + r * 4), 0);
    ((uint32_t*)(g_scr + PX_OFF + px + slice * 136 + 128))[lane] = ix;
  }
  asm volatile("bar.arrive 4,288;" ::: "memory");
  asm volatile("bar.sync 1,256;" ::: "memory");
  put_rows(2, tid >= 88); put_rows(3, tid + 768 < V_);
  asm volatile("bar.sync 1,256;" ::: "memory");
  TS(0, 1);
  uint32_t lc; asm volatile("add.u32 %0,%1,%2;" : "=r"(lc) : "r"((lane & 7) * 16), "r"(never));
  const uint64_t wdesc = (uint64_t)(((sbase + K1_W) & 0x3FFFF) >> 4) | ((uint64_t)(128 >> 4) << 16) | ((uint64_t)(256 >> 4) << 32);
  uint32_t a[2][6][4], d[2][26], ex[4] = {}, s[4] = {};
  float red[4] = {0.f, 0.f, 0.f, 0.f};
  auto ldsm = [&](uint32_t* o, uint32_t sh, uint32_t dep = 0) {
    asm volatile("ldmatrix.sync.aligned.m8n8.x4.trans.shared.b16 {%0,%1,%2,%3},[%4];"
                 : "=r"(o[0]), "=r"(o[1]), "=r"(o[2]), "=r"(o[3]) : "r"(sbase + ((sh & 0x1ff80) | (lc | (dep & never)))));
  };
  auto gather = [&](int t, int hf) {
    const int x = t & 1;
    const uint4 v = iv[(t >> 1) & 3];
#pragma unroll
    for (int kb = 3 * hf; kb < 3 * hf + 3; kb++) {
      const uint32_t ww = x ? (kb < 3 ? v.z : v.w) : (kb < 3 ? v.x : v.y);
      ldsm(a[x][kb], kb % 3 == 0 ? ww : kb % 3 == 1 ? ww >> 10 : __funnelshift_l(ww, ww, 12));
    }
  };
  auto issue = [&](int x) {
    asm volatile("wgmma.fence.sync.aligned;" ::: "memory");
#pragma unroll
    for (int kb = 0; kb < 6; kb++) {
      if (kb < G_K0) wgmma_h<G_N0 * 8>(d[x] + G_O0 * 2, a[x][kb], wdesc + kb * G_N0 * 16, kb);
      if (kb < G_K1) wgmma_h<G_N1 * 8>(d[x] + G_O1 * 2, a[x][kb], wdesc + (G_U1 + kb * G_N1) * 16, kb);
      if (kb < G_K2) wgmma_h<32>(d[x] + G_O2 * 2, a[x][kb], wdesc + (G_U2 + kb * G_N2) * 16, kb);
    }
    asm volatile("wgmma.commit_group.sync.aligned;" ::: "memory");
  };
  auto hmma_part = [&](int t) {
    constexpr FragIdx FI = make_fi();
    const int x = t & 1;
#pragma unroll
    for (int o = 0; o < 13; o++) {
      if (oct_wg(o)) asm volatile("" : "+r"(d[x][o * 2]), "+r"(d[x][o * 2 + 1]) :: "memory"); else d[x][o * 2] = d[x][o * 2 + 1] = 0;
    }
#pragma unroll
    for (int kb = 0; kb < 6; kb++)
#pragma unroll
      for (int o = 2 * kb + 1; o < 13; o++)
        if (!unit_wg(kb, o)) mma16816h(d[x] + o * 2, a[x][kb], bf[FI.v[2 * kb][o]], bf[FI.v[2 * kb + 1][o]]);
#pragma unroll
    for (int q = 0; q < 6; q++) if (!unit_wg(q, 2 * q)) mma1688h(d[x] + q * 4, a[x][q][0], a[x][q][1], bf[FI.v[2 * q][2 * q]]);
    mma1688h(d[x] + 24, r < 2 ? ex[t & 3] : 0u, r < 2 ? 0u : ex[t & 3], bf[FI.v[12][12]]);
  };
  auto dot_part = [&](int t, int hf) {
    const int x = t & 1;
    if (hf == 0) {
      const uint32_t pe = hfma2(r < 2 ? d[x][24] : d[x][25], ex[t & 3], 0u);
      s[0] = r < 2 ? pe : 0u; s[1] = r < 2 ? 0u : pe; s[2] = s[3] = 0;
    }
#pragma unroll
    for (int q = 3 * hf; q < 3 * hf + 3; q++)
#pragma unroll
      for (int e = 0; e < 4; e++) s[e] = hfma2(d[x][q * 4 + e], a[x][q][e], s[e]);
  };
  float* outp = g_partP + slice * B_ + range * 256;
  float k0 = 0.f, k1 = 0.f, x0 = 0.f, x1 = 0.f;
  auto red_stage = [&](int st, int grp) {
    const bool u16 = lane & 16, u8 = lane & 8;
    if (st == 0) {
      k0 = u16 ? red[2] : red[0]; x0 = __shfl_xor_sync(0xffffffffu, u16 ? red[0] : red[2], 16);
      k1 = u16 ? red[3] : red[1]; x1 = __shfl_xor_sync(0xffffffffu, u16 ? red[1] : red[3], 16);
      red[0] = red[1] = red[2] = red[3] = 0.f;
    }
    if (st == 1) { const float p0 = k0 + x0, p1 = k1 + x1; k0 = u8 ? p1 : p0; x0 = __shfl_xor_sync(0xffffffffu, u8 ? p0 : p1, 8); }
    if (st == 2) { k0 += x0; x0 = __shfl_xor_sync(0xffffffffu, k0, 4); }
    if (st == 3 && !(lane & 4)) outp[grp * 16 + r * 4 + ((lane >> 3) & 1) * 2 + (lane >> 4)] = (k0 + x0) * unscale * unscale * unscale2;
  };
  auto group = [&](bool first, int prv, int cur, int nxt) {
    const int pn = PX_OFF + px + nxt * 136 + lane;
#pragma unroll
    for (int t = 0; t < 8; t++) {
      issue((t & 1) ^ 1);
      SCHED_FENCE(never, t * 8);
      if (!first) {
        if (t == 0) { iv[3] = ldtex(tex, PX_OFF + px + cur * 136 + lane + 96); iv[0] = ldtex(tex, pn); }
        if (t == 2) iv[1] = ldtex(tex, pn + 32);
        if (t < 4) red_stage(t, prv);
      } else if (t == 4) {
        TS(4, 2);
        flag_wait(&g_flag[(cta >> 4) * 32], 16);
        TS(4, 3);
        iv[0] = ldtex(tex, pn); iv[1] = ldtex(tex, pn + 32);
      }
      if (t == 4) { ix = ldtex(texX, (px + nxt * 136 + 128) * 4 + lane).x; iv[2] = ldtex(tex, pn + 64); }
      dot_part(t, 0);
      SCHED_FENCE(never, t * 8 + 1);
      if (t == 3) ldsm(ex, ix >> 10);
      if (t == 7) ldsm(ex, ix);
      gather(t + 2, 0);
      dot_part(t, 1);
      SCHED_FENCE(never, t * 8 + 4);
      gather(t + 2, 1);
      asm volatile("wgmma.wait_group.sync.aligned 0;" ::: "memory");
      if (FM & 1) SCHED_FENCE(never, t * 8 + 2);
      asm volatile("" : "+r"(d[(t & 1) ^ 1][0]) :: "memory");
      mma1688f(red, hadd2(s[0], s[2]), hadd2(s[1], s[3]), (g | (d[(t & 1) ^ 1][0] & never)) == t ? 0x3c003c00u : 0u);
      hmma_part(t + 1);
      if (FM & 2) SCHED_FENCE(never, t * 8 + 3);
    }
  };
  gather(0, 0); gather(0, 1); issue(0); ldsm(ex, ix); gather(1, 0); gather(1, 1);
  asm volatile("wgmma.wait_group.sync.aligned 0;" ::: "memory");
  hmma_part(0);
  int prv = slice, cur = slice == 0;
  group(true, 0, prv, cur);
  TS(4, 1);
#pragma unroll 1
  for (int n = 1; n < NGRP; n++) {
    const int nxt = (n + (n >= slice)) & 15;
    if (n == TRIG) asm volatile("griddepcontrol.launch_dependents;");
    if (PXW && tid == 0) mbar_arrive(progG);
    group(false, prv, cur, nxt);
    prv = cur; cur = nxt;
  }
#pragma unroll
  for (int st = 0; st < 4; st++) red_stage(st, prv);
  TS(0, 2);
  if (MCW) asm volatile("barrier.cluster.wait.aligned;" ::: "memory");
  asm volatile("barrier.cluster.arrive.relaxed.aligned; barrier.cluster.wait.aligned;" ::: "memory");
}

constexpr int SM_U = 130048, SM_BAR = 128000, SM_J = SM_U + 98304, DEEP_SMEM = SM_J + 4096;

#define ELECT "{.reg .pred p; elect.sync _|p,0xffffffff; @p "
__device__ __forceinline__ void e_mc(uint32_t dst, const void* src, uint32_t bytes, uint32_t bar, uint64_t pol) {
  asm volatile(ELECT "cp.async.bulk.shared::cluster.global.mbarrier::complete_tx::bytes.multicast::cluster.L2::cache_hint [%0],[%1],%2,[%3],%4,%5;}"
               :: "r"(dst), "l"(src), "r"(bytes), "r"(bar), "h"((unsigned short)3), "l"(pol) : "memory");
}
__device__ __forceinline__ void e_g2s(uint32_t dst, const void* src, uint32_t bytes, uint32_t bar) {
  asm volatile(ELECT "cp.async.bulk.shared::cluster.global.mbarrier::complete_tx::bytes [%0],[%1],%2,[%3];}" :: "r"(dst), "l"(src), "r"(bytes), "r"(bar) : "memory");
}
__device__ __forceinline__ void e_pf(const void* src, uint32_t bytes) { asm volatile(ELECT "cp.async.bulk.prefetch.L2.global [%0],%1;}" :: "l"(src), "r"(bytes) : "memory"); }
__device__ __forceinline__ void e_expect(uint32_t bar, uint32_t bytes) { asm volatile(ELECT "mbarrier.arrive.expect_tx.shared::cta.b64 _,[%0],%1;}" :: "r"(bar), "r"(bytes) : "memory"); }

__global__ void __cluster_dims__(2, 1, 1) __launch_bounds__(TH + 128, 1)
k_deep(cudaTextureObject_t tex, const __nv_bfloat16* __restrict__ w2, const __nv_bfloat16* __restrict__ b2,
       __nv_bfloat16* __restrict__ out, int never) {
  extern __shared__ __align__(1024) uint4 sm[];
  constexpr int PF = DPF, DEPTH = DDEPTH, NW = TH / 32;
  static_assert(YD == 4 && PF == 4, "");
  const int tid = threadIdx.x;
  const int c = blockIdx.x >> 1, half = blockIdx.x & 1;
  const uint32_t sbase = (uint32_t)__cvta_generic_to_shared(sm);
  const uint32_t fullL = sbase + SM_BAR, fullU = fullL + 8, emptyL = fullL + 16, emptyU = fullL + 24, barJ = fullL + 32;
  TS(1, 0);
  if (tid == 0) {
    mbar_init(fullL, 1); mbar_init(fullU, 1); mbar_init(emptyL, 2 * NW); mbar_init(emptyU, 2 * NW); mbar_init(barJ, 1);
    asm volatile("fence.mbarrier_init.release.cluster;" ::: "memory");
  }
  __syncwarp();
  const int wrp = __shfl_sync(0xffffffffu, tid >> 5, 0);
  const char* base = (const char*)g_scr;
  uint32_t oL = (PL_OFF + c * NC * 8000) * 16u + half * 64000, oS = (PS_OFF + c * NC * 2000) * 16u + half * 16000;
  asm volatile("barrier.cluster.arrive.relaxed.aligned;" ::: "memory");
  flag_wait(&g_flag[8 * 32], 132);
  asm volatile("barrier.cluster.wait.aligned;" ::: "memory");
  if (wrp == NW) {
    asm volatile("fence.proxy.async.global;" ::: "memory");
    e_expect(fullU, 96000);
#pragma unroll
    for (int m = 0; m < 3; m++) e_mc(sbase + SM_U + m * 32032 + half * 16000, base + oS, 16000, fullU, m == 2 ? POL_EF : POL_N);
    e_expect(fullL, 128000);
    if (!STAG) e_mc(sbase + half * 64000, base + oL, 64000, fullL, POL_EF);
  }
  TS(5, 1);
  if (wrp >= NW) {
    asm volatile("setmaxnreg.dec.sync.aligned.u32 24;");
    if (wrp == NW) {
      uint32_t oT = (PT_OFF + c * 10 * 1024) * 16u + half * 8192;
      const uint32_t junk = sbase + SM_J, oW = (IX_OFF + half * IXH + ((c + (c >> 4) * 5) & 15) * 512) * 16u;
      auto warm = [&](uint32_t off) {
        asm volatile(ELECT "mbarrier.expect_tx.relaxed.cta.shared::cta.b64 [%0],%1;}" :: "r"(barJ), "r"(8192) : "memory");
        e_g2s(junk, base + off, 4096, barJ); e_g2s(junk, base + off + 4096, 4096, barJ);
      };
      uint32_t t0 = clock();
      if (!PREW) warm(oW);
      if (STAG) { if (STAG == 1) mbar_wait_fast(fullU, 0); else sleep_until(t0, STAG); e_mc(sbase + half * 64000, base + oL, 64000, fullL, POL_EF); }
      warm(oT);
      if (!(PREW & 4)) warm(oW + 131072);
#pragma unroll 1
      for (int k = 0; k + 1 < NC; k++) {
        oL += 128000; oS += 32000; oT += 16384;
        mbar_wait_fast(fullL, k & 1);
        t0 = clock();
        e_pf(base + oS, 16000);
        if (k + 2 < NC) {
          const uint32_t o2 = (IX_OFF + half * IXH + (k + 2) * 8192) * 16u + ((c + (c / (64 / WRED)) * (2 * k + 1)) & (64 / WRED - 1)) * (WRED * 2048);
#pragma unroll 1
          for (int q = 0; q < WRED / 4; q++) warm(o2 + q * 8192);
        } else warm((IX_OFF + half * IXH + NC * 8192 + (c & 3) * 512) * 16u);
        mbar_wait_fast(emptyU, k & 1);
        e_expect(fullU, 96000);
#pragma unroll 1
        for (int q = 0; q < 8; q++) {
          sleep_until(t0, q * PACE);
          e_pf(base + oL + q * 8000, 8000);
          if (q >= 2) e_mc(sbase + SM_U + ((q - 2) >> 1) * 32032 + half * 16000 + (q & 1) * 8000, base + oS + (q & 1) * 8000, 8000, fullU, q >= 6 ? POL_EF : POL_N);
        }
        warm(oT);
        e_expect(fullL, 128000);
        sleep_until(t0, RSV_T);
        unsigned long long now, slot = 0;
        asm volatile("mov.u64 %0,%globaltimer;" : "=l"(now));
        if ((tid & 31) == 0) { atomicMax(&g_slot, now + RSV_L); slot = atomicAdd(&g_slot, (unsigned long long)RSV); }
        slot = __shfl_sync(0xffffffffu, slot, 0);
        mbar_wait_fast(emptyL, k & 1);
        for (int it = 0; it < 4000; it++) { asm volatile("mov.u64 %0,%globaltimer;" : "=l"(now)); if (now >= slot) break; }
        e_mc(sbase + half * 64000, base + oL, 64000, fullL, POL_EF);
      }
      mbar_wait_fast(fullL, (NC - 1) & 1);
      mbar_wait_fast(emptyU, (NC - 1) & 1);
      mbar_arrive_lane0(fullU);
      warm(oT + 16384);
      mbar_arrive_lane0(barJ); mbar_wait_fast(barJ, 0);
    } else if (tid >= TH + 96) {
      if (tid == TH + 96) sts128(barJ + 32, *(const uint4*)(w2 + c * 8));
      asm volatile("bar.arrive 3,%0;" :: "n"(TH + 32) : "memory");
      asm volatile("griddepcontrol.wait;" ::: "memory");
      const int b = half * 8192 + c * 128 + (tid & 31) * 4;
      const float bias = __bfloat162float(b2[0]);
      float4 s = make_float4(bias, bias, bias, bias);
#pragma unroll 2
      for (int k = 0; k < 16; k++) { const float4 v = __ldcg((const float4*)(g_partP + k * B_ + b)); s.x += v.x; s.y += v.y; s.z += v.z; s.w += v.w; }
      asm volatile("red.global.add.v4.f32 [%0],{%1,%2,%3,%4};" :: "l"(g_acc + b), "f"(s.x), "f"(s.y), "f"(s.z), "f"(s.w) : "memory");
      asm volatile("bar.arrive 1,%0;" :: "n"(TH + 32) : "memory");
    }
    return;
  }
  asm volatile("setmaxnreg.inc.sync.aligned.u32 240;");
  const int lane = tid & 31;
  const int tbase = PT_OFF + c * 10 * 1024;
  const int ibase = IX_OFF + half * IXH + tid;
  const uint32_t lc = (tid & 7) << 4;
  uint4 acc[NS], wq[PF], x[DEPTH], y[YD], ye;
  uint32_t sw[NS] = {};
  auto sget = [&](int s) { return (s & 3) == 3 ? __byte_perm(__byte_perm(sw[s - 3], sw[s - 2], 0x0073), sw[s - 1], 0x0710) : sw[s]; };
  auto sa0 = [&](uint32_t v) { return sbase + SM_U + (((v << 5) & 0x1ffe0) | ((lc >> 2) & 16)); };
  auto sa1 = [&](uint32_t v) { return sbase + SM_U + (((v >> 7) & 0x1ffe0) | ((~lc >> 2) & 16)); };
  {
    uint4 i0[8];
#pragma unroll
    for (int q = 0; q < 8; q++) i0[q] = ldtex(tex, I0_OFF + (half * 8 + q) * TH + tid);
#pragma unroll
    for (int i = 0; i < PF; i++) if (!WQL) wq[i] = ldtex(tex, ibase + i * TH);
    auto wd = [&](int k) { return (k & 3) == 0 ? i0[k >> 2].x : (k & 3) == 1 ? i0[k >> 2].y : (k & 3) == 2 ? i0[k >> 2].z : i0[k >> 2].w; };
    TS(5, 2);
    mbar_wait_fast(fullU, 0);
#pragma unroll
    for (int i = 0; i < PF; i++) if (WQL) wq[i] = ldtex(tex, ibase + i * TH);
    TS(1, 1);
#pragma unroll
    for (int s = 0; s < NS; s++) acc[s] = add4(lds128(sa0(wd(s))), lds128(sa1(wd(s))));
    arrive_both(emptyU, lane);
    asm volatile("bar.sync 3,%0;" :: "n"(TH + 32) : "memory");
    TS(5, 3);
  }
#pragma unroll 1
  for (int k = 0; k < NC; k++) {
    const int ti = ibase + k * 8192;
    const int tb = tbase + k * 1024;
    const bool more = k + 1 < NC;
    TR(k * 4);
    if (CBAR & 1) asm volatile("bar.sync 4,%0;" :: "n"(TH) : "memory");
    mbar_wait_fast(fullL, k & 1);
    TR(k * 4 + 2);
    uint4 w, cc; uint32_t yc, yn;
    constexpr int TL = NS * 8, TT = TL + NS * 2;
#pragma unroll
    for (int t = 0; t < TT + DEPTH; t += 2) {
      if (t == TL + DEPTH && !more) break;
      if (t >= DEPTH) {
        const int u = t - DEPTH;
        uint4 p = add4(x[u % DEPTH], x[(u + 1) % DEPTH]);
        if (u < TL) {
          const int s = u >> 3, j = u & 7;
          if (j == 0) {
            cc = s >= YD ? add4(y[s % YD], p) : p;
            if (s + YD < NS) y[s % YD] = ldtex(tex, tb | (yc & 1023));
          } else cc = add4(cc, p);
          if (j == 6) acc[s] = add4(acc[s], cc);
        } else {
          const int s = (u - TL) >> 1;
          acc[s] = add4(acc[s], p);
        }
      }
      if ((CBAR & 4) && t == TL / 2) asm volatile("bar.sync 4,%0;" :: "n"(TH) : "memory");
      if ((CBAR & 8) && t == TL - 40) asm volatile("bar.sync 4,%0;" :: "n"(TH) : "memory");
      if (DEPTH == 8 && (t & 7) == 2) yc = yn;
      if (t < TL) {
        const int s = t >> 3, j = t & 7;
        if (j == 0) {
          if (ye_of(s - YD) >= 0) acc[ye_of(s - YD) & 3] = add4(acc[ye_of(s - YD) & 3], ye);
          w = wq[s % PF];
          if (!EARLY || s < NS - 4) wq[s % PF] = ldtex(tex, ti + (s + PF) * TH);
          else {
            if (s == NS - 4) { wq[0] = ldtex(tex, ti + NS * TH); ye = ldtex(tex, ti + (NS + 3) * TH); }
            if (s == NS - 3) { wq[1] = ldtex(tex, ti + (NS + 1) * TH); y[0] = ldtex(tex, ti + (NS + 2) * TH); }
            if (s == NS - 2) wq[2] = y[0];
            if (s == NS - 1) wq[3] = ye;
          }
          yn = __funnelshift_l(w.z, w.z, 5); if (DEPTH < 8) yc = yn;
          if ((s & 3) != 3) asm volatile("add.u32 %0,%1,%2;" : "=r"(sw[s]) : "r"(w.w), "r"(never));
          if (ye_of(s) >= 0) ye = ldtex(tex, tb | w.w);
        }
#pragma unroll
        for (int jj = j; jj < j + 2; jj++) {
          const uint32_t ww = jj < 3 ? w.x : jj < 6 ? w.y : w.z;
          const uint32_t sh = jj % 3 == 0 ? ww : jj % 3 == 1 ? ww >> 10 : __funnelshift_l(ww, ww, 12);
          x[(t + jj - j) % DEPTH] = lds128(sbase + ((sh & 0x1ff80) | lc) + jj * 16 - 128);
        }
      } else if (t < TT) {
        const int s = (t - TL) >> 1;
        if (s == 0) { arrive_both(emptyL, more ? lane : 9); TR(k * 4 + 3); if (CBAR & 2) asm volatile("bar.sync 4,%0;" :: "n"(TH) : "memory"); mbar_wait_fast(fullU, (k + 1) & 1); }
        const uint32_t sv = sget(s);
        x[t % DEPTH] = lds128(sa0(sv));
        x[(t + 1) % DEPTH] = lds128(sa1(sv));
      } else if (t == TT) arrive_both(emptyU, lane);
      if ((t & (FENCE_N - 1)) == FENCE_N - 2) SCHED_FENCE(never, t);
    }
  }
  TS(1, 2);
  const uint4 w2v = lds128(barJ + 32);
  const uint32_t cell = sbase + SM_U + tid * 16;
  const int t9 = tbase + 9 * 1024;
  uint4 za[4], i9 = wq[0];
  auto fetch = [&](int q) {
    y[0] = ldtex(tex, t9 | i9.x); y[1] = ldtex(tex, t9 | i9.y); y[2] = ldtex(tex, t9 | i9.z); y[3] = ldtex(tex, t9 | i9.w);
    if (q) {
      i9 = ldtex(tex, ibase + NC * 8192 + min(q + 1, 7) * TH);
      const uint32_t ca = cell + (q > 6 ? 0 : q - 1) * 16384;
#pragma unroll
      for (int s = 0; s < 4; s++) za[s] = lds128(ca + s * 4096);
    }
  };
  fetch(0);
  i9 = wq[1];
#pragma unroll
  for (int s = 0; s < 4; s++) za[s] = acc[s];
#pragma unroll
  for (int s = 0; s < 24; s++) sts128(cell + s * 4096, acc[4 + s]);
  float hw[8];
  {
    const uint32_t ww[4] = {w2v.x, w2v.y, w2v.z, w2v.w};
#pragma unroll
    for (int k = 0; k < 8; k++) hw[k] = 0.5f * ((k & 1) ? bf_hi(ww[k >> 1]) : bf_lo(ww[k >> 1]));
  }
  float* outp = g_acc + half * 8192 + tid;
#pragma unroll 1
  for (int q = 0; q < NS / 4; q++) {
    uint4 z[4];
#pragma unroll
    for (int s = 0; s < 4; s++) z[s] = add4(za[s], y[s]);
    if (q == 1) {
#pragma unroll
      for (int s = 0; s < 4; s++) sts128(cell + s * 4096, acc[28 + s]);
    }
    if (q < 7) fetch(q + 1);
    SCHED_FENCE(never, 999);
#pragma unroll
    for (int s = 0; s < 4; s++) {
      const uint32_t a[4] = {z[s].x, z[s].y, z[s].z, z[s].w};
      float r0 = 0.f;
#pragma unroll
      for (int k = 0; k < 8; k++) {
        const float v = (k & 1) ? bf_hi(a[k >> 1]) : bf_lo(a[k >> 1]);
        const float u = v * fmaf(v * v, 0.7978845608028654f * 0.044715f, 0.7978845608028654f);
        float th; asm("tanh.approx.f32 %0,%1;" : "=f"(th) : "f"(u));
        r0 = fmaf(fmaf(v, th, v), hw[k], r0);
      }
      asm volatile("red.global.add.f32 [%0],%1;" :: "l"(outp + s * TH), "f"(r0) : "memory");
    }
    outp += 4 * TH;
  }
  TS(1, 3);
  asm volatile("bar.sync 1,%0;" :: "n"(TH + 32) : "memory");
  if (tid == 0) {
    __threadfence();
    const unsigned old = atomicInc(&g_done[half * 32], 63);
    asm volatile("st.shared.u32 [%0],%1;" :: "r"(barJ + 8), "r"(old) : "memory");
  }
  asm volatile("bar.sync 2,%0;" :: "n"(TH) : "memory");
  uint32_t old; asm volatile("ld.shared.u32 %0,[%1];" : "=r"(old) : "r"(barJ + 8));
  if (old == 63) {
    if (half == 0 && tid == 9) g_slot = 0;
    if (half == 0 && tid < 9) g_flag[tid * 32] = 0;
    __threadfence();
    float4 v[8];
#pragma unroll
    for (int q = 0; q < 8; q++) v[q] = __ldcg((const float4*)(g_acc + half * 8192) + q * TH + tid);
#pragma unroll
    for (int q = 0; q < 8; q++) ((uint2*)(out + half * 8192))[q * TH + tid] = make_uint2(pack_bf2(v[q].x, v[q].y), pack_bf2(v[q].z, v[q].w));
    TS(6, 2);
  }
}

}

extern "C" void kernel_launch(void* const* d_in, const int* in_sizes, int n_in, void* d_out, int out_size) {
  const int* idx = (const int*)d_in[0];
  const __nv_bfloat16* table = (const __nv_bfloat16*)d_in[1];
  const __nv_bfloat16* wp = (const __nv_bfloat16*)d_in[2];
  const __nv_bfloat16* w1 = (const __nv_bfloat16*)d_in[3];
  const __nv_bfloat16* b1 = (const __nv_bfloat16*)d_in[4];
  const __nv_bfloat16* w2 = (const __nv_bfloat16*)d_in[5];
  const __nv_bfloat16* b2 = (const __nv_bfloat16*)d_in[6];
  static cudaTextureObject_t texScr = 0, texG = 0;
  static CUtensorMap mapW, mapL, mapS, mapT, mapE, mapC;
  static const void *c_tab = nullptr, *c_w1 = nullptr;
  if (c_tab != table || c_w1 != w1) {
    c_tab = table; c_w1 = w1;
    char* scr = nullptr; cudaGetSymbolAddress((void**)&scr, g_scr);
    auto mk_tex = [](const void* p, size_t bytes, cudaChannelFormatDesc d) {
      cudaResourceDesc rd = {}; rd.resType = cudaResourceTypeLinear; rd.res.linear.devPtr = (void*)p; rd.res.linear.desc = d; rd.res.linear.sizeInBytes = bytes;
      cudaTextureDesc td = {}; td.readMode = cudaReadModeElementType;
      cudaTextureObject_t t = 0; cudaCreateTextureObject(&t, &rd, &td, nullptr); return t;
    };
    if (!texScr) {
      texScr = mk_tex(scr, (size_t)SCR_N * 16, cudaCreateChannelDesc<uint4>());
      texG = mk_tex(scr + (size_t)PX_OFF * 16, (size_t)(SCR_N - PX_OFF) * 16, cudaCreateChannelDesc<unsigned>());
    }
    typedef CUresult (*EncFn)(CUtensorMap*, CUtensorMapDataType, cuuint32_t, void*, const cuuint64_t*, const cuuint64_t*, const cuuint32_t*,
                              const cuuint32_t*, CUtensorMapInterleave, CUtensorMapSwizzle, CUtensorMapL2promotion, CUtensorMapFloatOOBfill);
    EncFn enc = nullptr; cudaDriverEntryPointQueryResult qr;
    cudaGetDriverEntryPoint("cuTensorMapEncodeTiled", (void**)&enc, cudaEnableDefault, &qr);
    const cuuint32_t ones[4] = {1, 1, 1, 1};
    auto mk = [&](CUtensorMap* m, CUtensorMapDataType dt, int rank, void* p, const cuuint64_t* dim, const cuuint64_t* str, const cuuint32_t* box, CUtensorMapSwizzle sw) {
      enc(m, dt, rank, p, dim, str, box, ones, CU_TENSOR_MAP_INTERLEAVE_NONE, sw, CU_TENSOR_MAP_L2_PROMOTION_NONE, CU_TENSOR_MAP_FLOAT_OOB_FILL_NONE);
    };
    { cuuint64_t dim[2] = {H_, F_ * D_}, str[1] = {H_ * 2}; cuuint32_t box[2] = {32, 256};
      mk(&mapW, CU_TENSOR_MAP_DATA_TYPE_BFLOAT16, 2, (void*)w1, dim, str, box, CU_TENSOR_MAP_SWIZZLE_64B); }
    { cuuint64_t dim[4] = {64, V_, NC, 64}, str[3] = {128, 128000, 128000 * NC}; cuuint32_t box[4] = {32, 64, 1, 4};
      mk(&mapL, CU_TENSOR_MAP_DATA_TYPE_BFLOAT16, 4, scr + (size_t)PL_OFF * 16, dim, str, box, CU_TENSOR_MAP_SWIZZLE_64B); }
    { cuuint64_t dim[4] = {64, V_ / 4, NC, 64}, str[3] = {128, 32000, 32000 * NC}; cuuint32_t box[4] = {64, 16, 1, 4};
      mk(&mapS, CU_TENSOR_MAP_DATA_TYPE_BFLOAT16, 4, scr + (size_t)PS_OFF * 16, dim, str, box, CU_TENSOR_MAP_SWIZZLE_128B); }
    { cuuint64_t dim[3] = {2048, 10, 64}, str[2] = {16384, 163840}; cuuint32_t box[3] = {128, 2, 4};
      mk(&mapT, CU_TENSOR_MAP_DATA_TYPE_UINT64, 3, scr + (size_t)PT_OFF * 16, dim, str, box, CU_TENSOR_MAP_SWIZZLE_NONE); }
    { cuuint64_t dim[2] = {D_, V_}, str[1] = {D_ * 2}; cuuint32_t box[2] = {64, 128};
      mk(&mapE, CU_TENSOR_MAP_DATA_TYPE_BFLOAT16, 2, (void*)table, dim, str, box, CU_TENSOR_MAP_SWIZZLE_128B);
      cuuint32_t box2[2] = {8, 256};
      mk(&mapC, CU_TENSOR_MAP_DATA_TYPE_BFLOAT16, 2, (void*)table, dim, str, box2, CU_TENSOR_MAP_SWIZZLE_NONE); }
    cudaFuncSetAttribute(k_deep, cudaFuncAttributeMaxDynamicSharedMemorySize, DEEP_SMEM);
    cudaFuncSetAttribute(k_tens, cudaFuncAttributeMaxDynamicSharedMemorySize, K1_SMEM);
  }
  k_tens<<<132, 512, K1_SMEM, cudaStreamPerThread>>>(mapW, mapL, mapS, mapT, mapE, mapC, texScr, texG, idx, table, wp, w1, b1, 0);
  cudaLaunchAttribute at[1];
  at[0].id = cudaLaunchAttributeProgrammaticStreamSerialization; at[0].val.programmaticStreamSerializationAllowed = 1;
  cudaLaunchConfig_t cfg = {};
  cfg.stream = cudaStreamPerThread; cfg.attrs = at;
  cfg.gridDim = 128; cfg.blockDim = TH + 128; cfg.dynamicSmemBytes = DEEP_SMEM; cfg.numAttrs = PDL & 1;
  cudaLaunchKernelEx(&cfg, k_deep, texScr, w2, b2, (__nv_bfloat16*)d_out, 0);

}
```

```cpp
#include <cuda_runtime.h>
#include <cuda_bf16.h>
#include <cuda_fp16.h>
#include <stdint.h>
#include <cuda.h>

namespace {

constexpr int B_ = 16384, F_ = 100, D_ = 128, V_ = 1000, H_ = 512;
constexpr int NC = 9;
constexpr int PT_OFF = 0;
constexpr int PL_OFF = 64 * 10 * 1024;
constexpr int PS_OFF = PL_OFF + 64 * NC * 8000;
constexpr int IXH = NC * 8192 + 2048;
constexpr int IX_OFF = PS_OFF + 64 * NC * 2000;
constexpr int I0_OFF = IX_OFF + 2 * IXH;
constexpr int PX_OFF = I0_OFF + 4096;
constexpr int SCR_N = PX_OFF + 64 * 16 * 136;
static_assert(PX_OFF % 32 == 0, "");

__device__ __align__(1024) uint4 g_scr[SCR_N];
__device__ float g_acc[B_];
__device__ unsigned long long g_slot;
__device__ unsigned g_done[64];
__device__ float g_partP[16 * B_];
__device__ unsigned g_flag[25 * 32];

#define TS(k, i)
#define TR(slot)
#define PT(slot)

constexpr uint64_t POL_EF = 0x12F0000000000000ull, POL_N = 0x1000000000000000ull;
__device__ __forceinline__ uint32_t addbf2(uint32_t a, uint32_t b) { uint32_t r; asm("add.rn.bf16x2 %0,%1,%2;" : "=r"(r) : "r"(a), "r"(b)); return r; }
__device__ __forceinline__ uint4 add4(const uint4& a, const uint4& b) { return make_uint4(addbf2(a.x, b.x), addbf2(a.y, b.y), addbf2(a.z, b.z), addbf2(a.w, b.w)); }
__device__ __forceinline__ void acc4(uint4& a, const uint4& b, int never) {
  asm("{.reg .pred p; setp.eq.s32 p,%8,0;\n"
      "@p add.rn.bf16x2 %0,%0,%4; @p add.rn.bf16x2 %1,%1,%5; @p add.rn.bf16x2 %2,%2,%6; @p add.rn.bf16x2 %3,%3,%7;}"
      : "+r"(a.x), "+r"(a.y), "+r"(a.z), "+r"(a.w) : "r"(b.x), "r"(b.y), "r"(b.z), "r"(b.w), "r"(never));
}
__device__ __forceinline__ uint4 ldtex(cudaTextureObject_t t, int i) {
  uint4 v; asm volatile("tex.1d.v4.u32.s32 {%0,%1,%2,%3},[%4,{%5}];" : "=r"(v.x), "=r"(v.y), "=r"(v.z), "=r"(v.w) : "l"(t), "r"(i)); return v;
}
__device__ __forceinline__ uint4 lds128(uint32_t a) {
  uint4 v; asm volatile("ld.volatile.shared.v4.u32 {%0,%1,%2,%3},[%4];" : "=r"(v.x), "=r"(v.y), "=r"(v.z), "=r"(v.w) : "r"(a)); return v;
}
__device__ __forceinline__ void sts128(uint32_t a, const uint4& v) {
  asm volatile("st.shared.v4.u32 [%0],{%1,%2,%3,%4};" :: "r"(a), "r"(v.x), "r"(v.y), "r"(v.z), "r"(v.w) : "memory");
}
__device__ __forceinline__ void mbar_init(uint32_t bar, int n) { asm volatile("mbarrier.init.shared::cta.b64 [%0],%1;" :: "r"(bar), "r"(n) : "memory"); }
__device__ __forceinline__ void mbar_wait(uint32_t bar, uint32_t parity) {
  uint32_t ok; int it = 0;
  do { asm volatile("{.reg .pred p; mbarrier.try_wait.parity.shared::cta.b64 p,[%1],%2; selp.u32 %0,1,0,p;}" : "=r"(ok) : "r"(bar), "r"(parity) : "memory"); } while (!ok && ++it < (1 << 19));
}
__device__ __forceinline__ void mbar_expect(uint32_t bar, uint32_t bytes) { asm volatile("mbarrier.arrive.expect_tx.shared::cta.b64 _,[%0],%1;" :: "r"(bar), "r"(bytes) : "memory"); }
__device__ __forceinline__ void bulk_g2s(uint32_t dst, const void* src, uint32_t bytes, uint32_t bar) {
  asm volatile("cp.async.bulk.shared::cluster.global.mbarrier::complete_tx::bytes [%0],[%1],%2,[%3];" :: "r"(dst), "l"(src), "r"(bytes), "r"(bar) : "memory");
}
__device__ __forceinline__ void bulk_pf(const void* src, uint32_t bytes) { asm volatile("cp.async.bulk.prefetch.L2.global [%0],%1;" :: "l"(src), "r"(bytes) : "memory"); }
#define NOMMA 0
#define NGRP 16
#define PDL 1
#define FIN_S 128
#define WRED 4
#define RSV 24
#define RSV_T 7200
#define RSV_L 550
#define TRIG 14
#define PREW 5
#define PXW 3
#define WQL 1
#define EARLY 1
#define CBAR 0
#define X_SAMEK 0
#define X_SAMEW 0
#define FM 0
#define SWP 1
#define HOLD 1
#define MCW 1
#define TW 1
#define PP0 10
#define PT0 10000
#define PDT 0
#define RPNN "160"
#define RAUX "32"
#define RPRO "160"
#define PARK 0
#define NLOOK 128
#define NEF 25
#define ORD 0
#define WFENCE 0
#define SPLIT 1
#define IORD 1
#define IPF 3
#define IPACE 4500
#define WPF 1
#define QV 3
#define QORD(n) ((n) < 23 ? (n) + 2 : (n) - 23)
#define DYD 4
#define DPF 4
#define DDEPTH 4
#define FENCE_N 4
#define INPL 0
#define STAG 1
#define PACE 800
#define PM4 "pmevent 1; pmevent 2; pmevent 3; pmevent 4;"
#define PMFILL "pmevent 1;"
#define SCHED_FENCE(never, k) asm volatile("{.reg .pred p; setp.ne.u32 p,%0,%1; @p bra.uni SKIP_%=;" PMFILL "SKIP_%=: }" :: "r"(never), "r"(0x7fff0000 + (k)) : "memory")

__global__ void k_prod_naive(const __nv_bfloat16* __restrict__ table, const __nv_bfloat16* __restrict__ w1) {
  __shared__ float t[8][D_];
  int f = blockIdx.y, v0 = blockIdx.x * 8, h = threadIdx.x;
  for (int i = h; i < 8 * D_; i += 512) t[i / D_][i % D_] = __bfloat162float(table[v0 * D_ + i]);
  __syncthreads();
  float s[8] = {0, 0, 0, 0, 0, 0, 0, 0};
  for (int d = 0; d < D_; d++) { float w = __bfloat162float(w1[(size_t)(f * D_ + d) * H_ + h]);
#pragma unroll
    for (int k = 0; k < 8; k++) s[k] += t[k][d] * w; }
  __nv_bfloat16* P = (__nv_bfloat16*)g_scr;
  int c = h >> 3;
  for (int k = 0; k < 8; k++) {
    size_t e = f < 72 ? (size_t)PL_OFF + ((size_t)(c * NC + (f >> 3)) * 1000 + v0 + k) * 8 + (f & 7)
             : f < 90 ? (size_t)PS_OFF + ((size_t)(c * NC + ((f - 72) >> 1)) * 1000 + v0 + k) * 2 + (f & 1)
                      : (size_t)PT_OFF + (size_t)(c * 10 + f - 90) * 1024 + v0 + k;
    P[e * 8 + (h & 7)] = __float2bfloat16(s[k]);
  }
}
__global__ void k_pnn_naive(const int* __restrict__ idx, const __nv_bfloat16* __restrict__ table, const __nv_bfloat16* __restrict__ wp) {
  __shared__ float e[F_][33];
  int b = blockIdx.x, d0 = blockIdx.y * 32, tid = threadIdx.x;
  for (int i = tid; i < F_ * 32; i += 128) e[i >> 5][i & 31] = __bfloat162float(table[idx[b * F_ + (i >> 5)] * D_ + d0 + (i & 31)]);
  __syncthreads();
  float s = 0; int d = tid & 31;
  for (int i = tid >> 5; i < F_; i += 4) { float u = 0; for (int j = 0; j < F_; j++) u += __bfloat162float(wp[i * F_ + j]) * e[j][d]; s += u * e[i][d]; }
  for (int o = 16; o; o >>= 1) s += __shfl_xor_sync(~0u, s, o);
  if (d == 0) g_partP[(blockIdx.y * 4 + (tid >> 5)) * B_ + b] = s;
}
__device__ __forceinline__ void mbar_wait_fast(uint32_t bar, uint32_t parity) {
  asm volatile("{.reg .pred p; .reg .u32 n;\n"
               "mbarrier.try_wait.parity.shared::cta.b64 p,[%0],%1;\n"
               "@p bra DONE_%=;\n"
               "mov.u32 n,0;\n"
               "LOOP_%=: mbarrier.try_wait.parity.shared::cta.b64 p,[%0],%1;\n"
               "add.u32 n,n,1; setp.gt.or.u32 p,n,400000,p;\n"
               "@!p bra LOOP_%=;\n"
               "DONE_%=: }" :: "r"(bar), "r"(parity) : "memory");
}
__device__ __forceinline__ void sleep_until(uint32_t t0, uint32_t dt) { while ((uint32_t)clock() - t0 < dt) __nanosleep(40); }
__device__ __forceinline__ uint32_t s_mask(uint32_t v, int q) { return (1u << ((v + 3 - q) & 3)) | (16u << ((v + 3 + q) & 3)); }
__device__ __forceinline__ uint32_t s_cell(uint32_t v, int q, uint32_t m) {
  const int t = __ffs(~m) - 1;
  const int cp = t == 8 ? q >> 1 : ((t & 4 ? t - q : t + q) - v) & 3;
  return cp * 1001 + v;
}
__device__ __forceinline__ uint32_t pk3(uint32_t a, uint32_t b, uint32_t c) {
  const uint32_t w = c + (a << 12) + (b << 22); return __funnelshift_l(w, w, 27);
}
constexpr int TH = 256, NS = 8192 / TH, YD = DYD;
__host__ __device__ constexpr int ye_of(int s) { return s == 3 ? 0 : s == 11 ? 1 : s == 19 ? 2 : s == 23 ? 3 : -1; }
template <int N> __device__ __forceinline__ void wgmma_h(uint32_t* d, const uint32_t* a, uint64_t desc, int acc);
template <> __device__ __forceinline__ void wgmma_h<64>(uint32_t* d, const uint32_t* a, uint64_t desc, int acc) {
  asm volatile("{.reg .pred p; setp.ne.s32 p,%21,0;\n"
    "wgmma.mma_async.sync.aligned.m64n64k16.f16.f16.f16 {%0,%1,%2,%3,%4,%5,%6,%7,%8,%9,%10,%11,%12,%13,%14,%15},{%16,%17,%18,%19},%20,p,1,1,0;}"
    : "+r"(d[0]),"+r"(d[1]),"+r"(d[2]),"+r"(d[3]),"+r"(d[4]),"+r"(d[5]),"+r"(d[6]),"+r"(d[7]),"+r"(d[8]),"+r"(d[9]),"+r"(d[10]),"+r"(d[11]),"+r"(d[12]),"+r"(d[13]),"+r"(d[14]),"+r"(d[15])
    : "r"(a[0]), "r"(a[1]), "r"(a[2]), "r"(a[3]), "l"(desc), "r"(acc));
}
template <> __device__ __forceinline__ void wgmma_h<56>(uint32_t* d, const uint32_t* a, uint64_t desc, int acc) {
  asm volatile("{.reg .pred p; setp.ne.s32 p,%19,0;\n"
    "wgmma.mma_async.sync.aligned.m64n56k16.f16.f16.f16 {%0,%1,%2,%3,%4,%5,%6,%7,%8,%9,%10,%11,%12,%13},{%14,%15,%16,%17},%18,p,1,1,0;}"
    : "+r"(d[0]),"+r"(d[1]),"+r"(d[2]),"+r"(d[3]),"+r"(d[4]),"+r"(d[5]),"+r"(d[6]),"+r"(d[7]),"+r"(d[8]),"+r"(d[9]),"+r"(d[10]),"+r"(d[11]),"+r"(d[12]),"+r"(d[13])
    : "r"(a[0]), "r"(a[1]), "r"(a[2]), "r"(a[3]), "l"(desc), "r"(acc));
}
template <> __device__ __forceinline__ void wgmma_h<48>(uint32_t* d, const uint32_t* a, uint64_t desc, int acc) {
  asm volatile("{.reg .pred p; setp.ne.s32 p,%17,0;\n"
    "wgmma.mma_async.sync.aligned.m64n48k16.f16.f16.f16 {%0,%1,%2,%3,%4,%5,%6,%7,%8,%9,%10,%11},{%12,%13,%14,%15},%16,p,1,1,0;}"
    : "+r"(d[0]),"+r"(d[1]),"+r"(d[2]),"+r"(d[3]),"+r"(d[4]),"+r"(d[5]),"+r"(d[6]),"+r"(d[7]),"+r"(d[8]),"+r"(d[9]),"+r"(d[10]),"+r"(d[11])
    : "r"(a[0]), "r"(a[1]), "r"(a[2]), "r"(a[3]), "l"(desc), "r"(acc));
}
template <> __device__ __forceinline__ void wgmma_h<40>(uint32_t* d, const uint32_t* a, uint64_t desc, int acc) {
  asm volatile("{.reg .pred p; setp.ne.s32 p,%15,0;\n"
    "wgmma.mma_async.sync.aligned.m64n40k16.f16.f16.f16 {%0,%1,%2,%3,%4,%5,%6,%7,%8,%9},{%10,%11,%12,%13},%14,p,1,1,0;}"
    : "+r"(d[0]),"+r"(d[1]),"+r"(d[2]),"+r"(d[3]),"+r"(d[4]),"+r"(d[5]),"+r"(d[6]),"+r"(d[7]),"+r"(d[8]),"+r"(d[9])
    : "r"(a[0]), "r"(a[1]), "r"(a[2]), "r"(a[3]), "l"(desc), "r"(acc));
}
template <> __device__ __forceinline__ void wgmma_h<32>(uint32_t* d, const uint32_t* a, uint64_t desc, int acc) {
  asm volatile("{.reg .pred p; setp.ne.s32 p,%13,0;\n"
    "wgmma.mma_async.sync.aligned.m64n32k16.f16.f16.f16 {%0,%1,%2,%3,%4,%5,%6,%7},{%8,%9,%10,%11},%12,p,1,1,0;}"
    : "+r"(d[0]),"+r"(d[1]),"+r"(d[2]),"+r"(d[3]),"+r"(d[4]),"+r"(d[5]),"+r"(d[6]),"+r"(d[7])
    : "r"(a[0]), "r"(a[1]), "r"(a[2]), "r"(a[3]), "l"(desc), "r"(acc));
}
__device__ __forceinline__ void wgmma_p(float* d, const uint32_t* a, uint64_t desc, int acc) {
  asm volatile("{.reg .pred p; setp.ne.s32 p,%69,0;\n"
    "wgmma.mma_async.sync.aligned.m64n128k16.f32.bf16.bf16 {%0,%1,%2,%3,%4,%5,%6,%7,%8,%9,%10,%11,%12,%13,%14,%15,%16,%17,%18,%19,%20,%21,%22,%23,%24,%25,%26,%27,%28,%29,%30,%31,%32,%33,%34,%35,%36,%37,%38,%39,%40,%41,%42,%43,%44,%45,%46,%47,%48,%49,%50,%51,%52,%53,%54,%55,%56,%57,%58,%59,%60,%61,%62,%63},{%64,%65,%66,%67},%68,p,1,1,1;}"
    : "+f"(d[0]),"+f"(d[1]),"+f"(d[2]),"+f"(d[3]),"+f"(d[4]),"+f"(d[5]),"+f"(d[6]),"+f"(d[7]),"+f"(d[8]),"+f"(d[9]),"+f"(d[10]),"+f"(d[11]),"+f"(d[12]),"+f"(d[13]),"+f"(d[14]),"+f"(d[15]),"+f"(d[16]),"+f"(d[17]),"+f"(d[18]),"+f"(d[19]),"+f"(d[20]),"+f"(d[21]),"+f"(d[22]),"+f"(d[23]),"+f"(d[24]),"+f"(d[25]),"+f"(d[26]),"+f"(d[27]),"+f"(d[28]),"+f"(d[29]),"+f"(d[30]),"+f"(d[31]),"+f"(d[32]),"+f"(d[33]),"+f"(d[34]),"+f"(d[35]),"+f"(d[36]),"+f"(d[37]),"+f"(d[38]),"+f"(d[39]),"+f"(d[40]),"+f"(d[41]),"+f"(d[42]),"+f"(d[43]),"+f"(d[44]),"+f"(d[45]),"+f"(d[46]),"+f"(d[47]),"+f"(d[48]),"+f"(d[49]),"+f"(d[50]),"+f"(d[51]),"+f"(d[52]),"+f"(d[53]),"+f"(d[54]),"+f"(d[55]),"+f"(d[56]),"+f"(d[57]),"+f"(d[58]),"+f"(d[59]),"+f"(d[60]),"+f"(d[61]),"+f"(d[62]),"+f"(d[63])
    : "r"(a[0]), "r"(a[1]), "r"(a[2]), "r"(a[3]), "l"(desc), "r"(acc));
}

__device__ __forceinline__ void mma16816h(uint32_t* c, const uint32_t* a, uint32_t b0, uint32_t b1) {
  asm("mma.sync.aligned.m16n8k16.row.col.f16.f16.f16.f16 {%0,%1},{%2,%3,%4,%5},{%6,%7},{%0,%1};"
      : "+r"(c[0]), "+r"(c[1]) : "r"(a[0]), "r"(a[1]), "r"(a[2]), "r"(a[3]), "r"(b0), "r"(b1));
}
__device__ __forceinline__ void mma1688h(uint32_t* c, uint32_t a0, uint32_t a1, uint32_t b) {
  asm("mma.sync.aligned.m16n8k8.row.col.f16.f16.f16.f16 {%0,%1},{%2,%3},{%4},{%0,%1};" : "+r"(c[0]), "+r"(c[1]) : "r"(a0), "r"(a1), "r"(b));
}
__device__ __forceinline__ void mma1688f(float* c, uint32_t a0, uint32_t a1, uint32_t b) {
  asm("mma.sync.aligned.m16n8k8.row.col.f32.f16.f16.f32 {%0,%1,%2,%3},{%4,%5},{%6},{%0,%1,%2,%3};"
      : "+f"(c[0]), "+f"(c[1]), "+f"(c[2]), "+f"(c[3]) : "r"(a0), "r"(a1), "r"(b));
}
__device__ __forceinline__ uint32_t hadd2(uint32_t a, uint32_t b) { uint32_t r; asm("add.rn.f16x2 %0,%1,%2;" : "=r"(r) : "r"(a), "r"(b)); return r; }
__device__ __forceinline__ uint32_t hfma2(uint32_t a, uint32_t b, uint32_t c) { uint32_t r; asm("fma.rn.f16x2 %0,%1,%2,%3;" : "=r"(r) : "r"(a), "r"(b), "r"(c)); return r; }
__device__ __forceinline__ uint32_t pack_bf2(float lo, float hi) { uint32_t r; asm("cvt.rn.bf16x2.f32 %0,%1,%2;" : "=r"(r) : "f"(hi), "f"(lo)); return r; }
__device__ __forceinline__ uint32_t pack_h2(float lo, float hi) { uint32_t r; asm("cvt.rn.f16x2.f32 %0,%1,%2;" : "=r"(r) : "f"(hi), "f"(lo)); return r; }
__device__ __forceinline__ float bf_lo(uint32_t w) { return __uint_as_float(w << 16); }
__device__ __forceinline__ float bf_hi(uint32_t w) { return __uint_as_float(w & 0xffff0000u); }
__device__ __forceinline__ uint32_t absmax4(const uint4& v, uint32_t m) {
  return __vmaxu2(__vmaxu2(__vmaxu2(v.x & 0x7fff7fffu, v.y & 0x7fff7fffu), __vmaxu2(v.z & 0x7fff7fffu, v.w & 0x7fff7fffu)), m);
}
__device__ __forceinline__ float pow2_scale(uint32_t mbits, int p) { return __uint_as_float((uint32_t)min(max(253 + p - (int)(mbits >> 7), 2), 252) << 23); }

#define PV 4
constexpr int G_O0 = 8, G_O1 = 4, G_O2 = 0, G_N0 = 5, G_N1 = 4, G_N2 = 4, G_K0 = 5, G_K1 = 3, G_K2 = 1;
__host__ __device__ constexpr bool unit_wg(int kb, int on) {
  return (on >= G_O0 && on < G_O0 + G_N0 && kb < G_K0) || (on >= G_O1 && on < G_O1 + G_N1 && kb < G_K1) || (on >= G_O2 && on < G_O2 + G_N2 && kb < G_K2);
}
__host__ __device__ constexpr bool oct_wg(int on) { return unit_wg(0, on); }
constexpr int G_U1 = G_N0 * G_K0, G_U2 = G_U1 + G_N1 * G_K1, G_U = G_U2 + G_N2 * G_K2;
constexpr int K1_B = 130048, K1_STG = K1_B + 2 * 32768, K1_W = K1_STG + 16384, K1_BAR = K1_W + 48 * 256, K1_SMEM = K1_BAR + 256 + 6400;
__host__ __device__ constexpr int frag_index(int ok, int on) {
  int n = 0;
  for (int k = 0; k < 13; k++) for (int o = k; o < 13; o++) { if (k == ok && o == on) return n; if (!unit_wg(k >> 1, o)) n++; }
  return n;
}
constexpr int HU_N = 2 * G_U + frag_index(99, 99);
static_assert(HU_N <= 96, "");
struct FragIdx { int v[13][13]; };
__host__ __device__ constexpr FragIdx make_fi() { FragIdx f = {}; for (int k = 0; k < 13; k++) for (int o = 0; o < 13; o++) f.v[k][o] = frag_index(k, o); return f; }
__host__ __device__ constexpr uint64_t frag_tab(int first) {
  uint64_t t = 0;
  for (int k = 0; k < 13; k++) for (int o = k; o < 13; o++)
    if (!unit_wg(k >> 1, o)) { const int n = frag_index(k, o) - first; if (n >= 0 && n < 8) t |= (uint64_t)(k << 4 | o) << (8 * n); }
  return t;
}
__device__ __forceinline__ int hu_code(int hu) {
  constexpr uint64_t T0 = frag_tab(0), T1 = frag_tab(8), T2 = frag_tab(16), T3 = frag_tab(24);
  const int u = hu >> 1, f = hu - 2 * G_U;
  if (f >= 0) return (int)((f < 8 ? T0 : f < 16 ? T1 : f < 24 ? T2 : T3) >> (8 * (f & 7))) & 255;
  const int u0 = u < G_U1 ? u : u < G_U2 ? u - G_U1 : u - G_U2;
  const int kb = u < G_U1 ? u0 / G_N0 : u < G_U2 ? u0 / G_N1 : u0 / 4, on = u < G_U1 ? G_O0 + u0 % G_N0 : u < G_U2 ? G_O1 + u0 % G_N1 : G_O2 + u0 % 4;
  return (2 * kb + (hu & 1)) << 4 | on;
}

__device__ __forceinline__ void flag_arrive(unsigned* f, int lane) {
  __threadfence(); __syncwarp();
  if (lane == 0) asm volatile("red.release.gpu.global.add.u32 [%0],1;" :: "l"(f) : "memory");
}
__device__ __forceinline__ void flag_wait(const unsigned* f, unsigned n) {
  unsigned v; int it = 0;
  asm volatile("ld.acquire.gpu.global.u32 %0,[%1];" : "=r"(v) : "l"(f) : "memory");
  if (v < n) {
    do { __nanosleep(300); asm volatile("ld.relaxed.gpu.global.u32 %0,[%1];" : "=r"(v) : "l"(f) : "memory"); } while (v < n && ++it < (1 << 20));
    asm volatile("ld.acquire.gpu.global.u32 %0,[%1];" : "=r"(v) : "l"(f) : "memory");
  }
}
__device__ __forceinline__ void mbar_arrive(uint32_t bar) { asm volatile("mbarrier.arrive.shared::cta.b64 _,[%0];" :: "r"(bar) : "memory"); }
__device__ __forceinline__ void mbar_arrive_lane0(uint32_t bar) {
  asm volatile("{.reg .pred p; elect.sync _|p,0xffffffff; @p mbarrier.arrive.shared::cta.b64 _,[%0];}" :: "r"(bar) : "memory");
}

__device__ __forceinline__ void arrive_both(uint32_t bar, int lane) {
  asm volatile("{.reg .pred p; .reg .u32 a; setp.lt.u32 p,%1,2; mapa.shared::cluster.u32 a,%0,%1;\n"
               "@p mbarrier.arrive.shared::cluster.b64 _,[a];}" :: "r"(bar), "r"(lane) : "memory");
}
__device__ __forceinline__ void pack_role(const int* __restrict__ idx, uint32_t sbase, int pc) {
  constexpr int CH = 3200 + 32, BUF = 32 * 3328;
  const int tid = threadIdx.x, lane = tid & 31, warp = tid >> 5;
  const uint32_t full = sbase + 2 * BUF, empty = full + 16;
  if (tid == 0) { mbar_init(full, 1); mbar_init(full + 8, 1); mbar_init(empty, 18); mbar_init(empty + 8, 18); asm volatile("fence.proxy.async.shared::cta;" ::: "memory"); }
  __syncthreads();
  auto chunk = [&](int s) { return s * 3200 + (s >> 2) * 288; };
  auto load = [&](int n) {
    const int blk = pc * 16 + n;
    if (lane == 0) mbar_expect(full + (n & 1) * 8, 32 * 3200);
    __syncwarp();
    bulk_g2s(sbase + (n & 1) * BUF + chunk(lane), idx + ((blk >> 5) * 8192 + lane * TH + (blk & 31) * 8) * F_, 3200, full + (n & 1) * 8);
  };
  if (warp == 0) { load(0); load(1); }
  const int l = lane & 7;
  uint32_t rot[8], inc[3];
#pragma unroll
  for (int jj = 0; jj < 8; jj++) rot[jj] = ((l + jj) & 7) * 4;
#pragma unroll
  for (int q = 0; q < 3; q++) inc[q] = (l + 3 * q < 8) << 12 | (l + 3 * q + 1 < 8) << 22 | (q < 2 && l + 3 * q + 2 < 8);
  int loaded = 2;
#pragma unroll 1
  for (int task = warp; task < 288; task += 16) {
    const int n = task / 18, q = (task % 18) * 4 + (lane >> 3), sq = q / 9, k = q % 9;
    if (warp == 0 && n + 1 == loaded && loaded < 16) { mbar_wait(empty + (loaded & 1) * 8, ((loaded >> 1) - 1) & 1); load(loaded); loaded++; }
    mbar_wait(full + (n & 1) * 8, (n >> 1) & 1);
    const uint32_t buf = sbase + (n & 1) * BUF + l * 400, row = buf + chunk(sq * 4);
    auto ld = [&](uint32_t ad) { uint32_t v; asm volatile("ld.shared.u32 %0,[%1];" : "=r"(v) : "r"(ad)); return v; };
    const int blk = pc * 16 + n, half = blk >> 5, col = (blk & 31) * 8 + l;
    const int ks = k == NC - 1 ? 0 : k + 1;
    uint32_t cw[4], sv[8], m[2] = {0, 0};
    { const uint32_t a0 = row + (72 + 2 * ks + (l >> 2)) * 4;
#pragma unroll
      for (int u = 0; u < 8; u++) { sv[u] = ld((a0 ^ ((u >> 2) * 4)) + (u & 3) * 3200); m[u >> 2] |= s_mask(sv[u], l & 3) << (8 * (u & 3)); } }
#pragma unroll
    for (int h = 0; h < 2; h++) { m[h] |= __shfl_xor_sync(0xffffffffu, m[h], 1); m[h] |= __shfl_xor_sync(0xffffffffu, m[h], 2); }
#pragma unroll
    for (int u = 0; u < 4; u++) cw[u] = s_cell(sv[u], l & 3, (m[0] >> (8 * u)) & 255) | s_cell(sv[4 + u], l & 3, (m[1] >> (8 * u)) & 255) << 12;
    if (k == NC - 1) {
      g_scr[I0_OFF + (half * 8 + sq) * TH + col] = make_uint4(cw[0], cw[1], cw[2], cw[3]);
      g_scr[IX_OFF + half * IXH + NC * 8192 + sq * TH + col] = make_uint4(ld(row + 396), ld(row + 3596), ld(row + 6796), ld(row + 9996));
      cw[0] = cw[1] = cw[2] = cw[3] = 0;
    }
    const uint32_t ax = buf + chunk(min(sq + 1, 7) * 4) + (90 + k) * 4;
    const uint32_t yev = ld(buf + ((0x3210 >> (sq * 2 + (sq == 5) * 2)) & 3) * 3200 + (90 + k) * 4);
    uint4* dst = g_scr + IX_OFF + half * IXH + (k * NS + sq * 4) * TH + col;
#pragma unroll
    for (int u = 0; u < 4; u++) {
      uint32_t e[8];
#pragma unroll
      for (int jj = 0; jj < 8; jj++) e[jj] = ld(row + k * 32 + rot[jj] + u * 3200);
      dst[u * TH] = make_uint4(pk3(e[0], e[1], e[2] + inc[0]), pk3(e[3], e[4], e[5] + inc[1]), pk3(e[6], e[7], ld(ax + u * 3200) + inc[2]),
                               u < 3 ? __byte_perm(cw[u], cw[3], 0x4210 + (u << 12)) : yev);
    }
    mbar_arrive_lane0(empty + (n & 1) * 8);
  }
  (void)CH;
}

__global__ void __cluster_dims__(2, 1, 1) __launch_bounds__(512, 1)
k_tens(const __grid_constant__ CUtensorMap mapW, const __grid_constant__ CUtensorMap mapL, const __grid_constant__ CUtensorMap mapS,
       const __grid_constant__ CUtensorMap mapT, const __grid_constant__ CUtensorMap mapE, const __grid_constant__ CUtensorMap mapC, cudaTextureObject_t tex, cudaTextureObject_t texX,
       const int* __restrict__ idx, const __nv_bfloat16* __restrict__ table, const __nv_bfloat16* __restrict__ wp, const __nv_bfloat16* __restrict__ w1,
       const __nv_bfloat16* __restrict__ b1, int never) {
  extern __shared__ __align__(1024) uint4 sm[];
  const int tid = threadIdx.x, lane = tid & 31, cta = blockIdx.x;
  const uint32_t sbase = (uint32_t)__cvta_generic_to_shared(sm);
  const int g = lane >> 2, r = lane & 3;
  TS(0, 0);
  if (cta >= 128) {
    pack_role(idx, sbase, cta - 128);
    __syncthreads();
    if (tid < 32) flag_arrive(&g_flag[24 * 32], lane);
    TS(2, 1);
    asm volatile("barrier.cluster.arrive.relaxed.aligned; barrier.cluster.wait.aligned;" ::: "memory");
    return;
  }
  const uint32_t fullB = sbase + K1_BAR, emptyB = fullB + 24, fullE = fullB + 48, fullC = fullB + 56, fullI = fullB + 64, pxRdy = fullB + 72, fullS = fullB + 96, emptyS = fullB + 104, pkDone = fullB + 112, pkFull = fullB + 136;
  const int rb = cta & 7, hc = cta >> 3;
  if (MCW && (tid >> 5) != 12) asm volatile("barrier.cluster.arrive.relaxed.aligned;" ::: "memory");
  if (tid >= 384) {
    asm volatile("setmaxnreg.dec.sync.aligned.u32 " RAUX ";");
    if (tid < 416) {
      if (tid == 384) {
        for (int q = 0; q < 2; q++) { mbar_init(fullB + q * 8, 1); mbar_init(emptyB + q * 8, 8); }
        mbar_init(fullS, 4); mbar_init(emptyS, 1);
        mbar_init(fullE, 1); mbar_init(fullC, 1); mbar_init(fullI, 1); for (int q = 0; q < 3; q++) { mbar_init(pxRdy + q * 8, 1); mbar_init(pkDone + q * 8, 2); mbar_init(pkFull + q * 8, 1); }
        asm volatile("fence.proxy.async.shared::cta;" ::: "memory");
        mbar_expect(fullC, 16384);
        for (int q = 0; q < 4; q++)
          asm volatile("cp.async.bulk.tensor.2d.shared::cluster.global.mbarrier::complete_tx::bytes [%0],[%1,{%2,%3}],[%4];"
                       :: "r"(sbase + 32768 + q * 4096), "l"(&mapC), "r"((cta & 15) * 8), "r"(q * 256), "r"(fullC) : "memory");
        mbar_expect(fullE, 32768);
        for (int q = 0; q < 2; q++)
          asm volatile("cp.async.bulk.tensor.2d.shared::cluster.global.mbarrier::complete_tx::bytes [%0],[%1,{%2,%3}],[%4];"
                       :: "r"(sbase + K1_B + 32768 + q * 16384), "l"(&mapE), "r"(q * 64), "r"(rb * 128), "r"(fullE) : "memory");
      }
      __syncwarp();
      asm volatile("bar.arrive 2,512;" ::: "memory");
      if (MCW) asm volatile("fence.mbarrier_init.release.cluster; barrier.cluster.arrive.relaxed.aligned; barrier.cluster.wait.aligned;" ::: "memory");
      if (tid == 384) {
#pragma unroll 1
        for (int n = 0; n < 25; n++) {
          const int st = n & 1, q = QORD(n);
          if (n == IORD) {
            mbar_expect(fullI, 51200);
#pragma unroll 1
            for (int u = 0; u < 8; u++) bulk_g2s(sbase + 76800 + u * 6400, idx + ((cta >> 4) * 8 + u) * 256 * F_, 6400, fullI);
          }
          mbar_wait(emptyB + st * 8, (((n + 1) >> 1) & 1) ^ 1);
          mbar_expect(fullB + st * 8, 32768);
          asm volatile("cp.async.bulk.tensor.2d.shared::cluster.global.mbarrier::complete_tx::bytes.multicast::cluster [%0],[%1,{%2,%3}],[%4],%5;"
                       :: "r"(sbase + K1_B + st * 32768 + (cta & 1) * 16384), "l"(&mapW), "r"(hc * 32), "r"(q * 512 + (cta & 1) * 256),
                          "r"(fullB + st * 8), "h"((unsigned short)3) : "memory");
          if (n == 0) for (int u = 1; u < WPF; u++) bulk_pf(w1 + QORD(u) * 262144 + cta * 2048, 4096);
          if (WPF && n + WPF < 25) bulk_pf(w1 + QORD(n + WPF) * 262144 + cta * 2048, 4096);
        }
      }
    } else if (tid < 448) {
      ((float4*)g_acc)[cta * 32 + lane] = make_float4(0.f, 0.f, 0.f, 0.f);
      asm volatile("bar.sync 2,512;" ::: "memory");
      __syncwarp();
      if (tid == 416) {
        int pub = 0;
#pragma unroll 1
        for (int n = 0; n < 50; n++) {
          const int quad = QORD(n >> 1), mt = n & 1, v0 = rb * 128 + mt * 64;
          const uint32_t stg = sbase + K1_STG;
          const uint64_t pol = n < 2 * NEF ? POL_EF : POL_N;
          if (pub < 3) {
            uint32_t ok = 1;
            if (pub == 0 || n == 49) mbar_wait(pkDone + pub * 8, 0);
            else asm volatile("{.reg .pred p; mbarrier.test_wait.parity.shared::cta.b64 p,[%1],0; selp.u32 %0,1,0,p;}" : "=r"(ok) : "r"(pkDone + pub * 8) : "memory");
            if (ok) {
              asm volatile("cp.async.bulk.wait_group 0;" ::: "memory");
              asm volatile("red.release.gpu.global.add.u32 [%0],1;" :: "l"(&g_flag[((cta >> 4) * 3 + pub) * 32]) : "memory");
              pub++;
              if (n == 49) { n--; continue; }
            }
          }
          mbar_wait(fullS, n & 1);
          asm volatile("fence.proxy.async.shared::cta;" ::: "memory");
          if (quad < 18) {
            asm volatile("cp.async.bulk.tensor.4d.global.shared::cta.bulk_group.L2::cache_hint [%0,{%1,%2,%3,%4}],[%5],%6;"
                         :: "l"(&mapL), "r"((quad & 1) * 32), "r"(v0), "r"(quad >> 1), "r"(hc * 4), "r"(stg), "l"(pol) : "memory");
          } else {
#pragma unroll 1
            for (int hh = 0; hh < 2; hh++) {
              const int pq = quad * 2 + hh;
              if (pq < 45) asm volatile("cp.async.bulk.tensor.4d.global.shared::cta.bulk_group.L2::cache_hint [%0,{%1,%2,%3,%4}],[%5],%6;"
                         :: "l"(&mapS), "r"(0), "r"(v0 >> 2), "r"(pq - 36), "r"(hc * 4), "r"(stg + hh * 8192), "l"(pol) : "memory");
              else asm volatile("cp.async.bulk.tensor.3d.global.shared::cta.bulk_group.L2::cache_hint [%0,{%1,%2,%3}],[%4],%5;"
                         :: "l"(&mapT), "r"(v0 * 2), "r"((pq - 45) * 2), "r"(hc * 4), "r"(stg + hh * 8192), "l"(pol) : "memory");
            }
          }
          asm volatile("cp.async.bulk.commit_group;" ::: "memory");
          asm volatile("cp.async.bulk.wait_group.read 0;" ::: "memory");
          mbar_arrive(emptyS);
        }
        asm volatile("cp.async.bulk.wait_group 0;" ::: "memory");
        asm volatile("fence.proxy.async.global;" ::: "memory");
        asm volatile("red.release.gpu.global.add.u32 [%0],1;" :: "l"(&g_flag[24 * 32]) : "memory");
        flag_wait(&g_flag[24 * 32], 132);
        asm volatile("fence.proxy.async.global;" ::: "memory");
        const char* base = (const char*)g_scr;
        const int c = cta >> 1, half = cta & 1, ch = (c + (c >> 4) * 5) & 15;
        bulk_pf(base + (PS_OFF + c * NC * 2000) * 16u + half * 16000, 16000);
        if (PREW & 2) bulk_pf(base + (PL_OFF + c * NC * 8000) * 16u + half * 64000, 64000);
        bulk_pf(base + (PT_OFF + c * 10 * 1024) * 16u + half * 8192, 8192);
        mbar_expect(fullE, 18432);
        bulk_g2s(sbase + K1_B, base + (I0_OFF + half * 2048 + ch * 128) * 16u, 2048, fullE);
        bulk_g2s(sbase + K1_B + 2048, base + (IX_OFF + half * IXH + ch * 512) * 16u, 8192, fullE);
        bulk_g2s(sbase + K1_B + 10240, base + (IX_OFF + half * IXH + 8192 + ch * 512) * 16u, 8192, fullE);
        mbar_wait(fullE, 1);
      }
    } else {
      const int pw = (tid >> 5) & 1, rg = (cta >> 4) * 8 + ((cta & 15) >> 1), hf = cta & 1;
      const int* ip = idx + (rg * 256 + hf * 8) * F_;
      asm volatile("bar.sync 2,512;" ::: "memory");
      const uint32_t buf = sbase + K1_BAR + 256 + pw * 3200, bar = pkFull + pw * 8;
      const unsigned* fl = &g_flag[(cta >> 4) * 96];
      int batch = 0, rel = pw ? 3 : 0;
#pragma unroll 1
      for (int n = 1 + pw; n < 16; n += 2) {
        if (lane == 0) { mbar_expect(bar, 3200); bulk_g2s(buf, ip + n * 16 * F_, 3200, bar); if (n + 2 < 16) bulk_pf(ip + (n + 2) * 16 * F_, 3200); }
        uint32_t ok; int it = 0;
        do {
          if (rel < batch) {
            unsigned v; asm volatile("ld.relaxed.gpu.global.u32 %0,[%1];" : "=r"(v) : "l"(fl + rel * 32) : "memory");
            if (__all_sync(0xffffffffu, v >= 16)) { flag_wait(fl + rel * 32, 16); __syncwarp(); mbar_arrive_lane0(pxRdy + rel * 8); rel++; }
          }
          asm volatile("{.reg .pred p; mbarrier.test_wait.parity.shared::cta.b64 p,[%1],%2; selp.u32 %0,1,0,p;}" : "=r"(ok) : "r"(bar), "r"(((n - 1) >> 1) & 1) : "memory");
          ok = __all_sync(0xffffffffu, ok);
          if (!ok) __nanosleep(100);
        } while (!ok && ++it < (1 << 20));
        auto ld = [&](uint32_t ad) { uint32_t v; asm volatile("ld.shared.u32 %0,[%1];" : "=r"(v) : "r"(ad)); return v; };
        const uint32_t p0 = buf + ((lane >> 3) & 1) * 400 + ((lane >> 4) * 8 + (lane & 7)) * 4;
        auto wd = [&](int t, int h) { return pk3(ld(p0 + t * 800 + h * 192), ld(p0 + t * 800 + h * 192 + 64), ld(p0 + t * 800 + h * 192 + 128)); };
        uint4* dst = g_scr + PX_OFF + (rg * 16 + n) * 136;
        ((unsigned short*)(dst + 128))[lane * 2 + hf] = ld(buf + g * 400 + 384 + r * 4);
#pragma unroll
        for (int q = 0; q < 2; q++) dst[(hf * 2 + q) * 32 + lane] = make_uint4(wd(2 * q, 0), wd(2 * q, 1), wd(2 * q + 1, 0), wd(2 * q + 1, 1));
        __syncwarp();
        if (n <= 2 || n == 5 || n == 6 || n >= 14) { mbar_arrive_lane0(pkDone + batch * 8); batch++; }
      }
      for (; rel < 3; rel++) { flag_wait(fl + rel * 32, 16); __syncwarp(); mbar_arrive_lane0(pxRdy + rel * 8); }
    }
    return;
  }
  if (tid >= 256) {
    asm volatile("setmaxnreg.inc.sync.aligned.u32 " RPRO ";");
    const int w = (tid >> 5) & 3;
    const int srow = w * 16 + (lane & 7) + ((lane >> 3) & 1) * 8, sc = lane >> 4;
    uint32_t a[2][8][4];
    asm volatile("bar.sync 2,512;" ::: "memory");
    mbar_wait_fast(fullE, 0);
#pragma unroll
    for (int mt = 0; mt < 2; mt++)
#pragma unroll
      for (int ks = 0; ks < 8; ks++)
        asm volatile("ldmatrix.sync.aligned.m8n8.x4.shared.b16 {%0,%1,%2,%3},[%4];"
                     : "=r"(a[mt][ks][0]), "=r"(a[mt][ks][1]), "=r"(a[mt][ks][2]), "=r"(a[mt][ks][3])
                     : "r"(sbase + K1_B + 32768 + (ks >> 2) * 16384 + (mt * 64 + srow) * 128 + ((((ks & 3) * 2 + sc) ^ (lane & 7)) * 16)) : "memory");
    asm volatile("barrier.cluster.wait.aligned;" ::: "memory");
    arrive_both(emptyB + 8, lane);
    const uint32_t baseL = sc * 4096 + srow * 64 + ((srow >> 1) & 3) * 16, baseS = sc * 2048 + ((srow * 32) ^ (((srow >> 2) & 7) * 16)), baseT = sc * 2048 + srow * 16;
    const uint64_t desc0 = (uint64_t)(((sbase + K1_B) & 0x3FFFF) >> 4) | ((uint64_t)(8192 >> 4) << 16) | ((uint64_t)(512 >> 4) << 32) | (2ull << 62);
#pragma unroll 1
    for (int qn = 0; qn < 25; qn++) {
      const int quad = QORD(qn), st = qn & 1;
      const bool isL = quad < 18;
      PT(qn * 16);
      mbar_wait_fast(fullB + st * 8, (qn >> 1) & 1);
#pragma unroll
      for (int mt = 0; mt < 2; mt++) {
        float d[64];
        PT(qn * 16 + mt * 4 + 1);
        asm volatile("wgmma.fence.sync.aligned;" ::: "memory");
#pragma unroll
        for (int ks = 0; ks < 8; ks++) wgmma_p(d, a[mt][ks], desc0 + st * 2048 + ks * 64, ks);
        asm volatile("wgmma.commit_group.sync.aligned;" ::: "memory");
        mbar_wait_fast(emptyS, mt ^ 1);
        PT(qn * 16 + mt * 4 + 2);
        asm volatile("wgmma.wait_group.sync.aligned 0;" ::: "memory");
#pragma unroll
        for (int q = 0; q < 16; q++) asm volatile("" : "+f"(d[q * 4]), "+f"(d[q * 4 + 1]), "+f"(d[q * 4 + 2]), "+f"(d[q * 4 + 3]) :: "memory");
        PT(qn * 16 + mt * 4 + 3);
        if (mt) arrive_both(emptyB + st * 8, qn < 23 ? lane : 9);
        if (quad == 24) {
#pragma unroll
          for (int cq = 0; cq < 4; cq++) {
            const uint32_t bw = __ldg((const uint32_t*)(b1 + hc * 32 + cq * 8) + r);
#pragma unroll
            for (int e = 0; e < 4; e++) d[48 + cq * 4 + e] += (e & 1) ? bf_hi(bw) : bf_lo(bw);
          }
        }
#pragma unroll
        for (int h = 0; h < 2; h++) {
          const bool isS = quad * 2 + h < 45;
          const uint32_t base = (isL ? baseL ^ (h * 32) : (isS ? baseS : baseT) ^ (h * 8192)), xj = isS ? 16 : 1024, xc = isL ? 8192 : 4096;
#pragma unroll
          for (int e4 = 0; e4 < 4; e4++) {
            const float* e = d + h * 32 + e4 * 8;
            asm volatile("stmatrix.sync.aligned.m8n8.x4.shared.b16 [%0],{%1,%2,%3,%4};"
                         :: "r"(sbase + K1_STG + (base ^ ((e4 >> 1) * xj) ^ ((e4 & 1) * xc))),
                            "r"(pack_bf2(e[0], e[1])), "r"(pack_bf2(e[2], e[3])), "r"(pack_bf2(e[4], e[5])), "r"(pack_bf2(e[6], e[7])) : "memory");
          }
        }
        __syncwarp();
        mbar_arrive_lane0(fullS);
        if (!mt) PT(qn * 16 + 4);
      }
      PT(qn * 16 + 8);
    }
    return;
  }
  asm volatile("setmaxnreg.inc.sync.aligned.u32 " RPNN ";");
  const int slice = cta & 15;
  const int range = (cta >> 4) * 8 + __shfl_sync(0xffffffffu, tid >> 5, 0);
  uint4 iv[4], trow[4]; uint32_t ix;
  uint2 wrow[10];
#pragma unroll
  for (int q = 0; q < 10; q++) asm volatile("ld.global.nc.v2.u32 {%0,%1},[%2];" : "=r"(wrow[q].x), "=r"(wrow[q].y) : "l"((const uint2*)wp + min(tid + q * 256, 2499)));
  asm volatile("bar.sync 2,512;" ::: "memory");
  uint32_t me = 0, mw = 0;
#pragma unroll
  for (int q = 0; q < 10; q++) {
    mw = __vmaxu2(__vmaxu2(wrow[q].x & 0x7fff7fffu, wrow[q].y & 0x7fff7fffu), mw);
    const int e = min(tid + q * 256, 2499), row = e / 25;
    asm volatile("st.shared.v2.u32 [%0],{%1,%2};" :: "r"(sbase + (e + row) * 8), "r"(wrow[q].x), "r"(wrow[q].y) : "memory");
    if (e - row * 25 == 24) asm volatile("st.shared.v2.u32 [%0],{%1,%2};" :: "r"(sbase + (e + row) * 8 + 8), "r"(wrow[q].x), "r"(wrow[q].y) : "memory");
  }
  mbar_wait_fast(fullC, 0);
#pragma unroll
  for (int q = 0; q < 4; q++) { trow[q] = lds128(sbase + 32768 + (tid + q * 256) * 16); me = absmax4(trow[q], me); }
  me = __reduce_max_sync(0xffffffffu, max(me & 0xffff, me >> 16));
  mw = __reduce_max_sync(0xffffffffu, max(mw & 0xffff, mw >> 16));
  uint32_t* sred = (uint32_t*)((char*)sm + 128000);
  if (lane == 0) sred[tid >> 5] = me | mw << 16;
  TS(3, 0);
  asm volatile("bar.sync 1,256;" ::: "memory");
  { uint32_t m = 0;
#pragma unroll
    for (int q = 0; q < 8; q++) m = __vmaxu2(m, sred[q]);
    m = __shfl_sync(0xffffffffu, m, 0);
    me = m & 0xffff; mw = m >> 16; }
  const float se = pow2_scale(me, 3), sW = pow2_scale(mw, -2);
  TS(3, 1);
  auto put_rows = [&](int q, bool on) {
    const uint4 t = trow[q];
    const uint4 hv = make_uint4(pack_h2(bf_lo(t.x) * se, bf_hi(t.x) * se), pack_h2(bf_lo(t.y) * se, bf_hi(t.y) * se),
                                pack_h2(bf_lo(t.z) * se, bf_hi(t.z) * se), pack_h2(bf_lo(t.w) * se, bf_hi(t.w) * se));
    if (on)
#pragma unroll
      for (int s = 0; s < 8; s++) sts128(sbase + (tid + q * 256) * 128 + ((s + lane) & 7) * 16, hv);
  };
#pragma unroll 1
  for (int it = 0; it < 3; it++) {
    const int hu = ((tid >> 5) * 3 + it) * 4, code = hu_code(min(hu + (lane >> 3), HU_N - 1)), ok = code >> 4, on = code & 15;
    uint32_t x[4], y[4];
    asm volatile("ldmatrix.sync.aligned.m8n8.x4.shared.b16 {%0,%1,%2,%3},[%4];" : "=r"(x[0]), "=r"(x[1]), "=r"(x[2]), "=r"(x[3])
                 : "r"(sbase + (on * 8 + (lane & (on == 12 ? 3 : 7))) * 208 + ok * 16) : "memory");
    asm volatile("ldmatrix.sync.aligned.m8n8.x4.trans.shared.b16 {%0,%1,%2,%3},[%4];" : "=r"(y[0]), "=r"(y[1]), "=r"(y[2]), "=r"(y[3])
                 : "r"(sbase + (ok * 8 + (lane & (ok == 12 ? 3 : 7))) * 208 + on * 16) : "memory");
    const uint32_t lo = __ballot_sync(0xffffffffu, ok > on), dg = __ballot_sync(0xffffffffu, ok >= on);
#pragma unroll
    for (int q = 0; q < 4; q++) {
      const float m0 = (lo >> (8 * q)) & 1 ? 0.f : sW, m1 = (dg >> (8 * q)) & 1 ? 0.f : sW;
      asm volatile("st.shared.u32 [%0],%1;" :: "r"(sbase + K1_W + (hu + q) * 128 + lane * 4),
                   "r"(pack_h2(fmaf(bf_lo(x[q]), m0, bf_lo(y[q]) * m1), fmaf(bf_hi(x[q]), m0, bf_hi(y[q]) * m1))) : "memory");
    }
  }
  put_rows(1, true); put_rows(2, tid < 88);
  TS(3, 2);
  asm volatile("fence.proxy.async.shared::cta;" ::: "memory");
  asm volatile("bar.sync 1,256;" ::: "memory");
  put_rows(0, true);
  uint32_t bf[HU_N - 2 * G_U];
#pragma unroll
  for (int q = 0; q < HU_N - 2 * G_U; q++) asm volatile("ld.shared.u32 %0,[%1];" : "=r"(bf[q]) : "r"(sbase + K1_W + (2 * G_U + q) * 128 + lane * 4));
  const float unscale = __uint_as_float(0x7f000000u - __float_as_uint(se)), unscale2 = __uint_as_float(0x7f000000u - __float_as_uint(sW));
  TS(3, 3);
  const int px = range * 16 * 136;
  mbar_wait_fast(fullI, 0);
  {
    const uint32_t ib = sbase + 76800 + (tid >> 5) * 6400, p0 = ib + ((lane >> 3) & 1) * 400 + ((lane >> 4) * 8 + (lane & 7)) * 4;
    auto ld = [&](uint32_t ad) { uint32_t v; asm volatile("ld.shared.u32 %0,[%1];" : "=r"(v) : "r"(ad)); return v; };
    auto wd = [&](int t, int h) { return pk3(ld(p0 + t * 800 + h * 192), ld(p0 + t * 800 + h * 192 + 64), ld(p0 + t * 800 + h * 192 + 128)); };
#pragma unroll
    for (int q = 0; q < 4; q++) {
      iv[q] = make_uint4(wd(2 * q, 0), wd(2 * q, 1), wd(2 * q + 1, 0), wd(2 * q + 1, 1));
    }
    ix = ld(ib + g * 400 + 384 + r * 4) | ld(ib + (8 + g) * 400 + 384 + r * 4) << 16;
  }
  asm volatile("bar.sync 1,256;" ::: "memory");
  put_rows(2, tid >= 88); put_rows(3, tid + 768 < V_);
  asm volatile("bar.sync 1,256;" ::: "memory");
  TS(0, 1);
  uint32_t lc; asm volatile("add.u32 %0,%1,%2;" : "=r"(lc) : "r"((lane & 7) * 16), "r"(never));
  const uint64_t wdesc = (uint64_t)(((sbase + K1_W) & 0x3FFFF) >> 4) | ((uint64_t)(128 >> 4) << 16) | ((uint64_t)(256 >> 4) << 32);
  uint32_t a[2][6][4], d[2][26], ex[4] = {}, s[4] = {};
  float red[4] = {0.f, 0.f, 0.f, 0.f};
  auto ldsm = [&](uint32_t* o, uint32_t sh, uint32_t dep = 0) {
    asm volatile("ldmatrix.sync.aligned.m8n8.x4.trans.shared.b16 {%0,%1,%2,%3},[%4];"
                 : "=r"(o[0]), "=r"(o[1]), "=r"(o[2]), "=r"(o[3]) : "r"(sbase + ((sh & 0x1ff80) | (lc | (dep & never)))));
  };
  auto gather = [&](int t, int hf) {
    const int x = t & 1;
    const uint4 v = iv[(t >> 1) & 3];
#pragma unroll
    for (int kb = 3 * hf; kb < 3 * hf + 3; kb++) {
      const uint32_t ww = x ? (kb < 3 ? v.z : v.w) : (kb < 3 ? v.x : v.y);
      ldsm(a[x][kb], kb % 3 == 0 ? ww : kb % 3 == 1 ? ww >> 10 : __funnelshift_l(ww, ww, 12));
    }
  };
  auto issue = [&](int x) {
    asm volatile("wgmma.fence.sync.aligned;" ::: "memory");
#pragma unroll
    for (int kb = 0; kb < 6; kb++) {
      if (kb < G_K0) wgmma_h<G_N0 * 8>(d[x] + G_O0 * 2, a[x][kb], wdesc + kb * G_N0 * 16, kb);
      if (kb < G_K1) wgmma_h<G_N1 * 8>(d[x] + G_O1 * 2, a[x][kb], wdesc + (G_U1 + kb * G_N1) * 16, kb);
      if (kb < G_K2) wgmma_h<32>(d[x] + G_O2 * 2, a[x][kb], wdesc + (G_U2 + kb * G_N2) * 16, kb);
    }
    asm volatile("wgmma.commit_group.sync.aligned;" ::: "memory");
  };
  auto hmma_part = [&](int t) {
    constexpr FragIdx FI = make_fi();
    const int x = t & 1;
#pragma unroll
    for (int o = 0; o < 13; o++) {
      if (oct_wg(o)) asm volatile("" : "+r"(d[x][o * 2]), "+r"(d[x][o * 2 + 1]) :: "memory"); else d[x][o * 2] = d[x][o * 2 + 1] = 0;
    }
#pragma unroll
    for (int kb = 0; kb < 6; kb++)
#pragma unroll
      for (int o = 2 * kb + 1; o < 13; o++)
        if (!unit_wg(kb, o)) mma16816h(d[x] + o * 2, a[x][kb], bf[FI.v[2 * kb][o]], bf[FI.v[2 * kb + 1][o]]);
#pragma unroll
    for (int q = 0; q < 6; q++) if (!unit_wg(q, 2 * q)) mma1688h(d[x] + q * 4, a[x][q][0], a[x][q][1], bf[FI.v[2 * q][2 * q]]);
    mma1688h(d[x] + 24, r < 2 ? ex[t & 3] : 0u, r < 2 ? 0u : ex[t & 3], bf[FI.v[12][12]]);
  };
  auto dot_part = [&](int t, int hf) {
    const int x = t & 1;
    if (hf == 0) {
      const uint32_t pe = hfma2(r < 2 ? d[x][24] : d[x][25], ex[t & 3], 0u);
      s[0] = r < 2 ? pe : 0u; s[1] = r < 2 ? 0u : pe; s[2] = s[3] = 0;
    }
#pragma unroll
    for (int q = 3 * hf; q < 3 * hf + 3; q++)
#pragma unroll
      for (int e = 0; e < 4; e++) s[e] = hfma2(d[x][q * 4 + e], a[x][q][e], s[e]);
  };
  float* outp = g_partP + slice * B_ + range * 256;
  float k0 = 0.f, k1 = 0.f, x0 = 0.f, x1 = 0.f;
  auto red_stage = [&](int st, int grp) {
    const bool u16 = lane & 16, u8 = lane & 8;
    if (st == 0) {
      k0 = u16 ? red[2] : red[0]; x0 = __shfl_xor_sync(0xffffffffu, u16 ? red[0] : red[2], 16);
      k1 = u16 ? red[3] : red[1]; x1 = __shfl_xor_sync(0xffffffffu, u16 ? red[1] : red[3], 16);
      red[0] = red[1] = red[2] = red[3] = 0.f;
    }
    if (st == 1) { const float p0 = k0 + x0, p1 = k1 + x1; k0 = u8 ? p1 : p0; x0 = __shfl_xor_sync(0xffffffffu, u8 ? p0 : p1, 8); }
    if (st == 2) { k0 += x0; x0 = __shfl_xor_sync(0xffffffffu, k0, 4); }
    if (st == 3 && !(lane & 4)) outp[grp * 16 + r * 4 + ((lane >> 3) & 1) * 2 + (lane >> 4)] = (k0 + x0) * unscale * unscale * unscale2;
  };
  auto group = [&](bool first, int prv, int cur, int nxt) {
    const int pn = PX_OFF + px + nxt * 136 + lane;
#pragma unroll
    for (int t = 0; t < 8; t++) {
      issue((t & 1) ^ 1);
      SCHED_FENCE(never, t * 8);
      if (!first) {
        if (t == 0) { iv[3] = ldtex(tex, PX_OFF + px + cur * 136 + lane + 96); iv[0] = ldtex(tex, pn); }
        if (t == 2) iv[1] = ldtex(tex, pn + 32);
        if (t < 4) red_stage(t, prv);
      } else if (t == 4) {
        TS(4, 2);
        mbar_wait_fast(pxRdy, 0);
        TS(4, 3);
        iv[0] = ldtex(tex, pn); iv[1] = ldtex(tex, pn + 32);
      }
      if (t == 4) { ix = ldtex(texX, (px + nxt * 136 + 128) * 4 + lane).x; iv[2] = ldtex(tex, pn + 64); }
      dot_part(t, 0);
      SCHED_FENCE(never, t * 8 + 1);
      if (t == 3) ldsm(ex, ix >> 9);
      if (t == 7) ldsm(ex, ix << 7);
      gather(t + 2, 0);
      dot_part(t, 1);
      SCHED_FENCE(never, t * 8 + 4);
      gather(t + 2, 1);
      asm volatile("wgmma.wait_group.sync.aligned 0;" ::: "memory");
      if (FM & 1) SCHED_FENCE(never, t * 8 + 2);
      asm volatile("" : "+r"(d[(t & 1) ^ 1][0]) :: "memory");
      mma1688f(red, hadd2(s[0], s[2]), hadd2(s[1], s[3]), (g | (d[(t & 1) ^ 1][0] & never)) == t ? 0x3c003c00u : 0u);
      hmma_part(t + 1);
      if (FM & 2) SCHED_FENCE(never, t * 8 + 3);
    }
  };
  gather(0, 0); gather(0, 1); issue(0); ldsm(ex, ix << 7); gather(1, 0); gather(1, 1);
  asm volatile("wgmma.wait_group.sync.aligned 0;" ::: "memory");
  hmma_part(0);
  group(true, 0, 0, 1);
  TS(4, 1);
#pragma unroll 1
  for (int n = 1; n < NGRP; n++) {
    if (n == TRIG) asm volatile("griddepcontrol.launch_dependents;");
    if ((n & 11) == 2) mbar_wait_fast(pxRdy + 8 + (n & 4) * 2, 0);
    group(false, n - 1, n, min(n + 1, 15));
  }
#pragma unroll
  for (int st = 0; st < 4; st++) red_stage(st, 15);
  TS(0, 2);
  if (MCW) asm volatile("barrier.cluster.wait.aligned;" ::: "memory");
  asm volatile("barrier.cluster.arrive.relaxed.aligned; barrier.cluster.wait.aligned;" ::: "memory");
}

constexpr int SM_U = 130048, SM_BAR = 128000, SM_J = SM_U + 98304, DEEP_SMEM = SM_J + 4096;

#define ELECT "{.reg .pred p; elect.sync _|p,0xffffffff; @p "
__device__ __forceinline__ void e_mc(uint32_t dst, const void* src, uint32_t bytes, uint32_t bar, uint64_t pol) {
  asm volatile(ELECT "cp.async.bulk.shared::cluster.global.mbarrier::complete_tx::bytes.multicast::cluster.L2::cache_hint [%0],[%1],%2,[%3],%4,%5;}"
               :: "r"(dst), "l"(src), "r"(bytes), "r"(bar), "h"((unsigned short)3), "l"(pol) : "memory");
}
__device__ __forceinline__ void e_g2s(uint32_t dst, const void* src, uint32_t bytes, uint32_t bar) {
  asm volatile(ELECT "cp.async.bulk.shared::cluster.global.mbarrier::complete_tx::bytes [%0],[%1],%2,[%3];}" :: "r"(dst), "l"(src), "r"(bytes), "r"(bar) : "memory");
}
__device__ __forceinline__ void e_pf(const void* src, uint32_t bytes) { asm volatile(ELECT "cp.async.bulk.prefetch.L2.global [%0],%1;}" :: "l"(src), "r"(bytes) : "memory"); }
__device__ __forceinline__ void e_expect(uint32_t bar, uint32_t bytes) { asm volatile(ELECT "mbarrier.arrive.expect_tx.shared::cta.b64 _,[%0],%1;}" :: "r"(bar), "r"(bytes) : "memory"); }

__global__ void __cluster_dims__(2, 1, 1) __launch_bounds__(TH + 128, 1)
k_deep(cudaTextureObject_t tex, const __nv_bfloat16* __restrict__ w2, const __nv_bfloat16* __restrict__ b2,
       __nv_bfloat16* __restrict__ out, int never) {
  extern __shared__ __align__(1024) uint4 sm[];
  constexpr int PF = DPF, DEPTH = DDEPTH, NW = TH / 32;
  static_assert(YD == 4 && PF == 4, "");
  const int tid = threadIdx.x;
  const int c = blockIdx.x >> 1, half = blockIdx.x & 1;
  const uint32_t sbase = (uint32_t)__cvta_generic_to_shared(sm);
  const uint32_t fullL = sbase + SM_BAR, fullU = fullL + 8, emptyL = fullL + 16, emptyU = fullL + 24, barJ = fullL + 32;
  TS(1, 0);
  if (tid == 0) {
    mbar_init(fullL, 1); mbar_init(fullU, 1); mbar_init(emptyL, 2 * NW); mbar_init(emptyU, 2 * NW); mbar_init(barJ, 1);
    asm volatile("fence.mbarrier_init.release.cluster;" ::: "memory");
  }
  __syncwarp();
  const int wrp = __shfl_sync(0xffffffffu, tid >> 5, 0);
  const char* base = (const char*)g_scr;
  uint32_t oL = (PL_OFF + c * NC * 8000) * 16u + half * 64000, oS = (PS_OFF + c * NC * 2000) * 16u + half * 16000;
  asm volatile("barrier.cluster.arrive.relaxed.aligned;" ::: "memory");
  flag_wait(&g_flag[24 * 32], 132);
  asm volatile("barrier.cluster.wait.aligned;" ::: "memory");
  if (wrp == NW) {
    asm volatile("fence.proxy.async.global;" ::: "memory");
    e_expect(fullU, 96000);
#pragma unroll
    for (int m = 0; m < 3; m++) e_mc(sbase + SM_U + m * 32032 + half * 16000, base + oS, 16000, fullU, m == 2 ? POL_EF : POL_N);
    e_expect(fullL, 128000);
    if (!STAG) e_mc(sbase + half * 64000, base + oL, 64000, fullL, POL_EF);
  }
  TS(5, 1);
  if (wrp >= NW) {
    asm volatile("setmaxnreg.dec.sync.aligned.u32 24;");
    if (wrp == NW) {
      uint32_t oT = (PT_OFF + c * 10 * 1024) * 16u + half * 8192;
      const uint32_t junk = sbase + SM_J, oW = (IX_OFF + half * IXH + ((c + (c >> 4) * 5) & 15) * 512) * 16u;
      auto warm = [&](uint32_t off) {
        asm volatile(ELECT "mbarrier.expect_tx.relaxed.cta.shared::cta.b64 [%0],%1;}" :: "r"(barJ), "r"(8192) : "memory");
        e_g2s(junk, base + off, 4096, barJ); e_g2s(junk, base + off + 4096, 4096, barJ);
      };
      uint32_t t0 = clock();
      if (!PREW) warm(oW);
      if (STAG) { if (STAG == 1) mbar_wait_fast(fullU, 0); else sleep_until(t0, STAG); e_mc(sbase + half * 64000, base + oL, 64000, fullL, POL_EF); }
      warm(oT);
      if (!(PREW & 4)) warm(oW + 131072);
#pragma unroll 1
      for (int k = 0; k + 1 < NC; k++) {
        oL += 128000; oS += 32000; oT += 16384;
        mbar_wait_fast(fullL, k & 1);
        t0 = clock();
        e_pf(base + oS, 16000);
        if (k + 2 < NC) {
          const uint32_t o2 = (IX_OFF + half * IXH + (k + 2) * 8192) * 16u + ((c + (c / (64 / WRED)) * (2 * k + 1)) & (64 / WRED - 1)) * (WRED * 2048);
#pragma unroll 1
          for (int q = 0; q < WRED / 4; q++) warm(o2 + q * 8192);
        } else warm((IX_OFF + half * IXH + NC * 8192 + (c & 3) * 512) * 16u);
        mbar_wait_fast(emptyU, k & 1);
        e_expect(fullU, 96000);
#pragma unroll 1
        for (int q = 0; q < 8; q++) {
          sleep_until(t0, q * PACE);
          e_pf(base + oL + q * 8000, 8000);
          if (q >= 2) e_mc(sbase + SM_U + ((q - 2) >> 1) * 32032 + half * 16000 + (q & 1) * 8000, base + oS + (q & 1) * 8000, 8000, fullU, q >= 6 ? POL_EF : POL_N);
        }
        warm(oT);
        e_expect(fullL, 128000);
        sleep_until(t0, RSV_T);
        unsigned long long now, slot = 0;
        asm volatile("mov.u64 %0,%globaltimer;" : "=l"(now));
        if ((tid & 31) == 0) { atomicMax(&g_slot, now + RSV_L); slot = atomicAdd(&g_slot, (unsigned long long)RSV); }
        slot = __shfl_sync(0xffffffffu, slot, 0);
        mbar_wait_fast(emptyL, k & 1);
        for (int it = 0; it < 4000; it++) { asm volatile("mov.u64 %0,%globaltimer;" : "=l"(now)); if (now >= slot) break; }
        e_mc(sbase + half * 64000, base + oL, 64000, fullL, POL_EF);
      }
      mbar_wait_fast(fullL, (NC - 1) & 1);
      mbar_wait_fast(emptyU, (NC - 1) & 1);
      mbar_arrive_lane0(fullU);
      warm(oT + 16384);
      mbar_arrive_lane0(barJ); mbar_wait_fast(barJ, 0);
    } else if (tid >= TH + 96) {
      if (tid == TH + 96) sts128(barJ + 32, *(const uint4*)(w2 + c * 8));
      asm volatile("bar.arrive 3,%0;" :: "n"(TH + 32) : "memory");
      asm volatile("griddepcontrol.wait;" ::: "memory");
      const int b = half * 8192 + c * 128 + (tid & 31) * 4;
      const float bias = __bfloat162float(b2[0]);
      float4 s = make_float4(bias, bias, bias, bias);
#pragma unroll 2
      for (int k = 0; k < 16; k++) { const float4 v = __ldcg((const float4*)(g_partP + k * B_ + b)); s.x += v.x; s.y += v.y; s.z += v.z; s.w += v.w; }
      asm volatile("red.global.add.v4.f32 [%0],{%1,%2,%3,%4};" :: "l"(g_acc + b), "f"(s.x), "f"(s.y), "f"(s.z), "f"(s.w) : "memory");
      asm volatile("bar.arrive 1,%0;" :: "n"(TH + 32) : "memory");
    }
    return;
  }
  asm volatile("setmaxnreg.inc.sync.aligned.u32 240;");
  const int lane = tid & 31;
  const int tbase = PT_OFF + c * 10 * 1024;
  const int ibase = IX_OFF + half * IXH + tid;
  const uint32_t lc = (tid & 7) << 4;
  uint4 acc[NS], wq[PF], x[DEPTH], y[YD], ye;
  uint32_t sw[NS] = {};
  auto sget = [&](int s) { return (s & 3) == 3 ? __byte_perm(__byte_perm(sw[s - 3], sw[s - 2], 0x0073), sw[s - 1], 0x0710) : sw[s]; };
  auto sa0 = [&](uint32_t v) { return sbase + SM_U + (((v << 5) & 0x1ffe0) | ((lc >> 2) & 16)); };
  auto sa1 = [&](uint32_t v) { return sbase + SM_U + (((v >> 7) & 0x1ffe0) | ((~lc >> 2) & 16)); };
  {
    uint4 i0[8];
#pragma unroll
    for (int q = 0; q < 8; q++) i0[q] = ldtex(tex, I0_OFF + (half * 8 + q) * TH + tid);
#pragma unroll
    for (int i = 0; i < PF; i++) if (!WQL) wq[i] = ldtex(tex, ibase + i * TH);
    auto wd = [&](int k) { return (k & 3) == 0 ? i0[k >> 2].x : (k & 3) == 1 ? i0[k >> 2].y : (k & 3) == 2 ? i0[k >> 2].z : i0[k >> 2].w; };
    TS(5, 2);
    mbar_wait_fast(fullU, 0);
#pragma unroll
    for (int i = 0; i < PF; i++) if (WQL) wq[i] = ldtex(tex, ibase + i * TH);
    TS(1, 1);
#pragma unroll
    for (int s = 0; s < NS; s++) acc[s] = add4(lds128(sa0(wd(s))), lds128(sa1(wd(s))));
    arrive_both(emptyU, lane);
    asm volatile("bar.sync 3,%0;" :: "n"(TH + 32) : "memory");
    TS(5, 3);
  }
#pragma unroll 1
  for (int k = 0; k < NC; k++) {
    const int ti = ibase + k * 8192;
    const int tb = tbase + k * 1024;
    const bool more = k + 1 < NC;
    TR(k * 4);
    if (CBAR & 1) asm volatile("bar.sync 4,%0;" :: "n"(TH) : "memory");
    mbar_wait_fast(fullL, k & 1);
    TR(k * 4 + 2);
    uint4 w, cc; uint32_t yc, yn;
    constexpr int TL = NS * 8, TT = TL + NS * 2;
#pragma unroll
    for (int t = 0; t < TT + DEPTH; t += 2) {
      if (t == TL + DEPTH && !more) break;
      if (t >= DEPTH) {
        const int u = t - DEPTH;
        uint4 p = add4(x[u % DEPTH], x[(u + 1) % DEPTH]);
        if (u < TL) {
          const int s = u >> 3, j = u & 7;
          if (j == 0) {
            cc = s >= YD ? add4(y[s % YD], p) : p;
            if (s + YD < NS) y[s % YD] = ldtex(tex, tb | (yc & 1023));
          } else cc = add4(cc, p);
          if (j == 6) acc[s] = add4(acc[s], cc);
        } else {
          const int s = (u - TL) >> 1;
          acc[s] = add4(acc[s], p);
        }
      }
      if ((CBAR & 4) && t == TL / 2) asm volatile("bar.sync 4,%0;" :: "n"(TH) : "memory");
      if ((CBAR & 8) && t == TL - 40) asm volatile("bar.sync 4,%0;" :: "n"(TH) : "memory");
      if (DEPTH == 8 && (t & 7) == 2) yc = yn;
      if (t < TL) {
        const int s = t >> 3, j = t & 7;
        if (j == 0) {
          if (ye_of(s - YD) >= 0) acc[ye_of(s - YD) & 3] = add4(acc[ye_of(s - YD) & 3], ye);
          w = wq[s % PF];
          if (!EARLY || s < NS - 4) wq[s % PF] = ldtex(tex, ti + (s + PF) * TH);
          else {
            if (s == NS - 4) { wq[0] = ldtex(tex, ti + NS * TH); ye = ldtex(tex, ti + (NS + 3) * TH); }
            if (s == NS - 3) { wq[1] = ldtex(tex, ti + (NS + 1) * TH); y[0] = ldtex(tex, ti + (NS + 2) * TH); }
            if (s == NS - 2) wq[2] = y[0];
            if (s == NS - 1) wq[3] = ye;
          }
          yn = __funnelshift_l(w.z, w.z, 5); if (DEPTH < 8) yc = yn;
          if ((s & 3) != 3) asm volatile("add.u32 %0,%1,%2;" : "=r"(sw[s]) : "r"(w.w), "r"(never));
          if (ye_of(s) >= 0) ye = ldtex(tex, tb | w.w);
        }
#pragma unroll
        for (int jj = j; jj < j + 2; jj++) {
          const uint32_t ww = jj < 3 ? w.x : jj < 6 ? w.y : w.z;
          const uint32_t sh = jj % 3 == 0 ? ww : jj % 3 == 1 ? ww >> 10 : __funnelshift_l(ww, ww, 12);
          x[(t + jj - j) % DEPTH] = lds128(sbase + ((sh & 0x1ff80) | lc) + jj * 16 - 128);
        }
      } else if (t < TT) {
        const int s = (t - TL) >> 1;
        if (s == 0) { arrive_both(emptyL, more ? lane : 9); TR(k * 4 + 3); if (CBAR & 2) asm volatile("bar.sync 4,%0;" :: "n"(TH) : "memory"); mbar_wait_fast(fullU, (k + 1) & 1); }
        const uint32_t sv = sget(s);
        x[t % DEPTH] = lds128(sa0(sv));
        x[(t + 1) % DEPTH] = lds128(sa1(sv));
      } else if (t == TT) arrive_both(emptyU, lane);
      if ((t & (FENCE_N - 1)) == FENCE_N - 2) SCHED_FENCE(never, t);
    }
  }
  TS(1, 2);
  const uint4 w2v = lds128(barJ + 32);
  const uint32_t cell = sbase + SM_U + tid * 16;
  const int t9 = tbase + 9 * 1024;
  uint4 za[4], i9 = wq[0];
  auto fetch = [&](int q) {
    y[0] = ldtex(tex, t9 | i9.x); y[1] = ldtex(tex, t9 | i9.y); y[2] = ldtex(tex, t9 | i9.z); y[3] = ldtex(tex, t9 | i9.w);
    if (q) {
      i9 = ldtex(tex, ibase + NC * 8192 + min(q + 1, 7) * TH);
      const uint32_t ca = cell + (q > 6 ? 0 : q - 1) * 16384;
#pragma unroll
      for (int s = 0; s < 4; s++) za[s] = lds128(ca + s * 4096);
    }
  };
  fetch(0);
  i9 = wq[1];
#pragma unroll
  for (int s = 0; s < 4; s++) za[s] = acc[s];
#pragma unroll
  for (int s = 0; s < 24; s++) sts128(cell + s * 4096, acc[4 + s]);
  float hw[8];
  {
    const uint32_t ww[4] = {w2v.x, w2v.y, w2v.z, w2v.w};
#pragma unroll
    for (int k = 0; k < 8; k++) hw[k] = 0.5f * ((k & 1) ? bf_hi(ww[k >> 1]) : bf_lo(ww[k >> 1]));
  }
  float* outp = g_acc + half * 8192 + tid;
#pragma unroll 1
  for (int q = 0; q < NS / 4; q++) {
    uint4 z[4];
#pragma unroll
    for (int s = 0; s < 4; s++) z[s] = add4(za[s], y[s]);
    if (q == 1) {
#pragma unroll
      for (int s = 0; s < 4; s++) sts128(cell + s * 4096, acc[28 + s]);
    }
    if (q < 7) fetch(q + 1);
    SCHED_FENCE(never, 999);
#pragma unroll
    for (int s = 0; s < 4; s++) {
      const uint32_t a[4] = {z[s].x, z[s].y, z[s].z, z[s].w};
      float r0 = 0.f;
#pragma unroll
      for (int k = 0; k < 8; k++) {
        const float v = (k & 1) ? bf_hi(a[k >> 1]) : bf_lo(a[k >> 1]);
        const float u = v * fmaf(v * v, 0.7978845608028654f * 0.044715f, 0.7978845608028654f);
        float th; asm("tanh.approx.f32 %0,%1;" : "=f"(th) : "f"(u));
        r0 = fmaf(fmaf(v, th, v), hw[k], r0);
      }
      asm volatile("red.global.add.f32 [%0],%1;" :: "l"(outp + s * TH), "f"(r0) : "memory");
    }
    outp += 4 * TH;
  }
  TS(1, 3);
  asm volatile("bar.sync 1,%0;" :: "n"(TH + 32) : "memory");
  if (tid == 0) {
    __threadfence();
    const unsigned old = atomicInc(&g_done[half * 32], 63);
    asm volatile("st.shared.u32 [%0],%1;" :: "r"(barJ + 8), "r"(old) : "memory");
  }
  asm volatile("bar.sync 2,%0;" :: "n"(TH) : "memory");
  uint32_t old; asm volatile("ld.shared.u32 %0,[%1];" : "=r"(old) : "r"(barJ + 8));
  if (old == 63) {
    if (half == 0 && tid == 25) g_slot = 0;
    if (half == 0 && tid < 25) g_flag[tid * 32] = 0;
    __threadfence();
    float4 v[8];
#pragma unroll
    for (int q = 0; q < 8; q++) v[q] = __ldcg((const float4*)(g_acc + half * 8192) + q * TH + tid);
#pragma unroll
    for (int q = 0; q < 8; q++) ((uint2*)(out + half * 8192))[q * TH + tid] = make_uint2(pack_bf2(v[q].x, v[q].y), pack_bf2(v[q].z, v[q].w));
    TS(6, 2);
  }
}

}

extern "C" void kernel_launch(void* const* d_in, const int* in_sizes, int n_in, void* d_out, int out_size) {
  const int* idx = (const int*)d_in[0];
  const __nv_bfloat16* table = (const __nv_bfloat16*)d_in[1];
  const __nv_bfloat16* wp = (const __nv_bfloat16*)d_in[2];
  const __nv_bfloat16* w1 = (const __nv_bfloat16*)d_in[3];
  const __nv_bfloat16* b1 = (const __nv_bfloat16*)d_in[4];
  const __nv_bfloat16* w2 = (const __nv_bfloat16*)d_in[5];
  const __nv_bfloat16* b2 = (const __nv_bfloat16*)d_in[6];
  static cudaTextureObject_t texScr = 0, texG = 0;
  static CUtensorMap mapW, mapL, mapS, mapT, mapE, mapC;
  static const void *c_tab = nullptr, *c_w1 = nullptr;
  if (c_tab != table || c_w1 != w1) {
    c_tab = table; c_w1 = w1;
    char* scr = nullptr; cudaGetSymbolAddress((void**)&scr, g_scr);
    auto mk_tex = [](const void* p, size_t bytes, cudaChannelFormatDesc d) {
      cudaResourceDesc rd = {}; rd.resType = cudaResourceTypeLinear; rd.res.linear.devPtr = (void*)p; rd.res.linear.desc = d; rd.res.linear.sizeInBytes = bytes;
      cudaTextureDesc td = {}; td.readMode = cudaReadModeElementType;
      cudaTextureObject_t t = 0; cudaCreateTextureObject(&t, &rd, &td, nullptr); return t;
    };
    if (!texScr) {
      texScr = mk_tex(scr, (size_t)SCR_N * 16, cudaCreateChannelDesc<uint4>());
      texG = mk_tex(scr + (size_t)PX_OFF * 16, (size_t)(SCR_N - PX_OFF) * 16, cudaCreateChannelDesc<unsigned>());
    }
    typedef CUresult (*EncFn)(CUtensorMap*, CUtensorMapDataType, cuuint32_t, void*, const cuuint64_t*, const cuuint64_t*, const cuuint32_t*,
                              const cuuint32_t*, CUtensorMapInterleave, CUtensorMapSwizzle, CUtensorMapL2promotion, CUtensorMapFloatOOBfill);
    EncFn enc = nullptr; cudaDriverEntryPointQueryResult qr;
    cudaGetDriverEntryPoint("cuTensorMapEncodeTiled", (void**)&enc, cudaEnableDefault, &qr);
    const cuuint32_t ones[4] = {1, 1, 1, 1};
    auto mk = [&](CUtensorMap* m, CUtensorMapDataType dt, int rank, void* p, const cuuint64_t* dim, const cuuint64_t* str, const cuuint32_t* box, CUtensorMapSwizzle sw) {
      enc(m, dt, rank, p, dim, str, box, ones, CU_TENSOR_MAP_INTERLEAVE_NONE, sw, CU_TENSOR_MAP_L2_PROMOTION_NONE, CU_TENSOR_MAP_FLOAT_OOB_FILL_NONE);
    };
    { cuuint64_t dim[2] = {H_, F_ * D_}, str[1] = {H_ * 2}; cuuint32_t box[2] = {32, 256};
      mk(&mapW, CU_TENSOR_MAP_DATA_TYPE_BFLOAT16, 2, (void*)w1, dim, str, box, CU_TENSOR_MAP_SWIZZLE_64B); }
    { cuuint64_t dim[4] = {64, V_, NC, 64}, str[3] = {128, 128000, 128000 * NC}; cuuint32_t box[4] = {32, 64, 1, 4};
      mk(&mapL, CU_TENSOR_MAP_DATA_TYPE_BFLOAT16, 4, scr + (size_t)PL_OFF * 16, dim, str, box, CU_TENSOR_MAP_SWIZZLE_64B); }
    { cuuint64_t dim[4] = {64, V_ / 4, NC, 64}, str[3] = {128, 32000, 32000 * NC}; cuuint32_t box[4] = {64, 16, 1, 4};
      mk(&mapS, CU_TENSOR_MAP_DATA_TYPE_BFLOAT16, 4, scr + (size_t)PS_OFF * 16, dim, str, box, CU_TENSOR_MAP_SWIZZLE_128B); }
    { cuuint64_t dim[3] = {2048, 10, 64}, str[2] = {16384, 163840}; cuuint32_t box[3] = {128, 2, 4};
      mk(&mapT, CU_TENSOR_MAP_DATA_TYPE_UINT64, 3, scr + (size_t)PT_OFF * 16, dim, str, box, CU_TENSOR_MAP_SWIZZLE_NONE); }
    { cuuint64_t dim[2] = {D_, V_}, str[1] = {D_ * 2}; cuuint32_t box[2] = {64, 128};
      mk(&mapE, CU_TENSOR_MAP_DATA_TYPE_BFLOAT16, 2, (void*)table, dim, str, box, CU_TENSOR_MAP_SWIZZLE_128B);
      cuuint32_t box2[2] = {8, 256};
      mk(&mapC, CU_TENSOR_MAP_DATA_TYPE_BFLOAT16, 2, (void*)table, dim, str, box2, CU_TENSOR_MAP_SWIZZLE_NONE); }
    cudaFuncSetAttribute(k_deep, cudaFuncAttributeMaxDynamicSharedMemorySize, DEEP_SMEM);
    cudaFuncSetAttribute(k_tens, cudaFuncAttributeMaxDynamicSharedMemorySize, K1_SMEM);
  }
  k_tens<<<132, 512, K1_SMEM, cudaStreamPerThread>>>(mapW, mapL, mapS, mapT, mapE, mapC, texScr, texG, idx, table, wp, w1, b1, 0);
  cudaLaunchAttribute at[1];
  at[0].id = cudaLaunchAttributeProgrammaticStreamSerialization; at[0].val.programmaticStreamSerializationAllowed = 1;
  cudaLaunchConfig_t cfg = {};
  cfg.stream = cudaStreamPerThread; cfg.attrs = at;
  cfg.gridDim = 128; cfg.blockDim = TH + 128; cfg.dynamicSmemBytes = DEEP_SMEM; cfg.numAttrs = PDL & 1;
  cudaLaunchKernelEx(&cfg, k_deep, texScr, w2, b2, (__nv_bfloat16*)d_out, 0);

}
```

```cpp
#include <cuda_runtime.h>
#include <cuda_bf16.h>
#include <cuda_fp16.h>
#include <stdint.h>
#include <cuda.h>

namespace {

constexpr int B_ = 16384, F_ = 100, D_ = 128, V_ = 1000, H_ = 512;
constexpr int NC = 9;
constexpr int PT_OFF = 0;
constexpr int PL_OFF = 64 * 10 * 1024;
constexpr int PS_OFF = PL_OFF + 64 * NC * 8000;
constexpr int IXH = NC * 8192 + 2048;
constexpr int IX_OFF = PS_OFF + 64 * NC * 2000;
constexpr int I0_OFF = IX_OFF + 2 * IXH;
constexpr int PX_OFF = I0_OFF + 4096;
constexpr int SCR_N = PX_OFF + 64 * 16 * 136;
static_assert(PX_OFF % 32 == 0, "");

__device__ __align__(1024) uint4 g_scr[SCR_N];
__device__ float g_acc[B_];
__device__ unsigned long long g_slot;
__device__ unsigned g_done[64];
__device__ float g_partP[16 * B_];
__device__ unsigned g_flag[25 * 32];

#define TS(k, i)
#define TR(slot)
#define PT(slot)

constexpr uint64_t POL_EF = 0x12F0000000000000ull, POL_N = 0x1000000000000000ull;
__device__ __forceinline__ uint32_t addbf2(uint32_t a, uint32_t b) { uint32_t r; asm("add.rn.bf16x2 %0,%1,%2;" : "=r"(r) : "r"(a), "r"(b)); return r; }
__device__ __forceinline__ uint4 add4(const uint4& a, const uint4& b) { return make_uint4(addbf2(a.x, b.x), addbf2(a.y, b.y), addbf2(a.z, b.z), addbf2(a.w, b.w)); }
__device__ __forceinline__ void acc4(uint4& a, const uint4& b, int never) {
  asm("{.reg .pred p; setp.eq.s32 p,%8,0;\n"
      "@p add.rn.bf16x2 %0,%0,%4; @p add.rn.bf16x2 %1,%1,%5; @p add.rn.bf16x2 %2,%2,%6; @p add.rn.bf16x2 %3,%3,%7;}"
      : "+r"(a.x), "+r"(a.y), "+r"(a.z), "+r"(a.w) : "r"(b.x), "r"(b.y), "r"(b.z), "r"(b.w), "r"(never));
}
__device__ __forceinline__ uint4 ldtex(cudaTextureObject_t t, int i) {
  uint4 v; asm volatile("tex.1d.v4.u32.s32 {%0,%1,%2,%3},[%4,{%5}];" : "=r"(v.x), "=r"(v.y), "=r"(v.z), "=r"(v.w) : "l"(t), "r"(i)); return v;
}
__device__ __forceinline__ uint4 lds128(uint32_t a) {
  uint4 v; asm volatile("ld.volatile.shared.v4.u32 {%0,%1,%2,%3},[%4];" : "=r"(v.x), "=r"(v.y), "=r"(v.z), "=r"(v.w) : "r"(a)); return v;
}
__device__ __forceinline__ void sts128(uint32_t a, const uint4& v) {
  asm volatile("st.shared.v4.u32 [%0],{%1,%2,%3,%4};" :: "r"(a), "r"(v.x), "r"(v.y), "r"(v.z), "r"(v.w) : "memory");
}
__device__ __forceinline__ void mbar_init(uint32_t bar, int n) { asm volatile("mbarrier.init.shared::cta.b64 [%0],%1;" :: "r"(bar), "r"(n) : "memory"); }
__device__ __forceinline__ void mbar_wait(uint32_t bar, uint32_t parity) {
  uint32_t ok; int it = 0;
  do { asm volatile("{.reg .pred p; mbarrier.try_wait.parity.shared::cta.b64 p,[%1],%2; selp.u32 %0,1,0,p;}" : "=r"(ok) : "r"(bar), "r"(parity) : "memory"); } while (!ok && ++it < (1 << 19));
}
__device__ __forceinline__ void mbar_expect(uint32_t bar, uint32_t bytes) { asm volatile("mbarrier.arrive.expect_tx.shared::cta.b64 _,[%0],%1;" :: "r"(bar), "r"(bytes) : "memory"); }
__device__ __forceinline__ void bulk_g2s(uint32_t dst, const void* src, uint32_t bytes, uint32_t bar) {
  asm volatile("cp.async.bulk.shared::cluster.global.mbarrier::complete_tx::bytes [%0],[%1],%2,[%3];" :: "r"(dst), "l"(src), "r"(bytes), "r"(bar) : "memory");
}
__device__ __forceinline__ void bulk_pf(const void* src, uint32_t bytes) { asm volatile("cp.async.bulk.prefetch.L2.global [%0],%1;" :: "l"(src), "r"(bytes) : "memory"); }
#define NOMMA 0
#define NGRP 16
#define PDL 1
#define FIN_S 128
#define WRED 4
#define RSV 24
#define RSV_T 7200
#define RSV_L 550
#define TRIG 14
#define PREW 5
#define PXW 2
#define PXW0 5
#define WQL 1
#define EARLY 1
#define CBAR 0
#define X_SAMEK 0
#define X_SAMEW 0
#define FM 0
#define SWP 1
#define HOLD 1
#define MCW 1
#define TW 1
#define PP0 10
#define PT0 10000
#define PDT 0
#define RPNN "160"
#define RAUX "32"
#define RPRO "160"
#define PARK 0
#define NLOOK 128
#define NEF 25
#define ORD 0
#define WFENCE 0
#define SPLIT 1
#define IORD 1
#define IPF 3
#define IPACE 4500
#define WPF 1
#define QV 3
#define QORD(n) ((n) < 23 ? (n) + 2 : (n) - 23)
#define DYD 4
#define DPF 4
#define DDEPTH 4
#define FENCE_N 4
#define INPL 0
#define STAG 1
#define PACE 800
#define PM4 "pmevent 1; pmevent 2; pmevent 3; pmevent 4;"
#define PMFILL "pmevent 1;"
#define SCHED_FENCE(never, k) asm volatile("{.reg .pred p; setp.ne.u32 p,%0,%1; @p bra.uni SKIP_%=;" PMFILL "SKIP_%=: }" :: "r"(never), "r"(0x7fff0000 + (k)) : "memory")

__global__ void k_prod_naive(const __nv_bfloat16* __restrict__ table, const __nv_bfloat16* __restrict__ w1) {
  __shared__ float t[8][D_];
  int f = blockIdx.y, v0 = blockIdx.x * 8, h = threadIdx.x;
  for (int i = h; i < 8 * D_; i += 512) t[i / D_][i % D_] = __bfloat162float(table[v0 * D_ + i]);
  __syncthreads();
  float s[8] = {0, 0, 0, 0, 0, 0, 0, 0};
  for (int d = 0; d < D_; d++) { float w = __bfloat162float(w1[(size_t)(f * D_ + d) * H_ + h]);
#pragma unroll
    for (int k = 0; k < 8; k++) s[k] += t[k][d] * w; }
  __nv_bfloat16* P = (__nv_bfloat16*)g_scr;
  int c = h >> 3;
  for (int k = 0; k < 8; k++) {
    size_t e = f < 72 ? (size_t)PL_OFF + ((size_t)(c * NC + (f >> 3)) * 1000 + v0 + k) * 8 + (f & 7)
             : f < 90 ? (size_t)PS_OFF + ((size_t)(c * NC + ((f - 72) >> 1)) * 1000 + v0 + k) * 2 + (f & 1)
                      : (size_t)PT_OFF + (size_t)(c * 10 + f - 90) * 1024 + v0 + k;
    P[e * 8 + (h & 7)] = __float2bfloat16(s[k]);
  }
}
__global__ void k_pnn_naive(const int* __restrict__ idx, const __nv_bfloat16* __restrict__ table, const __nv_bfloat16* __restrict__ wp) {
  __shared__ float e[F_][33];
  int b = blockIdx.x, d0 = blockIdx.y * 32, tid = threadIdx.x;
  for (int i = tid; i < F_ * 32; i += 128) e[i >> 5][i & 31] = __bfloat162float(table[idx[b * F_ + (i >> 5)] * D_ + d0 + (i & 31)]);
  __syncthreads();
  float s = 0; int d = tid & 31;
  for (int i = tid >> 5; i < F_; i += 4) { float u = 0; for (int j = 0; j < F_; j++) u += __bfloat162float(wp[i * F_ + j]) * e[j][d]; s += u * e[i][d]; }
  for (int o = 16; o; o >>= 1) s += __shfl_xor_sync(~0u, s, o);
  if (d == 0) g_partP[(blockIdx.y * 4 + (tid >> 5)) * B_ + b] = s;
}
__device__ __forceinline__ void mbar_wait_fast(uint32_t bar, uint32_t parity) {
  asm volatile("{.reg .pred p; .reg .u32 n;\n"
               "mbarrier.try_wait.parity.shared::cta.b64 p,[%0],%1;\n"
               "@p bra DONE_%=;\n"
               "mov.u32 n,0;\n"
               "LOOP_%=: mbarrier.try_wait.parity.shared::cta.b64 p,[%0],%1;\n"
               "add.u32 n,n,1; setp.gt.or.u32 p,n,400000,p;\n"
               "@!p bra LOOP_%=;\n"
               "DONE_%=: }" :: "r"(bar), "r"(parity) : "memory");
}
__device__ __forceinline__ void sleep_until(uint32_t t0, uint32_t dt) { while ((uint32_t)clock() - t0 < dt) __nanosleep(40); }
__device__ __forceinline__ uint32_t s_mask(uint32_t v, int q) { return (1u << ((v + 3 - q) & 3)) | (16u << ((v + 3 + q) & 3)); }
__device__ __forceinline__ uint32_t s_cell(uint32_t v, int q, uint32_t m) {
  const int t = __ffs(~m) - 1;
  const int cp = t == 8 ? q >> 1 : ((t & 4 ? t - q : t + q) - v) & 3;
  return cp * 1001 + v;
}
__device__ __forceinline__ uint32_t pk3(uint32_t a, uint32_t b, uint32_t c) {
  const uint32_t w = c + (a << 12) + (b << 22); return __funnelshift_l(w, w, 27);
}
constexpr int TH = 256, NS = 8192 / TH, YD = DYD;
__host__ __device__ constexpr int ye_of(int s) { return s == 3 ? 0 : s == 11 ? 1 : s == 19 ? 2 : s == 23 ? 3 : -1; }
template <int N> __device__ __forceinline__ void wgmma_h(uint32_t* d, const uint32_t* a, uint64_t desc, int acc);
template <> __device__ __forceinline__ void wgmma_h<64>(uint32_t* d, const uint32_t* a, uint64_t desc, int acc) {
  asm volatile("{.reg .pred p; setp.ne.s32 p,%21,0;\n"
    "wgmma.mma_async.sync.aligned.m64n64k16.f16.f16.f16 {%0,%1,%2,%3,%4,%5,%6,%7,%8,%9,%10,%11,%12,%13,%14,%15},{%16,%17,%18,%19},%20,p,1,1,0;}"
    : "+r"(d[0]),"+r"(d[1]),"+r"(d[2]),"+r"(d[3]),"+r"(d[4]),"+r"(d[5]),"+r"(d[6]),"+r"(d[7]),"+r"(d[8]),"+r"(d[9]),"+r"(d[10]),"+r"(d[11]),"+r"(d[12]),"+r"(d[13]),"+r"(d[14]),"+r"(d[15])
    : "r"(a[0]), "r"(a[1]), "r"(a[2]), "r"(a[3]), "l"(desc), "r"(acc));
}
template <> __device__ __forceinline__ void wgmma_h<56>(uint32_t* d, const uint32_t* a, uint64_t desc, int acc) {
  asm volatile("{.reg .pred p; setp.ne.s32 p,%19,0;\n"
    "wgmma.mma_async.sync.aligned.m64n56k16.f16.f16.f16 {%0,%1,%2,%3,%4,%5,%6,%7,%8,%9,%10,%11,%12,%13},{%14,%15,%16,%17},%18,p,1,1,0;}"
    : "+r"(d[0]),"+r"(d[1]),"+r"(d[2]),"+r"(d[3]),"+r"(d[4]),"+r"(d[5]),"+r"(d[6]),"+r"(d[7]),"+r"(d[8]),"+r"(d[9]),"+r"(d[10]),"+r"(d[11]),"+r"(d[12]),"+r"(d[13])
    : "r"(a[0]), "r"(a[1]), "r"(a[2]), "r"(a[3]), "l"(desc), "r"(acc));
}
template <> __device__ __forceinline__ void wgmma_h<48>(uint32_t* d, const uint32_t* a, uint64_t desc, int acc) {
  asm volatile("{.reg .pred p; setp.ne.s32 p,%17,0;\n"
    "wgmma.mma_async.sync.aligned.m64n48k16.f16.f16.f16 {%0,%1,%2,%3,%4,%5,%6,%7,%8,%9,%10,%11},{%12,%13,%14,%15},%16,p,1,1,0;}"
    : "+r"(d[0]),"+r"(d[1]),"+r"(d[2]),"+r"(d[3]),"+r"(d[4]),"+r"(d[5]),"+r"(d[6]),"+r"(d[7]),"+r"(d[8]),"+r"(d[9]),"+r"(d[10]),"+r"(d[11])
    : "r"(a[0]), "r"(a[1]), "r"(a[2]), "r"(a[3]), "l"(desc), "r"(acc));
}
template <> __device__ __forceinline__ void wgmma_h<40>(uint32_t* d, const uint32_t* a, uint64_t desc, int acc) {
  asm volatile("{.reg .pred p; setp.ne.s32 p,%15,0;\n"
    "wgmma.mma_async.sync.aligned.m64n40k16.f16.f16.f16 {%0,%1,%2,%3,%4,%5,%6,%7,%8,%9},{%10,%11,%12,%13},%14,p,1,1,0;}"
    : "+r"(d[0]),"+r"(d[1]),"+r"(d[2]),"+r"(d[3]),"+r"(d[4]),"+r"(d[5]),"+r"(d[6]),"+r"(d[7]),"+r"(d[8]),"+r"(d[9])
    : "r"(a[0]), "r"(a[1]), "r"(a[2]), "r"(a[3]), "l"(desc), "r"(acc));
}
template <> __device__ __forceinline__ void wgmma_h<32>(uint32_t* d, const uint32_t* a, uint64_t desc, int acc) {
  asm volatile("{.reg .pred p; setp.ne.s32 p,%13,0;\n"
    "wgmma.mma_async.sync.aligned.m64n32k16.f16.f16.f16 {%0,%1,%2,%3,%4,%5,%6,%7},{%8,%9,%10,%11},%12,p,1,1,0;}"
    : "+r"(d[0]),"+r"(d[1]),"+r"(d[2]),"+r"(d[3]),"+r"(d[4]),"+r"(d[5]),"+r"(d[6]),"+r"(d[7])
    : "r"(a[0]), "r"(a[1]), "r"(a[2]), "r"(a[3]), "l"(desc), "r"(acc));
}
__device__ __forceinline__ void wgmma_p(float* d, const uint32_t* a, uint64_t desc, int acc) {
  asm volatile("{.reg .pred p; setp.ne.s32 p,%69,0;\n"
    "wgmma.mma_async.sync.aligned.m64n128k16.f32.bf16.bf16 {%0,%1,%2,%3,%4,%5,%6,%7,%8,%9,%10,%11,%12,%13,%14,%15,%16,%17,%18,%19,%20,%21,%22,%23,%24,%25,%26,%27,%28,%29,%30,%31,%32,%33,%34,%35,%36,%37,%38,%39,%40,%41,%42,%43,%44,%45,%46,%47,%48,%49,%50,%51,%52,%53,%54,%55,%56,%57,%58,%59,%60,%61,%62,%63},{%64,%65,%66,%67},%68,p,1,1,1;}"
    : "+f"(d[0]),"+f"(d[1]),"+f"(d[2]),"+f"(d[3]),"+f"(d[4]),"+f"(d[5]),"+f"(d[6]),"+f"(d[7]),"+f"(d[8]),"+f"(d[9]),"+f"(d[10]),"+f"(d[11]),"+f"(d[12]),"+f"(d[13]),"+f"(d[14]),"+f"(d[15]),"+f"(d[16]),"+f"(d[17]),"+f"(d[18]),"+f"(d[19]),"+f"(d[20]),"+f"(d[21]),"+f"(d[22]),"+f"(d[23]),"+f"(d[24]),"+f"(d[25]),"+f"(d[26]),"+f"(d[27]),"+f"(d[28]),"+f"(d[29]),"+f"(d[30]),"+f"(d[31]),"+f"(d[32]),"+f"(d[33]),"+f"(d[34]),"+f"(d[35]),"+f"(d[36]),"+f"(d[37]),"+f"(d[38]),"+f"(d[39]),"+f"(d[40]),"+f"(d[41]),"+f"(d[42]),"+f"(d[43]),"+f"(d[44]),"+f"(d[45]),"+f"(d[46]),"+f"(d[47]),"+f"(d[48]),"+f"(d[49]),"+f"(d[50]),"+f"(d[51]),"+f"(d[52]),"+f"(d[53]),"+f"(d[54]),"+f"(d[55]),"+f"(d[56]),"+f"(d[57]),"+f"(d[58]),"+f"(d[59]),"+f"(d[60]),"+f"(d[61]),"+f"(d[62]),"+f"(d[63])
    : "r"(a[0]), "r"(a[1]), "r"(a[2]), "r"(a[3]), "l"(desc), "r"(acc));
}

__device__ __forceinline__ void mma16816h(uint32_t* c, const uint32_t* a, uint32_t b0, uint32_t b1) {
  asm("mma.sync.aligned.m16n8k16.row.col.f16.f16.f16.f16 {%0,%1},{%2,%3,%4,%5},{%6,%7},{%0,%1};"
      : "+r"(c[0]), "+r"(c[1]) : "r"(a[0]), "r"(a[1]), "r"(a[2]), "r"(a[3]), "r"(b0), "r"(b1));
}
__device__ __forceinline__ void mma1688h(uint32_t* c, uint32_t a0, uint32_t a1, uint32_t b) {
  asm("mma.sync.aligned.m16n8k8.row.col.f16.f16.f16.f16 {%0,%1},{%2,%3},{%4},{%0,%1};" : "+r"(c[0]), "+r"(c[1]) : "r"(a0), "r"(a1), "r"(b));
}
__device__ __forceinline__ void mma1688f(float* c, uint32_t a0, uint32_t a1, uint32_t b) {
  asm("mma.sync.aligned.m16n8k8.row.col.f32.f16.f16.f32 {%0,%1,%2,%3},{%4,%5},{%6},{%0,%1,%2,%3};"
      : "+f"(c[0]), "+f"(c[1]), "+f"(c[2]), "+f"(c[3]) : "r"(a0), "r"(a1), "r"(b));
}
__device__ __forceinline__ uint32_t hadd2(uint32_t a, uint32_t b) { uint32_t r; asm("add.rn.f16x2 %0,%1,%2;" : "=r"(r) : "r"(a), "r"(b)); return r; }
__device__ __forceinline__ uint32_t hfma2(uint32_t a, uint32_t b, uint32_t c) { uint32_t r; asm("fma.rn.f16x2 %0,%1,%2,%3;" : "=r"(r) : "r"(a), "r"(b), "r"(c)); return r; }
__device__ __forceinline__ uint32_t pack_bf2(float lo, float hi) { uint32_t r; asm("cvt.rn.bf16x2.f32 %0,%1,%2;" : "=r"(r) : "f"(hi), "f"(lo)); return r; }
__device__ __forceinline__ uint32_t pack_h2(float lo, float hi) { uint32_t r; asm("cvt.rn.f16x2.f32 %0,%1,%2;" : "=r"(r) : "f"(hi), "f"(lo)); return r; }
__device__ __forceinline__ float bf_lo(uint32_t w) { return __uint_as_float(w << 16); }
__device__ __forceinline__ float bf_hi(uint32_t w) { return __uint_as_float(w & 0xffff0000u); }
__device__ __forceinline__ uint32_t absmax4(const uint4& v, uint32_t m) {
  return __vmaxu2(__vmaxu2(__vmaxu2(v.x & 0x7fff7fffu, v.y & 0x7fff7fffu), __vmaxu2(v.z & 0x7fff7fffu, v.w & 0x7fff7fffu)), m);
}
__device__ __forceinline__ float pow2_scale(uint32_t mbits, int p) { return __uint_as_float((uint32_t)min(max(253 + p - (int)(mbits >> 7), 2), 252) << 23); }

#define PV 4
constexpr int G_O0 = 8, G_O1 = 4, G_O2 = 0, G_N0 = 5, G_N1 = 4, G_N2 = 4, G_K0 = 5, G_K1 = 3, G_K2 = 1;
__host__ __device__ constexpr bool unit_wg(int kb, int on) {
  return (on >= G_O0 && on < G_O0 + G_N0 && kb < G_K0) || (on >= G_O1 && on < G_O1 + G_N1 && kb < G_K1) || (on >= G_O2 && on < G_O2 + G_N2 && kb < G_K2);
}
__host__ __device__ constexpr bool oct_wg(int on) { return unit_wg(0, on); }
constexpr int G_U1 = G_N0 * G_K0, G_U2 = G_U1 + G_N1 * G_K1, G_U = G_U2 + G_N2 * G_K2;
constexpr int K1_B = 130048, K1_STG = K1_B + 2 * 32768, K1_W = K1_STG + 16384, K1_BAR = K1_W + 48 * 256, K1_SMEM = K1_BAR + 256 + 6400;
__host__ __device__ constexpr int frag_index(int ok, int on) {
  int n = 0;
  for (int k = 0; k < 13; k++) for (int o = k; o < 13; o++) { if (k == ok && o == on) return n; if (!unit_wg(k >> 1, o)) n++; }
  return n;
}
constexpr int HU_N = 2 * G_U + frag_index(99, 99);
static_assert(HU_N <= 96, "");
struct FragIdx { int v[13][13]; };
__host__ __device__ constexpr FragIdx make_fi() { FragIdx f = {}; for (int k = 0; k < 13; k++) for (int o = 0; o < 13; o++) f.v[k][o] = frag_index(k, o); return f; }
__host__ __device__ constexpr uint64_t frag_tab(int first) {
  uint64_t t = 0;
  for (int k = 0; k < 13; k++) for (int o = k; o < 13; o++)
    if (!unit_wg(k >> 1, o)) { const int n = frag_index(k, o) - first; if (n >= 0 && n < 8) t |= (uint64_t)(k << 4 | o) << (8 * n); }
  return t;
}
__device__ __forceinline__ int hu_code(int hu) {
  constexpr uint64_t T0 = frag_tab(0), T1 = frag_tab(8), T2 = frag_tab(16), T3 = frag_tab(24);
  const int u = hu >> 1, f = hu - 2 * G_U;
  if (f >= 0) return (int)((f < 8 ? T0 : f < 16 ? T1 : f < 24 ? T2 : T3) >> (8 * (f & 7))) & 255;
  const int u0 = u < G_U1 ? u : u < G_U2 ? u - G_U1 : u - G_U2;
  const int kb = u < G_U1 ? u0 / G_N0 : u < G_U2 ? u0 / G_N1 : u0 / 4, on = u < G_U1 ? G_O0 + u0 % G_N0 : u < G_U2 ? G_O1 + u0 % G_N1 : G_O2 + u0 % 4;
  return (2 * kb + (hu & 1)) << 4 | on;
}

__device__ __forceinline__ void flag_arrive(unsigned* f, int lane) {
  __threadfence(); __syncwarp();
  if (lane == 0) asm volatile("red.release.gpu.global.add.u32 [%0],1;" :: "l"(f) : "memory");
}
__device__ __forceinline__ void flag_wait(const unsigned* f, unsigned n) {
  unsigned v; int it = 0;
  asm volatile("ld.acquire.gpu.global.u32 %0,[%1];" : "=r"(v) : "l"(f) : "memory");
  if (v < n) {
    do { __nanosleep(300); asm volatile("ld.relaxed.gpu.global.u32 %0,[%1];" : "=r"(v) : "l"(f) : "memory"); } while (v < n && ++it < (1 << 20));
    asm volatile("ld.acquire.gpu.global.u32 %0,[%1];" : "=r"(v) : "l"(f) : "memory");
  }
}
__device__ __forceinline__ void mbar_arrive(uint32_t bar) { asm volatile("mbarrier.arrive.shared::cta.b64 _,[%0];" :: "r"(bar) : "memory"); }
__device__ __forceinline__ void mbar_arrive_lane0(uint32_t bar) {
  asm volatile("{.reg .pred p; elect.sync _|p,0xffffffff; @p mbarrier.arrive.shared::cta.b64 _,[%0];}" :: "r"(bar) : "memory");
}

__device__ __forceinline__ void arrive_both(uint32_t bar, int lane) {
  asm volatile("{.reg .pred p; .reg .u32 a; setp.lt.u32 p,%1,2; mapa.shared::cluster.u32 a,%0,%1;\n"
               "@p mbarrier.arrive.shared::cluster.b64 _,[a];}" :: "r"(bar), "r"(lane) : "memory");
}
#define ELECT "{.reg .pred p; elect.sync _|p,0xffffffff; @p "
__device__ __forceinline__ void e_mc(uint32_t dst, const void* src, uint32_t bytes, uint32_t bar, uint64_t pol) {
  asm volatile(ELECT "cp.async.bulk.shared::cluster.global.mbarrier::complete_tx::bytes.multicast::cluster.L2::cache_hint [%0],[%1],%2,[%3],%4,%5;}"
               :: "r"(dst), "l"(src), "r"(bytes), "r"(bar), "h"((unsigned short)3), "l"(pol) : "memory");
}
__device__ __forceinline__ void e_g2s(uint32_t dst, const void* src, uint32_t bytes, uint32_t bar) {
  asm volatile(ELECT "cp.async.bulk.shared::cluster.global.mbarrier::complete_tx::bytes [%0],[%1],%2,[%3];}" :: "r"(dst), "l"(src), "r"(bytes), "r"(bar) : "memory");
}
__device__ __forceinline__ void e_pf(const void* src, uint32_t bytes) { asm volatile(ELECT "cp.async.bulk.prefetch.L2.global [%0],%1;}" :: "l"(src), "r"(bytes) : "memory"); }
__device__ __forceinline__ void e_expect(uint32_t bar, uint32_t bytes) { asm volatile(ELECT "mbarrier.arrive.expect_tx.shared::cta.b64 _,[%0],%1;}" :: "r"(bar), "r"(bytes) : "memory"); }
__device__ __forceinline__ void e_tma2d(uint32_t dst, const CUtensorMap* m, int x, int y, uint32_t bar) {
  asm volatile(ELECT "cp.async.bulk.tensor.2d.shared::cluster.global.mbarrier::complete_tx::bytes [%0],[%1,{%2,%3}],[%4];}" :: "r"(dst), "l"(m), "r"(x), "r"(y), "r"(bar) : "memory");
}

__device__ __forceinline__ void pack_role(const int* __restrict__ idx, uint32_t sbase, int pc) {
  constexpr int CH = 3200 + 32, BUF = 32 * 3328;
  const int tid = threadIdx.x, lane = tid & 31, warp = tid >> 5;
  const uint32_t full = sbase + 2 * BUF, empty = full + 16;
  if (tid == 0) { mbar_init(full, 1); mbar_init(full + 8, 1); mbar_init(empty, 18); mbar_init(empty + 8, 18); asm volatile("fence.proxy.async.shared::cta;" ::: "memory"); }
  __syncthreads();
  auto chunk = [&](int s) { return s * 3200 + (s >> 2) * 288; };
  auto load = [&](int n) {
    const int blk = pc * 16 + n;
    if (lane == 0) mbar_expect(full + (n & 1) * 8, 32 * 3200);
    __syncwarp();
    bulk_g2s(sbase + (n & 1) * BUF + chunk(lane), idx + ((blk >> 5) * 8192 + lane * TH + (blk & 31) * 8) * F_, 3200, full + (n & 1) * 8);
  };
  if (warp == 0) { load(0); load(1); }
  const int l = lane & 7;
  uint32_t rot[8], inc[3];
#pragma unroll
  for (int jj = 0; jj < 8; jj++) rot[jj] = ((l + jj) & 7) * 4;
#pragma unroll
  for (int q = 0; q < 3; q++) inc[q] = (l + 3 * q < 8) << 12 | (l + 3 * q + 1 < 8) << 22 | (q < 2 && l + 3 * q + 2 < 8);
  int loaded = 2;
#pragma unroll 1
  for (int task = warp; task < 288; task += 16) {
    const int n = task / 18, q = (task % 18) * 4 + (lane >> 3), sq = q / 9, k = q % 9;
    if (warp == 0 && n + 1 == loaded && loaded < 16) { mbar_wait(empty + (loaded & 1) * 8, ((loaded >> 1) - 1) & 1); load(loaded); loaded++; }
    mbar_wait(full + (n & 1) * 8, (n >> 1) & 1);
    const uint32_t buf = sbase + (n & 1) * BUF + l * 400, row = buf + chunk(sq * 4);
    auto ld = [&](uint32_t ad) { uint32_t v; asm volatile("ld.shared.u32 %0,[%1];" : "=r"(v) : "r"(ad)); return v; };
    const int blk = pc * 16 + n, half = blk >> 5, col = (blk & 31) * 8 + l;
    const int ks = k == NC - 1 ? 0 : k + 1;
    uint32_t cw[4], sv[8], m[2] = {0, 0};
    { const uint32_t a0 = row + (72 + 2 * ks + (l >> 2)) * 4;
#pragma unroll
      for (int u = 0; u < 8; u++) { sv[u] = ld((a0 ^ ((u >> 2) * 4)) + (u & 3) * 3200); m[u >> 2] |= s_mask(sv[u], l & 3) << (8 * (u & 3)); } }
#pragma unroll
    for (int h = 0; h < 2; h++) { m[h] |= __shfl_xor_sync(0xffffffffu, m[h], 1); m[h] |= __shfl_xor_sync(0xffffffffu, m[h], 2); }
#pragma unroll
    for (int u = 0; u < 4; u++) cw[u] = s_cell(sv[u], l & 3, (m[0] >> (8 * u)) & 255) | s_cell(sv[4 + u], l & 3, (m[1] >> (8 * u)) & 255) << 12;
    if (k == NC - 1) {
      auto wide = [&](uint32_t w) { return (w & 0xfff) << 5 | (w >> 12) << 18 | (l & 4 ? 1u << 4 : 1u << 17); };
      g_scr[I0_OFF + (half * 8 + sq) * TH + col] = make_uint4(wide(cw[0]), wide(cw[1]), wide(cw[2]), wide(cw[3]));
      g_scr[IX_OFF + half * IXH + NC * 8192 + sq * TH + col] = make_uint4(ld(row + 396), ld(row + 3596), ld(row + 6796), ld(row + 9996));
      cw[0] = cw[1] = cw[2] = cw[3] = 0;
    }
    const uint32_t ax = buf + chunk(min(sq + 1, 7) * 4) + (90 + k) * 4;
    const uint32_t yev = ld(buf + ((0x3210 >> (sq * 2 + (sq == 5) * 2)) & 3) * 3200 + (90 + k) * 4);
    uint4* dst = g_scr + IX_OFF + half * IXH + (k * NS + sq * 4) * TH + col;
#pragma unroll
    for (int u = 0; u < 4; u++) {
      uint32_t e[8];
#pragma unroll
      for (int jj = 0; jj < 8; jj++) e[jj] = ld(row + k * 32 + rot[jj] + u * 3200);
      dst[u * TH] = make_uint4(pk3(e[0], e[1], e[2] + inc[0]), pk3(e[3], e[4], e[5] + inc[1]), pk3(e[6], e[7], ld(ax + u * 3200) + inc[2]),
                               u < 3 ? __byte_perm(cw[u], cw[3], 0x4210 + (u << 12)) : yev);
    }
    mbar_arrive_lane0(empty + (n & 1) * 8);
  }
  (void)CH;
}

__global__ void __cluster_dims__(2, 1, 1) __launch_bounds__(512, 1)
k_tens(const __grid_constant__ CUtensorMap mapW, const __grid_constant__ CUtensorMap mapL, const __grid_constant__ CUtensorMap mapS,
       const __grid_constant__ CUtensorMap mapT, const __grid_constant__ CUtensorMap mapE, const __grid_constant__ CUtensorMap mapC, cudaTextureObject_t tex, cudaTextureObject_t texX,
       const int* __restrict__ idx, const __nv_bfloat16* __restrict__ table, const __nv_bfloat16* __restrict__ wp, const __nv_bfloat16* __restrict__ w1,
       const __nv_bfloat16* __restrict__ b1, int never) {
  extern __shared__ __align__(1024) uint4 sm[];
  const int tid = threadIdx.x, lane = tid & 31, cta = blockIdx.x;
  const uint32_t sbase = (uint32_t)__cvta_generic_to_shared(sm);
  const int g = lane >> 2, r = lane & 3;
  TS(0, 0);
  if (cta >= 128) {
    pack_role(idx, sbase, cta - 128);
    __syncthreads();
    if (tid < 32) flag_arrive(&g_flag[24 * 32], lane);
    TS(2, 1);
    asm volatile("barrier.cluster.arrive.relaxed.aligned; barrier.cluster.wait.aligned;" ::: "memory");
    return;
  }
  const uint32_t fullB = sbase + K1_BAR, emptyB = fullB + 24, fullE = fullB + 48, fullC = fullB + 56, fullI = fullB + 64, pxRdy = fullB + 72, fullS = fullB + 96, emptyS = fullB + 104, pkDone = fullB + 112, pkFull = fullB + 136, progG = fullB + 168;
  const int rb = cta & 7, hc = cta >> 3;
  if (__shfl_sync(0xffffffffu, tid >> 5, 0) == 12) {
    if (lane == 0) {
#pragma unroll
      for (int q = 0; q < 19; q++) if (q != 2 && q != 5) mbar_init(fullB + q * 8, q == 3 || q == 4 ? 8 : q == 12 ? 4 : q >= 14 && q < 17 ? 2 : 1);
      asm volatile("st.shared.u32 [%0],%1;" :: "r"(progG), "r"(0) : "memory");
    }
    asm volatile("fence.mbarrier_init.release.cluster; fence.proxy.async.shared::cta;" ::: "memory");
    __syncwarp();
    e_expect(fullC, 16384);
#pragma unroll
    for (int q = 0; q < 4; q++) e_tma2d(sbase + 32768 + q * 4096, &mapC, (cta & 15) * 8, q * 256, fullC);
    e_expect(fullE, 32768);
#pragma unroll
    for (int q = 0; q < 2; q++) e_tma2d(sbase + K1_B + 32768 + q * 16384, &mapE, q * 64, rb * 128, fullE);
    asm volatile("bar.arrive 2,512;" ::: "memory");
  }
  asm volatile("barrier.cluster.arrive.relaxed.aligned;" ::: "memory");
  if (tid >= 384) {
    asm volatile("setmaxnreg.dec.sync.aligned.u32 " RAUX ";");
    if (tid < 416) {
      asm volatile("barrier.cluster.wait.aligned;" ::: "memory");
      if (tid == 384) {
#pragma unroll 1
        for (int n = 0; n < 25; n++) {
          const int st = n & 1, q = QORD(n);
          if (n == IORD) {
            mbar_expect(fullI, 51200);
#pragma unroll 1
            for (int u = 0; u < 8; u++) bulk_g2s(sbase + 76800 + u * 6400, idx + ((cta >> 4) * 8 + u) * 256 * F_, 6400, fullI);
          }
          mbar_wait(emptyB + st * 8, (((n + 1) >> 1) & 1) ^ 1);
          mbar_expect(fullB + st * 8, 32768);
          asm volatile("cp.async.bulk.tensor.2d.shared::cluster.global.mbarrier::complete_tx::bytes.multicast::cluster [%0],[%1,{%2,%3}],[%4],%5;"
                       :: "r"(sbase + K1_B + st * 32768 + (cta & 1) * 16384), "l"(&mapW), "r"(hc * 32), "r"(q * 512 + (cta & 1) * 256),
                          "r"(fullB + st * 8), "h"((unsigned short)3) : "memory");
          if (n == 0) for (int u = 1; u < WPF; u++) bulk_pf(w1 + QORD(u) * 262144 + cta * 2048, 4096);
          if (WPF && n + WPF < 25) bulk_pf(w1 + QORD(n + WPF) * 262144 + cta * 2048, 4096);
        }
      }
    } else if (tid < 448) {
      ((float4*)g_acc)[cta * 32 + lane] = make_float4(0.f, 0.f, 0.f, 0.f);
      asm volatile("bar.sync 2,512;" ::: "memory");
      __syncwarp();
      if (tid == 416) {
        int pub = 0;
#pragma unroll 1
        for (int n = 0; n < 50; n++) {
          const int quad = QORD(n >> 1), mt = n & 1, v0 = rb * 128 + mt * 64;
          const uint32_t stg = sbase + K1_STG;
          const uint64_t pol = n < 2 * NEF ? POL_EF : POL_N;
          if (pub < 3) {
            uint32_t ok = 1;
            if (pub == 0 || n == 49) mbar_wait(pkDone + pub * 8, 0);
            else asm volatile("{.reg .pred p; mbarrier.test_wait.parity.shared::cta.b64 p,[%1],0; selp.u32 %0,1,0,p;}" : "=r"(ok) : "r"(pkDone + pub * 8) : "memory");
            if (ok) {
              asm volatile("cp.async.bulk.wait_group 0;" ::: "memory");
              asm volatile("red.release.gpu.global.add.u32 [%0],1;" :: "l"(&g_flag[((cta >> 4) * 3 + pub) * 32]) : "memory");
              pub++;
              if (n == 49) { n--; continue; }
            }
          }
          mbar_wait(fullS, n & 1);
          asm volatile("fence.proxy.async.shared::cta;" ::: "memory");
          if (quad < 18) {
            asm volatile("cp.async.bulk.tensor.4d.global.shared::cta.bulk_group.L2::cache_hint [%0,{%1,%2,%3,%4}],[%5],%6;"
                         :: "l"(&mapL), "r"((quad & 1) * 32), "r"(v0), "r"(quad >> 1), "r"(hc * 4), "r"(stg), "l"(pol) : "memory");
          } else {
#pragma unroll 1
            for (int hh = 0; hh < 2; hh++) {
              const int pq = quad * 2 + hh;
              if (pq < 45) asm volatile("cp.async.bulk.tensor.4d.global.shared::cta.bulk_group.L2::cache_hint [%0,{%1,%2,%3,%4}],[%5],%6;"
                         :: "l"(&mapS), "r"(0), "r"(v0 >> 2), "r"(pq - 36), "r"(hc * 4), "r"(stg + hh * 8192), "l"(pol) : "memory");
              else asm volatile("cp.async.bulk.tensor.3d.global.shared::cta.bulk_group.L2::cache_hint [%0,{%1,%2,%3}],[%4],%5;"
                         :: "l"(&mapT), "r"(v0 * 2), "r"((pq - 45) * 2), "r"(hc * 4), "r"(stg + hh * 8192), "l"(pol) : "memory");
            }
          }
          asm volatile("cp.async.bulk.commit_group;" ::: "memory");
          asm volatile("cp.async.bulk.wait_group.read 0;" ::: "memory");
          mbar_arrive(emptyS);
        }
        asm volatile("cp.async.bulk.wait_group 0;" ::: "memory");
        asm volatile("fence.proxy.async.global;" ::: "memory");
        asm volatile("red.release.gpu.global.add.u32 [%0],1;" :: "l"(&g_flag[24 * 32]) : "memory");
        flag_wait(&g_flag[24 * 32], 132);
        asm volatile("fence.proxy.async.global;" ::: "memory");
        const char* base = (const char*)g_scr;
        const int c = cta >> 1, half = cta & 1, ch = (c + (c >> 4) * 5) & 15;
        bulk_pf(base + (PS_OFF + c * NC * 2000) * 16u + half * 16000, 16000);
        if (PREW & 2) bulk_pf(base + (PL_OFF + c * NC * 8000) * 16u + half * 64000, 64000);
        bulk_pf(base + (PT_OFF + c * 10 * 1024) * 16u + half * 8192, 8192);
        mbar_expect(fullE, 18432);
        bulk_g2s(sbase + K1_B, base + (I0_OFF + half * 2048 + ch * 128) * 16u, 2048, fullE);
        bulk_g2s(sbase + K1_B + 2048, base + (IX_OFF + half * IXH + ch * 512) * 16u, 8192, fullE);
        bulk_g2s(sbase + K1_B + 10240, base + (IX_OFF + half * IXH + 8192 + ch * 512) * 16u, 8192, fullE);
        mbar_wait(fullE, 1);
      }
    } else {
      const int pw = (tid >> 5) & 1, rg = (cta >> 4) * 8 + ((cta & 15) >> 1), hf = cta & 1;
      const int* ip = idx + (rg * 256 + hf * 8) * F_;
      asm volatile("bar.sync 2,512;" ::: "memory");
      const uint32_t buf = sbase + K1_BAR + 256 + pw * 3200, bar = pkFull + pw * 8;
      const unsigned* fl = &g_flag[(cta >> 4) * 96];
      int batch = 0, rel = pw ? 3 : 0;
#pragma unroll 1
      for (int n = 1 + pw; n < 16; n += 2) {
        if (lane == 0) { mbar_expect(bar, 3200); bulk_g2s(buf, ip + n * 16 * F_, 3200, bar); if (n + 2 < 16) bulk_pf(ip + (n + 2) * 16 * F_, 3200); }
        uint32_t ok; int it = 0;
        do {
          if (rel < batch) {
            unsigned v; asm volatile("ld.relaxed.gpu.global.u32 %0,[%1];" : "=r"(v) : "l"(fl + rel * 32) : "memory");
            if (__all_sync(0xffffffffu, v >= 16)) { flag_wait(fl + rel * 32, 16); __syncwarp(); mbar_arrive_lane0(pxRdy + rel * 8); rel++; }
          }
          asm volatile("{.reg .pred p; mbarrier.test_wait.parity.shared::cta.b64 p,[%1],%2; selp.u32 %0,1,0,p;}" : "=r"(ok) : "r"(bar), "r"(((n - 1) >> 1) & 1) : "memory");
          ok = __all_sync(0xffffffffu, ok);
          if (!ok) __nanosleep(100);
        } while (!ok && ++it < (1 << 20));
        auto ld = [&](uint32_t ad) { uint32_t v; asm volatile("ld.shared.u32 %0,[%1];" : "=r"(v) : "r"(ad)); return v; };
        const uint32_t p0 = buf + ((lane >> 3) & 1) * 400 + ((lane >> 4) * 8 + (lane & 7)) * 4;
        auto wd = [&](int t, int h) { return pk3(ld(p0 + t * 800 + h * 192), ld(p0 + t * 800 + h * 192 + 64), ld(p0 + t * 800 + h * 192 + 128)); };
        uint4* dst = g_scr + PX_OFF + (rg * 16 + n) * 136;
        ((unsigned short*)(dst + 128))[lane * 2 + hf] = ld(buf + g * 400 + 384 + r * 4);
#pragma unroll
        for (int q = 0; q < 2; q++) dst[(hf * 2 + q) * 32 + lane] = make_uint4(wd(2 * q, 0), wd(2 * q, 1), wd(2 * q + 1, 0), wd(2 * q + 1, 1));
        __syncwarp();
        if (n <= 2 || n == 5 || n == 6 || n >= 14) { mbar_arrive_lane0(pkDone + batch * 8); batch++; }
      }
      for (; rel < 3; rel++) { flag_wait(fl + rel * 32, 16); __syncwarp(); mbar_arrive_lane0(pxRdy + rel * 8); }
      if (PXW && lane == 0) {
        mbar_wait(pxRdy + 16, 0);
        asm volatile("fence.proxy.async.global;" ::: "memory");
        const char* src = (const char*)(g_scr + PX_OFF + ((cta >> 4) * 8 + ((cta >> 1) & 3) * 2 + pw) * 16 * 136);
        int ph = pw;
#pragma unroll 1
        for (int n = PXW0; n < 16; n++) {
          uint32_t cur; int it = 0;
          do { asm volatile("ld.volatile.shared.u32 %0,[%1];" : "=r"(cur) : "r"(progG)); if (cur + PXW < n) __nanosleep(400); } while (cur + PXW < n && ++it < (1 << 16));
          if (cur + 1 >= n) continue;
          mbar_expect(bar, 2176); bulk_g2s(buf, src + n * 2176, 2176, bar);
          mbar_wait(bar, ph); ph ^= 1;
        }
      }
    }
    return;
  }
  if (tid >= 256) {
    asm volatile("setmaxnreg.inc.sync.aligned.u32 " RPRO ";");
    const int w = (tid >> 5) & 3;
    const int srow = w * 16 + (lane & 7) + ((lane >> 3) & 1) * 8, sc = lane >> 4;
    uint32_t a[2][8][4];
    asm volatile("bar.sync 2,512;" ::: "memory");
    mbar_wait_fast(fullE, 0);
#pragma unroll
    for (int mt = 0; mt < 2; mt++)
#pragma unroll
      for (int ks = 0; ks < 8; ks++)
        asm volatile("ldmatrix.sync.aligned.m8n8.x4.shared.b16 {%0,%1,%2,%3},[%4];"
                     : "=r"(a[mt][ks][0]), "=r"(a[mt][ks][1]), "=r"(a[mt][ks][2]), "=r"(a[mt][ks][3])
                     : "r"(sbase + K1_B + 32768 + (ks >> 2) * 16384 + (mt * 64 + srow) * 128 + ((((ks & 3) * 2 + sc) ^ (lane & 7)) * 16)) : "memory");
    asm volatile("barrier.cluster.wait.aligned;" ::: "memory");
    arrive_both(emptyB + 8, lane);
    const uint32_t baseL = sc * 4096 + srow * 64 + ((srow >> 1) & 3) * 16, baseS = sc * 2048 + ((srow * 32) ^ (((srow >> 2) & 7) * 16)), baseT = sc * 2048 + srow * 16;
    const uint64_t desc0 = (uint64_t)(((sbase + K1_B) & 0x3FFFF) >> 4) | ((uint64_t)(8192 >> 4) << 16) | ((uint64_t)(512 >> 4) << 32) | (2ull << 62);
#pragma unroll 1
    for (int qn = 0; qn < 25; qn++) {
      const int quad = QORD(qn), st = qn & 1;
      const bool isL = quad < 18;
      PT(qn * 16);
      mbar_wait_fast(fullB + st * 8, (qn >> 1) & 1);
#pragma unroll
      for (int mt = 0; mt < 2; mt++) {
        float d[64];
        PT(qn * 16 + mt * 4 + 1);
        asm volatile("wgmma.fence.sync.aligned;" ::: "memory");
#pragma unroll
        for (int ks = 0; ks < 8; ks++) wgmma_p(d, a[mt][ks], desc0 + st * 2048 + ks * 64, ks);
        asm volatile("wgmma.commit_group.sync.aligned;" ::: "memory");
        mbar_wait_fast(emptyS, mt ^ 1);
        PT(qn * 16 + mt * 4 + 2);
        asm volatile("wgmma.wait_group.sync.aligned 0;" ::: "memory");
#pragma unroll
        for (int q = 0; q < 16; q++) asm volatile("" : "+f"(d[q * 4]), "+f"(d[q * 4 + 1]), "+f"(d[q * 4 + 2]), "+f"(d[q * 4 + 3]) :: "memory");
        PT(qn * 16 + mt * 4 + 3);
        if (mt) arrive_both(emptyB + st * 8, qn < 23 ? lane : 9);
        if (quad == 24) {
#pragma unroll
          for (int cq = 0; cq < 4; cq++) {
            const uint32_t bw = __ldg((const uint32_t*)(b1 + hc * 32 + cq * 8) + r);
#pragma unroll
            for (int e = 0; e < 4; e++) d[48 + cq * 4 + e] += (e & 1) ? bf_hi(bw) : bf_lo(bw);
          }
        }
#pragma unroll
        for (int h = 0; h < 2; h++) {
          const bool isS = quad * 2 + h < 45;
          const uint32_t base = (isL ? baseL ^ (h * 32) : (isS ? baseS : baseT) ^ (h * 8192)), xj = isS ? 16 : 1024, xc = isL ? 8192 : 4096;
#pragma unroll
          for (int e4 = 0; e4 < 4; e4++) {
            const float* e = d + h * 32 + e4 * 8;
            asm volatile("stmatrix.sync.aligned.m8n8.x4.shared.b16 [%0],{%1,%2,%3,%4};"
                         :: "r"(sbase + K1_STG + (base ^ ((e4 >> 1) * xj) ^ ((e4 & 1) * xc))),
                            "r"(pack_bf2(e[0], e[1])), "r"(pack_bf2(e[2], e[3])), "r"(pack_bf2(e[4], e[5])), "r"(pack_bf2(e[6], e[7])) : "memory");
          }
        }
        __syncwarp();
        mbar_arrive_lane0(fullS);
        if (!mt) PT(qn * 16 + 4);
      }
      PT(qn * 16 + 8);
    }
    return;
  }
  const int slice = cta & 15;
  const int range = (cta >> 4) * 8 + __shfl_sync(0xffffffffu, tid >> 5, 0);
  uint4 iv[4], trow[4]; uint32_t ix;
  uint2 wrow[10];
#pragma unroll
  for (int q = 0; q < 10; q++) asm volatile("ld.global.nc.v2.u32 {%0,%1},[%2];" : "=r"(wrow[q].x), "=r"(wrow[q].y) : "l"((const uint2*)wp + min(tid + q * 256, 2499)));
  asm volatile("bar.sync 2,512;" ::: "memory");
  uint32_t me = 0, mw = 0;
#pragma unroll
  for (int q = 0; q < 10; q++) {
    mw = __vmaxu2(__vmaxu2(wrow[q].x & 0x7fff7fffu, wrow[q].y & 0x7fff7fffu), mw);
    const int e = min(tid + q * 256, 2499), row = e / 25;
    asm volatile("st.shared.v2.u32 [%0],{%1,%2};" :: "r"(sbase + (e + row) * 8), "r"(wrow[q].x), "r"(wrow[q].y) : "memory");
    if (e - row * 25 == 24) asm volatile("st.shared.v2.u32 [%0],{%1,%2};" :: "r"(sbase + (e + row) * 8 + 8), "r"(wrow[q].x), "r"(wrow[q].y) : "memory");
  }
  mbar_wait_fast(fullC, 0);
#pragma unroll
  for (int q = 0; q < 4; q++) { trow[q] = lds128(sbase + 32768 + (tid + q * 256) * 16); me = absmax4(trow[q], me); }
  me = __reduce_max_sync(0xffffffffu, max(me & 0xffff, me >> 16));
  mw = __reduce_max_sync(0xffffffffu, max(mw & 0xffff, mw >> 16));
  uint32_t* sred = (uint32_t*)((char*)sm + 128000);
  if (lane == 0) sred[tid >> 5] = me | mw << 16;
  TS(3, 0);
  asm volatile("setmaxnreg.inc.sync.aligned.u32 " RPNN ";");
  asm volatile("bar.sync 1,256;" ::: "memory");
  { uint32_t m = 0;
#pragma unroll
    for (int q = 0; q < 8; q++) m = __vmaxu2(m, sred[q]);
    m = __shfl_sync(0xffffffffu, m, 0);
    me = m & 0xffff; mw = m >> 16; }
  const float se = pow2_scale(me, 3), sW = pow2_scale(mw, -2);
  TS(3, 1);
  auto put_rows = [&](int q, bool on) {
    const uint4 t = trow[q];
    const uint4 hv = make_uint4(pack_h2(bf_lo(t.x) * se, bf_hi(t.x) * se), pack_h2(bf_lo(t.y) * se, bf_hi(t.y) * se),
                                pack_h2(bf_lo(t.z) * se, bf_hi(t.z) * se), pack_h2(bf_lo(t.w) * se, bf_hi(t.w) * se));
    if (on)
#pragma unroll
      for (int s = 0; s < 8; s++) sts128(sbase + (tid + q * 256) * 128 + ((s + lane) & 7) * 16, hv);
  };
#pragma unroll 1
  for (int it = 0; it < 3; it++) {
    const int hu = ((tid >> 5) * 3 + it) * 4, code = hu_code(min(hu + (lane >> 3), HU_N - 1)), ok = code >> 4, on = code & 15;
    uint32_t x[4], y[4];
    asm volatile("ldmatrix.sync.aligned.m8n8.x4.shared.b16 {%0,%1,%2,%3},[%4];" : "=r"(x[0]), "=r"(x[1]), "=r"(x[2]), "=r"(x[3])
                 : "r"(sbase + (on * 8 + (lane & (on == 12 ? 3 : 7))) * 208 + ok * 16) : "memory");
    asm volatile("ldmatrix.sync.aligned.m8n8.x4.trans.shared.b16 {%0,%1,%2,%3},[%4];" : "=r"(y[0]), "=r"(y[1]), "=r"(y[2]), "=r"(y[3])
                 : "r"(sbase + (ok * 8 + (lane & (ok == 12 ? 3 : 7))) * 208 + on * 16) : "memory");
    const uint32_t lo = __ballot_sync(0xffffffffu, ok > on), dg = __ballot_sync(0xffffffffu, ok >= on);
#pragma unroll
    for (int q = 0; q < 4; q++) {
      const float m0 = (lo >> (8 * q)) & 1 ? 0.f : sW, m1 = (dg >> (8 * q)) & 1 ? 0.f : sW;
      asm volatile("st.shared.u32 [%0],%1;" :: "r"(sbase + K1_W + (hu + q) * 128 + lane * 4),
                   "r"(pack_h2(fmaf(bf_lo(x[q]), m0, bf_lo(y[q]) * m1), fmaf(bf_hi(x[q]), m0, bf_hi(y[q]) * m1))) : "memory");
    }
  }
  put_rows(1, true); put_rows(2, tid < 88);
  TS(3, 2);
  asm volatile("fence.proxy.async.shared::cta;" ::: "memory");
  asm volatile("bar.sync 1,256;" ::: "memory");
  put_rows(0, true);
  uint32_t bf[HU_N - 2 * G_U];
#pragma unroll
  for (int q = 0; q < HU_N - 2 * G_U; q++) asm volatile("ld.shared.u32 %0,[%1];" : "=r"(bf[q]) : "r"(sbase + K1_W + (2 * G_U + q) * 128 + lane * 4));
  const float unscale = __uint_as_float(0x7f000000u - __float_as_uint(se)), unscale2 = __uint_as_float(0x7f000000u - __float_as_uint(sW));
  TS(3, 3);
  const int px = range * 16 * 136;
  mbar_wait_fast(fullI, 0);
  {
    const uint32_t ib = sbase + 76800 + (tid >> 5) * 6400, p0 = ib + ((lane >> 3) & 1) * 400 + ((lane >> 4) * 8 + (lane & 7)) * 4;
    auto ld = [&](uint32_t ad) { uint32_t v; asm volatile("ld.shared.u32 %0,[%1];" : "=r"(v) : "r"(ad)); return v; };
    auto wd = [&](int t, int h) { return pk3(ld(p0 + t * 800 + h * 192), ld(p0 + t * 800 + h * 192 + 64), ld(p0 + t * 800 + h * 192 + 128)); };
#pragma unroll
    for (int q = 0; q < 4; q++) {
      iv[q] = make_uint4(wd(2 * q, 0), wd(2 * q, 1), wd(2 * q + 1, 0), wd(2 * q + 1, 1));
    }
    ix = ld(ib + g * 400 + 384 + r * 4) | ld(ib + (8 + g) * 400 + 384 + r * 4) << 16;
  }
  asm volatile("bar.sync 1,256;" ::: "memory");
  put_rows(2, tid >= 88); put_rows(3, tid + 768 < V_);
  asm volatile("bar.sync 1,256;" ::: "memory");
  TS(0, 1);
  uint32_t lc; asm volatile("add.u32 %0,%1,%2;" : "=r"(lc) : "r"((lane & 7) * 16), "r"(never));
  const uint64_t wdesc = (uint64_t)(((sbase + K1_W) & 0x3FFFF) >> 4) | ((uint64_t)(128 >> 4) << 16) | ((uint64_t)(256 >> 4) << 32);
  uint32_t a[2][6][4], d[2][26], ex[4] = {}, s[4] = {};
  float red[4] = {0.f, 0.f, 0.f, 0.f};
  auto ldsm = [&](uint32_t* o, uint32_t sh, uint32_t dep = 0) {
    asm volatile("ldmatrix.sync.aligned.m8n8.x4.trans.shared.b16 {%0,%1,%2,%3},[%4];"
                 : "=r"(o[0]), "=r"(o[1]), "=r"(o[2]), "=r"(o[3]) : "r"(sbase + ((sh & 0x1ff80) | (lc | (dep & never)))));
  };
  auto gather = [&](int t, int hf) {
    const int x = t & 1;
    const uint4 v = iv[(t >> 1) & 3];
#pragma unroll
    for (int kb = 3 * hf; kb < 3 * hf + 3; kb++) {
      const uint32_t ww = x ? (kb < 3 ? v.z : v.w) : (kb < 3 ? v.x : v.y);
      ldsm(a[x][kb], kb % 3 == 0 ? ww : kb % 3 == 1 ? ww >> 10 : __funnelshift_l(ww, ww, 12));
    }
  };
  auto issue = [&](int x) {
    asm volatile("wgmma.fence.sync.aligned;" ::: "memory");
#pragma unroll
    for (int kb = 0; kb < 6; kb++) {
      if (kb < G_K0) wgmma_h<G_N0 * 8>(d[x] + G_O0 * 2, a[x][kb], wdesc + kb * G_N0 * 16, kb);
      if (kb < G_K1) wgmma_h<G_N1 * 8>(d[x] + G_O1 * 2, a[x][kb], wdesc + (G_U1 + kb * G_N1) * 16, kb);
      if (kb < G_K2) wgmma_h<32>(d[x] + G_O2 * 2, a[x][kb], wdesc + (G_U2 + kb * G_N2) * 16, kb);
    }
    asm volatile("wgmma.commit_group.sync.aligned;" ::: "memory");
  };
  auto hmma_part = [&](int t) {
    constexpr FragIdx FI = make_fi();
    const int x = t & 1;
#pragma unroll
    for (int o = 0; o < 13; o++) {
      if (oct_wg(o)) asm volatile("" : "+r"(d[x][o * 2]), "+r"(d[x][o * 2 + 1]) :: "memory"); else d[x][o * 2] = d[x][o * 2 + 1] = 0;
    }
#pragma unroll
    for (int kb = 0; kb < 6; kb++)
#pragma unroll
      for (int o = 2 * kb + 1; o < 13; o++)
        if (!unit_wg(kb, o)) mma16816h(d[x] + o * 2, a[x][kb], bf[FI.v[2 * kb][o]], bf[FI.v[2 * kb + 1][o]]);
#pragma unroll
    for (int q = 0; q < 6; q++) if (!unit_wg(q, 2 * q)) mma1688h(d[x] + q * 4, a[x][q][0], a[x][q][1], bf[FI.v[2 * q][2 * q]]);
    mma1688h(d[x] + 24, r < 2 ? ex[t & 3] : 0u, r < 2 ? 0u : ex[t & 3], bf[FI.v[12][12]]);
  };
  auto dot_part = [&](int t, int hf) {
    const int x = t & 1;
    if (hf == 0) {
      const uint32_t pe = hfma2(r < 2 ? d[x][24] : d[x][25], ex[t & 3], 0u);
      s[0] = r < 2 ? pe : 0u; s[1] = r < 2 ? 0u : pe; s[2] = s[3] = 0;
    }
#pragma unroll
    for (int q = 3 * hf; q < 3 * hf + 3; q++)
#pragma unroll
      for (int e = 0; e < 4; e++) s[e] = hfma2(d[x][q * 4 + e], a[x][q][e], s[e]);
  };
  float* outp = g_partP + slice * B_ + range * 256;
  float k0 = 0.f, k1 = 0.f, x0 = 0.f, x1 = 0.f;
  auto red_stage = [&](int st, int grp) {
    const bool u16 = lane & 16, u8 = lane & 8;
    if (st == 0) {
      k0 = u16 ? red[2] : red[0]; x0 = __shfl_xor_sync(0xffffffffu, u16 ? red[0] : red[2], 16);
      k1 = u16 ? red[3] : red[1]; x1 = __shfl_xor_sync(0xffffffffu, u16 ? red[1] : red[3], 16);
      red[0] = red[1] = red[2] = red[3] = 0.f;
    }
    if (st == 1) { const float p0 = k0 + x0, p1 = k1 + x1; k0 = u8 ? p1 : p0; x0 = __shfl_xor_sync(0xffffffffu, u8 ? p0 : p1, 8); }
    if (st == 2) { k0 += x0; x0 = __shfl_xor_sync(0xffffffffu, k0, 4); }
    if (st == 3 && !(lane & 4)) outp[grp * 16 + r * 4 + ((lane >> 3) & 1) * 2 + (lane >> 4)] = (k0 + x0) * unscale * unscale * unscale2;
  };
  auto group = [&](bool first, int prv, int cur, int nxt) {
    const int pn = PX_OFF + px + nxt * 136 + lane;
#pragma unroll
    for (int t = 0; t < 8; t++) {
      issue((t & 1) ^ 1);
      SCHED_FENCE(never, t * 8);
      if (!first) {
        if (t == 0) { iv[3] = ldtex(tex, PX_OFF + px + cur * 136 + lane + 96); iv[0] = ldtex(tex, pn); }
        if (t == 2) iv[1] = ldtex(tex, pn + 32);
        if (t < 4) red_stage(t, prv);
      } else if (t == 4) {
        TS(4, 2);
        mbar_wait_fast(pxRdy, 0);
        TS(4, 3);
        iv[0] = ldtex(tex, pn); iv[1] = ldtex(tex, pn + 32);
      }
      if (t == 4) { ix = ldtex(texX, (px + nxt * 136 + 128) * 4 + lane).x; iv[2] = ldtex(tex, pn + 64); }
      dot_part(t, 0);
      SCHED_FENCE(never, t * 8 + 1);
      if (t == 3) ldsm(ex, ix >> 9);
      if (t == 7) ldsm(ex, ix << 7);
      gather(t + 2, 0);
      dot_part(t, 1);
      SCHED_FENCE(never, t * 8 + 4);
      gather(t + 2, 1);
      asm volatile("wgmma.wait_group.sync.aligned 0;" ::: "memory");
      if (FM & 1) SCHED_FENCE(never, t * 8 + 2);
      asm volatile("" : "+r"(d[(t & 1) ^ 1][0]) :: "memory");
      mma1688f(red, hadd2(s[0], s[2]), hadd2(s[1], s[3]), (g | (d[(t & 1) ^ 1][0] & never)) == t ? 0x3c003c00u : 0u);
      hmma_part(t + 1);
      if (FM & 2) SCHED_FENCE(never, t * 8 + 3);
    }
  };
  gather(0, 0); gather(0, 1); issue(0); ldsm(ex, ix << 7); gather(1, 0); gather(1, 1);
  asm volatile("wgmma.wait_group.sync.aligned 0;" ::: "memory");
  hmma_part(0);
  group(true, 0, 0, 1);
  TS(4, 1);
#pragma unroll 1
  for (int n = 1; n < NGRP; n++) {
    if (n == TRIG) asm volatile("griddepcontrol.launch_dependents;");
    if ((n & 11) == 2) mbar_wait_fast(pxRdy + 8 + (n & 4) * 2, 0);
    if (PXW) asm volatile("st.volatile.shared.u32 [%0],%1;" :: "r"(progG), "r"(n) : "memory");
    group(false, n - 1, n, min(n + 1, 15));
  }
#pragma unroll
  for (int st = 0; st < 4; st++) red_stage(st, 15);
  TS(0, 2);
  asm volatile("barrier.cluster.wait.aligned;" ::: "memory");
  asm volatile("barrier.cluster.arrive.relaxed.aligned; barrier.cluster.wait.aligned;" ::: "memory");
}

constexpr int SM_U = 130048, SM_BAR = 128000, SM_J = SM_U + 98304, DEEP_SMEM = SM_J + 4096;

__global__ void __cluster_dims__(2, 1, 1) __launch_bounds__(TH + 128, 1)
k_deep(cudaTextureObject_t tex, const __nv_bfloat16* __restrict__ w2, const __nv_bfloat16* __restrict__ b2,
       __nv_bfloat16* __restrict__ out, int never) {
  extern __shared__ __align__(1024) uint4 sm[];
  constexpr int PF = DPF, DEPTH = DDEPTH, NW = TH / 32;
  static_assert(YD == 4 && PF == 4, "");
  const int tid = threadIdx.x;
  const int c = blockIdx.x >> 1, half = blockIdx.x & 1;
  const uint32_t sbase = (uint32_t)__cvta_generic_to_shared(sm);
  const uint32_t fullL = sbase + SM_BAR, fullU = fullL + 8, emptyL = fullL + 16, emptyU = fullL + 24, barJ = fullL + 32;
  TS(1, 0);
  if (tid == 0) {
    mbar_init(fullL, 1); mbar_init(fullU, 1); mbar_init(emptyL, 2 * NW); mbar_init(emptyU, 2 * NW); mbar_init(barJ, 1);
    asm volatile("fence.mbarrier_init.release.cluster;" ::: "memory");
  }
  __syncwarp();
  const int wrp = __shfl_sync(0xffffffffu, tid >> 5, 0);
  const char* base = (const char*)g_scr;
  uint32_t oL = (PL_OFF + c * NC * 8000) * 16u + half * 64000, oS = (PS_OFF + c * NC * 2000) * 16u + half * 16000;
  asm volatile("barrier.cluster.arrive.relaxed.aligned;" ::: "memory");
  flag_wait(&g_flag[24 * 32], 132);
  asm volatile("barrier.cluster.wait.aligned;" ::: "memory");
  if (wrp == NW) {
    asm volatile("fence.proxy.async.global;" ::: "memory");
    e_expect(fullU, 96000);
#pragma unroll
    for (int m = 0; m < 3; m++) e_mc(sbase + SM_U + m * 32032 + half * 16000, base + oS, 16000, fullU, m == 2 ? POL_EF : POL_N);
    e_expect(fullL, 128000);
    if (!STAG) e_mc(sbase + half * 64000, base + oL, 64000, fullL, POL_EF);
  }
  TS(5, 1);
  if (wrp >= NW) {
    asm volatile("setmaxnreg.dec.sync.aligned.u32 24;");
    if (wrp == NW) {
      uint32_t oT = (PT_OFF + c * 10 * 1024) * 16u + half * 8192;
      const uint32_t junk = sbase + SM_J, oW = (IX_OFF + half * IXH + ((c + (c >> 4) * 5) & 15) * 512) * 16u;
      auto warm = [&](uint32_t off) {
        asm volatile(ELECT "mbarrier.expect_tx.relaxed.cta.shared::cta.b64 [%0],%1;}" :: "r"(barJ), "r"(8192) : "memory");
        e_g2s(junk, base + off, 4096, barJ); e_g2s(junk, base + off + 4096, 4096, barJ);
      };
      uint32_t t0 = clock();
      if (!PREW) warm(oW);
      if (STAG) { if (STAG == 1) mbar_wait(fullU, 0); else sleep_until(t0, STAG); e_mc(sbase + half * 64000, base + oL, 64000, fullL, POL_EF); }
      warm(oT);
      if (!(PREW & 4)) warm(oW + 131072);
#pragma unroll 1
      for (int k = 0; k + 1 < NC; k++) {
        oL += 128000; oS += 32000; oT += 16384;
        mbar_wait(fullL, k & 1);
        t0 = clock();
        e_pf(base + oS, 16000);
        warm((IX_OFF + half * IXH + (k + 2) * 8192 + ((c + (c >> 4) * (2 * k + 1)) & (k + 2 < NC ? 15 : 3)) * 512) * 16u);
        mbar_wait(emptyU, k & 1);
        e_expect(fullU, 96000);
#pragma unroll 1
        for (int q = 0; q < 8; q++) {
          sleep_until(t0, q * PACE);
          e_pf(base + oL + q * 8000, 8000);
          if (q >= 2) e_mc(sbase + SM_U + ((q - 2) >> 1) * 32032 + half * 16000 + (q & 1) * 8000, base + oS + (q & 1) * 8000, 8000, fullU, q >= 6 ? POL_EF : POL_N);
        }
        warm(oT);
        e_expect(fullL, 128000);
        sleep_until(t0, RSV_T);
        unsigned long long now, slot = 0;
        asm volatile("mov.u64 %0,%globaltimer;" : "=l"(now));
        if ((tid & 31) == 0) { atomicMax(&g_slot, now + RSV_L); slot = atomicAdd(&g_slot, (unsigned long long)RSV); }
        slot = __shfl_sync(0xffffffffu, slot, 0);
        mbar_wait(emptyL, k & 1);
        for (int it = 0; it < 4000; it++) { asm volatile("mov.u64 %0,%globaltimer;" : "=l"(now)); if (now >= slot) break; }
        e_mc(sbase + half * 64000, base + oL, 64000, fullL, POL_EF);
      }
      mbar_wait(fullL, (NC - 1) & 1);
      mbar_wait(emptyU, (NC - 1) & 1);
      mbar_arrive_lane0(fullU);
      warm(oT + 16384);
      mbar_arrive_lane0(barJ); mbar_wait(barJ, 0);
    } else if (tid >= TH + 96) {
      if (tid == TH + 96) sts128(barJ + 32, *(const uint4*)(w2 + c * 8));
      asm volatile("bar.arrive 3,%0;" :: "n"(TH + 32) : "memory");
      asm volatile("griddepcontrol.wait;" ::: "memory");
      const int b = half * 8192 + c * 128 + (tid & 31) * 4;
      const float bias = __bfloat162float(b2[0]);
      float4 s = make_float4(bias, bias, bias, bias);
#pragma unroll 2
      for (int k = 0; k < 16; k++) { const float4 v = __ldcg((const float4*)(g_partP + k * B_ + b)); s.x += v.x; s.y += v.y; s.z += v.z; s.w += v.w; }
      asm volatile("red.global.add.v4.f32 [%0],{%1,%2,%3,%4};" :: "l"(g_acc + b), "f"(s.x), "f"(s.y), "f"(s.z), "f"(s.w) : "memory");
      asm volatile("bar.arrive 1,%0;" :: "n"(TH + 32) : "memory");
    }
    return;
  }
  asm volatile("setmaxnreg.inc.sync.aligned.u32 240;");
  const int lane = tid & 31;
  const int tbase = PT_OFF + c * 10 * 1024;
  const int ibase = IX_OFF + half * IXH + tid;
  const uint32_t lc = (tid & 7) << 4;
  uint4 acc[NS], wq[PF], x[DEPTH], y[YD], ye;
  uint32_t sw[NS] = {};
  auto sget = [&](int s) { return (s & 3) == 3 ? __byte_perm(__byte_perm(sw[s - 3], sw[s - 2], 0x0073), sw[s - 1], 0x0710) : sw[s]; };
  auto sa0 = [&](uint32_t v) { return sbase + SM_U + (((v << 5) & 0x1ffe0) | ((lc >> 2) & 16)); };
  uint32_t c1 = 0;
  auto sa1 = [&](uint32_t v) { return sbase + SM_U + (((v >> 7) & 0x1ffe0) | c1); };
  {
    uint4 i0[8];
#pragma unroll
    for (int q = 0; q < 8; q++) i0[q] = ldtex(tex, I0_OFF + (half * 8 + q) * TH + tid);
#pragma unroll
    for (int i = 0; i < PF; i++) if (!WQL) wq[i] = ldtex(tex, ibase + i * TH);
    auto wd = [&](int k) { return (k & 3) == 0 ? i0[k >> 2].x : (k & 3) == 1 ? i0[k >> 2].y : (k & 3) == 2 ? i0[k >> 2].z : i0[k >> 2].w; };
    TS(5, 2);
    mbar_wait_fast(fullU, 0);
#pragma unroll
    for (int i = 0; i < PF; i++) if (WQL) wq[i] = ldtex(tex, ibase + i * TH);
    TS(1, 1);
#pragma unroll
    for (int s = 0; s < NS; s++) acc[s] = add4(lds128(sbase + SM_U + (wd(s) & 0x1fff0)), lds128(sbase + SM_U + ((wd(s) >> 13) & 0x1fff0)));
    arrive_both(emptyU, lane);
    asm volatile("bar.sync 3,%0;" :: "n"(TH + 32) : "memory");
    TS(5, 3);
  }
#pragma unroll 1
  for (int k = 0; k < NC; k++) {
    const int ti = ibase + k * 8192;
    const int tb = tbase + k * 1024;
    const bool more = k + 1 < NC;
    TR(k * 4);
    if (CBAR & 1) asm volatile("bar.sync 4,%0;" :: "n"(TH) : "memory");
    mbar_wait_fast(fullL, k & 1);
    TR(k * 4 + 2);
    uint4 w, cc; uint32_t yc, yn;
    constexpr int TL = NS * 8, TT = TL + NS * 2;
#pragma unroll
    for (int t = 0; t < TT + DEPTH; t += 2) {
      if (t == TL + DEPTH && !more) break;
      if (t >= DEPTH) {
        const int u = t - DEPTH;
        uint4 p = add4(x[u % DEPTH], x[(u + 1) % DEPTH]);
        if (u < TL) {
          const int s = u >> 3, j = u & 7;
          if (j == 0) {
            cc = s >= YD ? add4(y[s % YD], p) : p;
            if (s + YD < NS) y[s % YD] = ldtex(tex, tb | (yc & 1023));
          } else cc = add4(cc, p);
          if (j == 6) acc[s] = add4(acc[s], cc);
        } else {
          const int s = (u - TL) >> 1;
          acc[s] = add4(acc[s], p);
        }
      }
      if ((CBAR & 4) && t == TL / 2) asm volatile("bar.sync 4,%0;" :: "n"(TH) : "memory");
      if ((CBAR & 8) && t == TL - 40) asm volatile("bar.sync 4,%0;" :: "n"(TH) : "memory");
      if (DEPTH == 8 && (t & 7) == 2) yc = yn;
      if (t < TL) {
        const int s = t >> 3, j = t & 7;
        if (j == 0) {
          if (ye_of(s - YD) >= 0) acc[ye_of(s - YD) & 3] = add4(acc[ye_of(s - YD) & 3], ye);
          w = wq[s % PF];
          if (!EARLY || s < NS - 4) wq[s % PF] = ldtex(tex, ti + (s + PF) * TH);
          else {
            if (s == NS - 4) { wq[0] = ldtex(tex, ti + NS * TH); ye = ldtex(tex, ti + (NS + 3) * TH); }
            if (s == NS - 3) { wq[1] = ldtex(tex, ti + (NS + 1) * TH); y[0] = ldtex(tex, ti + (NS + 2) * TH); }
            if (s == NS - 2) wq[2] = y[0];
            if (s == NS - 1) wq[3] = ye;
          }
          yn = __funnelshift_l(w.z, w.z, 5); if (DEPTH < 8) yc = yn;
          if ((s & 3) != 3) asm volatile("add.u32 %0,%1,%2;" : "=r"(sw[s]) : "r"(w.w), "r"(never));
          if (ye_of(s) >= 0) ye = ldtex(tex, tb | w.w);
        }
#pragma unroll
        for (int jj = j; jj < j + 2; jj++) {
          const uint32_t ww = jj < 3 ? w.x : jj < 6 ? w.y : w.z;
          const uint32_t sh = jj % 3 == 0 ? ww : jj % 3 == 1 ? ww >> 10 : __funnelshift_l(ww, ww, 12);
          x[(t + jj - j) % DEPTH] = lds128(sbase + ((sh & 0x1ff80) | lc) + jj * 16 - 128);
        }
      } else if (t < TT) {
        const int s = (t - TL) >> 1;
        if (s == 0) { asm volatile("add.u32 %0,%1,%2;" : "=r"(c1) : "r"((~lc >> 2) & 16), "r"(never)); arrive_both(emptyL, more ? lane : 9); TR(k * 4 + 3); if (CBAR & 2) asm volatile("bar.sync 4,%0;" :: "n"(TH) : "memory"); mbar_wait_fast(fullU, (k + 1) & 1); }
        const uint32_t sv = sget(s);
        x[t % DEPTH] = lds128(sa0(sv));
        x[(t + 1) % DEPTH] = lds128(sa1(sv));
      } else if (t == TT) arrive_both(emptyU, lane);
      if ((t & (FENCE_N - 1)) == FENCE_N - 2) SCHED_FENCE(never, t);
    }
  }
  TS(1, 2);
  const uint4 w2v = lds128(barJ + 32);
  const uint32_t cell = sbase + SM_U + tid * 16;
  const int t9 = tbase + 9 * 1024;
  uint4 za[4], i9 = wq[0];
  auto fetch = [&](int q) {
    y[0] = ldtex(tex, t9 | i9.x); y[1] = ldtex(tex, t9 | i9.y); y[2] = ldtex(tex, t9 | i9.z); y[3] = ldtex(tex, t9 | i9.w);
    if (q) {
      i9 = ldtex(tex, ibase + NC * 8192 + min(q + 1, 7) * TH);
      const uint32_t ca = cell + (q > 6 ? 0 : q - 1) * 16384;
#pragma unroll
      for (int s = 0; s < 4; s++) za[s] = lds128(ca + s * 4096);
    }
  };
  fetch(0);
  i9 = wq[1];
#pragma unroll
  for (int s = 0; s < 4; s++) za[s] = acc[s];
#pragma unroll
  for (int s = 0; s < 24; s++) sts128(cell + s * 4096, acc[4 + s]);
  float hw[8];
  {
    const uint32_t ww[4] = {w2v.x, w2v.y, w2v.z, w2v.w};
#pragma unroll
    for (int k = 0; k < 8; k++) hw[k] = 0.5f * ((k & 1) ? bf_hi(ww[k >> 1]) : bf_lo(ww[k >> 1]));
  }
  float* outp = g_acc + half * 8192 + tid;
#pragma unroll 1
  for (int q = 0; q < NS / 4; q++) {
    uint4 z[4];
#pragma unroll
    for (int s = 0; s < 4; s++) z[s] = add4(za[s], y[s]);
    if (q == 1) {
#pragma unroll
      for (int s = 0; s < 4; s++) sts128(cell + s * 4096, acc[28 + s]);
    }
    if (q < 7) fetch(q + 1);
    SCHED_FENCE(never, 999);
#pragma unroll
    for (int s = 0; s < 4; s++) {
      const uint32_t a[4] = {z[s].x, z[s].y, z[s].z, z[s].w};
      float r0 = 0.f;
#pragma unroll
      for (int k = 0; k < 8; k++) {
        const float v = (k & 1) ? bf_hi(a[k >> 1]) : bf_lo(a[k >> 1]);
        const float u = v * fmaf(v * v, 0.7978845608028654f * 0.044715f, 0.7978845608028654f);
        float th; asm("tanh.approx.f32 %0,%1;" : "=f"(th) : "f"(u));
        r0 = fmaf(fmaf(v, th, v), hw[k], r0);
      }
      asm volatile("red.global.add.f32 [%0],%1;" :: "l"(outp + s * TH), "f"(r0) : "memory");
    }
    outp += 4 * TH;
  }
  TS(1, 3);
  asm volatile("bar.sync 1,%0;" :: "n"(TH + 32) : "memory");
  if (tid == 0) {
    __threadfence();
    const unsigned old = atomicInc(&g_done[half * 32], 63);
    asm volatile("st.shared.u32 [%0],%1;" :: "r"(barJ + 8), "r"(old) : "memory");
  }
  asm volatile("bar.sync 2,%0;" :: "n"(TH) : "memory");
  uint32_t old; asm volatile("ld.shared.u32 %0,[%1];" : "=r"(old) : "r"(barJ + 8));
  if (old == 63) {
    if (half == 0 && tid == 25) g_slot = 0;
    if (half == 0 && tid < 25) g_flag[tid * 32] = 0;
    __threadfence();
    float4 v[8];
#pragma unroll
    for (int q = 0; q < 8; q++) v[q] = __ldcg((const float4*)(g_acc + half * 8192) + q * TH + tid);
#pragma unroll
    for (int q = 0; q < 8; q++) ((uint2*)(out + half * 8192))[q * TH + tid] = make_uint2(pack_bf2(v[q].x, v[q].y), pack_bf2(v[q].z, v[q].w));
    TS(6, 2);
  }
}

}

extern "C" void kernel_launch(void* const* d_in, const int* in_sizes, int n_in, void* d_out, int out_size) {
  const int* idx = (const int*)d_in[0];
  const __nv_bfloat16* table = (const __nv_bfloat16*)d_in[1];
  const __nv_bfloat16* wp = (const __nv_bfloat16*)d_in[2];
  const __nv_bfloat16* w1 = (const __nv_bfloat16*)d_in[3];
  const __nv_bfloat16* b1 = (const __nv_bfloat16*)d_in[4];
  const __nv_bfloat16* w2 = (const __nv_bfloat16*)d_in[5];
  const __nv_bfloat16* b2 = (const __nv_bfloat16*)d_in[6];
  static cudaTextureObject_t texScr = 0, texG = 0;
  static CUtensorMap mapW, mapL, mapS, mapT, mapE, mapC;
  static const void *c_tab = nullptr, *c_w1 = nullptr;
  if (c_tab != table || c_w1 != w1) {
    c_tab = table; c_w1 = w1;
    char* scr = nullptr; cudaGetSymbolAddress((void**)&scr, g_scr);
    auto mk_tex = [](const void* p, size_t bytes, cudaChannelFormatDesc d) {
      cudaResourceDesc rd = {}; rd.resType = cudaResourceTypeLinear; rd.res.linear.devPtr = (void*)p; rd.res.linear.desc = d; rd.res.linear.sizeInBytes = bytes;
      cudaTextureDesc td = {}; td.readMode = cudaReadModeElementType;
      cudaTextureObject_t t = 0; cudaCreateTextureObject(&t, &rd, &td, nullptr); return t;
    };
    if (!texScr) {
      texScr = mk_tex(scr, (size_t)SCR_N * 16, cudaCreateChannelDesc<uint4>());
      texG = mk_tex(scr + (size_t)PX_OFF * 16, (size_t)(SCR_N - PX_OFF) * 16, cudaCreateChannelDesc<unsigned>());
    }
    typedef CUresult (*EncFn)(CUtensorMap*, CUtensorMapDataType, cuuint32_t, void*, const cuuint64_t*, const cuuint64_t*, const cuuint32_t*,
                              const cuuint32_t*, CUtensorMapInterleave, CUtensorMapSwizzle, CUtensorMapL2promotion, CUtensorMapFloatOOBfill);
    EncFn enc = nullptr; cudaDriverEntryPointQueryResult qr;
    cudaGetDriverEntryPoint("cuTensorMapEncodeTiled", (void**)&enc, cudaEnableDefault, &qr);
    const cuuint32_t ones[4] = {1, 1, 1, 1};
    auto mk = [&](CUtensorMap* m, CUtensorMapDataType dt, int rank, void* p, const cuuint64_t* dim, const cuuint64_t* str, const cuuint32_t* box, CUtensorMapSwizzle sw) {
      enc(m, dt, rank, p, dim, str, box, ones, CU_TENSOR_MAP_INTERLEAVE_NONE, sw, CU_TENSOR_MAP_L2_PROMOTION_NONE, CU_TENSOR_MAP_FLOAT_OOB_FILL_NONE);
    };
    { cuuint64_t dim[2] = {H_, F_ * D_}, str[1] = {H_ * 2}; cuuint32_t box[2] = {32, 256};
      mk(&mapW, CU_TENSOR_MAP_DATA_TYPE_BFLOAT16, 2, (void*)w1, dim, str, box, CU_TENSOR_MAP_SWIZZLE_64B); }
    { cuuint64_t dim[4] = {64, V_, NC, 64}, str[3] = {128, 128000, 128000 * NC}; cuuint32_t box[4] = {32, 64, 1, 4};
      mk(&mapL, CU_TENSOR_MAP_DATA_TYPE_BFLOAT16, 4, scr + (size_t)PL_OFF * 16, dim, str, box, CU_TENSOR_MAP_SWIZZLE_64B); }
    { cuuint64_t dim[4] = {64, V_ / 4, NC, 64}, str[3] = {128, 32000, 32000 * NC}; cuuint32_t box[4] = {64, 16, 1, 4};
      mk(&mapS, CU_TENSOR_MAP_DATA_TYPE_BFLOAT16, 4, scr + (size_t)PS_OFF * 16, dim, str, box, CU_TENSOR_MAP_SWIZZLE_128B); }
    { cuuint64_t dim[3] = {2048, 10, 64}, str[2] = {16384, 163840}; cuuint32_t box[3] = {128, 2, 4};
      mk(&mapT, CU_TENSOR_MAP_DATA_TYPE_UINT64, 3, scr + (size_t)PT_OFF * 16, dim, str, box, CU_TENSOR_MAP_SWIZZLE_NONE); }
    { cuuint64_t dim[2] = {D_, V_}, str[1] = {D_ * 2}; cuuint32_t box[2] = {64, 128};
      mk(&mapE, CU_TENSOR_MAP_DATA_TYPE_BFLOAT16, 2, (void*)table, dim, str, box, CU_TENSOR_MAP_SWIZZLE_128B);
      cuuint32_t box2[2] = {8, 256};
      mk(&mapC, CU_TENSOR_MAP_DATA_TYPE_BFLOAT16, 2, (void*)table, dim, str, box2, CU_TENSOR_MAP_SWIZZLE_NONE); }
    cudaFuncSetAttribute(k_deep, cudaFuncAttributeMaxDynamicSharedMemorySize, DEEP_SMEM);
    cudaFuncSetAttribute(k_tens, cudaFuncAttributeMaxDynamicSharedMemorySize, K1_SMEM);
  }
  k_tens<<<132, 512, K1_SMEM, cudaStreamPerThread>>>(mapW, mapL, mapS, mapT, mapE, mapC, texScr, texG, idx, table, wp, w1, b1, 0);
  cudaLaunchAttribute at[1];
  at[0].id = cudaLaunchAttributeProgrammaticStreamSerialization; at[0].val.programmaticStreamSerializationAllowed = 1;
  cudaLaunchConfig_t cfg = {};
  cfg.stream = cudaStreamPerThread; cfg.attrs = at;
  cfg.gridDim = 128; cfg.blockDim = TH + 128; cfg.dynamicSmemBytes = DEEP_SMEM; cfg.numAttrs = PDL & 1;
  cudaLaunchKernelEx(&cfg, k_deep, texScr, w2, b2, (__nv_bfloat16*)d_out, 0);

}
```

```cpp
#include <cuda_runtime.h>
#include <cuda_bf16.h>
#include <cuda_fp16.h>
#include <stdint.h>
#include <cuda.h>

namespace {

constexpr int B_ = 16384, F_ = 100, D_ = 128, V_ = 1000, H_ = 512;
constexpr int NC = 9;
constexpr int PT_OFF = 0;
constexpr int PL_OFF = 64 * 10 * 1024;
constexpr int PS_OFF = PL_OFF + 64 * NC * 8000;
constexpr int IXH = NC * 8192 + 2048;
constexpr int IX_OFF = PS_OFF + 64 * NC * 2000;
constexpr int I0_OFF = IX_OFF + 2 * IXH;
constexpr int PX_OFF = I0_OFF + 4096;
constexpr int SCR_N = PX_OFF + 64 * 16 * 136;
static_assert(PX_OFF % 32 == 0, "");

__device__ __align__(1024) uint4 g_scr[SCR_N];
__device__ float g_acc[B_];
__device__ unsigned long long g_slot;
__device__ unsigned g_done[64];
__device__ float g_partP[16 * B_];
__device__ unsigned g_flag[25 * 32];

#define TS(k, i)
#define TR(slot)
#define PT(slot)

constexpr uint64_t POL_EF = 0x12F0000000000000ull, POL_N = 0x1000000000000000ull;
__device__ __forceinline__ uint32_t addbf2(uint32_t a, uint32_t b) { uint32_t r; asm("add.rn.bf16x2 %0,%1,%2;" : "=r"(r) : "r"(a), "r"(b)); return r; }
__device__ __forceinline__ uint4 add4(const uint4& a, const uint4& b) { return make_uint4(addbf2(a.x, b.x), addbf2(a.y, b.y), addbf2(a.z, b.z), addbf2(a.w, b.w)); }
__device__ __forceinline__ void acc4(uint4& a, const uint4& b, int never) {
  asm("{.reg .pred p; setp.eq.s32 p,%8,0;\n"
      "@p add.rn.bf16x2 %0,%0,%4; @p add.rn.bf16x2 %1,%1,%5; @p add.rn.bf16x2 %2,%2,%6; @p add.rn.bf16x2 %3,%3,%7;}"
      : "+r"(a.x), "+r"(a.y), "+r"(a.z), "+r"(a.w) : "r"(b.x), "r"(b.y), "r"(b.z), "r"(b.w), "r"(never));
}
__device__ __forceinline__ uint4 ldtex(cudaTextureObject_t t, int i) {
  uint4 v; asm volatile("tex.1d.v4.u32.s32 {%0,%1,%2,%3},[%4,{%5}];" : "=r"(v.x), "=r"(v.y), "=r"(v.z), "=r"(v.w) : "l"(t), "r"(i)); return v;
}
__device__ __forceinline__ uint4 lds128(uint32_t a) {
  uint4 v; asm volatile("ld.volatile.shared.v4.u32 {%0,%1,%2,%3},[%4];" : "=r"(v.x), "=r"(v.y), "=r"(v.z), "=r"(v.w) : "r"(a)); return v;
}
__device__ __forceinline__ void sts128(uint32_t a, const uint4& v) {
  asm volatile("st.shared.v4.u32 [%0],{%1,%2,%3,%4};" :: "r"(a), "r"(v.x), "r"(v.y), "r"(v.z), "r"(v.w) : "memory");
}
__device__ __forceinline__ void mbar_init(uint32_t bar, int n) { asm volatile("mbarrier.init.shared::cta.b64 [%0],%1;" :: "r"(bar), "r"(n) : "memory"); }
__device__ __forceinline__ void mbar_wait(uint32_t bar, uint32_t parity) {
  uint32_t ok; int it = 0;
  do { asm volatile("{.reg .pred p; mbarrier.try_wait.parity.shared::cta.b64 p,[%1],%2; selp.u32 %0,1,0,p;}" : "=r"(ok) : "r"(bar), "r"(parity) : "memory"); } while (!ok && ++it < (1 << 19));
}
__device__ __forceinline__ void mbar_expect(uint32_t bar, uint32_t bytes) { asm volatile("mbarrier.arrive.expect_tx.shared::cta.b64 _,[%0],%1;" :: "r"(bar), "r"(bytes) : "memory"); }
__device__ __forceinline__ void bulk_g2s(uint32_t dst, const void* src, uint32_t bytes, uint32_t bar) {
  asm volatile("cp.async.bulk.shared::cluster.global.mbarrier::complete_tx::bytes [%0],[%1],%2,[%3];" :: "r"(dst), "l"(src), "r"(bytes), "r"(bar) : "memory");
}
__device__ __forceinline__ void bulk_pf(const void* src, uint32_t bytes) { asm volatile("cp.async.bulk.prefetch.L2.global [%0],%1;" :: "l"(src), "r"(bytes) : "memory"); }
#define NOMMA 0
#define NGRP 16
#define PDL 1
#define FIN_S 128
#define WRED 4
#define RSV 24
#define RSV_T 7200
#define RSV_L 550
#define TRIG 14
#define PREW 5
#define PXW 2
#define PXW0 5
#define WQL 1
#define EARLY 1
#define CBAR 0
#define X_SAMEK 0
#define X_SAMEW 0
#define FM 0
#define SWP 1
#define HOLD 1
#define MCW 1
#define TW 1
#define PP0 10
#define PT0 10000
#define PDT 0
#define RPNN "160"
#define RAUX "32"
#define RPRO "160"
#define PARK 0
#define NLOOK 128
#define NEF 25
#define ORD 0
#define WFENCE 0
#define SPLIT 1
#define IORD 1
#define IPF 3
#define IPACE 4500
#define WPF 1
#define QV 3
#define QORD(n) ((n) < 23 ? (n) + 2 : (n) - 23)
#define DYD 4
#define DPF 4
#define DDEPTH 4
#define FENCE_N 4
#define INPL 0
#define STAG 1
#define PACE 800
#define PM4 "pmevent 1; pmevent 2; pmevent 3; pmevent 4;"
#define PMFILL "pmevent 1;"
#define SCHED_FENCE(never, k) asm volatile("{.reg .pred p; setp.ne.u32 p,%0,%1; @p bra.uni SKIP_%=;" PMFILL "SKIP_%=: }" :: "r"(never), "r"(0x7fff0000 + (k)) : "memory")

__global__ void k_prod_naive(const __nv_bfloat16* __restrict__ table, const __nv_bfloat16* __restrict__ w1) {
  __shared__ float t[8][D_];
  int f = blockIdx.y, v0 = blockIdx.x * 8, h = threadIdx.x;
  for (int i = h; i < 8 * D_; i += 512) t[i / D_][i % D_] = __bfloat162float(table[v0 * D_ + i]);
  __syncthreads();
  float s[8] = {0, 0, 0, 0, 0, 0, 0, 0};
  for (int d = 0; d < D_; d++) { float w = __bfloat162float(w1[(size_t)(f * D_ + d) * H_ + h]);
#pragma unroll
    for (int k = 0; k < 8; k++) s[k] += t[k][d] * w; }
  __nv_bfloat16* P = (__nv_bfloat16*)g_scr;
  int c = h >> 3;
  for (int k = 0; k < 8; k++) {
    size_t e = f < 72 ? (size_t)PL_OFF + ((size_t)(c * NC + (f >> 3)) * 1000 + v0 + k) * 8 + (f & 7)
             : f < 90 ? (size_t)PS_OFF + ((size_t)(c * NC + ((f - 72) >> 1)) * 1000 + v0 + k) * 2 + (f & 1)
                      : (size_t)PT_OFF + (size_t)(c * 10 + f - 90) * 1024 + v0 + k;
    P[e * 8 + (h & 7)] = __float2bfloat16(s[k]);
  }
}
__global__ void k_pnn_naive(const int* __restrict__ idx, const __nv_bfloat16* __restrict__ table, const __nv_bfloat16* __restrict__ wp) {
  __shared__ float e[F_][33];
  int b = blockIdx.x, d0 = blockIdx.y * 32, tid = threadIdx.x;
  for (int i = tid; i < F_ * 32; i += 128) e[i >> 5][i & 31] = __bfloat162float(table[idx[b * F_ + (i >> 5)] * D_ + d0 + (i & 31)]);
  __syncthreads();
  float s = 0; int d = tid & 31;
  for (int i = tid >> 5; i < F_; i += 4) { float u = 0; for (int j = 0; j < F_; j++) u += __bfloat162float(wp[i * F_ + j]) * e[j][d]; s += u * e[i][d]; }
  for (int o = 16; o; o >>= 1) s += __shfl_xor_sync(~0u, s, o);
  if (d == 0) g_partP[(blockIdx.y * 4 + (tid >> 5)) * B_ + b] = s;
}
__device__ __forceinline__ void mbar_wait_fast(uint32_t bar, uint32_t parity) {
  asm volatile("{.reg .pred p; .reg .u32 n;\n"
               "mbarrier.try_wait.parity.shared::cta.b64 p,[%0],%1;\n"
               "@p bra DONE_%=;\n"
               "mov.u32 n,0;\n"
               "LOOP_%=: mbarrier.try_wait.parity.shared::cta.b64 p,[%0],%1;\n"
               "add.u32 n,n,1; setp.gt.or.u32 p,n,400000,p;\n"
               "@!p bra LOOP_%=;\n"
               "DONE_%=: }" :: "r"(bar), "r"(parity) : "memory");
}
__device__ __forceinline__ void sleep_until(uint32_t t0, uint32_t dt) { while ((uint32_t)clock() - t0 < dt) __nanosleep(40); }
__device__ __forceinline__ uint32_t s_mask(uint32_t v, int q) { return (1u << ((v + 3 - q) & 3)) | (16u << ((v + 3 + q) & 3)); }
__device__ __forceinline__ uint32_t s_cell(uint32_t v, int q, uint32_t m) {
  const int t = __ffs(~m) - 1;
  const int cp = t == 8 ? q >> 1 : ((t & 4 ? t - q : t + q) - v) & 3;
  return cp * 1001 + v;
}
__device__ __forceinline__ uint32_t pk3(uint32_t a, uint32_t b, uint32_t c) {
  const uint32_t w = c + (a << 12) + (b << 22); return __funnelshift_l(w, w, 27);
}
constexpr int TH = 256, NS = 8192 / TH, YD = DYD;
__host__ __device__ constexpr int ye_of(int s) { return s == 3 ? 0 : s == 11 ? 1 : s == 19 ? 2 : s == 23 ? 3 : -1; }
template <int N> __device__ __forceinline__ void wgmma_h(uint32_t* d, const uint32_t* a, uint64_t desc, int acc);
template <> __device__ __forceinline__ void wgmma_h<64>(uint32_t* d, const uint32_t* a, uint64_t desc, int acc) {
  asm volatile("{.reg .pred p; setp.ne.s32 p,%21,0;\n"
    "wgmma.mma_async.sync.aligned.m64n64k16.f16.f16.f16 {%0,%1,%2,%3,%4,%5,%6,%7,%8,%9,%10,%11,%12,%13,%14,%15},{%16,%17,%18,%19},%20,p,1,1,0;}"
    : "+r"(d[0]),"+r"(d[1]),"+r"(d[2]),"+r"(d[3]),"+r"(d[4]),"+r"(d[5]),"+r"(d[6]),"+r"(d[7]),"+r"(d[8]),"+r"(d[9]),"+r"(d[10]),"+r"(d[11]),"+r"(d[12]),"+r"(d[13]),"+r"(d[14]),"+r"(d[15])
    : "r"(a[0]), "r"(a[1]), "r"(a[2]), "r"(a[3]), "l"(desc), "r"(acc));
}
template <> __device__ __forceinline__ void wgmma_h<56>(uint32_t* d, const uint32_t* a, uint64_t desc, int acc) {
  asm volatile("{.reg .pred p; setp.ne.s32 p,%19,0;\n"
    "wgmma.mma_async.sync.aligned.m64n56k16.f16.f16.f16 {%0,%1,%2,%3,%4,%5,%6,%7,%8,%9,%10,%11,%12,%13},{%14,%15,%16,%17},%18,p,1,1,0;}"
    : "+r"(d[0]),"+r"(d[1]),"+r"(d[2]),"+r"(d[3]),"+r"(d[4]),"+r"(d[5]),"+r"(d[6]),"+r"(d[7]),"+r"(d[8]),"+r"(d[9]),"+r"(d[10]),"+r"(d[11]),"+r"(d[12]),"+r"(d[13])
    : "r"(a[0]), "r"(a[1]), "r"(a[2]), "r"(a[3]), "l"(desc), "r"(acc));
}
template <> __device__ __forceinline__ void wgmma_h<48>(uint32_t* d, const uint32_t* a, uint64_t desc, int acc) {
  asm volatile("{.reg .pred p; setp.ne.s32 p,%17,0;\n"
    "wgmma.mma_async.sync.aligned.m64n48k16.f16.f16.f16 {%0,%1,%2,%3,%4,%5,%6,%7,%8,%9,%10,%11},{%12,%13,%14,%15},%16,p,1,1,0;}"
    : "+r"(d[0]),"+r"(d[1]),"+r"(d[2]),"+r"(d[3]),"+r"(d[4]),"+r"(d[5]),"+r"(d[6]),"+r"(d[7]),"+r"(d[8]),"+r"(d[9]),"+r"(d[10]),"+r"(d[11])
    : "r"(a[0]), "r"(a[1]), "r"(a[2]), "r"(a[3]), "l"(desc), "r"(acc));
}
template <> __device__ __forceinline__ void wgmma_h<40>(uint32_t* d, const uint32_t* a, uint64_t desc, int acc) {
  asm volatile("{.reg .pred p; setp.ne.s32 p,%15,0;\n"
    "wgmma.mma_async.sync.aligned.m64n40k16.f16.f16.f16 {%0,%1,%2,%3,%4,%5,%6,%7,%8,%9},{%10,%11,%12,%13},%14,p,1,1,0;}"
    : "+r"(d[0]),"+r"(d[1]),"+r"(d[2]),"+r"(d[3]),"+r"(d[4]),"+r"(d[5]),"+r"(d[6]),"+r"(d[7]),"+r"(d[8]),"+r"(d[9])
    : "r"(a[0]), "r"(a[1]), "r"(a[2]), "r"(a[3]), "l"(desc), "r"(acc));
}
template <> __device__ __forceinline__ void wgmma_h<32>(uint32_t* d, const uint32_t* a, uint64_t desc, int acc) {
  asm volatile("{.reg .pred p; setp.ne.s32 p,%13,0;\n"
    "wgmma.mma_async.sync.aligned.m64n32k16.f16.f16.f16 {%0,%1,%2,%3,%4,%5,%6,%7},{%8,%9,%10,%11},%12,p,1,1,0;}"
    : "+r"(d[0]),"+r"(d[1]),"+r"(d[2]),"+r"(d[3]),"+r"(d[4]),"+r"(d[5]),"+r"(d[6]),"+r"(d[7])
    : "r"(a[0]), "r"(a[1]), "r"(a[2]), "r"(a[3]), "l"(desc), "r"(acc));
}
__device__ __forceinline__ void wgmma_p(float* d, const uint32_t* a, uint64_t desc, int acc) {
  asm volatile("{.reg .pred p; setp.ne.s32 p,%69,0;\n"
    "wgmma.mma_async.sync.aligned.m64n128k16.f32.bf16.bf16 {%0,%1,%2,%3,%4,%5,%6,%7,%8,%9,%10,%11,%12,%13,%14,%15,%16,%17,%18,%19,%20,%21,%22,%23,%24,%25,%26,%27,%28,%29,%30,%31,%32,%33,%34,%35,%36,%37,%38,%39,%40,%41,%42,%43,%44,%45,%46,%47,%48,%49,%50,%51,%52,%53,%54,%55,%56,%57,%58,%59,%60,%61,%62,%63},{%64,%65,%66,%67},%68,p,1,1,1;}"
    : "+f"(d[0]),"+f"(d[1]),"+f"(d[2]),"+f"(d[3]),"+f"(d[4]),"+f"(d[5]),"+f"(d[6]),"+f"(d[7]),"+f"(d[8]),"+f"(d[9]),"+f"(d[10]),"+f"(d[11]),"+f"(d[12]),"+f"(d[13]),"+f"(d[14]),"+f"(d[15]),"+f"(d[16]),"+f"(d[17]),"+f"(d[18]),"+f"(d[19]),"+f"(d[20]),"+f"(d[21]),"+f"(d[22]),"+f"(d[23]),"+f"(d[24]),"+f"(d[25]),"+f"(d[26]),"+f"(d[27]),"+f"(d[28]),"+f"(d[29]),"+f"(d[30]),"+f"(d[31]),"+f"(d[32]),"+f"(d[33]),"+f"(d[34]),"+f"(d[35]),"+f"(d[36]),"+f"(d[37]),"+f"(d[38]),"+f"(d[39]),"+f"(d[40]),"+f"(d[41]),"+f"(d[42]),"+f"(d[43]),"+f"(d[44]),"+f"(d[45]),"+f"(d[46]),"+f"(d[47]),"+f"(d[48]),"+f"(d[49]),"+f"(d[50]),"+f"(d[51]),"+f"(d[52]),"+f"(d[53]),"+f"(d[54]),"+f"(d[55]),"+f"(d[56]),"+f"(d[57]),"+f"(d[58]),"+f"(d[59]),"+f"(d[60]),"+f"(d[61]),"+f"(d[62]),"+f"(d[63])
    : "r"(a[0]), "r"(a[1]), "r"(a[2]), "r"(a[3]), "l"(desc), "r"(acc));
}

__device__ __forceinline__ void mma16816h(uint32_t* c, const uint32_t* a, uint32_t b0, uint32_t b1) {
  asm("mma.sync.aligned.m16n8k16.row.col.f16.f16.f16.f16 {%0,%1},{%2,%3,%4,%5},{%6,%7},{%0,%1};"
      : "+r"(c[0]), "+r"(c[1]) : "r"(a[0]), "r"(a[1]), "r"(a[2]), "r"(a[3]), "r"(b0), "r"(b1));
}
__device__ __forceinline__ void mma1688h(uint32_t* c, uint32_t a0, uint32_t a1, uint32_t b) {
  asm("mma.sync.aligned.m16n8k8.row.col.f16.f16.f16.f16 {%0,%1},{%2,%3},{%4},{%0,%1};" : "+r"(c[0]), "+r"(c[1]) : "r"(a0), "r"(a1), "r"(b));
}
__device__ __forceinline__ void mma1688f(float* c, uint32_t a0, uint32_t a1, uint32_t b) {
  asm("mma.sync.aligned.m16n8k8.row.col.f32.f16.f16.f32 {%0,%1,%2,%3},{%4,%5},{%6},{%0,%1,%2,%3};"
      : "+f"(c[0]), "+f"(c[1]), "+f"(c[2]), "+f"(c[3]) : "r"(a0), "r"(a1), "r"(b));
}
__device__ __forceinline__ uint32_t hadd2(uint32_t a, uint32_t b) { uint32_t r; asm("add.rn.f16x2 %0,%1,%2;" : "=r"(r) : "r"(a), "r"(b)); return r; }
__device__ __forceinline__ uint32_t hfma2(uint32_t a, uint32_t b, uint32_t c) { uint32_t r; asm("fma.rn.f16x2 %0,%1,%2,%3;" : "=r"(r) : "r"(a), "r"(b), "r"(c)); return r; }
__device__ __forceinline__ uint32_t pack_bf2(float lo, float hi) { uint32_t r; asm("cvt.rn.bf16x2.f32 %0,%1,%2;" : "=r"(r) : "f"(hi), "f"(lo)); return r; }
__device__ __forceinline__ uint32_t pack_h2(float lo, float hi) { uint32_t r; asm("cvt.rn.f16x2.f32 %0,%1,%2;" : "=r"(r) : "f"(hi), "f"(lo)); return r; }
__device__ __forceinline__ float bf_lo(uint32_t w) { return __uint_as_float(w << 16); }
__device__ __forceinline__ float bf_hi(uint32_t w) { return __uint_as_float(w & 0xffff0000u); }
__device__ __forceinline__ uint32_t absmax4(const uint4& v, uint32_t m) {
  return __vmaxu2(__vmaxu2(__vmaxu2(v.x & 0x7fff7fffu, v.y & 0x7fff7fffu), __vmaxu2(v.z & 0x7fff7fffu, v.w & 0x7fff7fffu)), m);
}
__device__ __forceinline__ float pow2_scale(uint32_t mbits, int p) { return __uint_as_float((uint32_t)min(max(253 + p - (int)(mbits >> 7), 2), 252) << 23); }

#define PV 4
constexpr int G_O0 = 8, G_O1 = 4, G_O2 = 0, G_N0 = 5, G_N1 = 4, G_N2 = 4, G_K0 = 5, G_K1 = 3, G_K2 = 1;
__host__ __device__ constexpr bool unit_wg(int kb, int on) {
  return (on >= G_O0 && on < G_O0 + G_N0 && kb < G_K0) || (on >= G_O1 && on < G_O1 + G_N1 && kb < G_K1) || (on >= G_O2 && on < G_O2 + G_N2 && kb < G_K2);
}
__host__ __device__ constexpr bool oct_wg(int on) { return unit_wg(0, on); }
constexpr int G_U1 = G_N0 * G_K0, G_U2 = G_U1 + G_N1 * G_K1, G_U = G_U2 + G_N2 * G_K2;
constexpr int K1_B = 130048, K1_STG = K1_B + 2 * 32768, K1_W = K1_STG + 16384, K1_BAR = K1_W + 48 * 256, K1_SMEM = K1_BAR + 256 + 6400;
__host__ __device__ constexpr int frag_index(int ok, int on) {
  int n = 0;
  for (int k = 0; k < 13; k++) for (int o = k; o < 13; o++) { if (k == ok && o == on) return n; if (!unit_wg(k >> 1, o)) n++; }
  return n;
}
constexpr int HU_N = 2 * G_U + frag_index(99, 99);
static_assert(HU_N <= 96, "");
struct FragIdx { int v[13][13]; };
__host__ __device__ constexpr FragIdx make_fi() { FragIdx f = {}; for (int k = 0; k < 13; k++) for (int o = 0; o < 13; o++) f.v[k][o] = frag_index(k, o); return f; }
__host__ __device__ constexpr uint64_t frag_tab(int first) {
  uint64_t t = 0;
  for (int k = 0; k < 13; k++) for (int o = k; o < 13; o++)
    if (!unit_wg(k >> 1, o)) { const int n = frag_index(k, o) - first; if (n >= 0 && n < 8) t |= (uint64_t)(k << 4 | o) << (8 * n); }
  return t;
}
__device__ __forceinline__ int hu_code(int hu) {
  constexpr uint64_t T0 = frag_tab(0), T1 = frag_tab(8), T2 = frag_tab(16), T3 = frag_tab(24);
  const int u = hu >> 1, f = hu - 2 * G_U;
  if (f >= 0) return (int)((f < 8 ? T0 : f < 16 ? T1 : f < 24 ? T2 : T3) >> (8 * (f & 7))) & 255;
  const int u0 = u < G_U1 ? u : u < G_U2 ? u - G_U1 : u - G_U2;
  const int kb = u < G_U1 ? u0 / G_N0 : u < G_U2 ? u0 / G_N1 : u0 / 4, on = u < G_U1 ? G_O0 + u0 % G_N0 : u < G_U2 ? G_O1 + u0 % G_N1 : G_O2 + u0 % 4;
  return (2 * kb + (hu & 1)) << 4 | on;
}

__device__ __forceinline__ void flag_wait(const unsigned* f, unsigned n) {
  unsigned v; int it = 0;
  asm volatile("ld.acquire.gpu.global.u32 %0,[%1];" : "=r"(v) : "l"(f) : "memory");
  if (v < n) {
    do { __nanosleep(300); asm volatile("ld.relaxed.gpu.global.u32 %0,[%1];" : "=r"(v) : "l"(f) : "memory"); } while (v < n && ++it < (1 << 20));
    asm volatile("ld.acquire.gpu.global.u32 %0,[%1];" : "=r"(v) : "l"(f) : "memory");
  }
}
__device__ __forceinline__ void mbar_arrive(uint32_t bar) { asm volatile("mbarrier.arrive.shared::cta.b64 _,[%0];" :: "r"(bar) : "memory"); }
__device__ __forceinline__ void mbar_arrive_lane0(uint32_t bar) {
  asm volatile("{.reg .pred p; elect.sync _|p,0xffffffff; @p mbarrier.arrive.shared::cta.b64 _,[%0];}" :: "r"(bar) : "memory");
}

__device__ __forceinline__ void arrive_both(uint32_t bar, int lane) {
  asm volatile("{.reg .pred p; .reg .u32 a; setp.lt.u32 p,%1,2; mapa.shared::cluster.u32 a,%0,%1;\n"
               "@p mbarrier.arrive.shared::cluster.b64 _,[a];}" :: "r"(bar), "r"(lane) : "memory");
}
#define ELECT "{.reg .pred p; elect.sync _|p,0xffffffff; @p "
__device__ __forceinline__ void e_mc(uint32_t dst, const void* src, uint32_t bytes, uint32_t bar, uint64_t pol) {
  asm volatile(ELECT "cp.async.bulk.shared::cluster.global.mbarrier::complete_tx::bytes.multicast::cluster.L2::cache_hint [%0],[%1],%2,[%3],%4,%5;}"
               :: "r"(dst), "l"(src), "r"(bytes), "r"(bar), "h"((unsigned short)3), "l"(pol) : "memory");
}
__device__ __forceinline__ void e_g2s(uint32_t dst, const void* src, uint32_t bytes, uint32_t bar) {
  asm volatile(ELECT "cp.async.bulk.shared::cluster.global.mbarrier::complete_tx::bytes [%0],[%1],%2,[%3];}" :: "r"(dst), "l"(src), "r"(bytes), "r"(bar) : "memory");
}
__device__ __forceinline__ void e_pf(const void* src, uint32_t bytes) { asm volatile(ELECT "cp.async.bulk.prefetch.L2.global [%0],%1;}" :: "l"(src), "r"(bytes) : "memory"); }
__device__ __forceinline__ void e_expect(uint32_t bar, uint32_t bytes) { asm volatile(ELECT "mbarrier.arrive.expect_tx.shared::cta.b64 _,[%0],%1;}" :: "r"(bar), "r"(bytes) : "memory"); }
__device__ __forceinline__ void e_tma2d(uint32_t dst, const CUtensorMap* m, int x, int y, uint32_t bar) {
  asm volatile(ELECT "cp.async.bulk.tensor.2d.shared::cluster.global.mbarrier::complete_tx::bytes [%0],[%1,{%2,%3}],[%4];}" :: "r"(dst), "l"(m), "r"(x), "r"(y), "r"(bar) : "memory");
}

__device__ __forceinline__ void pack_role(const int* __restrict__ idx, uint32_t sbase, int pc) {
  constexpr int CH = 3200 + 32, BUF = 32 * 3328;
  const int tid = threadIdx.x, lane = tid & 31, warp = tid >> 5;
  const uint32_t full = sbase + 2 * BUF, empty = full + 16;
  if (tid == 0) { mbar_init(full, 1); mbar_init(full + 8, 1); mbar_init(empty, 18); mbar_init(empty + 8, 18); asm volatile("fence.proxy.async.shared::cta;" ::: "memory"); }
  __syncthreads();
  auto chunk = [&](int s) { return s * 3200 + (s >> 2) * 288; };
  auto load = [&](int n) {
    const int blk = pc * 16 + n;
    if (lane == 0) mbar_expect(full + (n & 1) * 8, 32 * 3200);
    __syncwarp();
    bulk_g2s(sbase + (n & 1) * BUF + chunk(lane), idx + ((blk >> 5) * 8192 + lane * TH + (blk & 31) * 8) * F_, 3200, full + (n & 1) * 8);
  };
  if (warp == 0) { load(0); load(1); }
  const int l = lane & 7;
  uint32_t rot[8], inc[3];
#pragma unroll
  for (int jj = 0; jj < 8; jj++) rot[jj] = ((l + jj) & 7) * 4;
#pragma unroll
  for (int q = 0; q < 3; q++) inc[q] = (l + 3 * q < 8) << 12 | (l + 3 * q + 1 < 8) << 22 | (q < 2 && l + 3 * q + 2 < 8);
  int loaded = 2;
#pragma unroll 1
  for (int task = warp; task < 288; task += 16) {
    const int n = task / 18, q = (task % 18) * 4 + (lane >> 3), sq = q / 9, k = q % 9;
    if (warp == 0 && n + 1 == loaded && loaded < 16) { mbar_wait(empty + (loaded & 1) * 8, ((loaded >> 1) - 1) & 1); load(loaded); loaded++; }
    mbar_wait(full + (n & 1) * 8, (n >> 1) & 1);
    const uint32_t buf = sbase + (n & 1) * BUF + l * 400, row = buf + chunk(sq * 4);
    auto ld = [&](uint32_t ad) { uint32_t v; asm volatile("ld.shared.u32 %0,[%1];" : "=r"(v) : "r"(ad)); return v; };
    const int blk = pc * 16 + n, half = blk >> 5, col = (blk & 31) * 8 + l;
    const int ks = k == NC - 1 ? 0 : k + 1;
    uint32_t cw[4], sv[8], m[2] = {0, 0};
    { const uint32_t a0 = row + (72 + 2 * ks + (l >> 2)) * 4;
#pragma unroll
      for (int u = 0; u < 8; u++) { sv[u] = ld((a0 ^ ((u >> 2) * 4)) + (u & 3) * 3200); m[u >> 2] |= s_mask(sv[u], l & 3) << (8 * (u & 3)); } }
#pragma unroll
    for (int h = 0; h < 2; h++) { m[h] |= __shfl_xor_sync(0xffffffffu, m[h], 1); m[h] |= __shfl_xor_sync(0xffffffffu, m[h], 2); }
#pragma unroll
    for (int u = 0; u < 4; u++) cw[u] = s_cell(sv[u], l & 3, (m[0] >> (8 * u)) & 255) | s_cell(sv[4 + u], l & 3, (m[1] >> (8 * u)) & 255) << 12;
    if (k == NC - 1) {
      auto wide = [&](uint32_t w) { return (w & 0xfff) << 5 | (w >> 12) << 18 | (l & 4 ? 1u << 4 : 1u << 17); };
      g_scr[I0_OFF + (half * 8 + sq) * TH + col] = make_uint4(wide(cw[0]), wide(cw[1]), wide(cw[2]), wide(cw[3]));
      g_scr[IX_OFF + half * IXH + NC * 8192 + sq * TH + col] = make_uint4(ld(row + 396), ld(row + 3596), ld(row + 6796), ld(row + 9996));
      cw[0] = cw[1] = cw[2] = cw[3] = 0;
    }
    const uint32_t ax = buf + chunk(min(sq + 1, 7) * 4) + (90 + k) * 4;
    const uint32_t yev = ld(buf + ((0x3210 >> (sq * 2 + (sq == 5) * 2)) & 3) * 3200 + (90 + k) * 4);
    uint4* dst = g_scr + IX_OFF + half * IXH + (k * NS + sq * 4) * TH + col;
#pragma unroll
    for (int u = 0; u < 4; u++) {
      uint32_t e[8];
#pragma unroll
      for (int jj = 0; jj < 8; jj++) e[jj] = ld(row + k * 32 + rot[jj] + u * 3200);
      dst[u * TH] = make_uint4(pk3(e[0], e[1], e[2] + inc[0]), pk3(e[3], e[4], e[5] + inc[1]), pk3(e[6], e[7], ld(ax + u * 3200) + inc[2]),
                               u < 3 ? __byte_perm(cw[u], cw[3], 0x4210 + (u << 12)) : yev);
    }
    mbar_arrive_lane0(empty + (n & 1) * 8);
  }
  (void)CH;
}

__global__ void __cluster_dims__(2, 1, 1) __launch_bounds__(512, 1)
k_tens(const __grid_constant__ CUtensorMap mapW, const __grid_constant__ CUtensorMap mapL, const __grid_constant__ CUtensorMap mapS,
       const __grid_constant__ CUtensorMap mapT, const __grid_constant__ CUtensorMap mapE, const __grid_constant__ CUtensorMap mapC, cudaTextureObject_t tex, cudaTextureObject_t texX,
       const int* __restrict__ idx, const __nv_bfloat16* __restrict__ table, const __nv_bfloat16* __restrict__ wp, const __nv_bfloat16* __restrict__ w1,
       const __nv_bfloat16* __restrict__ b1, int never) {
  extern __shared__ __align__(1024) uint4 sm[];
  const int tid = threadIdx.x, lane = tid & 31, cta = blockIdx.x;
  const uint32_t sbase = (uint32_t)__cvta_generic_to_shared(sm);
  const int g = lane >> 2, r = lane & 3;
  TS(0, 0);
  if (cta >= 128) {
    pack_role(idx, sbase, cta - 128);
    __syncthreads();
    if (tid == 0) {
      asm volatile("fence.acq_rel.gpu; griddepcontrol.launch_dependents;" ::: "memory");
      asm volatile("red.relaxed.gpu.global.add.u32 [%0],1;" :: "l"(&g_flag[24 * 32]) : "memory");
    }
    __syncwarp();
    TS(2, 1);
    asm volatile("barrier.cluster.arrive.relaxed.aligned; barrier.cluster.wait.aligned;" ::: "memory");
    return;
  }
  const uint32_t fullB = sbase + K1_BAR, emptyB = fullB + 24, fullE = fullB + 48, fullC = fullB + 56, fullI = fullB + 64, pxRdy = fullB + 72, fullS = fullB + 96, emptyS = fullB + 104, pkDone = fullB + 112, pkFull = fullB + 136, progG = fullB + 168;
  const int rb = cta & 7, hc = cta >> 3;
  if (__shfl_sync(0xffffffffu, tid >> 5, 0) == 12) {
    if (lane == 0) {
#pragma unroll
      for (int q = 0; q < 19; q++) if (q != 2 && q != 5) mbar_init(fullB + q * 8, q == 3 || q == 4 ? 8 : q == 12 ? 4 : q >= 14 && q < 17 ? 2 : 1);
      asm volatile("st.shared.u32 [%0],%1;" :: "r"(progG), "r"(0) : "memory");
    }
    asm volatile("fence.mbarrier_init.release.cluster; fence.proxy.async.shared::cta;" ::: "memory");
    __syncwarp();
    e_expect(fullC, 16384);
#pragma unroll
    for (int q = 0; q < 4; q++) e_tma2d(sbase + 32768 + q * 4096, &mapC, (cta & 15) * 8, q * 256, fullC);
    e_expect(fullE, 32768);
#pragma unroll
    for (int q = 0; q < 2; q++) e_tma2d(sbase + K1_B + 32768 + q * 16384, &mapE, q * 64, rb * 128, fullE);
    asm volatile("bar.arrive 2,512;" ::: "memory");
  }
  asm volatile("barrier.cluster.arrive.relaxed.aligned;" ::: "memory");
  if (tid >= 384) {
    asm volatile("setmaxnreg.dec.sync.aligned.u32 " RAUX ";");
    if (tid < 416) {
      asm volatile("barrier.cluster.wait.aligned;" ::: "memory");
      if (tid == 384) {
#pragma unroll 1
        for (int n = 0; n < 25; n++) {
          const int st = n & 1, q = QORD(n);
          if (n == IORD) {
            mbar_expect(fullI, 51200);
#pragma unroll 1
            for (int u = 0; u < 8; u++) bulk_g2s(sbase + 76800 + u * 6400, idx + ((cta >> 4) * 8 + u) * 256 * F_, 6400, fullI);
          }
          mbar_wait(emptyB + st * 8, (((n + 1) >> 1) & 1) ^ 1);
          mbar_expect(fullB + st * 8, 32768);
          asm volatile("cp.async.bulk.tensor.2d.shared::cluster.global.mbarrier::complete_tx::bytes.multicast::cluster [%0],[%1,{%2,%3}],[%4],%5;"
                       :: "r"(sbase + K1_B + st * 32768 + (cta & 1) * 16384), "l"(&mapW), "r"(hc * 32), "r"(q * 512 + (cta & 1) * 256),
                          "r"(fullB + st * 8), "h"((unsigned short)3) : "memory");
          if (n == 0) for (int u = 1; u < WPF; u++) bulk_pf(w1 + QORD(u) * 262144 + cta * 2048, 4096);
          if (WPF && n + WPF < 25) bulk_pf(w1 + QORD(n + WPF) * 262144 + cta * 2048, 4096);
        }
      }
    } else if (tid < 448) {
      ((float4*)g_acc)[cta * 32 + lane] = make_float4(0.f, 0.f, 0.f, 0.f);
      asm volatile("bar.sync 2,512;" ::: "memory");
      __syncwarp();
      if (tid == 416) {
        int pub = 0;
#pragma unroll 1
        for (int n = 0; n < 50; n++) {
          const int quad = QORD(n >> 1), mt = n & 1, v0 = rb * 128 + mt * 64;
          const uint32_t stg = sbase + K1_STG;
          const uint64_t pol = n < 2 * NEF ? POL_EF : POL_N;
          if (pub < 3) {
            uint32_t ok = 1;
            if (pub == 0 || n == 49) mbar_wait(pkDone + pub * 8, 0);
            else asm volatile("{.reg .pred p; mbarrier.test_wait.parity.shared::cta.b64 p,[%1],0; selp.u32 %0,1,0,p;}" : "=r"(ok) : "r"(pkDone + pub * 8) : "memory");
            if (ok) {
              asm volatile("cp.async.bulk.wait_group 0;" ::: "memory");
              asm volatile("red.release.gpu.global.add.u32 [%0],1;" :: "l"(&g_flag[((cta >> 4) * 3 + pub) * 32]) : "memory");
              pub++;
              if (n == 49) { n--; continue; }
            }
          }
          mbar_wait(fullS, n & 1);
          asm volatile("fence.proxy.async.shared::cta;" ::: "memory");
          if (quad < 18) {
            asm volatile("cp.async.bulk.tensor.4d.global.shared::cta.bulk_group.L2::cache_hint [%0,{%1,%2,%3,%4}],[%5],%6;"
                         :: "l"(&mapL), "r"((quad & 1) * 32), "r"(v0), "r"(quad >> 1), "r"(hc * 4), "r"(stg), "l"(pol) : "memory");
          } else {
#pragma unroll 1
            for (int hh = 0; hh < 2; hh++) {
              const int pq = quad * 2 + hh;
              if (pq < 45) asm volatile("cp.async.bulk.tensor.4d.global.shared::cta.bulk_group.L2::cache_hint [%0,{%1,%2,%3,%4}],[%5],%6;"
                         :: "l"(&mapS), "r"(0), "r"(v0 >> 2), "r"(pq - 36), "r"(hc * 4), "r"(stg + hh * 8192), "l"(pol) : "memory");
              else asm volatile("cp.async.bulk.tensor.3d.global.shared::cta.bulk_group.L2::cache_hint [%0,{%1,%2,%3}],[%4],%5;"
                         :: "l"(&mapT), "r"(v0 * 2), "r"((pq - 45) * 2), "r"(hc * 4), "r"(stg + hh * 8192), "l"(pol) : "memory");
            }
          }
          asm volatile("cp.async.bulk.commit_group;" ::: "memory");
          asm volatile("cp.async.bulk.wait_group.read 0;" ::: "memory");
          mbar_arrive(emptyS);
        }
        asm volatile("cp.async.bulk.wait_group 0;" ::: "memory");
        asm volatile("fence.proxy.async.global;" ::: "memory");
        asm volatile("fence.acq_rel.gpu; griddepcontrol.launch_dependents;" ::: "memory");
        asm volatile("red.relaxed.gpu.global.add.u32 [%0],1;" :: "l"(&g_flag[24 * 32]) : "memory");
        flag_wait(&g_flag[24 * 32], 132);
        asm volatile("fence.proxy.async.global;" ::: "memory");
        const char* base = (const char*)g_scr;
        const int c = cta >> 1, half = cta & 1, ch = (c + (c >> 4) * 5) & 15;
        bulk_pf(base + (PS_OFF + c * NC * 2000) * 16u + half * 16000, 16000);
        if (PREW & 2) bulk_pf(base + (PL_OFF + c * NC * 8000) * 16u + half * 64000, 64000);
        bulk_pf(base + (PT_OFF + c * 10 * 1024) * 16u + half * 8192, 8192);
        mbar_expect(fullE, 18432);
        bulk_g2s(sbase + K1_B, base + (I0_OFF + half * 2048 + ch * 128) * 16u, 2048, fullE);
        bulk_g2s(sbase + K1_B + 2048, base + (IX_OFF + half * IXH + ch * 512) * 16u, 8192, fullE);
        bulk_g2s(sbase + K1_B + 10240, base + (IX_OFF + half * IXH + 8192 + ch * 512) * 16u, 8192, fullE);
        mbar_wait(fullE, 1);
      }
    } else {
      const int pw = (tid >> 5) & 1, rg = (cta >> 4) * 8 + ((cta & 15) >> 1), hf = cta & 1;
      const int* ip = idx + (rg * 256 + hf * 8) * F_;
      asm volatile("bar.sync 2,512;" ::: "memory");
      const uint32_t buf = sbase + K1_BAR + 256 + pw * 3200, bar = pkFull + pw * 8;
      const unsigned* fl = &g_flag[(cta >> 4) * 96];
      int batch = 0, rel = pw ? 3 : 0;
#pragma unroll 1
      for (int n = 1 + pw; n < 16; n += 2) {
        if (lane == 0) { mbar_expect(bar, 3200); bulk_g2s(buf, ip + n * 16 * F_, 3200, bar); if (n + 2 < 16) bulk_pf(ip + (n + 2) * 16 * F_, 3200); }
        uint32_t ok; int it = 0;
        do {
          if (rel < batch) {
            unsigned v; asm volatile("ld.relaxed.gpu.global.u32 %0,[%1];" : "=r"(v) : "l"(fl + rel * 32) : "memory");
            if (__all_sync(0xffffffffu, v >= 16)) { flag_wait(fl + rel * 32, 16); __syncwarp(); mbar_arrive_lane0(pxRdy + rel * 8); rel++; }
          }
          asm volatile("{.reg .pred p; mbarrier.test_wait.parity.shared::cta.b64 p,[%1],%2; selp.u32 %0,1,0,p;}" : "=r"(ok) : "r"(bar), "r"(((n - 1) >> 1) & 1) : "memory");
          ok = __all_sync(0xffffffffu, ok);
          if (!ok) __nanosleep(100);
        } while (!ok && ++it < (1 << 20));
        auto ld = [&](uint32_t ad) { uint32_t v; asm volatile("ld.shared.u32 %0,[%1];" : "=r"(v) : "r"(ad)); return v; };
        const uint32_t p0 = buf + ((lane >> 3) & 1) * 400 + ((lane >> 4) * 8 + (lane & 7)) * 4;
        auto wd = [&](int t, int h) { return pk3(ld(p0 + t * 800 + h * 192), ld(p0 + t * 800 + h * 192 + 64), ld(p0 + t * 800 + h * 192 + 128)); };
        uint4* dst = g_scr + PX_OFF + (rg * 16 + n) * 136;
        ((unsigned short*)(dst + 128))[lane * 2 + hf] = ld(buf + g * 400 + 384 + r * 4);
#pragma unroll
        for (int q = 0; q < 2; q++) dst[(hf * 2 + q) * 32 + lane] = make_uint4(wd(2 * q, 0), wd(2 * q, 1), wd(2 * q + 1, 0), wd(2 * q + 1, 1));
        __syncwarp();
        if (n <= 2 || n == 5 || n == 6 || n >= 14) { mbar_arrive_lane0(pkDone + batch * 8); batch++; }
      }
      for (; rel < 3; rel++) { flag_wait(fl + rel * 32, 16); __syncwarp(); mbar_arrive_lane0(pxRdy + rel * 8); }
      if (PXW && lane == 0) {
        mbar_wait(pxRdy + 16, 0);
        asm volatile("fence.proxy.async.global;" ::: "memory");
        const char* src = (const char*)(g_scr + PX_OFF + ((cta >> 4) * 8 + ((cta >> 1) & 3) * 2 + pw) * 16 * 136);
        int ph = pw;
#pragma unroll 1
        for (int n = PXW0; n < 16; n++) {
          uint32_t cur; int it = 0;
          do { asm volatile("ld.volatile.shared.u32 %0,[%1];" : "=r"(cur) : "r"(progG)); if (cur + PXW < n) __nanosleep(400); } while (cur + PXW < n && ++it < (1 << 16));
          if (cur + 1 >= n) continue;
          mbar_expect(bar, 2176); bulk_g2s(buf, src + n * 2176, 2176, bar);
          mbar_wait(bar, ph); ph ^= 1;
        }
      }
    }
    return;
  }
  if (tid >= 256) {
    asm volatile("setmaxnreg.inc.sync.aligned.u32 " RPRO ";");
    const int w = (tid >> 5) & 3;
    const int srow = w * 16 + (lane & 7) + ((lane >> 3) & 1) * 8, sc = lane >> 4;
    uint32_t a[2][8][4];
    asm volatile("bar.sync 2,512;" ::: "memory");
    mbar_wait_fast(fullE, 0);
#pragma unroll
    for (int mt = 0; mt < 2; mt++)
#pragma unroll
      for (int ks = 0; ks < 8; ks++)
        asm volatile("ldmatrix.sync.aligned.m8n8.x4.shared.b16 {%0,%1,%2,%3},[%4];"
                     : "=r"(a[mt][ks][0]), "=r"(a[mt][ks][1]), "=r"(a[mt][ks][2]), "=r"(a[mt][ks][3])
                     : "r"(sbase + K1_B + 32768 + (ks >> 2) * 16384 + (mt * 64 + srow) * 128 + ((((ks & 3) * 2 + sc) ^ (lane & 7)) * 16)) : "memory");
    asm volatile("barrier.cluster.wait.aligned;" ::: "memory");
    arrive_both(emptyB + 8, lane);
    const uint32_t baseL = sc * 4096 + srow * 64 + ((srow >> 1) & 3) * 16, baseS = sc * 2048 + ((srow * 32) ^ (((srow >> 2) & 7) * 16)), baseT = sc * 2048 + srow * 16;
    const uint64_t desc0 = (uint64_t)(((sbase + K1_B) & 0x3FFFF) >> 4) | ((uint64_t)(8192 >> 4) << 16) | ((uint64_t)(512 >> 4) << 32) | (2ull << 62);
#pragma unroll 1
    for (int qn = 0; qn < 25; qn++) {
      const int quad = QORD(qn), st = qn & 1;
      const bool isL = quad < 18;
      PT(qn * 16);
      mbar_wait_fast(fullB + st * 8, (qn >> 1) & 1);
#pragma unroll
      for (int mt = 0; mt < 2; mt++) {
        float d[64];
        PT(qn * 16 + mt * 4 + 1);
        asm volatile("wgmma.fence.sync.aligned;" ::: "memory");
#pragma unroll
        for (int ks = 0; ks < 8; ks++) wgmma_p(d, a[mt][ks], desc0 + st * 2048 + ks * 64, ks);
        asm volatile("wgmma.commit_group.sync.aligned;" ::: "memory");
        mbar_wait_fast(emptyS, mt ^ 1);
        PT(qn * 16 + mt * 4 + 2);
        asm volatile("wgmma.wait_group.sync.aligned 0;" ::: "memory");
#pragma unroll
        for (int q = 0; q < 16; q++) asm volatile("" : "+f"(d[q * 4]), "+f"(d[q * 4 + 1]), "+f"(d[q * 4 + 2]), "+f"(d[q * 4 + 3]) :: "memory");
        PT(qn * 16 + mt * 4 + 3);
        if (mt) arrive_both(emptyB + st * 8, qn < 23 ? lane : 9);
        if (quad == 24) {
#pragma unroll
          for (int cq = 0; cq < 4; cq++) {
            const uint32_t bw = __ldg((const uint32_t*)(b1 + hc * 32 + cq * 8) + r);
#pragma unroll
            for (int e = 0; e < 4; e++) d[48 + cq * 4 + e] += (e & 1) ? bf_hi(bw) : bf_lo(bw);
          }
        }
#pragma unroll
        for (int h = 0; h < 2; h++) {
          const bool isS = quad * 2 + h < 45;
          const uint32_t base = (isL ? baseL ^ (h * 32) : (isS ? baseS : baseT) ^ (h * 8192)), xj = isS ? 16 : 1024, xc = isL ? 8192 : 4096;
#pragma unroll
          for (int e4 = 0; e4 < 4; e4++) {
            const float* e = d + h * 32 + e4 * 8;
            asm volatile("stmatrix.sync.aligned.m8n8.x4.shared.b16 [%0],{%1,%2,%3,%4};"
                         :: "r"(sbase + K1_STG + (base ^ ((e4 >> 1) * xj) ^ ((e4 & 1) * xc))),
                            "r"(pack_bf2(e[0], e[1])), "r"(pack_bf2(e[2], e[3])), "r"(pack_bf2(e[4], e[5])), "r"(pack_bf2(e[6], e[7])) : "memory");
          }
        }
        __syncwarp();
        mbar_arrive_lane0(fullS);
        if (!mt) PT(qn * 16 + 4);
      }
      PT(qn * 16 + 8);
    }
    return;
  }
  const int slice = cta & 15;
  const int range = (cta >> 4) * 8 + __shfl_sync(0xffffffffu, tid >> 5, 0);
  uint4 iv[4], trow[4]; uint32_t ix;
  uint2 wrow[10];
#pragma unroll
  for (int q = 0; q < 10; q++) asm volatile("ld.global.nc.v2.u32 {%0,%1},[%2];" : "=r"(wrow[q].x), "=r"(wrow[q].y) : "l"((const uint2*)wp + min(tid + q * 256, 2499)));
  asm volatile("bar.sync 2,512;" ::: "memory");
  uint32_t me = 0, mw = 0;
#pragma unroll
  for (int q = 0; q < 10; q++) {
    mw = __vmaxu2(__vmaxu2(wrow[q].x & 0x7fff7fffu, wrow[q].y & 0x7fff7fffu), mw);
    const int e = min(tid + q * 256, 2499), row = e / 25;
    asm volatile("st.shared.v2.u32 [%0],{%1,%2};" :: "r"(sbase + (e + row) * 8), "r"(wrow[q].x), "r"(wrow[q].y) : "memory");
    if (e - row * 25 == 24) asm volatile("st.shared.v2.u32 [%0],{%1,%2};" :: "r"(sbase + (e + row) * 8 + 8), "r"(wrow[q].x), "r"(wrow[q].y) : "memory");
  }
  mbar_wait_fast(fullC, 0);
#pragma unroll
  for (int q = 0; q < 4; q++) { trow[q] = lds128(sbase + 32768 + (tid + q * 256) * 16); me = absmax4(trow[q], me); }
  me = __reduce_max_sync(0xffffffffu, max(me & 0xffff, me >> 16));
  mw = __reduce_max_sync(0xffffffffu, max(mw & 0xffff, mw >> 16));
  uint32_t* sred = (uint32_t*)((char*)sm + 128000);
  if (lane == 0) sred[tid >> 5] = me | mw << 16;
  TS(3, 0);
  asm volatile("setmaxnreg.inc.sync.aligned.u32 " RPNN ";");
  asm volatile("bar.sync 1,256;" ::: "memory");
  { uint32_t m = 0;
#pragma unroll
    for (int q = 0; q < 8; q++) m = __vmaxu2(m, sred[q]);
    m = __shfl_sync(0xffffffffu, m, 0);
    me = m & 0xffff; mw = m >> 16; }
  const float se = pow2_scale(me, 3), sW = pow2_scale(mw, -2);
  TS(3, 1);
  auto put_rows = [&](int q, bool on) {
    const uint4 t = trow[q];
    const uint4 hv = make_uint4(pack_h2(bf_lo(t.x) * se, bf_hi(t.x) * se), pack_h2(bf_lo(t.y) * se, bf_hi(t.y) * se),
                                pack_h2(bf_lo(t.z) * se, bf_hi(t.z) * se), pack_h2(bf_lo(t.w) * se, bf_hi(t.w) * se));
    if (on)
#pragma unroll
      for (int s = 0; s < 8; s++) sts128(sbase + (tid + q * 256) * 128 + ((s + lane) & 7) * 16, hv);
  };
#pragma unroll 1
  for (int it = 0; it < 3; it++) {
    const int hu = ((tid >> 5) * 3 + it) * 4, code = hu_code(min(hu + (lane >> 3), HU_N - 1)), ok = code >> 4, on = code & 15;
    uint32_t x[4], y[4];
    asm volatile("ldmatrix.sync.aligned.m8n8.x4.shared.b16 {%0,%1,%2,%3},[%4];" : "=r"(x[0]), "=r"(x[1]), "=r"(x[2]), "=r"(x[3])
                 : "r"(sbase + (on * 8 + (lane & (on == 12 ? 3 : 7))) * 208 + ok * 16) : "memory");
    asm volatile("ldmatrix.sync.aligned.m8n8.x4.trans.shared.b16 {%0,%1,%2,%3},[%4];" : "=r"(y[0]), "=r"(y[1]), "=r"(y[2]), "=r"(y[3])
                 : "r"(sbase + (ok * 8 + (lane & (ok == 12 ? 3 : 7))) * 208 + on * 16) : "memory");
    const uint32_t lo = __ballot_sync(0xffffffffu, ok > on), dg = __ballot_sync(0xffffffffu, ok >= on);
#pragma unroll
    for (int q = 0; q < 4; q++) {
      const float m0 = (lo >> (8 * q)) & 1 ? 0.f : sW, m1 = (dg >> (8 * q)) & 1 ? 0.f : sW;
      asm volatile("st.shared.u32 [%0],%1;" :: "r"(sbase + K1_W + (hu + q) * 128 + lane * 4),
                   "r"(pack_h2(fmaf(bf_lo(x[q]), m0, bf_lo(y[q]) * m1), fmaf(bf_hi(x[q]), m0, bf_hi(y[q]) * m1))) : "memory");
    }
  }
  put_rows(1, true); put_rows(2, tid < 88);
  TS(3, 2);
  asm volatile("fence.proxy.async.shared::cta;" ::: "memory");
  asm volatile("bar.sync 1,256;" ::: "memory");
  put_rows(0, true);
  uint32_t bf[HU_N - 2 * G_U];
#pragma unroll
  for (int q = 0; q < HU_N - 2 * G_U; q++) asm volatile("ld.shared.u32 %0,[%1];" : "=r"(bf[q]) : "r"(sbase + K1_W + (2 * G_U + q) * 128 + lane * 4));
  const float unscale = __uint_as_float(0x7f000000u - __float_as_uint(se)), unscale2 = __uint_as_float(0x7f000000u - __float_as_uint(sW));
  TS(3, 3);
  const int px = range * 16 * 136;
  mbar_wait_fast(fullI, 0);
  {
    const uint32_t ib = sbase + 76800 + (tid >> 5) * 6400, p0 = ib + ((lane >> 3) & 1) * 400 + ((lane >> 4) * 8 + (lane & 7)) * 4;
    auto ld = [&](uint32_t ad) { uint32_t v; asm volatile("ld.shared.u32 %0,[%1];" : "=r"(v) : "r"(ad)); return v; };
    auto wd = [&](int t, int h) { return pk3(ld(p0 + t * 800 + h * 192), ld(p0 + t * 800 + h * 192 + 64), ld(p0 + t * 800 + h * 192 + 128)); };
#pragma unroll
    for (int q = 0; q < 4; q++) {
      iv[q] = make_uint4(wd(2 * q, 0), wd(2 * q, 1), wd(2 * q + 1, 0), wd(2 * q + 1, 1));
    }
    ix = ld(ib + g * 400 + 384 + r * 4) | ld(ib + (8 + g) * 400 + 384 + r * 4) << 16;
  }
  asm volatile("bar.sync 1,256;" ::: "memory");
  put_rows(2, tid >= 88); put_rows(3, tid + 768 < V_);
  asm volatile("bar.sync 1,256;" ::: "memory");
  TS(0, 1);
  uint32_t lc; asm volatile("add.u32 %0,%1,%2;" : "=r"(lc) : "r"((lane & 7) * 16), "r"(never));
  const uint64_t wdesc = (uint64_t)(((sbase + K1_W) & 0x3FFFF) >> 4) | ((uint64_t)(128 >> 4) << 16) | ((uint64_t)(256 >> 4) << 32);
  uint32_t a[2][6][4], d[2][26], ex[4] = {}, s[4] = {};
  float red[4] = {0.f, 0.f, 0.f, 0.f};
  auto ldsm = [&](uint32_t* o, uint32_t sh, uint32_t dep = 0) {
    asm volatile("ldmatrix.sync.aligned.m8n8.x4.trans.shared.b16 {%0,%1,%2,%3},[%4];"
                 : "=r"(o[0]), "=r"(o[1]), "=r"(o[2]), "=r"(o[3]) : "r"(sbase + ((sh & 0x1ff80) | (lc | (dep & never)))));
  };
  auto gather = [&](int t, int hf) {
    const int x = t & 1;
    const uint4 v = iv[(t >> 1) & 3];
#pragma unroll
    for (int kb = 3 * hf; kb < 3 * hf + 3; kb++) {
      const uint32_t ww = x ? (kb < 3 ? v.z : v.w) : (kb < 3 ? v.x : v.y);
      ldsm(a[x][kb], kb % 3 == 0 ? ww : kb % 3 == 1 ? ww >> 10 : __funnelshift_l(ww, ww, 12));
    }
  };
  auto issue = [&](int x) {
    asm volatile("wgmma.fence.sync.aligned;" ::: "memory");
#pragma unroll
    for (int kb = 0; kb < 6; kb++) {
      if (kb < G_K0) wgmma_h<G_N0 * 8>(d[x] + G_O0 * 2, a[x][kb], wdesc + kb * G_N0 * 16, kb);
      if (kb < G_K1) wgmma_h<G_N1 * 8>(d[x] + G_O1 * 2, a[x][kb], wdesc + (G_U1 + kb * G_N1) * 16, kb);
      if (kb < G_K2) wgmma_h<32>(d[x] + G_O2 * 2, a[x][kb], wdesc + (G_U2 + kb * G_N2) * 16, kb);
    }
    asm volatile("wgmma.commit_group.sync.aligned;" ::: "memory");
  };
  auto hmma_part = [&](int t) {
    constexpr FragIdx FI = make_fi();
    const int x = t & 1;
#pragma unroll
    for (int o = 0; o < 13; o++) {
      if (oct_wg(o)) asm volatile("" : "+r"(d[x][o * 2]), "+r"(d[x][o * 2 + 1]) :: "memory"); else d[x][o * 2] = d[x][o * 2 + 1] = 0;
    }
#pragma unroll
    for (int kb = 0; kb < 6; kb++)
#pragma unroll
      for (int o = 2 * kb + 1; o < 13; o++)
        if (!unit_wg(kb, o)) mma16816h(d[x] + o * 2, a[x][kb], bf[FI.v[2 * kb][o]], bf[FI.v[2 * kb + 1][o]]);
#pragma unroll
    for (int q = 0; q < 6; q++) if (!unit_wg(q, 2 * q)) mma1688h(d[x] + q * 4, a[x][q][0], a[x][q][1], bf[FI.v[2 * q][2 * q]]);
    mma1688h(d[x] + 24, r < 2 ? ex[t & 3] : 0u, r < 2 ? 0u : ex[t & 3], bf[FI.v[12][12]]);
  };
  auto dot_part = [&](int t, int hf) {
    const int x = t & 1;
    if (hf == 0) {
      const uint32_t pe = hfma2(r < 2 ? d[x][24] : d[x][25], ex[t & 3], 0u);
      s[0] = r < 2 ? pe : 0u; s[1] = r < 2 ? 0u : pe; s[2] = s[3] = 0;
    }
#pragma unroll
    for (int q = 3 * hf; q < 3 * hf + 3; q++)
#pragma unroll
      for (int e = 0; e < 4; e++) s[e] = hfma2(d[x][q * 4 + e], a[x][q][e], s[e]);
  };
  float* outp = g_partP + slice * B_ + range * 256;
  float k0 = 0.f, k1 = 0.f, x0 = 0.f, x1 = 0.f;
  auto red_stage = [&](int st, int grp) {
    const bool u16 = lane & 16, u8 = lane & 8;
    if (st == 0) {
      k0 = u16 ? red[2] : red[0]; x0 = __shfl_xor_sync(0xffffffffu, u16 ? red[0] : red[2], 16);
      k1 = u16 ? red[3] : red[1]; x1 = __shfl_xor_sync(0xffffffffu, u16 ? red[1] : red[3], 16);
      red[0] = red[1] = red[2] = red[3] = 0.f;
    }
    if (st == 1) { const float p0 = k0 + x0, p1 = k1 + x1; k0 = u8 ? p1 : p0; x0 = __shfl_xor_sync(0xffffffffu, u8 ? p0 : p1, 8); }
    if (st == 2) { k0 += x0; x0 = __shfl_xor_sync(0xffffffffu, k0, 4); }
    if (st == 3 && !(lane & 4)) outp[grp * 16 + r * 4 + ((lane >> 3) & 1) * 2 + (lane >> 4)] = (k0 + x0) * unscale * unscale * unscale2;
  };
  auto group = [&](bool first, int prv, int cur, int nxt) {
    const int pn = PX_OFF + px + nxt * 136 + lane;
#pragma unroll
    for (int t = 0; t < 8; t++) {
      issue((t & 1) ^ 1);
      SCHED_FENCE(never, t * 8);
      if (!first) {
        if (t == 0) { iv[3] = ldtex(tex, PX_OFF + px + cur * 136 + lane + 96); iv[0] = ldtex(tex, pn); }
        if (t == 2) iv[1] = ldtex(tex, pn + 32);
        if (t < 4) red_stage(t, prv);
      } else if (t == 4) {
        TS(4, 2);
        mbar_wait_fast(pxRdy, 0);
        TS(4, 3);
        iv[0] = ldtex(tex, pn); iv[1] = ldtex(tex, pn + 32);
      }
      if (t == 4) { ix = ldtex(texX, (px + nxt * 136 + 128) * 4 + lane).x; iv[2] = ldtex(tex, pn + 64); }
      dot_part(t, 0);
      SCHED_FENCE(never, t * 8 + 1);
      if (t == 3) ldsm(ex, ix >> 9);
      if (t == 7) ldsm(ex, ix << 7);
      gather(t + 2, 0);
      dot_part(t, 1);
      SCHED_FENCE(never, t * 8 + 4);
      gather(t + 2, 1);
      asm volatile("wgmma.wait_group.sync.aligned 0;" ::: "memory");
      if (FM & 1) SCHED_FENCE(never, t * 8 + 2);
      asm volatile("" : "+r"(d[(t & 1) ^ 1][0]) :: "memory");
      mma1688f(red, hadd2(s[0], s[2]), hadd2(s[1], s[3]), (g | (d[(t & 1) ^ 1][0] & never)) == t ? 0x3c003c00u : 0u);
      hmma_part(t + 1);
      if (FM & 2) SCHED_FENCE(never, t * 8 + 3);
    }
  };
  gather(0, 0); gather(0, 1); issue(0); ldsm(ex, ix << 7); gather(1, 0); gather(1, 1);
  asm volatile("wgmma.wait_group.sync.aligned 0;" ::: "memory");
  hmma_part(0);
  group(true, 0, 0, 1);
  TS(4, 1);
#pragma unroll 1
  for (int n = 1; n < NGRP; n++) {
    if ((n & 11) == 2) mbar_wait_fast(pxRdy + 8 + (n & 4) * 2, 0);
    if (PXW) asm volatile("st.volatile.shared.u32 [%0],%1;" :: "r"(progG), "r"(n) : "memory");
    group(false, n - 1, n, min(n + 1, 15));
  }
#pragma unroll
  for (int st = 0; st < 4; st++) red_stage(st, 15);
  TS(0, 2);
  asm volatile("barrier.cluster.wait.aligned;" ::: "memory");
  asm volatile("barrier.cluster.arrive.relaxed.aligned; barrier.cluster.wait.aligned;" ::: "memory");
}

constexpr int SM_U = 130048, SM_BAR = 128000, SM_J = SM_U + 98304, DEEP_SMEM = SM_J + 4096;

__global__ void __cluster_dims__(2, 1, 1) __launch_bounds__(TH + 128, 1)
k_deep(cudaTextureObject_t tex, const __nv_bfloat16* __restrict__ w2, const __nv_bfloat16* __restrict__ b2,
       __nv_bfloat16* __restrict__ out, int never) {
  extern __shared__ __align__(1024) uint4 sm[];
  constexpr int PF = DPF, DEPTH = DDEPTH, NW = TH / 32;
  static_assert(YD == 4 && PF == 4, "");
  const int tid = threadIdx.x;
  const int c = blockIdx.x >> 1, half = blockIdx.x & 1;
  const uint32_t sbase = (uint32_t)__cvta_generic_to_shared(sm);
  const uint32_t fullL = sbase + SM_BAR, fullU = fullL + 8, emptyL = fullL + 16, emptyU = fullL + 24, barJ = fullL + 32;
  TS(1, 0);
  if (tid == 0) {
    mbar_init(fullL, 1); mbar_init(fullU, 1); mbar_init(emptyL, 2 * NW); mbar_init(emptyU, 2 * NW); mbar_init(barJ, 1);
    asm volatile("fence.mbarrier_init.release.cluster;" ::: "memory");
  }
  __syncwarp();
  const int wrp = __shfl_sync(0xffffffffu, tid >> 5, 0);
  const char* base = (const char*)g_scr;
  uint32_t oL = (PL_OFF + c * NC * 8000) * 16u + half * 64000, oS = (PS_OFF + c * NC * 2000) * 16u + half * 16000;
  asm volatile("barrier.cluster.arrive.relaxed.aligned; barrier.cluster.wait.aligned;" ::: "memory");
  if (wrp == NW) {
    asm volatile("fence.proxy.async.global;" ::: "memory");
    e_expect(fullU, 96000);
#pragma unroll
    for (int m = 0; m < 3; m++) e_mc(sbase + SM_U + m * 32032 + half * 16000, base + oS, 16000, fullU, m == 2 ? POL_EF : POL_N);
    e_expect(fullL, 128000);
    if (!STAG) e_mc(sbase + half * 64000, base + oL, 64000, fullL, POL_EF);
  }
  TS(5, 1);
  if (wrp >= NW) {
    asm volatile("setmaxnreg.dec.sync.aligned.u32 24;");
    if (wrp == NW) {
      uint32_t oT = (PT_OFF + c * 10 * 1024) * 16u + half * 8192;
      const uint32_t junk = sbase + SM_J, oW = (IX_OFF + half * IXH + ((c + (c >> 4) * 5) & 15) * 512) * 16u;
      auto warm = [&](uint32_t off) {
        asm volatile(ELECT "mbarrier.expect_tx.relaxed.cta.shared::cta.b64 [%0],%1;}" :: "r"(barJ), "r"(8192) : "memory");
        e_g2s(junk, base + off, 4096, barJ); e_g2s(junk, base + off + 4096, 4096, barJ);
      };
      uint32_t t0 = clock();
      if (!PREW) warm(oW);
      if (STAG) { if (STAG == 1) mbar_wait(fullU, 0); else sleep_until(t0, STAG); e_mc(sbase + half * 64000, base + oL, 64000, fullL, POL_EF); }
      warm(oT);
      if (!(PREW & 4)) warm(oW + 131072);
#pragma unroll 1
      for (int k = 0; k + 1 < NC; k++) {
        oL += 128000; oS += 32000; oT += 16384;
        mbar_wait(fullL, k & 1);
        t0 = clock();
        e_pf(base + oS, 16000);
        warm((IX_OFF + half * IXH + (k + 2) * 8192 + ((c + (c >> 4) * (2 * k + 1)) & (k + 2 < NC ? 15 : 3)) * 512) * 16u);
        mbar_wait(emptyU, k & 1);
        e_expect(fullU, 96000);
#pragma unroll 1
        for (int q = 0; q < 8; q++) {
          sleep_until(t0, q * PACE);
          e_pf(base + oL + q * 8000, 8000);
          if (q >= 2) e_mc(sbase + SM_U + ((q - 2) >> 1) * 32032 + half * 16000 + (q & 1) * 8000, base + oS + (q & 1) * 8000, 8000, fullU, q >= 6 ? POL_EF : POL_N);
        }
        warm(oT);
        e_expect(fullL, 128000);
        sleep_until(t0, RSV_T);
        unsigned long long now, slot = 0;
        asm volatile("mov.u64 %0,%globaltimer;" : "=l"(now));
        if ((tid & 31) == 0) { atomicMax(&g_slot, now + RSV_L); slot = atomicAdd(&g_slot, (unsigned long long)RSV); }
        slot = __shfl_sync(0xffffffffu, slot, 0);
        mbar_wait(emptyL, k & 1);
        for (int it = 0; it < 4000; it++) { asm volatile("mov.u64 %0,%globaltimer;" : "=l"(now)); if (now >= slot) break; }
        e_mc(sbase + half * 64000, base + oL, 64000, fullL, POL_EF);
      }
      mbar_wait(fullL, (NC - 1) & 1);
      mbar_wait(emptyU, (NC - 1) & 1);
      mbar_arrive_lane0(fullU);
      warm(oT + 16384);
      mbar_arrive_lane0(barJ); mbar_wait(barJ, 0);
    } else if (tid >= TH + 96) {
      if (tid == TH + 96) sts128(barJ + 32, *(const uint4*)(w2 + c * 8));
      asm volatile("bar.arrive 3,%0;" :: "n"(TH + 32) : "memory");
      asm volatile("griddepcontrol.wait;" ::: "memory");
      const int b = half * 8192 + c * 128 + (tid & 31) * 4;
      const float bias = __bfloat162float(b2[0]);
      float4 s = make_float4(bias, bias, bias, bias);
#pragma unroll 2
      for (int k = 0; k < 16; k++) { const float4 v = __ldcg((const float4*)(g_partP + k * B_ + b)); s.x += v.x; s.y += v.y; s.z += v.z; s.w += v.w; }
      asm volatile("red.global.add.v4.f32 [%0],{%1,%2,%3,%4};" :: "l"(g_acc + b), "f"(s.x), "f"(s.y), "f"(s.z), "f"(s.w) : "memory");
      asm volatile("bar.arrive 1,%0;" :: "n"(TH + 32) : "memory");
    }
    return;
  }
  asm volatile("setmaxnreg.inc.sync.aligned.u32 240;");
  const int lane = tid & 31;
  const int tbase = PT_OFF + c * 10 * 1024;
  const int ibase = IX_OFF + half * IXH + tid;
  const uint32_t lc = (tid & 7) << 4;
  uint4 acc[NS], wq[PF], x[DEPTH], y[YD], ye;
  uint32_t sw[NS] = {};
  auto sget = [&](int s) { return (s & 3) == 3 ? __byte_perm(__byte_perm(sw[s - 3], sw[s - 2], 0x0073), sw[s - 1], 0x0710) : sw[s]; };
  auto sa0 = [&](uint32_t v) { return sbase + SM_U + (((v << 5) & 0x1ffe0) | ((lc >> 2) & 16)); };
  uint32_t c1 = 0;
  auto sa1 = [&](uint32_t v) { return sbase + SM_U + (((v >> 7) & 0x1ffe0) | c1); };
  {
    uint4 i0[8];
#pragma unroll
    for (int q = 0; q < 8; q++) i0[q] = ldtex(tex, I0_OFF + (half * 8 + q) * TH + tid);
#pragma unroll
    for (int i = 0; i < PF; i++) if (!WQL) wq[i] = ldtex(tex, ibase + i * TH);
    auto wd = [&](int k) { return (k & 3) == 0 ? i0[k >> 2].x : (k & 3) == 1 ? i0[k >> 2].y : (k & 3) == 2 ? i0[k >> 2].z : i0[k >> 2].w; };
    TS(5, 2);
    mbar_wait_fast(fullU, 0);
#pragma unroll
    for (int i = 0; i < PF; i++) if (WQL) wq[i] = ldtex(tex, ibase + i * TH);
    TS(1, 1);
#pragma unroll
    for (int s = 0; s < NS; s++) acc[s] = add4(lds128(sbase + SM_U + (wd(s) & 0x1fff0)), lds128(sbase + SM_U + ((wd(s) >> 13) & 0x1fff0)));
    arrive_both(emptyU, lane);
    asm volatile("bar.sync 3,%0;" :: "n"(TH + 32) : "memory");
    TS(5, 3);
  }
#pragma unroll 1
  for (int k = 0; k < NC; k++) {
    const int ti = ibase + k * 8192;
    const int tb = tbase + k * 1024;
    const bool more = k + 1 < NC;
    TR(k * 4);
    if (CBAR & 1) asm volatile("bar.sync 4,%0;" :: "n"(TH) : "memory");
    mbar_wait_fast(fullL, k & 1);
    TR(k * 4 + 2);
    uint4 w, cc; uint32_t yc, yn;
    constexpr int TL = NS * 8, TT = TL + NS * 2;
#pragma unroll
    for (int t = 0; t < TT + DEPTH; t += 2) {
      if (t == TL + DEPTH && !more) break;
      if (t >= DEPTH) {
        const int u = t - DEPTH;
        uint4 p = add4(x[u % DEPTH], x[(u + 1) % DEPTH]);
        if (u < TL) {
          const int s = u >> 3, j = u & 7;
          if (j == 0) {
            cc = s >= YD ? add4(y[s % YD], p) : p;
            if (s + YD < NS) y[s % YD] = ldtex(tex, tb | (yc & 1023));
          } else cc = add4(cc, p);
          if (j == 6) acc[s] = add4(acc[s], cc);
        } else {
          const int s = (u - TL) >> 1;
          acc[s] = add4(acc[s], p);
        }
      }
      if ((CBAR & 4) && t == TL / 2) asm volatile("bar.sync 4,%0;" :: "n"(TH) : "memory");
      if ((CBAR & 8) && t == TL - 40) asm volatile("bar.sync 4,%0;" :: "n"(TH) : "memory");
      if (DEPTH == 8 && (t & 7) == 2) yc = yn;
      if (t < TL) {
        const int s = t >> 3, j = t & 7;
        if (j == 0) {
          if (ye_of(s - YD) >= 0) acc[ye_of(s - YD) & 3] = add4(acc[ye_of(s - YD) & 3], ye);
          w = wq[s % PF];
          if (!EARLY || s < NS - 4) wq[s % PF] = ldtex(tex, ti + (s + PF) * TH);
          else {
            if (s == NS - 4) { wq[0] = ldtex(tex, ti + NS * TH); ye = ldtex(tex, ti + (NS + 3) * TH); }
            if (s == NS - 3) { wq[1] = ldtex(tex, ti + (NS + 1) * TH); y[0] = ldtex(tex, ti + (NS + 2) * TH); }
            if (s == NS - 2) wq[2] = y[0];
            if (s == NS - 1) wq[3] = ye;
          }
          yn = __funnelshift_l(w.z, w.z, 5); if (DEPTH < 8) yc = yn;
          if ((s & 3) != 3) asm volatile("add.u32 %0,%1,%2;" : "=r"(sw[s]) : "r"(w.w), "r"(never));
          if (ye_of(s) >= 0) ye = ldtex(tex, tb | w.w);
        }
#pragma unroll
        for (int jj = j; jj < j + 2; jj++) {
          const uint32_t ww = jj < 3 ? w.x : jj < 6 ? w.y : w.z;
          const uint32_t sh = jj % 3 == 0 ? ww : jj % 3 == 1 ? ww >> 10 : __funnelshift_l(ww, ww, 12);
          x[(t + jj - j) % DEPTH] = lds128(sbase + ((sh & 0x1ff80) | lc) + jj * 16 - 128);
        }
      } else if (t < TT) {
        const int s = (t - TL) >> 1;
        if (s == 0) { asm volatile("add.u32 %0,%1,%2;" : "=r"(c1) : "r"((~lc >> 2) & 16), "r"(never)); arrive_both(emptyL, more ? lane : 9); TR(k * 4 + 3); if (CBAR & 2) asm volatile("bar.sync 4,%0;" :: "n"(TH) : "memory"); mbar_wait_fast(fullU, (k + 1) & 1); }
        const uint32_t sv = sget(s);
        x[t % DEPTH] = lds128(sa0(sv));
        x[(t + 1) % DEPTH] = lds128(sa1(sv));
      } else if (t == TT) arrive_both(emptyU, lane);
      if ((t & (FENCE_N - 1)) == FENCE_N - 2) SCHED_FENCE(never, t);
    }
  }
  TS(1, 2);
  const uint4 w2v = lds128(barJ + 32);
  const uint32_t cell = sbase + SM_U + tid * 16;
  const int t9 = tbase + 9 * 1024;
  uint4 za[4], i9 = wq[0];
  auto fetch = [&](int q) {
    y[0] = ldtex(tex, t9 | i9.x); y[1] = ldtex(tex, t9 | i9.y); y[2] = ldtex(tex, t9 | i9.z); y[3] = ldtex(tex, t9 | i9.w);
    if (q) {
      i9 = ldtex(tex, ibase + NC * 8192 + min(q + 1, 7) * TH);
      const uint32_t ca = cell + (q > 6 ? 0 : q - 1) * 16384;
#pragma unroll
      for (int s = 0; s < 4; s++) za[s] = lds128(ca + s * 4096);
    }
  };
  fetch(0);
  i9 = wq[1];
#pragma unroll
  for (int s = 0; s < 4; s++) za[s] = acc[s];
#pragma unroll
  for (int s = 0; s < 24; s++) sts128(cell + s * 4096, acc[4 + s]);
  float hw[8];
  {
    const uint32_t ww[4] = {w2v.x, w2v.y, w2v.z, w2v.w};
#pragma unroll
    for (int k = 0; k < 8; k++) hw[k] = 0.5f * ((k & 1) ? bf_hi(ww[k >> 1]) : bf_lo(ww[k >> 1]));
  }
  float* outp = g_acc + half * 8192 + tid;
#pragma unroll 1
  for (int q = 0; q < NS / 4; q++) {
    uint4 z[4];
#pragma unroll
    for (int s = 0; s < 4; s++) z[s] = add4(za[s], y[s]);
    if (q == 1) {
#pragma unroll
      for (int s = 0; s < 4; s++) sts128(cell + s * 4096, acc[28 + s]);
    }
    if (q < 7) fetch(q + 1);
    SCHED_FENCE(never, 999);
#pragma unroll
    for (int s = 0; s < 4; s++) {
      const uint32_t a[4] = {z[s].x, z[s].y, z[s].z, z[s].w};
      float r0 = 0.f;
#pragma unroll
      for (int k = 0; k < 8; k++) {
        const float v = (k & 1) ? bf_hi(a[k >> 1]) : bf_lo(a[k >> 1]);
        const float u = v * fmaf(v * v, 0.7978845608028654f * 0.044715f, 0.7978845608028654f);
        float th; asm("tanh.approx.f32 %0,%1;" : "=f"(th) : "f"(u));
        r0 = fmaf(fmaf(v, th, v), hw[k], r0);
      }
      asm volatile("red.global.add.f32 [%0],%1;" :: "l"(outp + s * TH), "f"(r0) : "memory");
    }
    outp += 4 * TH;
  }
  TS(1, 3);
  asm volatile("bar.sync 1,%0;" :: "n"(TH + 32) : "memory");
  if (tid == 0) {
    unsigned old; asm volatile("atom.acq_rel.gpu.global.inc.u32 %0,[%1],63;" : "=r"(old) : "l"(&g_done[half * 32]) : "memory");
    asm volatile("st.shared.u32 [%0],%1;" :: "r"(barJ + 8), "r"(old) : "memory");
  }
  asm volatile("bar.sync 2,%0;" :: "n"(TH) : "memory");
  uint32_t old; asm volatile("ld.shared.u32 %0,[%1];" : "=r"(old) : "r"(barJ + 8));
  if (old == 63) {
    if (half == 0 && tid == 25) g_slot = 0;
    if (half == 0 && tid < 25) g_flag[tid * 32] = 0;
    float4 v[8];
#pragma unroll
    for (int q = 0; q < 8; q++) v[q] = __ldcg((const float4*)(g_acc + half * 8192) + q * TH + tid);
#pragma unroll
    for (int q = 0; q < 8; q++) ((uint2*)(out + half * 8192))[q * TH + tid] = make_uint2(pack_bf2(v[q].x, v[q].y), pack_bf2(v[q].z, v[q].w));
    TS(6, 2);
  }
}

}

extern "C" void kernel_launch(void* const* d_in, const int* in_sizes, int n_in, void* d_out, int out_size) {
  const int* idx = (const int*)d_in[0];
  const __nv_bfloat16* table = (const __nv_bfloat16*)d_in[1];
  const __nv_bfloat16* wp = (const __nv_bfloat16*)d_in[2];
  const __nv_bfloat16* w1 = (const __nv_bfloat16*)d_in[3];
  const __nv_bfloat16* b1 = (const __nv_bfloat16*)d_in[4];
  const __nv_bfloat16* w2 = (const __nv_bfloat16*)d_in[5];
  const __nv_bfloat16* b2 = (const __nv_bfloat16*)d_in[6];
  static cudaTextureObject_t texScr = 0, texG = 0;
  static CUtensorMap mapW, mapL, mapS, mapT, mapE, mapC;
  static const void *c_tab = nullptr, *c_w1 = nullptr;
  if (c_tab != table || c_w1 != w1) {
    c_tab = table; c_w1 = w1;
    char* scr = nullptr; cudaGetSymbolAddress((void**)&scr, g_scr);
    auto mk_tex = [](const void* p, size_t bytes, cudaChannelFormatDesc d) {
      cudaResourceDesc rd = {}; rd.resType = cudaResourceTypeLinear; rd.res.linear.devPtr = (void*)p; rd.res.linear.desc = d; rd.res.linear.sizeInBytes = bytes;
      cudaTextureDesc td = {}; td.readMode = cudaReadModeElementType;
      cudaTextureObject_t t = 0; cudaCreateTextureObject(&t, &rd, &td, nullptr); return t;
    };
    if (!texScr) {
      texScr = mk_tex(scr, (size_t)SCR_N * 16, cudaCreateChannelDesc<uint4>());
      texG = mk_tex(scr + (size_t)PX_OFF * 16, (size_t)(SCR_N - PX_OFF) * 16, cudaCreateChannelDesc<unsigned>());
    }
    typedef CUresult (*EncFn)(CUtensorMap*, CUtensorMapDataType, cuuint32_t, void*, const cuuint64_t*, const cuuint64_t*, const cuuint32_t*,
                              const cuuint32_t*, CUtensorMapInterleave, CUtensorMapSwizzle, CUtensorMapL2promotion, CUtensorMapFloatOOBfill);
    EncFn enc = nullptr; cudaDriverEntryPointQueryResult qr;
    cudaGetDriverEntryPoint("cuTensorMapEncodeTiled", (void**)&enc, cudaEnableDefault, &qr);
    const cuuint32_t ones[4] = {1, 1, 1, 1};
    auto mk = [&](CUtensorMap* m, CUtensorMapDataType dt, int rank, void* p, const cuuint64_t* dim, const cuuint64_t* str, const cuuint32_t* box, CUtensorMapSwizzle sw) {
      enc(m, dt, rank, p, dim, str, box, ones, CU_TENSOR_MAP_INTERLEAVE_NONE, sw, CU_TENSOR_MAP_L2_PROMOTION_NONE, CU_TENSOR_MAP_FLOAT_OOB_FILL_NONE);
    };
    { cuuint64_t dim[2] = {H_, F_ * D_}, str[1] = {H_ * 2}; cuuint32_t box[2] = {32, 256};
      mk(&mapW, CU_TENSOR_MAP_DATA_TYPE_BFLOAT16, 2, (void*)w1, dim, str, box, CU_TENSOR_MAP_SWIZZLE_64B); }
    { cuuint64_t dim[4] = {64, V_, NC, 64}, str[3] = {128, 128000, 128000 * NC}; cuuint32_t box[4] = {32, 64, 1, 4};
      mk(&mapL, CU_TENSOR_MAP_DATA_TYPE_BFLOAT16, 4, scr + (size_t)PL_OFF * 16, dim, str, box, CU_TENSOR_MAP_SWIZZLE_64B); }
    { cuuint64_t dim[4] = {64, V_ / 4, NC, 64}, str[3] = {128, 32000, 32000 * NC}; cuuint32_t box[4] = {64, 16, 1, 4};
      mk(&mapS, CU_TENSOR_MAP_DATA_TYPE_BFLOAT16, 4, scr + (size_t)PS_OFF * 16, dim, str, box, CU_TENSOR_MAP_SWIZZLE_128B); }
    { cuuint64_t dim[3] = {2048, 10, 64}, str[2] = {16384, 163840}; cuuint32_t box[3] = {128, 2, 4};
      mk(&mapT, CU_TENSOR_MAP_DATA_TYPE_UINT64, 3, scr + (size_t)PT_OFF * 16, dim, str, box, CU_TENSOR_MAP_SWIZZLE_NONE); }
    { cuuint64_t dim[2] = {D_, V_}, str[1] = {D_ * 2}; cuuint32_t box[2] = {64, 128};
      mk(&mapE, CU_TENSOR_MAP_DATA_TYPE_BFLOAT16, 2, (void*)table, dim, str, box, CU_TENSOR_MAP_SWIZZLE_128B);
      cuuint32_t box2[2] = {8, 256};
      mk(&mapC, CU_TENSOR_MAP_DATA_TYPE_BFLOAT16, 2, (void*)table, dim, str, box2, CU_TENSOR_MAP_SWIZZLE_NONE); }
    cudaFuncSetAttribute(k_deep, cudaFuncAttributeMaxDynamicSharedMemorySize, DEEP_SMEM);
    cudaFuncSetAttribute(k_tens, cudaFuncAttributeMaxDynamicSharedMemorySize, K1_SMEM);
  }
  k_tens<<<132, 512, K1_SMEM, cudaStreamPerThread>>>(mapW, mapL, mapS, mapT, mapE, mapC, texScr, texG, idx, table, wp, w1, b1, 0);
  cudaLaunchAttribute at[1];
  at[0].id = cudaLaunchAttributeProgrammaticStreamSerialization; at[0].val.programmaticStreamSerializationAllowed = 1;
  cudaLaunchConfig_t cfg = {};
  cfg.stream = cudaStreamPerThread; cfg.attrs = at;
  cfg.gridDim = 128; cfg.blockDim = TH + 128; cfg.dynamicSmemBytes = DEEP_SMEM; cfg.numAttrs = PDL & 1;
  cudaLaunchKernelEx(&cfg, k_deep, texScr, w2, b2, (__nv_bfloat16*)d_out, 0);

}
```

```cpp
#include <cuda_runtime.h>
#include <cuda_bf16.h>
#include <cuda_fp16.h>
#include <stdint.h>
#include <cuda.h>

namespace {

constexpr int B_ = 16384, F_ = 100, D_ = 128, V_ = 1000, H_ = 512;
constexpr int NC = 9;
constexpr int PT_OFF = 0;
constexpr int PL_OFF = 64 * 10 * 1024;
constexpr int PS_OFF = PL_OFF + 64 * NC * 8000;
constexpr int IXH = NC * 8192 + 2048;
constexpr int IX_OFF = PS_OFF + 64 * NC * 2000;
constexpr int I0_OFF = IX_OFF + 2 * IXH;
constexpr int PX_OFF = I0_OFF + 4096;
constexpr int SCR_N = PX_OFF + 64 * 16 * 136;
static_assert(PX_OFF % 32 == 0, "");

__device__ __align__(1024) uint4 g_scr[SCR_N];
__device__ float g_acc[B_];
__device__ unsigned long long g_slot;
__device__ unsigned g_done[64];
__device__ float g_partP[16 * B_];
__device__ unsigned g_flag[25 * 32];

#define TS(k, i)
#define TR(slot)
#define PT(slot)

constexpr uint64_t POL_EF = 0x12F0000000000000ull, POL_N = 0x1000000000000000ull;
__device__ __forceinline__ uint32_t addbf2(uint32_t a, uint32_t b) { uint32_t r; asm("add.rn.bf16x2 %0,%1,%2;" : "=r"(r) : "r"(a), "r"(b)); return r; }
__device__ __forceinline__ uint4 add4(const uint4& a, const uint4& b) { return make_uint4(addbf2(a.x, b.x), addbf2(a.y, b.y), addbf2(a.z, b.z), addbf2(a.w, b.w)); }
__device__ __forceinline__ void acc4(uint4& a, const uint4& b, int never) {
  asm("{.reg .pred p; setp.eq.s32 p,%8,0;\n"
      "@p add.rn.bf16x2 %0,%0,%4; @p add.rn.bf16x2 %1,%1,%5; @p add.rn.bf16x2 %2,%2,%6; @p add.rn.bf16x2 %3,%3,%7;}"
      : "+r"(a.x), "+r"(a.y), "+r"(a.z), "+r"(a.w) : "r"(b.x), "r"(b.y), "r"(b.z), "r"(b.w), "r"(never));
}
__device__ __forceinline__ uint4 ldtex(cudaTextureObject_t t, int i) {
  uint4 v; asm volatile("tex.1d.v4.u32.s32 {%0,%1,%2,%3},[%4,{%5}];" : "=r"(v.x), "=r"(v.y), "=r"(v.z), "=r"(v.w) : "l"(t), "r"(i)); return v;
}
__device__ __forceinline__ uint4 lds128(uint32_t a) {
  uint4 v; asm volatile("ld.volatile.shared.v4.u32 {%0,%1,%2,%3},[%4];" : "=r"(v.x), "=r"(v.y), "=r"(v.z), "=r"(v.w) : "r"(a)); return v;
}
__device__ __forceinline__ void sts128(uint32_t a, const uint4& v) {
  asm volatile("st.shared.v4.u32 [%0],{%1,%2,%3,%4};" :: "r"(a), "r"(v.x), "r"(v.y), "r"(v.z), "r"(v.w) : "memory");
}
__device__ __forceinline__ void mbar_init(uint32_t bar, int n) { asm volatile("mbarrier.init.shared::cta.b64 [%0],%1;" :: "r"(bar), "r"(n) : "memory"); }
__device__ __forceinline__ void mbar_wait(uint32_t bar, uint32_t parity) {
  uint32_t ok; int it = 0;
  do { asm volatile("{.reg .pred p; mbarrier.try_wait.parity.shared::cta.b64 p,[%1],%2; selp.u32 %0,1,0,p;}" : "=r"(ok) : "r"(bar), "r"(parity) : "memory"); } while (!ok && ++it < (1 << 19));
}
__device__ __forceinline__ void mbar_expect(uint32_t bar, uint32_t bytes) { asm volatile("mbarrier.arrive.expect_tx.shared::cta.b64 _,[%0],%1;" :: "r"(bar), "r"(bytes) : "memory"); }
__device__ __forceinline__ void bulk_g2s(uint32_t dst, const void* src, uint32_t bytes, uint32_t bar) {
  asm volatile("cp.async.bulk.shared::cluster.global.mbarrier::complete_tx::bytes [%0],[%1],%2,[%3];" :: "r"(dst), "l"(src), "r"(bytes), "r"(bar) : "memory");
}
__device__ __forceinline__ void bulk_pf(const void* src, uint32_t bytes) { asm volatile("cp.async.bulk.prefetch.L2.global [%0],%1;" :: "l"(src), "r"(bytes) : "memory"); }
#define NOMMA 0
#define NGRP 16
#define PDL 1
#define FIN_S 128
#define WRED 4
#define RSV 24
#define RSV_T 7200
#define RSV_L 550
#define TRIG 14
#define PREW 5
#define PXW 2
#define PXW0 5
#define WQL 1
#define EARLY 1
#define CBAR 0
#define X_SAMEK 0
#define X_SAMEW 0
#define FM 0
#define SWP 1
#define HOLD 1
#define MCW 1
#define TW 1
#define PP0 10
#define PT0 10000
#define PDT 0
#define RPNN "160"
#define RAUX "32"
#define RPRO "160"
#define PARK 0
#define NLOOK 128
#define NEF 25
#define ORD 0
#define WFENCE 0
#define SPLIT 1
#define IORD 1
#define IPF 3
#define IPACE 4500
#define WPF 1
#define QV 3
#define QORD(n) ((n) < 23 ? (n) + 2 : (n) - 23)
#define DYD 4
#define DPF 4
#define DDEPTH 4
#define FENCE_N 4
#define INPL 0
#define STAG 1
#define PACE 800
#define PM4 "pmevent 1; pmevent 2; pmevent 3; pmevent 4;"
#define PMFILL "pmevent 1;"
#define SCHED_FENCE(never, k) asm volatile("{.reg .pred p; setp.ne.u32 p,%0,%1; @p bra.uni SKIP_%=;" PMFILL "SKIP_%=: }" :: "r"(never), "r"(0x7fff0000 + (k)) : "memory")

__global__ void k_prod_naive(const __nv_bfloat16* __restrict__ table, const __nv_bfloat16* __restrict__ w1) {
  __shared__ float t[8][D_];
  int f = blockIdx.y, v0 = blockIdx.x * 8, h = threadIdx.x;
  for (int i = h; i < 8 * D_; i += 512) t[i / D_][i % D_] = __bfloat162float(table[v0 * D_ + i]);
  __syncthreads();
  float s[8] = {0, 0, 0, 0, 0, 0, 0, 0};
  for (int d = 0; d < D_; d++) { float w = __bfloat162float(w1[(size_t)(f * D_ + d) * H_ + h]);
#pragma unroll
    for (int k = 0; k < 8; k++) s[k] += t[k][d] * w; }
  __nv_bfloat16* P = (__nv_bfloat16*)g_scr;
  int c = h >> 3;
  for (int k = 0; k < 8; k++) {
    size_t e = f < 72 ? (size_t)PL_OFF + ((size_t)(c * NC + (f >> 3)) * 1000 + v0 + k) * 8 + (f & 7)
             : f < 90 ? (size_t)PS_OFF + ((size_t)(c * NC + ((f - 72) >> 1)) * 1000 + v0 + k) * 2 + (f & 1)
                      : (size_t)PT_OFF + (size_t)(c * 10 + f - 90) * 1024 + v0 + k;
    P[e * 8 + (h & 7)] = __float2bfloat16(s[k]);
  }
}
__global__ void k_pnn_naive(const int* __restrict__ idx, const __nv_bfloat16* __restrict__ table, const __nv_bfloat16* __restrict__ wp) {
  __shared__ float e[F_][33];
  int b = blockIdx.x, d0 = blockIdx.y * 32, tid = threadIdx.x;
  for (int i = tid; i < F_ * 32; i += 128) e[i >> 5][i & 31] = __bfloat162float(table[idx[b * F_ + (i >> 5)] * D_ + d0 + (i & 31)]);
  __syncthreads();
  float s = 0; int d = tid & 31;
  for (int i = tid >> 5; i < F_; i += 4) { float u = 0; for (int j = 0; j < F_; j++) u += __bfloat162float(wp[i * F_ + j]) * e[j][d]; s += u * e[i][d]; }
  for (int o = 16; o; o >>= 1) s += __shfl_xor_sync(~0u, s, o);
  if (d == 0) g_partP[(blockIdx.y * 4 + (tid >> 5)) * B_ + b] = s;
}
__device__ __forceinline__ void mbar_wait_fast(uint32_t bar, uint32_t parity) {
  asm volatile("{.reg .pred p; .reg .u32 n;\n"
               "mbarrier.try_wait.parity.shared::cta.b64 p,[%0],%1;\n"
               "@p bra DONE_%=;\n"
               "mov.u32 n,0;\n"
               "LOOP_%=: mbarrier.try_wait.parity.shared::cta.b64 p,[%0],%1;\n"
               "add.u32 n,n,1; setp.gt.or.u32 p,n,400000,p;\n"
               "@!p bra LOOP_%=;\n"
               "DONE_%=: }" :: "r"(bar), "r"(parity) : "memory");
}
__device__ __forceinline__ void sleep_until(uint32_t t0, uint32_t dt) { while ((uint32_t)clock() - t0 < dt) __nanosleep(40); }
__device__ __forceinline__ uint32_t s_mask(uint32_t v, int q) { return (1u << ((v + 3 - q) & 3)) | (16u << ((v + 3 + q) & 3)); }
__device__ __forceinline__ uint32_t s_cell(uint32_t v, int q, uint32_t m) {
  const int t = __ffs(~m) - 1;
  const int cp = t == 8 ? q >> 1 : ((t & 4 ? t - q : t + q) - v) & 3;
  return cp * 1001 + v;
}
__device__ __forceinline__ uint32_t pk3(uint32_t a, uint32_t b, uint32_t c) {
  const uint32_t w = c + (a << 12) + (b << 22); return __funnelshift_l(w, w, 27);
}
constexpr int TH = 256, NS = 8192 / TH, YD = DYD;
__host__ __device__ constexpr int ye_of(int s) { return s == 3 ? 0 : s == 11 ? 1 : s == 19 ? 2 : s == 23 ? 3 : -1; }
template <int N> __device__ __forceinline__ void wgmma_h(uint32_t* d, const uint32_t* a, uint64_t desc, int acc);
template <> __device__ __forceinline__ void wgmma_h<64>(uint32_t* d, const uint32_t* a, uint64_t desc, int acc) {
  asm volatile("{.reg .pred p; setp.ne.s32 p,%21,0;\n"
    "wgmma.mma_async.sync.aligned.m64n64k16.f16.f16.f16 {%0,%1,%2,%3,%4,%5,%6,%7,%8,%9,%10,%11,%12,%13,%14,%15},{%16,%17,%18,%19},%20,p,1,1,0;}"
    : "+r"(d[0]),"+r"(d[1]),"+r"(d[2]),"+r"(d[3]),"+r"(d[4]),"+r"(d[5]),"+r"(d[6]),"+r"(d[7]),"+r"(d[8]),"+r"(d[9]),"+r"(d[10]),"+r"(d[11]),"+r"(d[12]),"+r"(d[13]),"+r"(d[14]),"+r"(d[15])
    : "r"(a[0]), "r"(a[1]), "r"(a[2]), "r"(a[3]), "l"(desc), "r"(acc));
}
template <> __device__ __forceinline__ void wgmma_h<56>(uint32_t* d, const uint32_t* a, uint64_t desc, int acc) {
  asm volatile("{.reg .pred p; setp.ne.s32 p,%19,0;\n"
    "wgmma.mma_async.sync.aligned.m64n56k16.f16.f16.f16 {%0,%1,%2,%3,%4,%5,%6,%7,%8,%9,%10,%11,%12,%13},{%14,%15,%16,%17},%18,p,1,1,0;}"
    : "+r"(d[0]),"+r"(d[1]),"+r"(d[2]),"+r"(d[3]),"+r"(d[4]),"+r"(d[5]),"+r"(d[6]),"+r"(d[7]),"+r"(d[8]),"+r"(d[9]),"+r"(d[10]),"+r"(d[11]),"+r"(d[12]),"+r"(d[13])
    : "r"(a[0]), "r"(a[1]), "r"(a[2]), "r"(a[3]), "l"(desc), "r"(acc));
}
template <> __device__ __forceinline__ void wgmma_h<48>(uint32_t* d, const uint32_t* a, uint64_t desc, int acc) {
  asm volatile("{.reg .pred p; setp.ne.s32 p,%17,0;\n"
    "wgmma.mma_async.sync.aligned.m64n48k16.f16.f16.f16 {%0,%1,%2,%3,%4,%5,%6,%7,%8,%9,%10,%11},{%12,%13,%14,%15},%16,p,1,1,0;}"
    : "+r"(d[0]),"+r"(d[1]),"+r"(d[2]),"+r"(d[3]),"+r"(d[4]),"+r"(d[5]),"+r"(d[6]),"+r"(d[7]),"+r"(d[8]),"+r"(d[9]),"+r"(d[10]),"+r"(d[11])
    : "r"(a[0]), "r"(a[1]), "r"(a[2]), "r"(a[3]), "l"(desc), "r"(acc));
}
template <> __device__ __forceinline__ void wgmma_h<40>(uint32_t* d, const uint32_t* a, uint64_t desc, int acc) {
  asm volatile("{.reg .pred p; setp.ne.s32 p,%15,0;\n"
    "wgmma.mma_async.sync.aligned.m64n40k16.f16.f16.f16 {%0,%1,%2,%3,%4,%5,%6,%7,%8,%9},{%10,%11,%12,%13},%14,p,1,1,0;}"
    : "+r"(d[0]),"+r"(d[1]),"+r"(d[2]),"+r"(d[3]),"+r"(d[4]),"+r"(d[5]),"+r"(d[6]),"+r"(d[7]),"+r"(d[8]),"+r"(d[9])
    : "r"(a[0]), "r"(a[1]), "r"(a[2]), "r"(a[3]), "l"(desc), "r"(acc));
}
template <> __device__ __forceinline__ void wgmma_h<32>(uint32_t* d, const uint32_t* a, uint64_t desc, int acc) {
  asm volatile("{.reg .pred p; setp.ne.s32 p,%13,0;\n"
    "wgmma.mma_async.sync.aligned.m64n32k16.f16.f16.f16 {%0,%1,%2,%3,%4,%5,%6,%7},{%8,%9,%10,%11},%12,p,1,1,0;}"
    : "+r"(d[0]),"+r"(d[1]),"+r"(d[2]),"+r"(d[3]),"+r"(d[4]),"+r"(d[5]),"+r"(d[6]),"+r"(d[7])
    : "r"(a[0]), "r"(a[1]), "r"(a[2]), "r"(a[3]), "l"(desc), "r"(acc));
}
__device__ __forceinline__ void wgmma_p(float* d, const uint32_t* a, uint64_t desc, int acc) {
  asm volatile("{.reg .pred p; setp.ne.s32 p,%69,0;\n"
    "wgmma.mma_async.sync.aligned.m64n128k16.f32.bf16.bf16 {%0,%1,%2,%3,%4,%5,%6,%7,%8,%9,%10,%11,%12,%13,%14,%15,%16,%17,%18,%19,%20,%21,%22,%23,%24,%25,%26,%27,%28,%29,%30,%31,%32,%33,%34,%35,%36,%37,%38,%39,%40,%41,%42,%43,%44,%45,%46,%47,%48,%49,%50,%51,%52,%53,%54,%55,%56,%57,%58,%59,%60,%61,%62,%63},{%64,%65,%66,%67},%68,p,1,1,1;}"
    : "+f"(d[0]),"+f"(d[1]),"+f"(d[2]),"+f"(d[3]),"+f"(d[4]),"+f"(d[5]),"+f"(d[6]),"+f"(d[7]),"+f"(d[8]),"+f"(d[9]),"+f"(d[10]),"+f"(d[11]),"+f"(d[12]),"+f"(d[13]),"+f"(d[14]),"+f"(d[15]),"+f"(d[16]),"+f"(d[17]),"+f"(d[18]),"+f"(d[19]),"+f"(d[20]),"+f"(d[21]),"+f"(d[22]),"+f"(d[23]),"+f"(d[24]),"+f"(d[25]),"+f"(d[26]),"+f"(d[27]),"+f"(d[28]),"+f"(d[29]),"+f"(d[30]),"+f"(d[31]),"+f"(d[32]),"+f"(d[33]),"+f"(d[34]),"+f"(d[35]),"+f"(d[36]),"+f"(d[37]),"+f"(d[38]),"+f"(d[39]),"+f"(d[40]),"+f"(d[41]),"+f"(d[42]),"+f"(d[43]),"+f"(d[44]),"+f"(d[45]),"+f"(d[46]),"+f"(d[47]),"+f"(d[48]),"+f"(d[49]),"+f"(d[50]),"+f"(d[51]),"+f"(d[52]),"+f"(d[53]),"+f"(d[54]),"+f"(d[55]),"+f"(d[56]),"+f"(d[57]),"+f"(d[58]),"+f"(d[59]),"+f"(d[60]),"+f"(d[61]),"+f"(d[62]),"+f"(d[63])
    : "r"(a[0]), "r"(a[1]), "r"(a[2]), "r"(a[3]), "l"(desc), "r"(acc));
}

__device__ __forceinline__ void mma16816h(uint32_t* c, const uint32_t* a, uint32_t b0, uint32_t b1) {
  asm("mma.sync.aligned.m16n8k16.row.col.f16.f16.f16.f16 {%0,%1},{%2,%3,%4,%5},{%6,%7},{%0,%1};"
      : "+r"(c[0]), "+r"(c[1]) : "r"(a[0]), "r"(a[1]), "r"(a[2]), "r"(a[3]), "r"(b0), "r"(b1));
}
__device__ __forceinline__ void mma1688h(uint32_t* c, uint32_t a0, uint32_t a1, uint32_t b) {
  asm("mma.sync.aligned.m16n8k8.row.col.f16.f16.f16.f16 {%0,%1},{%2,%3},{%4},{%0,%1};" : "+r"(c[0]), "+r"(c[1]) : "r"(a0), "r"(a1), "r"(b));
}
__device__ __forceinline__ void mma1688f(float* c, uint32_t a0, uint32_t a1, uint32_t b) {
  asm("mma.sync.aligned.m16n8k8.row.col.f32.f16.f16.f32 {%0,%1,%2,%3},{%4,%5},{%6},{%0,%1,%2,%3};"
      : "+f"(c[0]), "+f"(c[1]), "+f"(c[2]), "+f"(c[3]) : "r"(a0), "r"(a1), "r"(b));
}
__device__ __forceinline__ uint32_t hadd2(uint32_t a, uint32_t b) { uint32_t r; asm("add.rn.f16x2 %0,%1,%2;" : "=r"(r) : "r"(a), "r"(b)); return r; }
__device__ __forceinline__ uint32_t hfma2(uint32_t a, uint32_t b, uint32_t c) { uint32_t r; asm("fma.rn.f16x2 %0,%1,%2,%3;" : "=r"(r) : "r"(a), "r"(b), "r"(c)); return r; }
__device__ __forceinline__ uint32_t pack_bf2(float lo, float hi) { uint32_t r; asm("cvt.rn.bf16x2.f32 %0,%1,%2;" : "=r"(r) : "f"(hi), "f"(lo)); return r; }
__device__ __forceinline__ uint32_t pack_h2(float lo, float hi) { uint32_t r; asm("cvt.rn.f16x2.f32 %0,%1,%2;" : "=r"(r) : "f"(hi), "f"(lo)); return r; }
__device__ __forceinline__ float bf_lo(uint32_t w) { return __uint_as_float(w << 16); }
__device__ __forceinline__ float bf_hi(uint32_t w) { return __uint_as_float(w & 0xffff0000u); }
__device__ __forceinline__ uint32_t absmax4(const uint4& v, uint32_t m) {
  return __vmaxu2(__vmaxu2(__vmaxu2(v.x & 0x7fff7fffu, v.y & 0x7fff7fffu), __vmaxu2(v.z & 0x7fff7fffu, v.w & 0x7fff7fffu)), m);
}
__device__ __forceinline__ float pow2_scale(uint32_t mbits, int p) { return __uint_as_float((uint32_t)min(max(253 + p - (int)(mbits >> 7), 2), 252) << 23); }

#define PV 4
constexpr int G_O0 = 8, G_O1 = 4, G_O2 = 0, G_N0 = 5, G_N1 = 4, G_N2 = 4, G_K0 = 5, G_K1 = 3, G_K2 = 1;
__host__ __device__ constexpr bool unit_wg(int kb, int on) {
  return (on >= G_O0 && on < G_O0 + G_N0 && kb < G_K0) || (on >= G_O1 && on < G_O1 + G_N1 && kb < G_K1) || (on >= G_O2 && on < G_O2 + G_N2 && kb < G_K2);
}
__host__ __device__ constexpr bool oct_wg(int on) { return unit_wg(0, on); }
constexpr int G_U1 = G_N0 * G_K0, G_U2 = G_U1 + G_N1 * G_K1, G_U = G_U2 + G_N2 * G_K2;
constexpr int K1_B = 130048, K1_STG = K1_B + 2 * 32768, K1_W = K1_STG + 16384, K1_BAR = K1_W + 48 * 256, K1_SMEM = K1_BAR + 256 + 6400;
__host__ __device__ constexpr int frag_index(int ok, int on) {
  int n = 0;
  for (int k = 0; k < 13; k++) for (int o = k; o < 13; o++) { if (k == ok && o == on) return n; if (!unit_wg(k >> 1, o)) n++; }
  return n;
}
constexpr int HU_N = 2 * G_U + frag_index(99, 99);
static_assert(HU_N <= 96, "");
struct FragIdx { int v[13][13]; };
__host__ __device__ constexpr FragIdx make_fi() { FragIdx f = {}; for (int k = 0; k < 13; k++) for (int o = 0; o < 13; o++) f.v[k][o] = frag_index(k, o); return f; }
__host__ __device__ constexpr uint64_t frag_tab(int first) {
  uint64_t t = 0;
  for (int k = 0; k < 13; k++) for (int o = k; o < 13; o++)
    if (!unit_wg(k >> 1, o)) { const int n = frag_index(k, o) - first; if (n >= 0 && n < 8) t |= (uint64_t)(k << 4 | o) << (8 * n); }
  return t;
}
__device__ __forceinline__ int hu_code(int hu) {
  constexpr uint64_t T0 = frag_tab(0), T1 = frag_tab(8), T2 = frag_tab(16), T3 = frag_tab(24);
  const int u = hu >> 1, f = hu - 2 * G_U;
  if (f >= 0) return (int)((f < 8 ? T0 : f < 16 ? T1 : f < 24 ? T2 : T3) >> (8 * (f & 7))) & 255;
  const int u0 = u < G_U1 ? u : u < G_U2 ? u - G_U1 : u - G_U2;
  const int kb = u < G_U1 ? u0 / G_N0 : u < G_U2 ? u0 / G_N1 : u0 / 4, on = u < G_U1 ? G_O0 + u0 % G_N0 : u < G_U2 ? G_O1 + u0 % G_N1 : G_O2 + u0 % 4;
  return (2 * kb + (hu & 1)) << 4 | on;
}

__device__ __forceinline__ void flag_wait(const unsigned* f, unsigned n) {
  unsigned v; int it = 0;
  asm volatile("ld.acquire.gpu.global.u32 %0,[%1];" : "=r"(v) : "l"(f) : "memory");
  if (v < n) {
    do { __nanosleep(300); asm volatile("ld.relaxed.gpu.global.u32 %0,[%1];" : "=r"(v) : "l"(f) : "memory"); } while (v < n && ++it < (1 << 20));
    asm volatile("ld.acquire.gpu.global.u32 %0,[%1];" : "=r"(v) : "l"(f) : "memory");
  }
}
__device__ __forceinline__ void mbar_arrive(uint32_t bar) { asm volatile("mbarrier.arrive.shared::cta.b64 _,[%0];" :: "r"(bar) : "memory"); }
__device__ __forceinline__ void mbar_arrive_lane0(uint32_t bar) {
  asm volatile("{.reg .pred p; elect.sync _|p,0xffffffff; @p mbarrier.arrive.shared::cta.b64 _,[%0];}" :: "r"(bar) : "memory");
}

__device__ __forceinline__ void arrive_both(uint32_t bar, int lane) {
  asm volatile("{.reg .pred p; .reg .u32 a; setp.lt.u32 p,%1,2; mapa.shared::cluster.u32 a,%0,%1;\n"
               "@p mbarrier.arrive.shared::cluster.b64 _,[a];}" :: "r"(bar), "r"(lane) : "memory");
}
#define ELECT "{.reg .pred p; elect.sync _|p,0xffffffff; @p "
__device__ __forceinline__ void e_mc(uint32_t dst, const void* src, uint32_t bytes, uint32_t bar, uint64_t pol) {
  asm volatile(ELECT "cp.async.bulk.shared::cluster.global.mbarrier::complete_tx::bytes.multicast::cluster.L2::cache_hint [%0],[%1],%2,[%3],%4,%5;}"
               :: "r"(dst), "l"(src), "r"(bytes), "r"(bar), "h"((unsigned short)3), "l"(pol) : "memory");
}
__device__ __forceinline__ void e_g2s(uint32_t dst, const void* src, uint32_t bytes, uint32_t bar) {
  asm volatile(ELECT "cp.async.bulk.shared::cluster.global.mbarrier::complete_tx::bytes [%0],[%1],%2,[%3];}" :: "r"(dst), "l"(src), "r"(bytes), "r"(bar) : "memory");
}
__device__ __forceinline__ void e_pf(const void* src, uint32_t bytes) { asm volatile(ELECT "cp.async.bulk.prefetch.L2.global [%0],%1;}" :: "l"(src), "r"(bytes) : "memory"); }
__device__ __forceinline__ void e_expect(uint32_t bar, uint32_t bytes) { asm volatile(ELECT "mbarrier.arrive.expect_tx.shared::cta.b64 _,[%0],%1;}" :: "r"(bar), "r"(bytes) : "memory"); }
__device__ __forceinline__ void e_tma2d(uint32_t dst, const CUtensorMap* m, int x, int y, uint32_t bar) {
  asm volatile(ELECT "cp.async.bulk.tensor.2d.shared::cluster.global.mbarrier::complete_tx::bytes [%0],[%1,{%2,%3}],[%4];}" :: "r"(dst), "l"(m), "r"(x), "r"(y), "r"(bar) : "memory");
}

__device__ __forceinline__ void pack_role(const int* __restrict__ idx, uint32_t sbase, int pc) {
  constexpr int CH = 3200 + 32, BUF = 32 * 3328;
  const int tid = threadIdx.x, lane = tid & 31, warp = tid >> 5;
  const uint32_t full = sbase + 2 * BUF, empty = full + 16;
  if (tid == 0) { mbar_init(full, 1); mbar_init(full + 8, 1); mbar_init(empty, 18); mbar_init(empty + 8, 18); asm volatile("fence.proxy.async.shared::cta;" ::: "memory"); }
  __syncthreads();
  auto chunk = [&](int s) { return s * 3200 + (s >> 2) * 288; };
  auto load = [&](int n) {
    const int blk = pc * 16 + n;
    if (lane == 0) mbar_expect(full + (n & 1) * 8, 32 * 3200);
    __syncwarp();
    bulk_g2s(sbase + (n & 1) * BUF + chunk(lane), idx + ((blk >> 5) * 8192 + lane * TH + (blk & 31) * 8) * F_, 3200, full + (n & 1) * 8);
  };
  if (warp == 0) { load(0); load(1); }
  const int l = lane & 7;
  uint32_t rot[8], inc[3];
#pragma unroll
  for (int jj = 0; jj < 8; jj++) rot[jj] = ((l + jj) & 7) * 4;
#pragma unroll
  for (int q = 0; q < 3; q++) inc[q] = (l + 3 * q < 8) << 12 | (l + 3 * q + 1 < 8) << 22 | (q < 2 && l + 3 * q + 2 < 8);
  int loaded = 2;
#pragma unroll 1
  for (int task = warp; task < 288; task += 16) {
    const int n = task / 18, q = (task % 18) * 4 + (lane >> 3), sq = q / 9, k = q % 9;
    if (warp == 0 && n + 1 == loaded && loaded < 16) { mbar_wait(empty + (loaded & 1) * 8, ((loaded >> 1) - 1) & 1); load(loaded); loaded++; }
    mbar_wait(full + (n & 1) * 8, (n >> 1) & 1);
    const uint32_t buf = sbase + (n & 1) * BUF + l * 400, row = buf + chunk(sq * 4);
    auto ld = [&](uint32_t ad) { uint32_t v; asm volatile("ld.shared.u32 %0,[%1];" : "=r"(v) : "r"(ad)); return v; };
    const int blk = pc * 16 + n, half = blk >> 5, col = (blk & 31) * 8 + l;
    const int ks = k == NC - 1 ? 0 : k + 1;
    uint32_t cw[4], sv[8], m[2] = {0, 0};
    { const uint32_t a0 = row + (72 + 2 * ks + (l >> 2)) * 4;
#pragma unroll
      for (int u = 0; u < 8; u++) { sv[u] = ld((a0 ^ ((u >> 2) * 4)) + (u & 3) * 3200); m[u >> 2] |= s_mask(sv[u], l & 3) << (8 * (u & 3)); } }
#pragma unroll
    for (int h = 0; h < 2; h++) { m[h] |= __shfl_xor_sync(0xffffffffu, m[h], 1); m[h] |= __shfl_xor_sync(0xffffffffu, m[h], 2); }
#pragma unroll
    for (int u = 0; u < 4; u++) cw[u] = s_cell(sv[u], l & 3, (m[0] >> (8 * u)) & 255) | s_cell(sv[4 + u], l & 3, (m[1] >> (8 * u)) & 255) << 12;
    if (k == NC - 1) {
      auto wide = [&](uint32_t w) { return (w & 0xfff) << 5 | (w >> 12) << 18 | (l & 4 ? 1u << 4 : 1u << 17); };
      g_scr[I0_OFF + (half * 8 + sq) * TH + col] = make_uint4(wide(cw[0]), wide(cw[1]), wide(cw[2]), wide(cw[3]));
      g_scr[IX_OFF + half * IXH + NC * 8192 + sq * TH + col] = make_uint4(ld(row + 396), ld(row + 3596), ld(row + 6796), ld(row + 9996));
      cw[0] = cw[1] = cw[2] = cw[3] = 0;
    }
    const uint32_t ax = buf + chunk(min(sq + 1, 7) * 4) + (90 + k) * 4;
    const uint32_t yev = ld(buf + ((0x3210 >> (sq * 2 + (sq == 5) * 2)) & 3) * 3200 + (90 + k) * 4);
    uint4* dst = g_scr + IX_OFF + half * IXH + (k * NS + sq * 4) * TH + col;
#pragma unroll
    for (int u = 0; u < 4; u++) {
      uint32_t e[8];
#pragma unroll
      for (int jj = 0; jj < 8; jj++) e[jj] = ld(row + k * 32 + rot[jj] + u * 3200);
      dst[u * TH] = make_uint4(pk3(e[0], e[1], e[2] + inc[0]), pk3(e[3], e[4], e[5] + inc[1]), pk3(e[6], e[7], ld(ax + u * 3200) + inc[2]),
                               u < 3 ? __byte_perm(cw[u], cw[3], 0x4210 + (u << 12)) : yev);
    }
    mbar_arrive_lane0(empty + (n & 1) * 8);
  }
  (void)CH;
}

__global__ void __cluster_dims__(2, 1, 1) __launch_bounds__(512, 1)
k_tens(const __grid_constant__ CUtensorMap mapW, const __grid_constant__ CUtensorMap mapL, const __grid_constant__ CUtensorMap mapS,
       const __grid_constant__ CUtensorMap mapT, const __grid_constant__ CUtensorMap mapE, const __grid_constant__ CUtensorMap mapC, cudaTextureObject_t tex, cudaTextureObject_t texX,
       const int* __restrict__ idx, const __nv_bfloat16* __restrict__ table, const __nv_bfloat16* __restrict__ wp, const __nv_bfloat16* __restrict__ w1,
       const __nv_bfloat16* __restrict__ b1, int never) {
  extern __shared__ __align__(1024) uint4 sm[];
  const int tid = threadIdx.x, lane = tid & 31, cta = blockIdx.x;
  const uint32_t sbase = (uint32_t)__cvta_generic_to_shared(sm);
  const int g = lane >> 2, r = lane & 3;
  TS(0, 0);
  if (cta >= 128) {
    pack_role(idx, sbase, cta - 128);
    __syncthreads();
    if (tid == 0) {
      asm volatile("fence.acq_rel.gpu; griddepcontrol.launch_dependents;" ::: "memory");
      asm volatile("red.relaxed.gpu.global.add.u32 [%0],1;" :: "l"(&g_flag[24 * 32]) : "memory");
    }
    __syncwarp();
    TS(2, 1);
    asm volatile("barrier.cluster.arrive.relaxed.aligned; barrier.cluster.wait.aligned;" ::: "memory");
    return;
  }
  const uint32_t fullB = sbase + K1_BAR, emptyB = fullB + 24, fullE = fullB + 48, fullC = fullB + 56, fullI = fullB + 64, pxRdy = fullB + 72, fullS = fullB + 96, emptyS = fullB + 104, pkDone = fullB + 112, pkFull = fullB + 136, progG = fullB + 168;
  const int rb = cta & 7, hc = cta >> 3;
  if (__shfl_sync(0xffffffffu, tid >> 5, 0) == 12) {
    if (lane == 0) {
#pragma unroll
      for (int q = 0; q < 19; q++) if (q != 2 && q != 5) mbar_init(fullB + q * 8, q == 3 || q == 4 ? 8 : q == 12 ? 4 : q >= 14 && q < 17 ? 2 : 1);
      asm volatile("st.shared.u32 [%0],%1;" :: "r"(progG), "r"(0) : "memory");
    }
    asm volatile("fence.mbarrier_init.release.cluster; fence.proxy.async.shared::cta;" ::: "memory");
    __syncwarp();
    e_expect(fullC, 16384);
#pragma unroll
    for (int q = 0; q < 4; q++) e_tma2d(sbase + 32768 + q * 4096, &mapC, (cta & 15) * 8, q * 256, fullC);
    e_expect(fullE, 32768);
#pragma unroll
    for (int q = 0; q < 2; q++) e_tma2d(sbase + K1_B + 32768 + q * 16384, &mapE, q * 64, rb * 128, fullE);
    asm volatile("bar.arrive 2,512;" ::: "memory");
  }
  asm volatile("barrier.cluster.arrive.relaxed.aligned;" ::: "memory");
  if (tid >= 384) {
    asm volatile("setmaxnreg.dec.sync.aligned.u32 " RAUX ";");
    if (tid < 416) {
      asm volatile("barrier.cluster.wait.aligned;" ::: "memory");
      if (tid == 384) {
#pragma unroll 1
        for (int n = 0; n < 25; n++) {
          const int st = n & 1, q = QORD(n);
          if (n == IORD) {
            mbar_expect(fullI, 51200);
#pragma unroll 1
            for (int u = 0; u < 8; u++) bulk_g2s(sbase + 76800 + u * 6400, idx + ((cta >> 4) * 8 + u) * 256 * F_, 6400, fullI);
          }
          mbar_wait(emptyB + st * 8, (((n + 1) >> 1) & 1) ^ 1);
          mbar_expect(fullB + st * 8, 32768);
          asm volatile("cp.async.bulk.tensor.2d.shared::cluster.global.mbarrier::complete_tx::bytes.multicast::cluster [%0],[%1,{%2,%3}],[%4],%5;"
                       :: "r"(sbase + K1_B + st * 32768 + (cta & 1) * 16384), "l"(&mapW), "r"(hc * 32), "r"(q * 512 + (cta & 1) * 256),
                          "r"(fullB + st * 8), "h"((unsigned short)3) : "memory");
          if (n == 0) for (int u = 1; u < WPF; u++) bulk_pf(w1 + QORD(u) * 262144 + cta * 2048, 4096);
          if (WPF && n + WPF < 25) bulk_pf(w1 + QORD(n + WPF) * 262144 + cta * 2048, 4096);
        }
      }
    } else if (tid < 448) {
      ((float4*)g_acc)[cta * 32 + lane] = make_float4(0.f, 0.f, 0.f, 0.f);
      asm volatile("bar.sync 2,512;" ::: "memory");
      __syncwarp();
      if (tid == 416) {
        int pub = 0;
#pragma unroll 1
        for (int n = 0; n < 50; n++) {
          const int quad = QORD(n >> 1), mt = n & 1, v0 = rb * 128 + mt * 64;
          const uint32_t stg = sbase + K1_STG;
          const uint64_t pol = n < 2 * NEF ? POL_EF : POL_N;
          if (pub < 3) {
            uint32_t ok = 1;
            if (pub == 0 || n == 49) mbar_wait(pkDone + pub * 8, 0);
            else asm volatile("{.reg .pred p; mbarrier.test_wait.parity.shared::cta.b64 p,[%1],0; selp.u32 %0,1,0,p;}" : "=r"(ok) : "r"(pkDone + pub * 8) : "memory");
            if (ok) {
              asm volatile("cp.async.bulk.wait_group 0;" ::: "memory");
              asm volatile("red.release.gpu.global.add.u32 [%0],1;" :: "l"(&g_flag[((cta >> 4) * 3 + pub) * 32]) : "memory");
              pub++;
              if (n == 49) { n--; continue; }
            }
          }
          mbar_wait(fullS, n & 1);
          asm volatile("fence.proxy.async.shared::cta;" ::: "memory");
          if (quad < 18) {
            asm volatile("cp.async.bulk.tensor.4d.global.shared::cta.bulk_group.L2::cache_hint [%0,{%1,%2,%3,%4}],[%5],%6;"
                         :: "l"(&mapL), "r"((quad & 1) * 32), "r"(hc * 4), "r"(v0), "r"(quad >> 1), "r"(stg), "l"(pol) : "memory");
          } else {
#pragma unroll 1
            for (int hh = 0; hh < 2; hh++) {
              const int pq = quad * 2 + hh;
              asm volatile("cp.async.bulk.tensor.4d.global.shared::cta.bulk_group.L2::cache_hint [%0,{%1,%2,%3,%4}],[%5],%6;"
                         :: "l"(pq < 45 ? &mapS : &mapT), "r"(0), "r"(hc * 4), "r"(v0 >> (pq < 45 ? 2 : 3)), "r"(pq < 45 ? pq - 36 : (pq - 45) * 2), "r"(stg + hh * 8192), "l"(pol) : "memory");
            }
          }
          asm volatile("cp.async.bulk.commit_group;" ::: "memory");
          asm volatile("cp.async.bulk.wait_group.read 0;" ::: "memory");
          mbar_arrive(emptyS);
        }
        asm volatile("cp.async.bulk.wait_group 0;" ::: "memory");
        asm volatile("fence.proxy.async.global;" ::: "memory");
        asm volatile("fence.acq_rel.gpu; griddepcontrol.launch_dependents;" ::: "memory");
        asm volatile("red.relaxed.gpu.global.add.u32 [%0],1;" :: "l"(&g_flag[24 * 32]) : "memory");
        flag_wait(&g_flag[24 * 32], 132);
        asm volatile("fence.proxy.async.global;" ::: "memory");
        const char* base = (const char*)g_scr;
        const int c = cta >> 1, half = cta & 1, ch = (c + (c >> 4) * 5) & 15;
        bulk_pf(base + (PS_OFF + c * NC * 2000) * 16u + half * 16000, 16000);
        if (PREW & 2) bulk_pf(base + (PL_OFF + c * NC * 8000) * 16u + half * 64000, 64000);
        bulk_pf(base + (PT_OFF + c * 10 * 1024) * 16u + half * 8192, 8192);
        mbar_expect(fullE, 18432);
        bulk_g2s(sbase + K1_B, base + (I0_OFF + half * 2048 + ch * 128) * 16u, 2048, fullE);
        bulk_g2s(sbase + K1_B + 2048, base + (IX_OFF + half * IXH + ch * 512) * 16u, 8192, fullE);
        bulk_g2s(sbase + K1_B + 10240, base + (IX_OFF + half * IXH + 8192 + ch * 512) * 16u, 8192, fullE);
        mbar_wait(fullE, 1);
      }
    } else {
      const int pw = (tid >> 5) & 1, rg = (cta >> 4) * 8 + ((cta & 15) >> 1), hf = cta & 1;
      const int* ip = idx + (rg * 256 + hf * 8) * F_;
      asm volatile("bar.sync 2,512;" ::: "memory");
      const uint32_t buf = sbase + K1_BAR + 256 + pw * 3200, bar = pkFull + pw * 8;
      const unsigned* fl = &g_flag[(cta >> 4) * 96];
      int batch = 0, rel = pw ? 3 : 0;
#pragma unroll 1
      for (int n = 1 + pw; n < 16; n += 2) {
        if (lane == 0) { mbar_expect(bar, 3200); bulk_g2s(buf, ip + n * 16 * F_, 3200, bar); if (n + 2 < 16) bulk_pf(ip + (n + 2) * 16 * F_, 3200); }
        uint32_t ok; int it = 0;
        do {
          if (rel < batch) {
            unsigned v; asm volatile("ld.relaxed.gpu.global.u32 %0,[%1];" : "=r"(v) : "l"(fl + rel * 32) : "memory");
            if (__all_sync(0xffffffffu, v >= 16)) { flag_wait(fl + rel * 32, 16); __syncwarp(); mbar_arrive_lane0(pxRdy + rel * 8); rel++; }
          }
          asm volatile("{.reg .pred p; mbarrier.test_wait.parity.shared::cta.b64 p,[%1],%2; selp.u32 %0,1,0,p;}" : "=r"(ok) : "r"(bar), "r"(((n - 1) >> 1) & 1) : "memory");
          ok = __all_sync(0xffffffffu, ok);
          if (!ok) __nanosleep(100);
        } while (!ok && ++it < (1 << 20));
        auto ld = [&](uint32_t ad) { uint32_t v; asm volatile("ld.shared.u32 %0,[%1];" : "=r"(v) : "r"(ad)); return v; };
        const uint32_t p0 = buf + ((lane >> 3) & 1) * 400 + ((lane >> 4) * 8 + (lane & 7)) * 4;
        auto wd = [&](int t, int h) { return pk3(ld(p0 + t * 800 + h * 192), ld(p0 + t * 800 + h * 192 + 64), ld(p0 + t * 800 + h * 192 + 128)); };
        uint4* dst = g_scr + PX_OFF + (rg * 16 + n) * 136;
        ((unsigned short*)(dst + 128))[lane * 2 + hf] = ld(buf + g * 400 + 384 + r * 4);
#pragma unroll
        for (int q = 0; q < 2; q++) dst[(hf * 2 + q) * 32 + lane] = make_uint4(wd(2 * q, 0), wd(2 * q, 1), wd(2 * q + 1, 0), wd(2 * q + 1, 1));
        __syncwarp();
        if (n <= 2 || n == 5 || n == 6 || n >= 14) { mbar_arrive_lane0(pkDone + batch * 8); batch++; }
      }
      for (; rel < 3; rel++) { flag_wait(fl + rel * 32, 16); __syncwarp(); mbar_arrive_lane0(pxRdy + rel * 8); }
      if (PXW && lane == 0) {
        mbar_wait(pxRdy + 16, 0);
        asm volatile("fence.proxy.async.global;" ::: "memory");
        const char* src = (const char*)(g_scr + PX_OFF + ((cta >> 4) * 8 + ((cta >> 1) & 3) * 2 + pw) * 16 * 136);
        int ph = pw;
#pragma unroll 1
        for (int n = PXW0; n < 16; n++) {
          uint32_t cur; int it = 0;
          do { asm volatile("ld.volatile.shared.u32 %0,[%1];" : "=r"(cur) : "r"(progG)); if (cur + PXW < n) __nanosleep(400); } while (cur + PXW < n && ++it < (1 << 16));
          if (cur + 1 >= n) continue;
          mbar_expect(bar, 2176); bulk_g2s(buf, src + n * 2176, 2176, bar);
          mbar_wait(bar, ph); ph ^= 1;
        }
      }
    }
    return;
  }
  if (tid >= 256) {
    asm volatile("setmaxnreg.inc.sync.aligned.u32 " RPRO ";");
    const int w = (tid >> 5) & 3;
    const int srow = w * 16 + ((lane & 15) ^ ((lane & 1) << 2)), sc = lane >> 4;
    uint32_t a[2][8][4];
    asm volatile("bar.sync 2,512;" ::: "memory");
    mbar_wait_fast(fullE, 0);
#pragma unroll
    for (int mt = 0; mt < 2; mt++)
#pragma unroll
      for (int ks = 0; ks < 8; ks++)
        asm volatile("ldmatrix.sync.aligned.m8n8.x4.shared.b16 {%0,%1,%2,%3},[%4];"
                     : "=r"(a[mt][ks][0]), "=r"(a[mt][ks][1]), "=r"(a[mt][ks][2]), "=r"(a[mt][ks][3])
                     : "r"(sbase + K1_B + 32768 + (ks >> 2) * 16384 + (mt * 64 + srow) * 128 + ((((ks & 3) * 2 + sc) ^ (srow & 7)) * 16)) : "memory");
    asm volatile("barrier.cluster.wait.aligned;" ::: "memory");
    arrive_both(emptyB + 8, lane);
    const int v = w * 16 + (g ^ ((g & 1) << 2));
    const uint32_t baseL = v * 256 + r * 64 + ((v & 1) * 2 + (r >> 1)) * 16, baseS = (v >> 2) * 512 + r * 128 + (((v & 3) * 2) ^ ((v & 4) + r)) * 16,
                   baseT = (v >> 3) * 512 + r * 128 + ((v & 7) ^ r) * 16;
    const uint64_t desc0 = (uint64_t)(((sbase + K1_B) & 0x3FFFF) >> 4) | ((uint64_t)(8192 >> 4) << 16) | ((uint64_t)(512 >> 4) << 32) | (2ull << 62);
#pragma unroll 1
    for (int qn = 0; qn < 25; qn++) {
      const int quad = QORD(qn), st = qn & 1;
      const bool isL = quad < 18;
      PT(qn * 16);
      mbar_wait_fast(fullB + st * 8, (qn >> 1) & 1);
#pragma unroll
      for (int mt = 0; mt < 2; mt++) {
        float d[64];
        PT(qn * 16 + mt * 4 + 1);
        asm volatile("wgmma.fence.sync.aligned;" ::: "memory");
#pragma unroll
        for (int ks = 0; ks < 8; ks++) wgmma_p(d, a[mt][ks], desc0 + st * 2048 + ks * 64, ks);
        asm volatile("wgmma.commit_group.sync.aligned;" ::: "memory");
        mbar_wait_fast(emptyS, mt ^ 1);
        PT(qn * 16 + mt * 4 + 2);
        asm volatile("wgmma.wait_group.sync.aligned 0;" ::: "memory");
#pragma unroll
        for (int q = 0; q < 16; q++) asm volatile("" : "+f"(d[q * 4]), "+f"(d[q * 4 + 1]), "+f"(d[q * 4 + 2]), "+f"(d[q * 4 + 3]) :: "memory");
        PT(qn * 16 + mt * 4 + 3);
        if (mt) arrive_both(emptyB + st * 8, qn < 23 ? lane : 9);
        if (quad == 24) {
#pragma unroll
          for (int cq = 0; cq < 4; cq++) {
            const uint32_t bw = __ldg((const uint32_t*)(b1 + hc * 32 + cq * 8) + r);
#pragma unroll
            for (int e = 0; e < 4; e++) d[48 + cq * 4 + e] += (e & 1) ? bf_hi(bw) : bf_lo(bw);
          }
        }
#pragma unroll
        for (int h = 0; h < 2; h++) {
          const bool isS = quad * 2 + h < 45;
          const uint32_t base = (isL ? baseL ^ (h * 32) : (isS ? baseS : baseT) ^ (h * 8192)), xj = isS ? 16 : 4096, xr = isL ? 2048 : isS ? 1024 : 576;
#pragma unroll
          for (int e4 = 0; e4 < 4; e4++) {
            const float* e = d + h * 32 + (e4 >> 1) * 16 + (e4 & 1) * 2;
            sts128(sbase + K1_STG + (base ^ ((e4 >> 1) * xj) ^ ((e4 & 1) * xr)),
                   make_uint4(pack_bf2(e[0], e[1]), pack_bf2(e[4], e[5]), pack_bf2(e[8], e[9]), pack_bf2(e[12], e[13])));
          }
        }
        __syncwarp();
        mbar_arrive_lane0(fullS);
        if (!mt) PT(qn * 16 + 4);
      }
      PT(qn * 16 + 8);
    }
    return;
  }
  const int slice = cta & 15;
  const int range = (cta >> 4) * 8 + __shfl_sync(0xffffffffu, tid >> 5, 0);
  uint4 iv[4], trow[4]; uint32_t ix;
  uint2 wrow[10];
#pragma unroll
  for (int q = 0; q < 10; q++) asm volatile("ld.global.nc.v2.u32 {%0,%1},[%2];" : "=r"(wrow[q].x), "=r"(wrow[q].y) : "l"((const uint2*)wp + min(tid + q * 256, 2499)));
  asm volatile("bar.sync 2,512;" ::: "memory");
  uint32_t me = 0, mw = 0;
#pragma unroll
  for (int q = 0; q < 10; q++) {
    mw = __vmaxu2(__vmaxu2(wrow[q].x & 0x7fff7fffu, wrow[q].y & 0x7fff7fffu), mw);
    const int e = min(tid + q * 256, 2499), row = e / 25;
    asm volatile("st.shared.v2.u32 [%0],{%1,%2};" :: "r"(sbase + (e + row) * 8), "r"(wrow[q].x), "r"(wrow[q].y) : "memory");
    if (e - row * 25 == 24) asm volatile("st.shared.v2.u32 [%0],{%1,%2};" :: "r"(sbase + (e + row) * 8 + 8), "r"(wrow[q].x), "r"(wrow[q].y) : "memory");
  }
  mbar_wait_fast(fullC, 0);
#pragma unroll
  for (int q = 0; q < 4; q++) { trow[q] = lds128(sbase + 32768 + (tid + q * 256) * 16); me = absmax4(trow[q], me); }
  me = __reduce_max_sync(0xffffffffu, max(me & 0xffff, me >> 16));
  mw = __reduce_max_sync(0xffffffffu, max(mw & 0xffff, mw >> 16));
  uint32_t* sred = (uint32_t*)((char*)sm + 128000);
  if (lane == 0) sred[tid >> 5] = me | mw << 16;
  TS(3, 0);
  asm volatile("setmaxnreg.inc.sync.aligned.u32 " RPNN ";");
  asm volatile("bar.sync 1,256;" ::: "memory");
  { uint32_t m = 0;
#pragma unroll
    for (int q = 0; q < 8; q++) m = __vmaxu2(m, sred[q]);
    m = __shfl_sync(0xffffffffu, m, 0);
    me = m & 0xffff; mw = m >> 16; }
  const float se = pow2_scale(me, 3), sW = pow2_scale(mw, -2);
  TS(3, 1);
  auto put_rows = [&](int q, bool on) {
    const uint4 t = trow[q];
    const uint4 hv = make_uint4(pack_h2(bf_lo(t.x) * se, bf_hi(t.x) * se), pack_h2(bf_lo(t.y) * se, bf_hi(t.y) * se),
                                pack_h2(bf_lo(t.z) * se, bf_hi(t.z) * se), pack_h2(bf_lo(t.w) * se, bf_hi(t.w) * se));
    if (on)
#pragma unroll
      for (int s = 0; s < 8; s++) sts128(sbase + (tid + q * 256) * 128 + ((s + lane) & 7) * 16, hv);
  };
#pragma unroll 1
  for (int it = 0; it < 3; it++) {
    const int hu = ((tid >> 5) * 3 + it) * 4, code = hu_code(min(hu + (lane >> 3), HU_N - 1)), ok = code >> 4, on = code & 15;
    uint32_t x[4], y[4];
    asm volatile("ldmatrix.sync.aligned.m8n8.x4.shared.b16 {%0,%1,%2,%3},[%4];" : "=r"(x[0]), "=r"(x[1]), "=r"(x[2]), "=r"(x[3])
                 : "r"(sbase + (on * 8 + (lane & (on == 12 ? 3 : 7))) * 208 + ok * 16) : "memory");
    asm volatile("ldmatrix.sync.aligned.m8n8.x4.trans.shared.b16 {%0,%1,%2,%3},[%4];" : "=r"(y[0]), "=r"(y[1]), "=r"(y[2]), "=r"(y[3])
                 : "r"(sbase + (ok * 8 + (lane & (ok == 12 ? 3 : 7))) * 208 + on * 16) : "memory");
    const uint32_t lo = __ballot_sync(0xffffffffu, ok > on), dg = __ballot_sync(0xffffffffu, ok >= on);
#pragma unroll
    for (int q = 0; q < 4; q++) {
      const float m0 = (lo >> (8 * q)) & 1 ? 0.f : sW, m1 = (dg >> (8 * q)) & 1 ? 0.f : sW;
      asm volatile("st.shared.u32 [%0],%1;" :: "r"(sbase + K1_W + (hu + q) * 128 + lane * 4),
                   "r"(pack_h2(fmaf(bf_lo(x[q]), m0, bf_lo(y[q]) * m1), fmaf(bf_hi(x[q]), m0, bf_hi(y[q]) * m1))) : "memory");
    }
  }
  put_rows(1, true); put_rows(2, tid < 88);
  TS(3, 2);
  asm volatile("fence.proxy.async.shared::cta;" ::: "memory");
  asm volatile("bar.sync 1,256;" ::: "memory");
  put_rows(0, true);
  uint32_t bf[HU_N - 2 * G_U];
#pragma unroll
  for (int q = 0; q < HU_N - 2 * G_U; q++) asm volatile("ld.shared.u32 %0,[%1];" : "=r"(bf[q]) : "r"(sbase + K1_W + (2 * G_U + q) * 128 + lane * 4));
  const float unscale = __uint_as_float(0x7f000000u - __float_as_uint(se)), unscale2 = __uint_as_float(0x7f000000u - __float_as_uint(sW));
  TS(3, 3);
  const int px = range * 16 * 136;
  mbar_wait_fast(fullI, 0);
  {
    const uint32_t ib = sbase + 76800 + (tid >> 5) * 6400, p0 = ib + ((lane >> 3) & 1) * 400 + ((lane >> 4) * 8 + (lane & 7)) * 4;
    auto ld = [&](uint32_t ad) { uint32_t v; asm volatile("ld.shared.u32 %0,[%1];" : "=r"(v) : "r"(ad)); return v; };
    auto wd = [&](int t, int h) { return pk3(ld(p0 + t * 800 + h * 192), ld(p0 + t * 800 + h * 192 + 64), ld(p0 + t * 800 + h * 192 + 128)); };
#pragma unroll
    for (int q = 0; q < 4; q++) {
      iv[q] = make_uint4(wd(2 * q, 0), wd(2 * q, 1), wd(2 * q + 1, 0), wd(2 * q + 1, 1));
    }
    ix = ld(ib + g * 400 + 384 + r * 4) | ld(ib + (8 + g) * 400 + 384 + r * 4) << 16;
  }
  asm volatile("bar.sync 1,256;" ::: "memory");
  put_rows(2, tid >= 88); put_rows(3, tid + 768 < V_);
  asm volatile("bar.sync 1,256;" ::: "memory");
  TS(0, 1);
  uint32_t lc; asm volatile("add.u32 %0,%1,%2;" : "=r"(lc) : "r"((lane & 7) * 16), "r"(never));
  const uint64_t wdesc = (uint64_t)(((sbase + K1_W) & 0x3FFFF) >> 4) | ((uint64_t)(128 >> 4) << 16) | ((uint64_t)(256 >> 4) << 32);
  uint32_t a[2][6][4], d[2][26], ex[4] = {}, s[4] = {};
  float red[4] = {0.f, 0.f, 0.f, 0.f};
  auto ldsm = [&](uint32_t* o, uint32_t sh, uint32_t dep = 0) {
    asm volatile("ldmatrix.sync.aligned.m8n8.x4.trans.shared.b16 {%0,%1,%2,%3},[%4];"
                 : "=r"(o[0]), "=r"(o[1]), "=r"(o[2]), "=r"(o[3]) : "r"(sbase + ((sh & 0x1ff80) | (lc | (dep & never)))));
  };
  auto gather = [&](int t, int hf) {
    const int x = t & 1;
    const uint4 v = iv[(t >> 1) & 3];
#pragma unroll
    for (int kb = 3 * hf; kb < 3 * hf + 3; kb++) {
      const uint32_t ww = x ? (kb < 3 ? v.z : v.w) : (kb < 3 ? v.x : v.y);
      ldsm(a[x][kb], kb % 3 == 0 ? ww : kb % 3 == 1 ? ww >> 10 : __funnelshift_l(ww, ww, 12));
    }
  };
  auto issue = [&](int x) {
    asm volatile("wgmma.fence.sync.aligned;" ::: "memory");
#pragma unroll
    for (int kb = 0; kb < 6; kb++) {
      if (kb < G_K0) wgmma_h<G_N0 * 8>(d[x] + G_O0 * 2, a[x][kb], wdesc + kb * G_N0 * 16, kb);
      if (kb < G_K1) wgmma_h<G_N1 * 8>(d[x] + G_O1 * 2, a[x][kb], wdesc + (G_U1 + kb * G_N1) * 16, kb);
      if (kb < G_K2) wgmma_h<32>(d[x] + G_O2 * 2, a[x][kb], wdesc + (G_U2 + kb * G_N2) * 16, kb);
    }
    asm volatile("wgmma.commit_group.sync.aligned;" ::: "memory");
  };
  auto hmma_part = [&](int t) {
    constexpr FragIdx FI = make_fi();
    const int x = t & 1;
#pragma unroll
    for (int o = 0; o < 13; o++) {
      if (oct_wg(o)) asm volatile("" : "+r"(d[x][o * 2]), "+r"(d[x][o * 2 + 1]) :: "memory"); else d[x][o * 2] = d[x][o * 2 + 1] = 0;
    }
#pragma unroll
    for (int kb = 0; kb < 6; kb++)
#pragma unroll
      for (int o = 2 * kb + 1; o < 13; o++)
        if (!unit_wg(kb, o)) mma16816h(d[x] + o * 2, a[x][kb], bf[FI.v[2 * kb][o]], bf[FI.v[2 * kb + 1][o]]);
#pragma unroll
    for (int q = 0; q < 6; q++) if (!unit_wg(q, 2 * q)) mma1688h(d[x] + q * 4, a[x][q][0], a[x][q][1], bf[FI.v[2 * q][2 * q]]);
    mma1688h(d[x] + 24, r < 2 ? ex[t & 3] : 0u, r < 2 ? 0u : ex[t & 3], bf[FI.v[12][12]]);
  };
  auto dot_part = [&](int t, int hf) {
    const int x = t & 1;
    if (hf == 0) {
      const uint32_t pe = hfma2(r < 2 ? d[x][24] : d[x][25], ex[t & 3], 0u);
      s[0] = r < 2 ? pe : 0u; s[1] = r < 2 ? 0u : pe; s[2] = s[3] = 0;
    }
#pragma unroll
    for (int q = 3 * hf; q < 3 * hf + 3; q++)
#pragma unroll
      for (int e = 0; e < 4; e++) s[e] = hfma2(d[x][q * 4 + e], a[x][q][e], s[e]);
  };
  float* outp = g_partP + slice * B_ + range * 256;
  float k0 = 0.f, k1 = 0.f, x0 = 0.f, x1 = 0.f;
  auto red_stage = [&](int st, int grp) {
    const bool u16 = lane & 16, u8 = lane & 8;
    if (st == 0) {
      k0 = u16 ? red[2] : red[0]; x0 = __shfl_xor_sync(0xffffffffu, u16 ? red[0] : red[2], 16);
      k1 = u16 ? red[3] : red[1]; x1 = __shfl_xor_sync(0xffffffffu, u16 ? red[1] : red[3], 16);
      red[0] = red[1] = red[2] = red[3] = 0.f;
    }
    if (st == 1) { const float p0 = k0 + x0, p1 = k1 + x1; k0 = u8 ? p1 : p0; x0 = __shfl_xor_sync(0xffffffffu, u8 ? p0 : p1, 8); }
    if (st == 2) { k0 += x0; x0 = __shfl_xor_sync(0xffffffffu, k0, 4); }
    if (st == 3 && !(lane & 4)) outp[grp * 16 + r * 4 + ((lane >> 3) & 1) * 2 + (lane >> 4)] = (k0 + x0) * unscale * unscale * unscale2;
  };
  auto group = [&](bool first, int prv, int cur, int nxt) {
    const int pn = PX_OFF + px + nxt * 136 + lane;
#pragma unroll
    for (int t = 0; t < 8; t++) {
      issue((t & 1) ^ 1);
      SCHED_FENCE(never, t * 8);
      if (!first) {
        if (t == 0) { iv[3] = ldtex(tex, PX_OFF + px + cur * 136 + lane + 96); iv[0] = ldtex(tex, pn); }
        if (t == 2) iv[1] = ldtex(tex, pn + 32);
        if (t < 4) red_stage(t, prv);
      } else if (t == 4) {
        TS(4, 2);
        mbar_wait_fast(pxRdy, 0);
        TS(4, 3);
        iv[0] = ldtex(tex, pn); iv[1] = ldtex(tex, pn + 32);
      }
      if (t == 4) { ix = ldtex(texX, (px + nxt * 136 + 128) * 4 + lane).x; iv[2] = ldtex(tex, pn + 64); }
      dot_part(t, 0);
      SCHED_FENCE(never, t * 8 + 1);
      if (t == 3) ldsm(ex, ix >> 9);
      if (t == 7) ldsm(ex, ix << 7);
      gather(t + 2, 0);
      dot_part(t, 1);
      SCHED_FENCE(never, t * 8 + 4);
      gather(t + 2, 1);
      asm volatile("wgmma.wait_group.sync.aligned 0;" ::: "memory");
      if (FM & 1) SCHED_FENCE(never, t * 8 + 2);
      asm volatile("" : "+r"(d[(t & 1) ^ 1][0]) :: "memory");
      mma1688f(red, hadd2(s[0], s[2]), hadd2(s[1], s[3]), (g | (d[(t & 1) ^ 1][0] & never)) == t ? 0x3c003c00u : 0u);
      hmma_part(t + 1);
      if (FM & 2) SCHED_FENCE(never, t * 8 + 3);
    }
  };
  gather(0, 0); gather(0, 1); issue(0); ldsm(ex, ix << 7); gather(1, 0); gather(1, 1);
  asm volatile("wgmma.wait_group.sync.aligned 0;" ::: "memory");
  hmma_part(0);
  group(true, 0, 0, 1);
  TS(4, 1);
#pragma unroll 1
  for (int n = 1; n < NGRP; n++) {
    if ((n & 11) == 2) mbar_wait_fast(pxRdy + 8 + (n & 4) * 2, 0);
    if (PXW) asm volatile("st.volatile.shared.u32 [%0],%1;" :: "r"(progG), "r"(n) : "memory");
    group(false, n - 1, n, min(n + 1, 15));
  }
#pragma unroll
  for (int st = 0; st < 4; st++) red_stage(st, 15);
  TS(0, 2);
  asm volatile("barrier.cluster.wait.aligned;" ::: "memory");
  asm volatile("barrier.cluster.arrive.relaxed.aligned; barrier.cluster.wait.aligned;" ::: "memory");
}

constexpr int SM_U = 130048, SM_BAR = 128000, SM_J = SM_U + 98304, DEEP_SMEM = SM_J + 4096;

__global__ void __cluster_dims__(2, 1, 1) __launch_bounds__(TH + 128, 1)
k_deep(cudaTextureObject_t tex, const __nv_bfloat16* __restrict__ w2, const __nv_bfloat16* __restrict__ b2,
       __nv_bfloat16* __restrict__ out, int never) {
  extern __shared__ __align__(1024) uint4 sm[];
  constexpr int PF = DPF, DEPTH = DDEPTH, NW = TH / 32;
  static_assert(YD == 4 && PF == 4, "");
  const int tid = threadIdx.x;
  const int c = blockIdx.x >> 1, half = blockIdx.x & 1;
  const uint32_t sbase = (uint32_t)__cvta_generic_to_shared(sm);
  const uint32_t fullL = sbase + SM_BAR, fullU = fullL + 8, emptyL = fullL + 16, emptyU = fullL + 24, barJ = fullL + 32;
  TS(1, 0);
  if (tid == 0) {
    mbar_init(fullL, 1); mbar_init(fullU, 1); mbar_init(emptyL, 2 * NW); mbar_init(emptyU, 2 * NW); mbar_init(barJ, 1);
    asm volatile("fence.mbarrier_init.release.cluster;" ::: "memory");
  }
  __syncwarp();
  const int wrp = __shfl_sync(0xffffffffu, tid >> 5, 0);
  const char* base = (const char*)g_scr;
  uint32_t oL = (PL_OFF + c * NC * 8000) * 16u + half * 64000, oS = (PS_OFF + c * NC * 2000) * 16u + half * 16000;
  asm volatile("barrier.cluster.arrive.relaxed.aligned; barrier.cluster.wait.aligned;" ::: "memory");
  if (wrp == NW) {
    asm volatile("fence.proxy.async.global;" ::: "memory");
    e_expect(fullU, 96000);
#pragma unroll
    for (int m = 0; m < 3; m++) e_mc(sbase + SM_U + m * 32032 + half * 16000, base + oS, 16000, fullU, m == 2 ? POL_EF : POL_N);
    e_expect(fullL, 128000);
    if (!STAG) e_mc(sbase + half * 64000, base + oL, 64000, fullL, POL_EF);
  }
  TS(5, 1);
  if (wrp >= NW) {
    asm volatile("setmaxnreg.dec.sync.aligned.u32 24;");
    if (wrp == NW) {
      uint32_t oT = (PT_OFF + c * 10 * 1024) * 16u + half * 8192;
      const uint32_t junk = sbase + SM_J, oW = (IX_OFF + half * IXH + ((c + (c >> 4) * 5) & 15) * 512) * 16u;
      auto warm = [&](uint32_t off) {
        asm volatile(ELECT "mbarrier.expect_tx.relaxed.cta.shared::cta.b64 [%0],%1;}" :: "r"(barJ), "r"(8192) : "memory");
        e_g2s(junk, base + off, 4096, barJ); e_g2s(junk, base + off + 4096, 4096, barJ);
      };
      uint32_t t0 = clock();
      if (!PREW) warm(oW);
      if (STAG) { if (STAG == 1) mbar_wait(fullU, 0); else sleep_until(t0, STAG); e_mc(sbase + half * 64000, base + oL, 64000, fullL, POL_EF); }
      warm(oT);
      if (!(PREW & 4)) warm(oW + 131072);
#pragma unroll 1
      for (int k = 0; k + 1 < NC; k++) {
        oL += 128000; oS += 32000; oT += 16384;
        mbar_wait(fullL, k & 1);
        t0 = clock();
        e_pf(base + oS, 16000);
        warm((IX_OFF + half * IXH + (k + 2) * 8192 + ((c + (c >> 4) * (2 * k + 1)) & (k + 2 < NC ? 15 : 3)) * 512) * 16u);
        mbar_wait(emptyU, k & 1);
        e_expect(fullU, 96000);
#pragma unroll 1
        for (int q = 0; q < 8; q++) {
          sleep_until(t0, q * PACE);
          e_pf(base + oL + q * 8000, 8000);
          if (q >= 2) e_mc(sbase + SM_U + ((q - 2) >> 1) * 32032 + half * 16000 + (q & 1) * 8000, base + oS + (q & 1) * 8000, 8000, fullU, q >= 6 ? POL_EF : POL_N);
        }
        warm(oT);
        e_expect(fullL, 128000);
        sleep_until(t0, RSV_T);
        unsigned long long now, slot = 0;
        asm volatile("mov.u64 %0,%globaltimer;" : "=l"(now));
        if ((tid & 31) == 0) { atomicMax(&g_slot, now + RSV_L); slot = atomicAdd(&g_slot, (unsigned long long)RSV); }
        slot = __shfl_sync(0xffffffffu, slot, 0);
        mbar_wait(emptyL, k & 1);
        for (int it = 0; it < 4000; it++) { asm volatile("mov.u64 %0,%globaltimer;" : "=l"(now)); if (now >= slot) break; }
        e_mc(sbase + half * 64000, base + oL, 64000, fullL, POL_EF);
      }
      mbar_wait(fullL, (NC - 1) & 1);
      mbar_wait(emptyU, (NC - 1) & 1);
      mbar_arrive_lane0(fullU);
      warm(oT + 16384);
      mbar_arrive_lane0(barJ); mbar_wait(barJ, 0);
    } else if (tid >= TH + 96) {
      if (tid < TH + 100) asm volatile("st.shared.u32 [%0],%1;" :: "r"(barJ + 32 + (tid & 3) * 4), "r"(((const uint32_t*)w2)[(c >> 2) * 16 + (tid & 3) * 4 + (c & 3)]) : "memory");
      asm volatile("bar.arrive 3,%0;" :: "n"(TH + 32) : "memory");
      asm volatile("griddepcontrol.wait;" ::: "memory");
      const int b = half * 8192 + c * 128 + (tid & 31) * 4;
      const float bias = __bfloat162float(b2[0]);
      float4 s = make_float4(bias, bias, bias, bias);
#pragma unroll 2
      for (int k = 0; k < 16; k++) { const float4 v = __ldcg((const float4*)(g_partP + k * B_ + b)); s.x += v.x; s.y += v.y; s.z += v.z; s.w += v.w; }
      asm volatile("red.global.add.v4.f32 [%0],{%1,%2,%3,%4};" :: "l"(g_acc + b), "f"(s.x), "f"(s.y), "f"(s.z), "f"(s.w) : "memory");
      asm volatile("bar.arrive 1,%0;" :: "n"(TH + 32) : "memory");
    }
    return;
  }
  asm volatile("setmaxnreg.inc.sync.aligned.u32 240;");
  const int lane = tid & 31;
  const int tbase = PT_OFF + c * 10 * 1024;
  const int ibase = IX_OFF + half * IXH + tid;
  const uint32_t lc = (tid & 7) << 4;
  uint4 acc[NS], wq[PF], x[DEPTH], y[YD], ye;
  uint32_t sw[NS] = {};
  auto sget = [&](int s) { return (s & 3) == 3 ? __byte_perm(__byte_perm(sw[s - 3], sw[s - 2], 0x0073), sw[s - 1], 0x0710) : sw[s]; };
  auto sa0 = [&](uint32_t v) { return sbase + SM_U + (((v << 5) & 0x1ffe0) | ((lc >> 2) & 16)); };
  uint32_t c1 = 0;
  auto sa1 = [&](uint32_t v) { return sbase + SM_U + (((v >> 7) & 0x1ffe0) | c1); };
  {
    uint4 i0[8];
#pragma unroll
    for (int q = 0; q < 8; q++) i0[q] = ldtex(tex, I0_OFF + (half * 8 + q) * TH + tid);
#pragma unroll
    for (int i = 0; i < PF; i++) if (!WQL) wq[i] = ldtex(tex, ibase + i * TH);
    auto wd = [&](int k) { return (k & 3) == 0 ? i0[k >> 2].x : (k & 3) == 1 ? i0[k >> 2].y : (k & 3) == 2 ? i0[k >> 2].z : i0[k >> 2].w; };
    TS(5, 2);
    mbar_wait_fast(fullU, 0);
#pragma unroll
    for (int i = 0; i < PF; i++) if (WQL) wq[i] = ldtex(tex, ibase + i * TH);
    TS(1, 1);
#pragma unroll
    for (int s = 0; s < NS; s++) acc[s] = add4(lds128(sbase + SM_U + (wd(s) & 0x1fff0)), lds128(sbase + SM_U + ((wd(s) >> 13) & 0x1fff0)));
    arrive_both(emptyU, lane);
    asm volatile("bar.sync 3,%0;" :: "n"(TH + 32) : "memory");
    TS(5, 3);
  }
#pragma unroll 1
  for (int k = 0; k < NC; k++) {
    const int ti = ibase + k * 8192;
    const int tb = tbase + k * 1024;
    const bool more = k + 1 < NC;
    TR(k * 4);
    if (CBAR & 1) asm volatile("bar.sync 4,%0;" :: "n"(TH) : "memory");
    mbar_wait_fast(fullL, k & 1);
    TR(k * 4 + 2);
    uint4 w, cc; uint32_t yc, yn;
    constexpr int TL = NS * 8, TT = TL + NS * 2;
#pragma unroll
    for (int t = 0; t < TT + DEPTH; t += 2) {
      if (t == TL + DEPTH && !more) break;
      if (t >= DEPTH) {
        const int u = t - DEPTH;
        uint4 p = add4(x[u % DEPTH], x[(u + 1) % DEPTH]);
        if (u < TL) {
          const int s = u >> 3, j = u & 7;
          if (j == 0) {
            cc = s >= YD ? add4(y[s % YD], p) : p;
            if (s + YD < NS) y[s % YD] = ldtex(tex, tb | (yc & 1023));
          } else cc = add4(cc, p);
          if (j == 6) acc[s] = add4(acc[s], cc);
        } else {
          const int s = (u - TL) >> 1;
          acc[s] = add4(acc[s], p);
        }
      }
      if ((CBAR & 4) && t == TL / 2) asm volatile("bar.sync 4,%0;" :: "n"(TH) : "memory");
      if ((CBAR & 8) && t == TL - 40) asm volatile("bar.sync 4,%0;" :: "n"(TH) : "memory");
      if (DEPTH == 8 && (t & 7) == 2) yc = yn;
      if (t < TL) {
        const int s = t >> 3, j = t & 7;
        if (j == 0) {
          if (ye_of(s - YD) >= 0) acc[ye_of(s - YD) & 3] = add4(acc[ye_of(s - YD) & 3], ye);
          w = wq[s % PF];
          if (!EARLY || s < NS - 4) wq[s % PF] = ldtex(tex, ti + (s + PF) * TH);
          else {
            if (s == NS - 4) { wq[0] = ldtex(tex, ti + NS * TH); ye = ldtex(tex, ti + (NS + 3) * TH); }
            if (s == NS - 3) { wq[1] = ldtex(tex, ti + (NS + 1) * TH); y[0] = ldtex(tex, ti + (NS + 2) * TH); }
            if (s == NS - 2) wq[2] = y[0];
            if (s == NS - 1) wq[3] = ye;
          }
          yn = __funnelshift_l(w.z, w.z, 5); if (DEPTH < 8) yc = yn;
          if ((s & 3) != 3) asm volatile("add.u32 %0,%1,%2;" : "=r"(sw[s]) : "r"(w.w), "r"(never));
          if (ye_of(s) >= 0) ye = ldtex(tex, tb | w.w);
        }
#pragma unroll
        for (int jj = j; jj < j + 2; jj++) {
          const uint32_t ww = jj < 3 ? w.x : jj < 6 ? w.y : w.z;
          const uint32_t sh = jj % 3 == 0 ? ww : jj % 3 == 1 ? ww >> 10 : __funnelshift_l(ww, ww, 12);
          x[(t + jj - j) % DEPTH] = lds128(sbase + ((sh & 0x1ff80) | lc) + jj * 16 - 128);
        }
      } else if (t < TT) {
        const int s = (t - TL) >> 1;
        if (s == 0) { asm volatile("add.u32 %0,%1,%2;" : "=r"(c1) : "r"((~lc >> 2) & 16), "r"(never)); arrive_both(emptyL, more ? lane : 9); TR(k * 4 + 3); if (CBAR & 2) asm volatile("bar.sync 4,%0;" :: "n"(TH) : "memory"); mbar_wait_fast(fullU, (k + 1) & 1); }
        const uint32_t sv = sget(s);
        x[t % DEPTH] = lds128(sa0(sv));
        x[(t + 1) % DEPTH] = lds128(sa1(sv));
      } else if (t == TT) arrive_both(emptyU, lane);
      if ((t & (FENCE_N - 1)) == FENCE_N - 2) SCHED_FENCE(never, t);
    }
  }
  TS(1, 2);
  const uint4 w2v = lds128(barJ + 32);
  const uint32_t cell = sbase + SM_U + tid * 16;
  const int t9 = tbase + 9 * 1024;
  uint4 za[4], i9 = wq[0];
  auto fetch = [&](int q) {
    y[0] = ldtex(tex, t9 | i9.x); y[1] = ldtex(tex, t9 | i9.y); y[2] = ldtex(tex, t9 | i9.z); y[3] = ldtex(tex, t9 | i9.w);
    if (q) {
      i9 = ldtex(tex, ibase + NC * 8192 + min(q + 1, 7) * TH);
      const uint32_t ca = cell + (q > 6 ? 0 : q - 1) * 16384;
#pragma unroll
      for (int s = 0; s < 4; s++) za[s] = lds128(ca + s * 4096);
    }
  };
  fetch(0);
  i9 = wq[1];
#pragma unroll
  for (int s = 0; s < 4; s++) za[s] = acc[s];
#pragma unroll
  for (int s = 0; s < 24; s++) sts128(cell + s * 4096, acc[4 + s]);
  float hw[8];
  {
    const uint32_t ww[4] = {w2v.x, w2v.y, w2v.z, w2v.w};
#pragma unroll
    for (int k = 0; k < 8; k++) hw[k] = 0.5f * ((k & 1) ? bf_hi(ww[k >> 1]) : bf_lo(ww[k >> 1]));
  }
  float* outp = g_acc + half * 8192 + tid;
#pragma unroll 1
  for (int q = 0; q < NS / 4; q++) {
    uint4 z[4];
#pragma unroll
    for (int s = 0; s < 4; s++) z[s] = add4(za[s], y[s]);
    if (q == 1) {
#pragma unroll
      for (int s = 0; s < 4; s++) sts128(cell + s * 4096, acc[28 + s]);
    }
    if (q < 7) fetch(q + 1);
    SCHED_FENCE(never, 999);
#pragma unroll
    for (int s = 0; s < 4; s++) {
      const uint32_t a[4] = {z[s].x, z[s].y, z[s].z, z[s].w};
      float r0 = 0.f;
#pragma unroll
      for (int k = 0; k < 8; k++) {
        const float v = (k & 1) ? bf_hi(a[k >> 1]) : bf_lo(a[k >> 1]);
        const float u = v * fmaf(v * v, 0.7978845608028654f * 0.044715f, 0.7978845608028654f);
        float th; asm("tanh.approx.f32 %0,%1;" : "=f"(th) : "f"(u));
        r0 = fmaf(fmaf(v, th, v), hw[k], r0);
      }
      asm volatile("red.global.add.f32 [%0],%1;" :: "l"(outp + s * TH), "f"(r0) : "memory");
    }
    outp += 4 * TH;
  }
  TS(1, 3);
  asm volatile("bar.sync 1,%0;" :: "n"(TH + 32) : "memory");
  if (tid == 0) {
    unsigned old; asm volatile("atom.acq_rel.gpu.global.inc.u32 %0,[%1],63;" : "=r"(old) : "l"(&g_done[half * 32]) : "memory");
    asm volatile("st.shared.u32 [%0],%1;" :: "r"(barJ + 8), "r"(old) : "memory");
  }
  asm volatile("bar.sync 2,%0;" :: "n"(TH) : "memory");
  uint32_t old; asm volatile("ld.shared.u32 %0,[%1];" : "=r"(old) : "r"(barJ + 8));
  if (old == 63) {
    if (half == 0 && tid == 25) g_slot = 0;
    if (half == 0 && tid < 25) g_flag[tid * 32] = 0;
    float4 v[8];
#pragma unroll
    for (int q = 0; q < 8; q++) v[q] = __ldcg((const float4*)(g_acc + half * 8192) + q * TH + tid);
#pragma unroll
    for (int q = 0; q < 8; q++) ((uint2*)(out + half * 8192))[q * TH + tid] = make_uint2(pack_bf2(v[q].x, v[q].y), pack_bf2(v[q].z, v[q].w));
    TS(6, 2);
  }
}

}

extern "C" void kernel_launch(void* const* d_in, const int* in_sizes, int n_in, void* d_out, int out_size) {
  const int* idx = (const int*)d_in[0];
  const __nv_bfloat16* table = (const __nv_bfloat16*)d_in[1];
  const __nv_bfloat16* wp = (const __nv_bfloat16*)d_in[2];
  const __nv_bfloat16* w1 = (const __nv_bfloat16*)d_in[3];
  const __nv_bfloat16* b1 = (const __nv_bfloat16*)d_in[4];
  const __nv_bfloat16* w2 = (const __nv_bfloat16*)d_in[5];
  const __nv_bfloat16* b2 = (const __nv_bfloat16*)d_in[6];
  static cudaTextureObject_t texScr = 0, texG = 0;
  static CUtensorMap mapW, mapL, mapS, mapT, mapE, mapC;
  static const void *c_tab = nullptr, *c_w1 = nullptr;
  if (c_tab != table || c_w1 != w1) {
    c_tab = table; c_w1 = w1;
    char* scr = nullptr; cudaGetSymbolAddress((void**)&scr, g_scr);
    auto mk_tex = [](const void* p, size_t bytes, cudaChannelFormatDesc d) {
      cudaResourceDesc rd = {}; rd.resType = cudaResourceTypeLinear; rd.res.linear.devPtr = (void*)p; rd.res.linear.desc = d; rd.res.linear.sizeInBytes = bytes;
      cudaTextureDesc td = {}; td.readMode = cudaReadModeElementType;
      cudaTextureObject_t t = 0; cudaCreateTextureObject(&t, &rd, &td, nullptr); return t;
    };
    if (!texScr) {
      texScr = mk_tex(scr, (size_t)SCR_N * 16, cudaCreateChannelDesc<uint4>());
      texG = mk_tex(scr + (size_t)PX_OFF * 16, (size_t)(SCR_N - PX_OFF) * 16, cudaCreateChannelDesc<unsigned>());
    }
    typedef CUresult (*EncFn)(CUtensorMap*, CUtensorMapDataType, cuuint32_t, void*, const cuuint64_t*, const cuuint64_t*, const cuuint32_t*,
                              const cuuint32_t*, CUtensorMapInterleave, CUtensorMapSwizzle, CUtensorMapL2promotion, CUtensorMapFloatOOBfill);
    EncFn enc = nullptr; cudaDriverEntryPointQueryResult qr;
    cudaGetDriverEntryPoint("cuTensorMapEncodeTiled", (void**)&enc, cudaEnableDefault, &qr);
    const cuuint32_t ones[4] = {1, 1, 1, 1};
    auto mk = [&](CUtensorMap* m, CUtensorMapDataType dt, int rank, void* p, const cuuint64_t* dim, const cuuint64_t* str, const cuuint32_t* box, CUtensorMapSwizzle sw) {
      enc(m, dt, rank, p, dim, str, box, ones, CU_TENSOR_MAP_INTERLEAVE_NONE, sw, CU_TENSOR_MAP_L2_PROMOTION_NONE, CU_TENSOR_MAP_FLOAT_OOB_FILL_NONE);
    };
    { cuuint64_t dim[2] = {H_, F_ * D_}, str[1] = {H_ * 2}; cuuint32_t box[2] = {32, 256};
      mk(&mapW, CU_TENSOR_MAP_DATA_TYPE_BFLOAT16, 2, (void*)w1, dim, str, box, CU_TENSOR_MAP_SWIZZLE_64B); }
    { cuuint64_t dim[4] = {64, 64, V_, NC}, str[3] = {128000 * NC, 128, 128000}; cuuint32_t box[4] = {32, 4, 64, 1};
      mk(&mapL, CU_TENSOR_MAP_DATA_TYPE_BFLOAT16, 4, scr + (size_t)PL_OFF * 16, dim, str, box, CU_TENSOR_MAP_SWIZZLE_64B); }
    { cuuint64_t dim[4] = {64, 64, V_ / 4, NC}, str[3] = {32000 * NC, 128, 32000}; cuuint32_t box[4] = {64, 4, 16, 1};
      mk(&mapS, CU_TENSOR_MAP_DATA_TYPE_BFLOAT16, 4, scr + (size_t)PS_OFF * 16, dim, str, box, CU_TENSOR_MAP_SWIZZLE_128B); }
    { cuuint64_t dim[4] = {64, 64, V_ / 8, 10}, str[3] = {163840, 128, 16384}; cuuint32_t box[4] = {64, 4, 8, 2};
      mk(&mapT, CU_TENSOR_MAP_DATA_TYPE_BFLOAT16, 4, scr + (size_t)PT_OFF * 16, dim, str, box, CU_TENSOR_MAP_SWIZZLE_128B); }
    { cuuint64_t dim[2] = {D_, V_}, str[1] = {D_ * 2}; cuuint32_t box[2] = {64, 128};
      mk(&mapE, CU_TENSOR_MAP_DATA_TYPE_BFLOAT16, 2, (void*)table, dim, str, box, CU_TENSOR_MAP_SWIZZLE_128B);
      cuuint32_t box2[2] = {8, 256};
      mk(&mapC, CU_TENSOR_MAP_DATA_TYPE_BFLOAT16, 2, (void*)table, dim, str, box2, CU_TENSOR_MAP_SWIZZLE_NONE); }
    cudaFuncSetAttribute(k_deep, cudaFuncAttributeMaxDynamicSharedMemorySize, DEEP_SMEM);
    cudaFuncSetAttribute(k_tens, cudaFuncAttributeMaxDynamicSharedMemorySize, K1_SMEM);
  }
  k_tens<<<132, 512, K1_SMEM, cudaStreamPerThread>>>(mapW, mapL, mapS, mapT, mapE, mapC, texScr, texG, idx, table, wp, w1, b1, 0);
  cudaLaunchAttribute at[1];
  at[0].id = cudaLaunchAttributeProgrammaticStreamSerialization; at[0].val.programmaticStreamSerializationAllowed = 1;
  cudaLaunchConfig_t cfg = {};
  cfg.stream = cudaStreamPerThread; cfg.attrs = at;
  cfg.gridDim = 128; cfg.blockDim = TH + 128; cfg.dynamicSmemBytes = DEEP_SMEM; cfg.numAttrs = PDL & 1;
  cudaLaunchKernelEx(&cfg, k_deep, texScr, w2, b2, (__nv_bfloat16*)d_out, 0);

}
```

```cpp
#include <cuda_runtime.h>
#include <cuda_bf16.h>
#include <cuda_fp16.h>
#include <stdint.h>
#include <cuda.h>

namespace {

constexpr int B_ = 16384, F_ = 100, D_ = 128, V_ = 1000, H_ = 512;
constexpr int NC = 9;
constexpr int PT_OFF = 0;
constexpr int PL_OFF = 64 * 10 * 1024;
constexpr int PS_OFF = PL_OFF + 64 * NC * 8000;
constexpr int IXH = NC * 8192 + 2048;
constexpr int IX_OFF = PS_OFF + 64 * NC * 2000;
constexpr int I0_OFF = IX_OFF + 2 * IXH;
constexpr int PX_OFF = I0_OFF + 4096;
constexpr int SCR_N = PX_OFF + 64 * 16 * 136;
static_assert(PX_OFF % 32 == 0, "");

__device__ __align__(1024) uint4 g_scr[SCR_N];
__device__ float g_acc[B_];
__device__ unsigned long long g_slot;
__device__ unsigned g_done[64];
__device__ float g_partP[16 * B_];
__device__ unsigned g_flag[25 * 32];

#define TS(k, i)
#define TR(slot)
#define PT(slot)

constexpr uint64_t POL_EF = 0x12F0000000000000ull, POL_N = 0x1000000000000000ull;
__device__ __forceinline__ uint32_t addbf2(uint32_t a, uint32_t b) { uint32_t r; asm("add.rn.bf16x2 %0,%1,%2;" : "=r"(r) : "r"(a), "r"(b)); return r; }
__device__ __forceinline__ uint4 add4(const uint4& a, const uint4& b) { return make_uint4(addbf2(a.x, b.x), addbf2(a.y, b.y), addbf2(a.z, b.z), addbf2(a.w, b.w)); }
__device__ __forceinline__ uint4 ldtex(cudaTextureObject_t t, int i) {
  uint4 v; asm volatile("tex.1d.v4.u32.s32 {%0,%1,%2,%3},[%4,{%5}];" : "=r"(v.x), "=r"(v.y), "=r"(v.z), "=r"(v.w) : "l"(t), "r"(i)); return v;
}
__device__ __forceinline__ uint4 lds128(uint32_t a) {
  uint4 v; asm volatile("ld.volatile.shared.v4.u32 {%0,%1,%2,%3},[%4];" : "=r"(v.x), "=r"(v.y), "=r"(v.z), "=r"(v.w) : "r"(a)); return v;
}
__device__ __forceinline__ void sts128(uint32_t a, const uint4& v) {
  asm volatile("st.shared.v4.u32 [%0],{%1,%2,%3,%4};" :: "r"(a), "r"(v.x), "r"(v.y), "r"(v.z), "r"(v.w) : "memory");
}
__device__ __forceinline__ void mbar_init(uint32_t bar, int n) { asm volatile("mbarrier.init.shared::cta.b64 [%0],%1;" :: "r"(bar), "r"(n) : "memory"); }
__device__ __forceinline__ void mbar_wait(uint32_t bar, uint32_t parity) {
  uint32_t ok; int it = 0;
  do { asm volatile("{.reg .pred p; mbarrier.try_wait.parity.shared::cta.b64 p,[%1],%2; selp.u32 %0,1,0,p;}" : "=r"(ok) : "r"(bar), "r"(parity) : "memory"); } while (!ok && ++it < (1 << 19));
}
__device__ __forceinline__ void mbar_expect(uint32_t bar, uint32_t bytes) { asm volatile("mbarrier.arrive.expect_tx.shared::cta.b64 _,[%0],%1;" :: "r"(bar), "r"(bytes) : "memory"); }
__device__ __forceinline__ void bulk_g2s(uint32_t dst, const void* src, uint32_t bytes, uint32_t bar) {
  asm volatile("cp.async.bulk.shared::cluster.global.mbarrier::complete_tx::bytes [%0],[%1],%2,[%3];" :: "r"(dst), "l"(src), "r"(bytes), "r"(bar) : "memory");
}
__device__ __forceinline__ void bulk_pf(const void* src, uint32_t bytes) { asm volatile("cp.async.bulk.prefetch.L2.global [%0],%1;" :: "l"(src), "r"(bytes) : "memory"); }
#define SCHED_FENCE(never, k) asm volatile("{.reg .pred p; setp.ne.u32 p,%0,%1; @p bra.uni SKIP_%=; pmevent 1; SKIP_%=: }" :: "r"(never), "r"(0x7fff0000 + (k)) : "memory")
#define PDL 1
#define RSV 22
#define PACE 800
__device__ __forceinline__ int quad_of(int n) { return n < 23 ? n + 2 : n - 23; }
__device__ __forceinline__ void mbar_wait_fast(uint32_t bar, uint32_t parity) {
  asm volatile("{.reg .pred p; .reg .u32 n;\n"
               "mbarrier.try_wait.parity.shared::cta.b64 p,[%0],%1;\n"
               "@p bra DONE_%=;\n"
               "mov.u32 n,0;\n"
               "LOOP_%=: mbarrier.try_wait.parity.shared::cta.b64 p,[%0],%1;\n"
               "add.u32 n,n,1; setp.gt.or.u32 p,n,400000,p;\n"
               "@!p bra LOOP_%=;\n"
               "DONE_%=: }" :: "r"(bar), "r"(parity) : "memory");
}
__device__ __forceinline__ void sleep_until(uint32_t t0, uint32_t dt) { while ((uint32_t)clock() - t0 < dt) __nanosleep(40); }
__device__ __forceinline__ uint32_t s_mask(uint32_t v, int q) { return (1u << ((v + 3 - q) & 3)) | (16u << ((v + 3 + q) & 3)); }
__device__ __forceinline__ uint32_t s_cell(uint32_t v, int q, uint32_t m) {
  const int t = __ffs(~m) - 1;
  const int cp = t == 8 ? q >> 1 : ((t & 4 ? t - q : t + q) - v) & 3;
  return cp * 1001 + v;
}
__device__ __forceinline__ uint32_t pk3(uint32_t a, uint32_t b, uint32_t c) {
  const uint32_t w = c + (a << 12) + (b << 22); return __funnelshift_l(w, w, 27);
}
constexpr int TH = 256, NS = 8192 / TH, YD = 4;
__host__ __device__ constexpr int ye_of(int s) { return s == 3 ? 0 : s == 11 ? 1 : s == 19 ? 2 : s == 23 ? 3 : -1; }
template <int N> __device__ __forceinline__ void wgmma_h(uint32_t* d, const uint32_t* a, uint64_t desc, int acc);
template <> __device__ __forceinline__ void wgmma_h<40>(uint32_t* d, const uint32_t* a, uint64_t desc, int acc) {
  asm volatile("{.reg .pred p; setp.ne.s32 p,%15,0;\n"
    "wgmma.mma_async.sync.aligned.m64n40k16.f16.f16.f16 {%0,%1,%2,%3,%4,%5,%6,%7,%8,%9},{%10,%11,%12,%13},%14,p,1,1,0;}"
    : "+r"(d[0]),"+r"(d[1]),"+r"(d[2]),"+r"(d[3]),"+r"(d[4]),"+r"(d[5]),"+r"(d[6]),"+r"(d[7]),"+r"(d[8]),"+r"(d[9])
    : "r"(a[0]), "r"(a[1]), "r"(a[2]), "r"(a[3]), "l"(desc), "r"(acc));
}
template <> __device__ __forceinline__ void wgmma_h<32>(uint32_t* d, const uint32_t* a, uint64_t desc, int acc) {
  asm volatile("{.reg .pred p; setp.ne.s32 p,%13,0;\n"
    "wgmma.mma_async.sync.aligned.m64n32k16.f16.f16.f16 {%0,%1,%2,%3,%4,%5,%6,%7},{%8,%9,%10,%11},%12,p,1,1,0;}"
    : "+r"(d[0]),"+r"(d[1]),"+r"(d[2]),"+r"(d[3]),"+r"(d[4]),"+r"(d[5]),"+r"(d[6]),"+r"(d[7])
    : "r"(a[0]), "r"(a[1]), "r"(a[2]), "r"(a[3]), "l"(desc), "r"(acc));
}
__device__ __forceinline__ void wgmma_p(float* d, const uint32_t* a, uint64_t desc, int acc) {
  asm volatile("{.reg .pred p; setp.ne.s32 p,%69,0;\n"
    "wgmma.mma_async.sync.aligned.m64n128k16.f32.bf16.bf16 {%0,%1,%2,%3,%4,%5,%6,%7,%8,%9,%10,%11,%12,%13,%14,%15,%16,%17,%18,%19,%20,%21,%22,%23,%24,%25,%26,%27,%28,%29,%30,%31,%32,%33,%34,%35,%36,%37,%38,%39,%40,%41,%42,%43,%44,%45,%46,%47,%48,%49,%50,%51,%52,%53,%54,%55,%56,%57,%58,%59,%60,%61,%62,%63},{%64,%65,%66,%67},%68,p,1,1,1;}"
    : "+f"(d[0]),"+f"(d[1]),"+f"(d[2]),"+f"(d[3]),"+f"(d[4]),"+f"(d[5]),"+f"(d[6]),"+f"(d[7]),"+f"(d[8]),"+f"(d[9]),"+f"(d[10]),"+f"(d[11]),"+f"(d[12]),"+f"(d[13]),"+f"(d[14]),"+f"(d[15]),"+f"(d[16]),"+f"(d[17]),"+f"(d[18]),"+f"(d[19]),"+f"(d[20]),"+f"(d[21]),"+f"(d[22]),"+f"(d[23]),"+f"(d[24]),"+f"(d[25]),"+f"(d[26]),"+f"(d[27]),"+f"(d[28]),"+f"(d[29]),"+f"(d[30]),"+f"(d[31]),"+f"(d[32]),"+f"(d[33]),"+f"(d[34]),"+f"(d[35]),"+f"(d[36]),"+f"(d[37]),"+f"(d[38]),"+f"(d[39]),"+f"(d[40]),"+f"(d[41]),"+f"(d[42]),"+f"(d[43]),"+f"(d[44]),"+f"(d[45]),"+f"(d[46]),"+f"(d[47]),"+f"(d[48]),"+f"(d[49]),"+f"(d[50]),"+f"(d[51]),"+f"(d[52]),"+f"(d[53]),"+f"(d[54]),"+f"(d[55]),"+f"(d[56]),"+f"(d[57]),"+f"(d[58]),"+f"(d[59]),"+f"(d[60]),"+f"(d[61]),"+f"(d[62]),"+f"(d[63])
    : "r"(a[0]), "r"(a[1]), "r"(a[2]), "r"(a[3]), "l"(desc), "r"(acc));
}

__device__ __forceinline__ void mma16816h(uint32_t* c, const uint32_t* a, uint32_t b0, uint32_t b1) {
  asm("mma.sync.aligned.m16n8k16.row.col.f16.f16.f16.f16 {%0,%1},{%2,%3,%4,%5},{%6,%7},{%0,%1};"
      : "+r"(c[0]), "+r"(c[1]) : "r"(a[0]), "r"(a[1]), "r"(a[2]), "r"(a[3]), "r"(b0), "r"(b1));
}
__device__ __forceinline__ void mma1688h(uint32_t* c, uint32_t a0, uint32_t a1, uint32_t b) {
  asm("mma.sync.aligned.m16n8k8.row.col.f16.f16.f16.f16 {%0,%1},{%2,%3},{%4},{%0,%1};" : "+r"(c[0]), "+r"(c[1]) : "r"(a0), "r"(a1), "r"(b));
}
__device__ __forceinline__ void mma1688f(float* c, uint32_t a0, uint32_t a1, uint32_t b) {
  asm("mma.sync.aligned.m16n8k8.row.col.f32.f16.f16.f32 {%0,%1,%2,%3},{%4,%5},{%6},{%0,%1,%2,%3};"
      : "+f"(c[0]), "+f"(c[1]), "+f"(c[2]), "+f"(c[3]) : "r"(a0), "r"(a1), "r"(b));
}
__device__ __forceinline__ uint32_t hadd2(uint32_t a, uint32_t b) { uint32_t r; asm("add.rn.f16x2 %0,%1,%2;" : "=r"(r) : "r"(a), "r"(b)); return r; }
__device__ __forceinline__ uint32_t hfma2(uint32_t a, uint32_t b, uint32_t c) { uint32_t r; asm("fma.rn.f16x2 %0,%1,%2,%3;" : "=r"(r) : "r"(a), "r"(b), "r"(c)); return r; }
__device__ __forceinline__ uint32_t pack_bf2(float lo, float hi) { uint32_t r; asm("cvt.rn.bf16x2.f32 %0,%1,%2;" : "=r"(r) : "f"(hi), "f"(lo)); return r; }
__device__ __forceinline__ uint32_t pack_h2(float lo, float hi) { uint32_t r; asm("cvt.rn.f16x2.f32 %0,%1,%2;" : "=r"(r) : "f"(hi), "f"(lo)); return r; }
__device__ __forceinline__ float bf_lo(uint32_t w) { return __uint_as_float(w << 16); }
__device__ __forceinline__ float bf_hi(uint32_t w) { return __uint_as_float(w & 0xffff0000u); }
__device__ __forceinline__ uint32_t absmax4(const uint4& v, uint32_t m) {
  return __vmaxu2(__vmaxu2(__vmaxu2(v.x & 0x7fff7fffu, v.y & 0x7fff7fffu), __vmaxu2(v.z & 0x7fff7fffu, v.w & 0x7fff7fffu)), m);
}
__device__ __forceinline__ float pow2_scale(uint32_t mbits, int p) { return __uint_as_float((uint32_t)min(max(253 + p - (int)(mbits >> 7), 2), 252) << 23); }

constexpr int G_O0 = 8, G_O1 = 4, G_O2 = 0, G_N0 = 5, G_N1 = 4, G_N2 = 4, G_K0 = 5, G_K1 = 3, G_K2 = 1;
__host__ __device__ constexpr bool unit_wg(int kb, int on) {
  return (on >= G_O0 && on < G_O0 + G_N0 && kb < G_K0) || (on >= G_O1 && on < G_O1 + G_N1 && kb < G_K1) || (on >= G_O2 && on < G_O2 + G_N2 && kb < G_K2);
}
constexpr int G_U1 = G_N0 * G_K0, G_U2 = G_U1 + G_N1 * G_K1, G_U = G_U2 + G_N2 * G_K2;
constexpr int K1_B = 130048, K1_STG = K1_B + 2 * 32768, K1_W = K1_STG + 16384, K1_BAR = K1_W + 48 * 256, K1_SMEM = K1_BAR + 256 + 6400;
__host__ __device__ constexpr int frag_index(int ok, int on) {
  int n = 0;
  for (int k = 0; k < 13; k++) for (int o = k; o < 13; o++) { if (k == ok && o == on) return n; if (!unit_wg(k >> 1, o)) n++; }
  return n;
}
constexpr int HU_N = 2 * G_U + frag_index(99, 99);
static_assert(HU_N <= 96, "");
struct FragIdx { int v[13][13]; };
__host__ __device__ constexpr FragIdx make_fi() { FragIdx f = {}; for (int k = 0; k < 13; k++) for (int o = 0; o < 13; o++) f.v[k][o] = frag_index(k, o); return f; }
__host__ __device__ constexpr uint64_t frag_tab(int first) {
  uint64_t t = 0;
  for (int k = 0; k < 13; k++) for (int o = k; o < 13; o++)
    if (!unit_wg(k >> 1, o)) { const int n = frag_index(k, o) - first; if (n >= 0 && n < 8) t |= (uint64_t)(k << 4 | o) << (8 * n); }
  return t;
}
__device__ __forceinline__ int hu_code(int hu) {
  constexpr uint64_t T0 = frag_tab(0), T1 = frag_tab(8), T2 = frag_tab(16), T3 = frag_tab(24);
  const int u = hu >> 1, f = hu - 2 * G_U;
  if (f >= 0) return (int)((f < 8 ? T0 : f < 16 ? T1 : f < 24 ? T2 : T3) >> (8 * (f & 7))) & 255;
  const int u0 = u < G_U1 ? u : u < G_U2 ? u - G_U1 : u - G_U2;
  const int kb = u < G_U1 ? u0 / G_N0 : u < G_U2 ? u0 / G_N1 : u0 / 4, on = u < G_U1 ? G_O0 + u0 % G_N0 : u < G_U2 ? G_O1 + u0 % G_N1 : G_O2 + u0 % 4;
  return (2 * kb + (hu & 1)) << 4 | on;
}

__device__ __forceinline__ void flag_wait(const unsigned* f, unsigned n) {
  unsigned v; int it = 0;
  asm volatile("ld.acquire.gpu.global.u32 %0,[%1];" : "=r"(v) : "l"(f) : "memory");
  if (v < n) {
    do { __nanosleep(300); asm volatile("ld.relaxed.gpu.global.u32 %0,[%1];" : "=r"(v) : "l"(f) : "memory"); } while (v < n && ++it < (1 << 20));
    asm volatile("ld.acquire.gpu.global.u32 %0,[%1];" : "=r"(v) : "l"(f) : "memory");
  }
}
__device__ __forceinline__ void mbar_arrive(uint32_t bar) { asm volatile("mbarrier.arrive.shared::cta.b64 _,[%0];" :: "r"(bar) : "memory"); }
__device__ __forceinline__ void mbar_arrive_lane0(uint32_t bar) {
  asm volatile("{.reg .pred p; elect.sync _|p,0xffffffff; @p mbarrier.arrive.shared::cta.b64 _,[%0];}" :: "r"(bar) : "memory");
}

__device__ __forceinline__ void arrive_both(uint32_t bar, int lane) {
  asm volatile("{.reg .pred p; .reg .u32 a; setp.lt.u32 p,%1,2; mapa.shared::cluster.u32 a,%0,%1;\n"
               "@p mbarrier.arrive.shared::cluster.b64 _,[a];}" :: "r"(bar), "r"(lane) : "memory");
}
#define ELECT "{.reg .pred p; elect.sync _|p,0xffffffff; @p "
__device__ __forceinline__ void e_mc(uint32_t dst, const void* src, uint32_t bytes, uint32_t bar, uint64_t pol) {
  asm volatile(ELECT "cp.async.bulk.shared::cluster.global.mbarrier::complete_tx::bytes.multicast::cluster.L2::cache_hint [%0],[%1],%2,[%3],%4,%5;}"
               :: "r"(dst), "l"(src), "r"(bytes), "r"(bar), "h"((unsigned short)3), "l"(pol) : "memory");
}
__device__ __forceinline__ void e_g2s(uint32_t dst, const void* src, uint32_t bytes, uint32_t bar) {
  asm volatile(ELECT "cp.async.bulk.shared::cluster.global.mbarrier::complete_tx::bytes [%0],[%1],%2,[%3];}" :: "r"(dst), "l"(src), "r"(bytes), "r"(bar) : "memory");
}
__device__ __forceinline__ void e_pf(const void* src, uint32_t bytes) { asm volatile(ELECT "cp.async.bulk.prefetch.L2.global [%0],%1;}" :: "l"(src), "r"(bytes) : "memory"); }
__device__ __forceinline__ void e_expect(uint32_t bar, uint32_t bytes) { asm volatile(ELECT "mbarrier.arrive.expect_tx.shared::cta.b64 _,[%0],%1;}" :: "r"(bar), "r"(bytes) : "memory"); }
__device__ __forceinline__ void e_tma2d(uint32_t dst, const CUtensorMap* m, int x, int y, uint32_t bar) {
  asm volatile(ELECT "cp.async.bulk.tensor.2d.shared::cluster.global.mbarrier::complete_tx::bytes [%0],[%1,{%2,%3}],[%4];}" :: "r"(dst), "l"(m), "r"(x), "r"(y), "r"(bar) : "memory");
}

__device__ __forceinline__ void pack_role(const int* __restrict__ idx, uint32_t sbase, int pc) {
  constexpr int BUF = 32 * 3328;
  const int tid = threadIdx.x, lane = tid & 31, warp = tid >> 5;
  const uint32_t full = sbase + 2 * BUF, empty = full + 16;
  if (tid == 0) { mbar_init(full, 1); mbar_init(full + 8, 1); mbar_init(empty, 18); mbar_init(empty + 8, 18); asm volatile("fence.proxy.async.shared::cta;" ::: "memory"); }
  __syncthreads();
  auto chunk = [&](int s) { return s * 3200 + (s >> 2) * 288; };
  auto load = [&](int n) {
    const int blk = pc * 16 + n;
    if (lane == 0) mbar_expect(full + (n & 1) * 8, 32 * 3200);
    __syncwarp();
    bulk_g2s(sbase + (n & 1) * BUF + chunk(lane), idx + ((blk >> 5) * 8192 + lane * TH + (blk & 31) * 8) * F_, 3200, full + (n & 1) * 8);
  };
  if (warp == 0) { load(0); load(1); }
  const int l = lane & 7;
  uint32_t rot[8], inc[3];
#pragma unroll
  for (int jj = 0; jj < 8; jj++) rot[jj] = ((l + jj) & 7) * 4;
#pragma unroll
  for (int q = 0; q < 3; q++) inc[q] = (l + 3 * q < 8) << 12 | (l + 3 * q + 1 < 8) << 22 | (q < 2 && l + 3 * q + 2 < 8);
  int loaded = 2;
#pragma unroll 1
  for (int task = warp; task < 288; task += 16) {
    const int n = task / 18, q = (task % 18) * 4 + (lane >> 3), sq = q / 9, k = q % 9;
    if (warp == 0 && n + 1 == loaded && loaded < 16) { mbar_wait(empty + (loaded & 1) * 8, ((loaded >> 1) - 1) & 1); load(loaded); loaded++; }
    mbar_wait(full + (n & 1) * 8, (n >> 1) & 1);
    const uint32_t buf = sbase + (n & 1) * BUF + l * 400, row = buf + chunk(sq * 4);
    auto ld = [&](uint32_t ad) { uint32_t v; asm volatile("ld.shared.u32 %0,[%1];" : "=r"(v) : "r"(ad)); return v; };
    const int blk = pc * 16 + n, half = blk >> 5, col = (blk & 31) * 8 + l;
    const int ks = k == NC - 1 ? 0 : k + 1;
    uint32_t cw[4], sv[8], m[2] = {0, 0};
    { const uint32_t a0 = row + (72 + 2 * ks + (l >> 2)) * 4;
#pragma unroll
      for (int u = 0; u < 8; u++) { sv[u] = ld((a0 ^ ((u >> 2) * 4)) + (u & 3) * 3200); m[u >> 2] |= s_mask(sv[u], l & 3) << (8 * (u & 3)); } }
#pragma unroll
    for (int h = 0; h < 2; h++) { m[h] |= __shfl_xor_sync(0xffffffffu, m[h], 1); m[h] |= __shfl_xor_sync(0xffffffffu, m[h], 2); }
#pragma unroll
    for (int u = 0; u < 4; u++) cw[u] = s_cell(sv[u], l & 3, (m[0] >> (8 * u)) & 255) | s_cell(sv[4 + u], l & 3, (m[1] >> (8 * u)) & 255) << 12;
    if (k == NC - 1) {
      auto wide = [&](uint32_t w) { return (w & 0xfff) << 5 | (w >> 12) << 18 | (l & 4 ? 1u << 4 : 1u << 17); };
      g_scr[I0_OFF + (half * 8 + sq) * TH + col] = make_uint4(wide(cw[0]), wide(cw[1]), wide(cw[2]), wide(cw[3]));
      g_scr[IX_OFF + half * IXH + NC * 8192 + sq * TH + col] = make_uint4(ld(row + 396), ld(row + 3596), ld(row + 6796), ld(row + 9996));
      cw[0] = cw[1] = cw[2] = cw[3] = 0;
    }
    const uint32_t ax = buf + chunk(min(sq + 1, 7) * 4) + (90 + k) * 4;
    const uint32_t yev = ld(buf + ((0x3210 >> (sq * 2 + (sq == 5) * 2)) & 3) * 3200 + (90 + k) * 4);
    uint4* dst = g_scr + IX_OFF + half * IXH + (k * NS + sq * 4) * TH + col;
#pragma unroll
    for (int u = 0; u < 4; u++) {
      uint32_t e[8];
#pragma unroll
      for (int jj = 0; jj < 8; jj++) e[jj] = ld(row + k * 32 + rot[jj] + u * 3200);
      dst[u * TH] = make_uint4(pk3(e[0], e[1], e[2] + inc[0]), pk3(e[3], e[4], e[5] + inc[1]), pk3(e[6], e[7], ld(ax + u * 3200) + inc[2]),
                               u < 3 ? __byte_perm(cw[u], cw[3], 0x4210 + (u << 12)) : yev);
    }
    mbar_arrive_lane0(empty + (n & 1) * 8);
  }
}

__global__ void __cluster_dims__(2, 1, 1) __launch_bounds__(512, 1)
k_tens(const __grid_constant__ CUtensorMap mapW, const __grid_constant__ CUtensorMap mapL, const __grid_constant__ CUtensorMap mapS,
       const __grid_constant__ CUtensorMap mapT, const __grid_constant__ CUtensorMap mapE, const __grid_constant__ CUtensorMap mapC, cudaTextureObject_t tex, cudaTextureObject_t texX,
       const int* __restrict__ idx, const __nv_bfloat16* __restrict__ table, const __nv_bfloat16* __restrict__ wp, const __nv_bfloat16* __restrict__ w1,
       const __nv_bfloat16* __restrict__ b1, int never) {
  extern __shared__ __align__(1024) uint4 sm[];
  const int tid = threadIdx.x, lane = tid & 31, cta = blockIdx.x;
  const uint32_t sbase = (uint32_t)__cvta_generic_to_shared(sm);
  const int g = lane >> 2, r = lane & 3;
  TS(0, 0);
  if (cta >= 128) {
    pack_role(idx, sbase, cta - 128);
    __syncthreads();
    if (tid == 0) {
      asm volatile("fence.acq_rel.gpu; griddepcontrol.launch_dependents;" ::: "memory");
      asm volatile("red.relaxed.gpu.global.add.u32 [%0],1;" :: "l"(&g_flag[24 * 32]) : "memory");
    }
    __syncwarp();
    TS(2, 1);
    asm volatile("barrier.cluster.arrive.relaxed.aligned; barrier.cluster.wait.aligned;" ::: "memory");
    return;
  }
  const uint32_t fullB = sbase + K1_BAR, emptyB = fullB + 24, fullE = fullB + 48, fullC = fullB + 56, fullI = fullB + 64, pxRdy = fullB + 72, fullS = fullB + 96, emptyS = fullB + 104, pkDone = fullB + 112, pkFull = fullB + 136, progG = fullB + 168;
  const int rb = cta & 7, hc = cta >> 3;
  if (__shfl_sync(0xffffffffu, tid >> 5, 0) == 12) {
    if (lane == 0) {
#pragma unroll
      for (int q = 0; q < 19; q++) if (q != 2 && q != 5) mbar_init(fullB + q * 8, q == 3 || q == 4 ? 8 : q == 12 ? 4 : q >= 14 && q < 17 ? 2 : 1);
      asm volatile("st.shared.u32 [%0],%1;" :: "r"(progG), "r"(0) : "memory");
    }
    asm volatile("fence.mbarrier_init.release.cluster; fence.proxy.async.shared::cta;" ::: "memory");
    __syncwarp();
    e_expect(fullC, 16384);
#pragma unroll
    for (int q = 0; q < 4; q++) e_tma2d(sbase + 32768 + q * 4096, &mapC, (cta & 15) * 8, q * 256, fullC);
    e_expect(fullE, 32768);
#pragma unroll
    for (int q = 0; q < 2; q++) e_tma2d(sbase + K1_B + 32768 + q * 16384, &mapE, q * 64, rb * 128, fullE);
    asm volatile("bar.arrive 2,512;" ::: "memory");
  }
  asm volatile("barrier.cluster.arrive.relaxed.aligned;" ::: "memory");
  if (tid >= 384) {
    asm volatile("setmaxnreg.dec.sync.aligned.u32 32;");
    if (tid < 416) {
      asm volatile("barrier.cluster.wait.aligned;" ::: "memory");
      if (tid == 384) {
#pragma unroll 1
        for (int n = 0; n < 25; n++) {
          const int st = n & 1, q = quad_of(n);
          if (n == 1) {
            mbar_expect(fullI, 51200);
#pragma unroll 1
            for (int u = 0; u < 8; u++) bulk_g2s(sbase + 76800 + u * 6400, idx + ((cta >> 4) * 8 + u) * 256 * F_, 6400, fullI);
          }
          mbar_wait(emptyB + st * 8, (((n + 1) >> 1) & 1) ^ 1);
          mbar_expect(fullB + st * 8, 32768);
          asm volatile("cp.async.bulk.tensor.2d.shared::cluster.global.mbarrier::complete_tx::bytes.multicast::cluster [%0],[%1,{%2,%3}],[%4],%5;"
                       :: "r"(sbase + K1_B + st * 32768 + (cta & 1) * 16384), "l"(&mapW), "r"(hc * 32), "r"(q * 512 + (cta & 1) * 256),
                          "r"(fullB + st * 8), "h"((unsigned short)3) : "memory");
          if (n + 1 < 25) bulk_pf(w1 + quad_of(n + 1) * 262144 + cta * 2048, 4096);
        }
      }
    } else if (tid < 448) {
      ((float4*)g_acc)[cta * 32 + lane] = make_float4(0.f, 0.f, 0.f, 0.f);
      asm volatile("bar.sync 2,512;" ::: "memory");
      __syncwarp();
      if (tid == 416) {
        int pub = 0;
#pragma unroll 1
        for (int n = 0; n < 50; n++) {
          const int quad = quad_of(n >> 1), mt = n & 1, v0 = rb * 128 + mt * 64;
          const uint32_t stg = sbase + K1_STG;
          if (pub < 3) {
            uint32_t ok = 1;
            if (pub == 0 || n == 49) mbar_wait(pkDone + pub * 8, 0);
            else asm volatile("{.reg .pred p; mbarrier.test_wait.parity.shared::cta.b64 p,[%1],0; selp.u32 %0,1,0,p;}" : "=r"(ok) : "r"(pkDone + pub * 8) : "memory");
            if (ok) {
              asm volatile("cp.async.bulk.wait_group 0;" ::: "memory");
              asm volatile("red.release.gpu.global.add.u32 [%0],1;" :: "l"(&g_flag[((cta >> 4) * 3 + pub) * 32]) : "memory");
              pub++;
              if (n == 49) { n--; continue; }
            }
          }
          mbar_wait(fullS, n & 1);
          asm volatile("fence.proxy.async.shared::cta;" ::: "memory");
          if (quad < 18) {
            asm volatile("cp.async.bulk.tensor.4d.global.shared::cta.bulk_group.L2::cache_hint [%0,{%1,%2,%3,%4}],[%5],%6;"
                         :: "l"(&mapL), "r"((quad & 1) * 32), "r"(hc * 4), "r"(v0), "r"(quad >> 1), "r"(stg), "l"(POL_EF) : "memory");
          } else {
#pragma unroll 1
            for (int hh = 0; hh < 2; hh++) {
              const int pq = quad * 2 + hh;
              asm volatile("cp.async.bulk.tensor.4d.global.shared::cta.bulk_group.L2::cache_hint [%0,{%1,%2,%3,%4}],[%5],%6;"
                         :: "l"(pq < 45 ? &mapS : &mapT), "r"(0), "r"(hc * 4), "r"(v0 >> (pq < 45 ? 2 : 3)), "r"(pq < 45 ? pq - 36 : (pq - 45) * 2), "r"(stg + hh * 8192), "l"(POL_EF) : "memory");
            }
          }
          asm volatile("cp.async.bulk.commit_group;" ::: "memory");
          asm volatile("cp.async.bulk.wait_group.read 0;" ::: "memory");
          mbar_arrive(emptyS);
        }
        asm volatile("cp.async.bulk.wait_group 0;" ::: "memory");
        asm volatile("fence.proxy.async.global;" ::: "memory");
        asm volatile("fence.acq_rel.gpu; griddepcontrol.launch_dependents;" ::: "memory");
        asm volatile("red.relaxed.gpu.global.add.u32 [%0],1;" :: "l"(&g_flag[24 * 32]) : "memory");
        flag_wait(&g_flag[24 * 32], 132);
        asm volatile("fence.proxy.async.global;" ::: "memory");
        const char* base = (const char*)g_scr;
        const int c = cta >> 1, half = cta & 1, ch = (c + (c >> 4) * 5) & 15;
        bulk_pf(base + (PS_OFF + c * NC * 2000) * 16u + half * 16000, 16000);
        bulk_pf(base + (PT_OFF + c * 10 * 1024) * 16u + half * 8000, 8000);
        mbar_expect(fullE, 18432);
        bulk_g2s(sbase + K1_B, base + (I0_OFF + half * 2048 + ch * 128) * 16u, 2048, fullE);
        bulk_g2s(sbase + K1_B + 2048, base + (IX_OFF + half * IXH + ch * 512) * 16u, 8192, fullE);
        bulk_g2s(sbase + K1_B + 10240, base + (IX_OFF + half * IXH + 8192 + ch * 512) * 16u, 8192, fullE);
        mbar_wait(fullE, 1);
      }
    } else {
      const int pw = (tid >> 5) & 1, rg = (cta >> 4) * 8 + ((cta & 15) >> 1), hf = cta & 1;
      const int* ip = idx + (rg * 256 + hf * 8) * F_;
      asm volatile("bar.sync 2,512;" ::: "memory");
      const uint32_t buf = sbase + K1_BAR + 256 + pw * 3200, bar = pkFull + pw * 8;
      const unsigned* fl = &g_flag[(cta >> 4) * 96];
      int batch = 0, rel = pw ? 3 : 0;
#pragma unroll 1
      for (int n = 1 + pw; n < 16; n += 2) {
        if (lane == 0) { mbar_expect(bar, 3200); bulk_g2s(buf, ip + n * 16 * F_, 3200, bar); if (n + 2 < 16) bulk_pf(ip + (n + 2) * 16 * F_, 3200); }
        uint32_t ok; int it = 0;
        do {
          if (rel < batch) {
            unsigned v; asm volatile("ld.relaxed.gpu.global.u32 %0,[%1];" : "=r"(v) : "l"(fl + rel * 32) : "memory");
            if (__all_sync(0xffffffffu, v >= 16)) { flag_wait(fl + rel * 32, 16); __syncwarp(); mbar_arrive_lane0(pxRdy + rel * 8); rel++; }
          }
          asm volatile("{.reg .pred p; mbarrier.test_wait.parity.shared::cta.b64 p,[%1],%2; selp.u32 %0,1,0,p;}" : "=r"(ok) : "r"(bar), "r"(((n - 1) >> 1) & 1) : "memory");
          ok = __all_sync(0xffffffffu, ok);
          if (!ok) __nanosleep(100);
        } while (!ok && ++it < (1 << 20));
        auto ld = [&](uint32_t ad) { uint32_t v; asm volatile("ld.shared.u32 %0,[%1];" : "=r"(v) : "r"(ad)); return v; };
        const uint32_t p0 = buf + ((lane >> 3) & 1) * 400 + ((lane >> 4) * 8 + (lane & 7)) * 4;
        auto wd = [&](int t, int h) { return pk3(ld(p0 + t * 800 + h * 192), ld(p0 + t * 800 + h * 192 + 64), ld(p0 + t * 800 + h * 192 + 128)); };
        uint4* dst = g_scr + PX_OFF + (rg * 16 + n) * 136;
        ((unsigned short*)(dst + 128))[lane * 2 + hf] = ld(buf + g * 400 + 384 + r * 4);
#pragma unroll
        for (int q = 0; q < 2; q++) dst[(hf * 2 + q) * 32 + lane] = make_uint4(wd(2 * q, 0), wd(2 * q, 1), wd(2 * q + 1, 0), wd(2 * q + 1, 1));
        __syncwarp();
        if (n <= 2 || n == 5 || n == 6 || n >= 14) { mbar_arrive_lane0(pkDone + batch * 8); batch++; }
      }
      for (; rel < 3; rel++) { flag_wait(fl + rel * 32, 16); __syncwarp(); mbar_arrive_lane0(pxRdy + rel * 8); }
      if (lane == 0) {
        mbar_wait(pxRdy + 16, 0);
        asm volatile("fence.proxy.async.global;" ::: "memory");
        const char* src = (const char*)(g_scr + PX_OFF + ((cta >> 4) * 8 + ((cta >> 1) & 3) * 2 + pw) * 16 * 136);
        int ph = pw;
#pragma unroll 1
        for (int n = 5; n < 16; n++) {
          uint32_t cur; int it = 0;
          do { asm volatile("ld.volatile.shared.u32 %0,[%1];" : "=r"(cur) : "r"(progG)); if (cur + 2 < n) __nanosleep(400); } while (cur + 2 < n && ++it < (1 << 16));
          if (cur + 1 >= n) continue;
          mbar_expect(bar, 2176); bulk_g2s(buf, src + n * 2176, 2176, bar);
          mbar_wait(bar, ph); ph ^= 1;
        }
      }
    }
    return;
  }
  if (tid >= 256) {
    asm volatile("setmaxnreg.inc.sync.aligned.u32 160;");
    const int w = (tid >> 5) & 3;
    const int srow = w * 16 + ((lane & 15) ^ ((lane & 1) << 2)), sc = lane >> 4;
    uint32_t a[2][8][4];
    asm volatile("bar.sync 2,512;" ::: "memory");
    mbar_wait_fast(fullE, 0);
#pragma unroll
    for (int mt = 0; mt < 2; mt++)
#pragma unroll
      for (int ks = 0; ks < 8; ks++)
        asm volatile("ldmatrix.sync.aligned.m8n8.x4.shared.b16 {%0,%1,%2,%3},[%4];"
                     : "=r"(a[mt][ks][0]), "=r"(a[mt][ks][1]), "=r"(a[mt][ks][2]), "=r"(a[mt][ks][3])
                     : "r"(sbase + K1_B + 32768 + (ks >> 2) * 16384 + (mt * 64 + srow) * 128 + ((((ks & 3) * 2 + sc) ^ (srow & 7)) * 16)) : "memory");
    asm volatile("barrier.cluster.wait.aligned;" ::: "memory");
    arrive_both(emptyB + 8, lane);
    const int v = w * 16 + (g ^ ((g & 1) << 2));
    const uint32_t baseL = v * 256 + r * 64 + ((v & 1) * 2 + (r >> 1)) * 16, baseS = (v >> 2) * 512 + r * 128 + (((v & 3) * 2) ^ ((v & 4) + r)) * 16,
                   baseT = (v >> 3) * 512 + r * 128 + ((v & 7) ^ r) * 16;
    const uint64_t desc0 = (uint64_t)(((sbase + K1_B) & 0x3FFFF) >> 4) | ((uint64_t)(8192 >> 4) << 16) | ((uint64_t)(512 >> 4) << 32) | (2ull << 62);
#pragma unroll 1
    for (int qn = 0; qn < 25; qn++) {
      const int quad = quad_of(qn), st = qn & 1;
      const bool isL = quad < 18;
      PT(qn * 16);
      mbar_wait_fast(fullB + st * 8, (qn >> 1) & 1);
#pragma unroll
      for (int mt = 0; mt < 2; mt++) {
        float d[64];
        PT(qn * 16 + mt * 4 + 1);
        asm volatile("wgmma.fence.sync.aligned;" ::: "memory");
#pragma unroll
        for (int ks = 0; ks < 8; ks++) wgmma_p(d, a[mt][ks], desc0 + st * 2048 + ks * 64, ks);
        asm volatile("wgmma.commit_group.sync.aligned;" ::: "memory");
        mbar_wait_fast(emptyS, mt ^ 1);
        PT(qn * 16 + mt * 4 + 2);
        asm volatile("wgmma.wait_group.sync.aligned 0;" ::: "memory");
#pragma unroll
        for (int q = 0; q < 16; q++) asm volatile("" : "+f"(d[q * 4]), "+f"(d[q * 4 + 1]), "+f"(d[q * 4 + 2]), "+f"(d[q * 4 + 3]) :: "memory");
        PT(qn * 16 + mt * 4 + 3);
        if (mt) arrive_both(emptyB + st * 8, qn < 23 ? lane : 9);
        if (quad == 24) {
#pragma unroll
          for (int cq = 0; cq < 4; cq++) {
            const uint32_t bw = __ldg((const uint32_t*)(b1 + hc * 32 + cq * 8) + r);
#pragma unroll
            for (int e = 0; e < 4; e++) d[48 + cq * 4 + e] += (e & 1) ? bf_hi(bw) : bf_lo(bw);
          }
        }
#pragma unroll
        for (int h = 0; h < 2; h++) {
          const bool isS = quad * 2 + h < 45;
          const uint32_t base = (isL ? baseL ^ (h * 32) : (isS ? baseS : baseT) ^ (h * 8192)), xj = isS ? 16 : 4096, xr = isL ? 2048 : isS ? 1024 : 576;
#pragma unroll
          for (int e4 = 0; e4 < 4; e4++) {
            const float* e = d + h * 32 + (e4 >> 1) * 16 + (e4 & 1) * 2;
            sts128(sbase + K1_STG + (base ^ ((e4 >> 1) * xj) ^ ((e4 & 1) * xr)),
                   make_uint4(pack_bf2(e[0], e[1]), pack_bf2(e[4], e[5]), pack_bf2(e[8], e[9]), pack_bf2(e[12], e[13])));
          }
        }
        __syncwarp();
        mbar_arrive_lane0(fullS);
        if (!mt) PT(qn * 16 + 4);
      }
      PT(qn * 16 + 8);
    }
    return;
  }
  const int slice = cta & 15;
  const int range = (cta >> 4) * 8 + __shfl_sync(0xffffffffu, tid >> 5, 0);
  uint4 iv[4], trow[4]; uint32_t ix;
  uint2 wrow[10];
#pragma unroll
  for (int q = 0; q < 10; q++) asm volatile("ld.global.nc.v2.u32 {%0,%1},[%2];" : "=r"(wrow[q].x), "=r"(wrow[q].y) : "l"((const uint2*)wp + min(tid + q * 256, 2499)));
  asm volatile("bar.sync 2,512;" ::: "memory");
  uint32_t me = 0, mw = 0;
#pragma unroll
  for (int q = 0; q < 10; q++) {
    mw = __vmaxu2(__vmaxu2(wrow[q].x & 0x7fff7fffu, wrow[q].y & 0x7fff7fffu), mw);
    const int e = min(tid + q * 256, 2499), row = e / 25;
    asm volatile("st.shared.v2.u32 [%0],{%1,%2};" :: "r"(sbase + (e + row) * 8), "r"(wrow[q].x), "r"(wrow[q].y) : "memory");
    if (e - row * 25 == 24) asm volatile("st.shared.v2.u32 [%0],{%1,%2};" :: "r"(sbase + (e + row) * 8 + 8), "r"(wrow[q].x), "r"(wrow[q].y) : "memory");
  }
  mbar_wait_fast(fullC, 0);
#pragma unroll
  for (int q = 0; q < 4; q++) { trow[q] = lds128(sbase + 32768 + (tid + q * 256) * 16); me = absmax4(trow[q], me); }
  me = __reduce_max_sync(0xffffffffu, max(me & 0xffff, me >> 16));
  mw = __reduce_max_sync(0xffffffffu, max(mw & 0xffff, mw >> 16));
  uint32_t* sred = (uint32_t*)((char*)sm + 128000);
  if (lane == 0) sred[tid >> 5] = me | mw << 16;
  TS(3, 0);
  asm volatile("setmaxnreg.inc.sync.aligned.u32 160;");
  asm volatile("bar.sync 1,256;" ::: "memory");
  { uint32_t m = 0;
#pragma unroll
    for (int q = 0; q < 8; q++) m = __vmaxu2(m, sred[q]);
    m = __shfl_sync(0xffffffffu, m, 0);
    me = m & 0xffff; mw = m >> 16; }
  const float se = pow2_scale(me, 3), sW = pow2_scale(mw, -2);
  TS(3, 1);
  auto put_rows = [&](int q, bool on) {
    const uint4 t = trow[q];
    const uint4 hv = make_uint4(pack_h2(bf_lo(t.x) * se, bf_hi(t.x) * se), pack_h2(bf_lo(t.y) * se, bf_hi(t.y) * se),
                                pack_h2(bf_lo(t.z) * se, bf_hi(t.z) * se), pack_h2(bf_lo(t.w) * se, bf_hi(t.w) * se));
    if (on)
#pragma unroll
      for (int s = 0; s < 8; s++) sts128(sbase + (tid + q * 256) * 128 + ((s + lane) & 7) * 16, hv);
  };
#pragma unroll 1
  for (int it = 0; it < 3; it++) {
    const int hu = ((tid >> 5) * 3 + it) * 4, code = hu_code(min(hu + (lane >> 3), HU_N - 1)), ok = code >> 4, on = code & 15;
    uint32_t x[4], y[4];
    asm volatile("ldmatrix.sync.aligned.m8n8.x4.shared.b16 {%0,%1,%2,%3},[%4];" : "=r"(x[0]), "=r"(x[1]), "=r"(x[2]), "=r"(x[3])
                 : "r"(sbase + (on * 8 + (lane & (on == 12 ? 3 : 7))) * 208 + ok * 16) : "memory");
    asm volatile("ldmatrix.sync.aligned.m8n8.x4.trans.shared.b16 {%0,%1,%2,%3},[%4];" : "=r"(y[0]), "=r"(y[1]), "=r"(y[2]), "=r"(y[3])
                 : "r"(sbase + (ok * 8 + (lane & (ok == 12 ? 3 : 7))) * 208 + on * 16) : "memory");
    const uint32_t lo = __ballot_sync(0xffffffffu, ok > on), dg = __ballot_sync(0xffffffffu, ok >= on);
#pragma unroll
    for (int q = 0; q < 4; q++) {
      const float m0 = (lo >> (8 * q)) & 1 ? 0.f : sW, m1 = (dg >> (8 * q)) & 1 ? 0.f : sW;
      asm volatile("st.shared.u32 [%0],%1;" :: "r"(sbase + K1_W + (hu + q) * 128 + lane * 4),
                   "r"(pack_h2(fmaf(bf_lo(x[q]), m0, bf_lo(y[q]) * m1), fmaf(bf_hi(x[q]), m0, bf_hi(y[q]) * m1))) : "memory");
    }
  }
  put_rows(1, true); put_rows(2, tid < 88);
  TS(3, 2);
  asm volatile("fence.proxy.async.shared::cta;" ::: "memory");
  asm volatile("bar.sync 1,256;" ::: "memory");
  put_rows(0, true);
  uint32_t bf[HU_N - 2 * G_U];
#pragma unroll
  for (int q = 0; q < HU_N - 2 * G_U; q++) asm volatile("ld.shared.u32 %0,[%1];" : "=r"(bf[q]) : "r"(sbase + K1_W + (2 * G_U + q) * 128 + lane * 4));
  const float unscale = __uint_as_float(0x7f000000u - __float_as_uint(se)), unscale2 = __uint_as_float(0x7f000000u - __float_as_uint(sW));
  TS(3, 3);
  const int px = range * 16 * 136;
  mbar_wait_fast(fullI, 0);
  {
    const uint32_t ib = sbase + 76800 + (tid >> 5) * 6400, p0 = ib + ((lane >> 3) & 1) * 400 + ((lane >> 4) * 8 + (lane & 7)) * 4;
    auto ld = [&](uint32_t ad) { uint32_t v; asm volatile("ld.shared.u32 %0,[%1];" : "=r"(v) : "r"(ad)); return v; };
    auto wd = [&](int t, int h) { return pk3(ld(p0 + t * 800 + h * 192), ld(p0 + t * 800 + h * 192 + 64), ld(p0 + t * 800 + h * 192 + 128)); };
#pragma unroll
    for (int q = 0; q < 4; q++) {
      iv[q] = make_uint4(wd(2 * q, 0), wd(2 * q, 1), wd(2 * q + 1, 0), wd(2 * q + 1, 1));
    }
    ix = ld(ib + g * 400 + 384 + r * 4) | ld(ib + (8 + g) * 400 + 384 + r * 4) << 16;
  }
  asm volatile("bar.sync 1,256;" ::: "memory");
  put_rows(2, tid >= 88); put_rows(3, tid + 768 < V_);
  asm volatile("bar.sync 1,256;" ::: "memory");
  TS(0, 1);
  uint32_t lc; asm volatile("add.u32 %0,%1,%2;" : "=r"(lc) : "r"((lane & 7) * 16), "r"(never));
  const uint64_t wdesc = (uint64_t)(((sbase + K1_W) & 0x3FFFF) >> 4) | ((uint64_t)(128 >> 4) << 16) | ((uint64_t)(256 >> 4) << 32);
  uint32_t a[2][6][4], d[2][26], ex[4] = {}, s[4] = {};
  float red[4] = {0.f, 0.f, 0.f, 0.f};
  auto ldsm = [&](uint32_t* o, uint32_t sh) {
    asm volatile("ldmatrix.sync.aligned.m8n8.x4.trans.shared.b16 {%0,%1,%2,%3},[%4];"
                 : "=r"(o[0]), "=r"(o[1]), "=r"(o[2]), "=r"(o[3]) : "r"(sbase + ((sh & 0x1ff80) | lc)));
  };
  auto gather = [&](int t, int hf) {
    const int x = t & 1;
    const uint4 v = iv[(t >> 1) & 3];
#pragma unroll
    for (int kb = 3 * hf; kb < 3 * hf + 3; kb++) {
      const uint32_t ww = x ? (kb < 3 ? v.z : v.w) : (kb < 3 ? v.x : v.y);
      ldsm(a[x][kb], kb % 3 == 0 ? ww : kb % 3 == 1 ? ww >> 10 : __funnelshift_l(ww, ww, 12));
    }
  };
  auto issue = [&](int x) {
    asm volatile("wgmma.fence.sync.aligned;" ::: "memory");
#pragma unroll
    for (int kb = 0; kb < 6; kb++) {
      if (kb < G_K0) wgmma_h<G_N0 * 8>(d[x] + G_O0 * 2, a[x][kb], wdesc + kb * G_N0 * 16, kb);
      if (kb < G_K1) wgmma_h<G_N1 * 8>(d[x] + G_O1 * 2, a[x][kb], wdesc + (G_U1 + kb * G_N1) * 16, kb);
      if (kb < G_K2) wgmma_h<32>(d[x] + G_O2 * 2, a[x][kb], wdesc + (G_U2 + kb * G_N2) * 16, kb);
    }
    asm volatile("wgmma.commit_group.sync.aligned;" ::: "memory");
  };
  auto hmma_part = [&](int t) {
    constexpr FragIdx FI = make_fi();
    const int x = t & 1;
#pragma unroll
    for (int o = 0; o < 13; o++) asm volatile("" : "+r"(d[x][o * 2]), "+r"(d[x][o * 2 + 1]) :: "memory");
#pragma unroll
    for (int kb = 0; kb < 6; kb++)
#pragma unroll
      for (int o = 2 * kb + 1; o < 13; o++)
        if (!unit_wg(kb, o)) mma16816h(d[x] + o * 2, a[x][kb], bf[FI.v[2 * kb][o]], bf[FI.v[2 * kb + 1][o]]);
#pragma unroll
    for (int q = 0; q < 6; q++) if (!unit_wg(q, 2 * q)) mma1688h(d[x] + q * 4, a[x][q][0], a[x][q][1], bf[FI.v[2 * q][2 * q]]);
    mma1688h(d[x] + 24, r < 2 ? ex[t & 3] : 0u, r < 2 ? 0u : ex[t & 3], bf[FI.v[12][12]]);
  };
  auto dot_part = [&](int t, int hf) {
    const int x = t & 1;
    if (hf == 0) {
      const uint32_t pe = hfma2(r < 2 ? d[x][24] : d[x][25], ex[t & 3], 0u);
      s[0] = r < 2 ? pe : 0u; s[1] = r < 2 ? 0u : pe; s[2] = s[3] = 0;
    }
#pragma unroll
    for (int q = 3 * hf; q < 3 * hf + 3; q++)
#pragma unroll
      for (int e = 0; e < 4; e++) s[e] = hfma2(d[x][q * 4 + e], a[x][q][e], s[e]);
  };
  float* outp = g_partP + slice * B_ + range * 256;
  float k0 = 0.f, k1 = 0.f, x0 = 0.f, x1 = 0.f;
  auto red_stage = [&](int st, int grp) {
    const bool u16 = lane & 16, u8 = lane & 8;
    if (st == 0) {
      k0 = u16 ? red[2] : red[0]; x0 = __shfl_xor_sync(0xffffffffu, u16 ? red[0] : red[2], 16);
      k1 = u16 ? red[3] : red[1]; x1 = __shfl_xor_sync(0xffffffffu, u16 ? red[1] : red[3], 16);
      red[0] = red[1] = red[2] = red[3] = 0.f;
    }
    if (st == 1) { const float p0 = k0 + x0, p1 = k1 + x1; k0 = u8 ? p1 : p0; x0 = __shfl_xor_sync(0xffffffffu, u8 ? p0 : p1, 8); }
    if (st == 2) { k0 += x0; x0 = __shfl_xor_sync(0xffffffffu, k0, 4); }
    if (st == 3 && !(lane & 4)) outp[grp * 16 + r * 4 + ((lane >> 3) & 1) * 2 + (lane >> 4)] = (k0 + x0) * unscale * unscale * unscale2;
  };
  auto group = [&](bool first, int prv, int cur, int nxt) {
    const int pn = PX_OFF + px + nxt * 136 + lane;
#pragma unroll
    for (int t = 0; t < 8; t++) {
      issue((t & 1) ^ 1);
      SCHED_FENCE(never, t * 8);
      if (!first) {
        if (t == 0) { iv[3] = ldtex(tex, PX_OFF + px + cur * 136 + lane + 96); iv[0] = ldtex(tex, pn); }
        if (t == 2) iv[1] = ldtex(tex, pn + 32);
        if (t < 4) red_stage(t, prv);
      } else if (t == 4) {
        TS(4, 2);
        mbar_wait_fast(pxRdy, 0);
        TS(4, 3);
        iv[0] = ldtex(tex, pn); iv[1] = ldtex(tex, pn + 32);
      }
      if (t == 4) { ix = ldtex(texX, (px + nxt * 136 + 128) * 4 + lane).x; iv[2] = ldtex(tex, pn + 64); }
      dot_part(t, 0);
      SCHED_FENCE(never, t * 8 + 1);
      if (t == 3) ldsm(ex, ix >> 9);
      if (t == 7) ldsm(ex, ix << 7);
      gather(t + 2, 0);
      dot_part(t, 1);
      SCHED_FENCE(never, t * 8 + 4);
      gather(t + 2, 1);
      asm volatile("wgmma.wait_group.sync.aligned 0;" ::: "memory");
      asm volatile("" : "+r"(d[(t & 1) ^ 1][0]) :: "memory");
      mma1688f(red, hadd2(s[0], s[2]), hadd2(s[1], s[3]), (g | (d[(t & 1) ^ 1][0] & never)) == t ? 0x3c003c00u : 0u);
      hmma_part(t + 1);
    }
  };
  gather(0, 0); gather(0, 1); issue(0); ldsm(ex, ix << 7); gather(1, 0); gather(1, 1);
  asm volatile("wgmma.wait_group.sync.aligned 0;" ::: "memory");
  hmma_part(0);
  group(true, 0, 0, 1);
  TS(4, 1);
#pragma unroll 1
  for (int n = 1; n < 16; n++) {
    if ((n & 11) == 2) mbar_wait_fast(pxRdy + 8 + (n & 4) * 2, 0);
    asm volatile("st.volatile.shared.u32 [%0],%1;" :: "r"(progG), "r"(n) : "memory");
    group(false, n - 1, n, min(n + 1, 15));
  }
#pragma unroll
  for (int st = 0; st < 4; st++) red_stage(st, 15);
  TS(0, 2);
  asm volatile("barrier.cluster.wait.aligned;" ::: "memory");
  asm volatile("barrier.cluster.arrive.relaxed.aligned; barrier.cluster.wait.aligned;" ::: "memory");
}

constexpr int SM_U = 130048, SM_BAR = 128000, SM_J = SM_U + 98304, DEEP_SMEM = SM_J + 4096;

__global__ void __cluster_dims__(2, 1, 1) __launch_bounds__(TH + 128, 1)
k_deep(cudaTextureObject_t tex, const __nv_bfloat16* __restrict__ w2, const __nv_bfloat16* __restrict__ b2,
       __nv_bfloat16* __restrict__ out, int never) {
  extern __shared__ __align__(1024) uint4 sm[];
  constexpr int PF = 4, DEPTH = 4, NW = TH / 32;
  const int tid = threadIdx.x;
  const int c = blockIdx.x >> 1, half = blockIdx.x & 1;
  const uint32_t sbase = (uint32_t)__cvta_generic_to_shared(sm);
  const uint32_t fullL = sbase + SM_BAR, fullU = fullL + 8, emptyL = fullL + 16, emptyU = fullL + 24, barJ = fullL + 32;
  TS(1, 0);
  if (tid == 0) {
    mbar_init(fullL, 1); mbar_init(fullU, 1); mbar_init(emptyL, 2 * NW); mbar_init(emptyU, 2 * NW); mbar_init(barJ, 1);
    asm volatile("fence.mbarrier_init.release.cluster;" ::: "memory");
  }
  __syncwarp();
  const int wrp = __shfl_sync(0xffffffffu, tid >> 5, 0);
  const char* base = (const char*)g_scr;
  uint32_t oL = (PL_OFF + c * NC * 8000) * 16u + half * 64000, oS = (PS_OFF + c * NC * 2000) * 16u + half * 16000;
  asm volatile("barrier.cluster.arrive.relaxed.aligned; barrier.cluster.wait.aligned;" ::: "memory");
  if (wrp == NW) {
    asm volatile("fence.proxy.async.global;" ::: "memory");
    e_expect(fullU, 96000);
#pragma unroll
    for (int m = 0; m < 3; m++) e_mc(sbase + SM_U + m * 32032 + half * 16000, base + oS, 16000, fullU, m == 2 ? POL_EF : POL_N);
    e_expect(fullL, 128000);
  }
  TS(5, 1);
  if (wrp >= NW) {
    asm volatile("setmaxnreg.dec.sync.aligned.u32 24;");
    if (wrp == NW) {
      uint32_t oT = (PT_OFF + c * 10 * 1024) * 16u + half * 8000;
      auto warm = [&](uint32_t off, uint32_t hb) {
        asm volatile(ELECT "mbarrier.expect_tx.relaxed.cta.shared::cta.b64 [%0],%1;}" :: "r"(barJ), "r"(2 * hb) : "memory");
        e_g2s(sbase + SM_J, base + off, hb, barJ); e_g2s(sbase + SM_J, base + off + hb, hb, barJ);
      };
      mbar_wait(fullU, 0);
      e_mc(sbase + half * 64000, base + oL, 64000, fullL, POL_EF);
      warm(oT, 4000);
#pragma unroll 1
      for (int k = 0; k + 1 < NC; k++) {
        oL += 128000; oS += 32000; oT += 16384;
        mbar_wait(fullL, k & 1);
        const uint32_t t0 = clock();
        e_pf(base + oS, 16000);
        warm((IX_OFF + half * IXH + (k + 2) * 8192 + ((c + (c >> 4) * (2 * k + 1)) & (k + 2 < NC ? 15 : 3)) * 512) * 16u, 4096);
        mbar_wait(emptyU, k & 1);
        e_expect(fullU, 96000);
#pragma unroll 1
        for (int q = 0; q < 8; q++) {
          sleep_until(t0, q * PACE);
          e_pf(base + oL + q * 8000, 8000);
          if (q >= 2) e_mc(sbase + SM_U + ((q - 2) >> 1) * 32032 + half * 16000 + (q & 1) * 8000, base + oS + (q & 1) * 8000, 8000, fullU, q >= 6 ? POL_EF : POL_N);
        }
        warm(oT, 4000);
        e_expect(fullL, 128000);
        sleep_until(t0, 7200);
        unsigned long long now, slot = 0;
        asm volatile("mov.u64 %0,%globaltimer;" : "=l"(now));
        if ((tid & 31) == 0) { atomicMax(&g_slot, now + 550); slot = atomicAdd(&g_slot, (unsigned long long)RSV); }
        slot = __shfl_sync(0xffffffffu, slot, 0);
        mbar_wait(emptyL, k & 1);
        for (int it = 0; it < 4000; it++) { asm volatile("mov.u64 %0,%globaltimer;" : "=l"(now)); if (now >= slot) break; }

        e_mc(sbase + half * 64000, base + oL, 64000, fullL, POL_EF);
      }
      mbar_wait(fullL, (NC - 1) & 1);
      mbar_wait(emptyU, (NC - 1) & 1);
      mbar_arrive_lane0(fullU);
      warm(oT + 16384, 4000);
      mbar_arrive_lane0(barJ); mbar_wait(barJ, 0);
    } else if (tid >= TH + 96) {
      if (tid < TH + 100) asm volatile("st.shared.u32 [%0],%1;" :: "r"(barJ + 32 + (tid & 3) * 4), "r"(((const uint32_t*)w2)[(c >> 2) * 16 + (tid & 3) * 4 + (c & 3)]) : "memory");
      asm volatile("bar.arrive 3,%0;" :: "n"(TH + 32) : "memory");
      asm volatile("griddepcontrol.wait;" ::: "memory");
      const int b = half * 8192 + c * 128 + (tid & 31) * 4;
      const float bias = __bfloat162float(b2[0]);
      float4 s = make_float4(bias, bias, bias, bias);
#pragma unroll 2
      for (int k = 0; k < 16; k++) { const float4 v = __ldcg((const float4*)(g_partP + k * B_ + b)); s.x += v.x; s.y += v.y; s.z += v.z; s.w += v.w; }
      asm volatile("red.global.add.v4.f32 [%0],{%1,%2,%3,%4};" :: "l"(g_acc + b), "f"(s.x), "f"(s.y), "f"(s.z), "f"(s.w) : "memory");
      asm volatile("bar.arrive 1,%0;" :: "n"(TH + 32) : "memory");
    }
    return;
  }
  asm volatile("setmaxnreg.inc.sync.aligned.u32 240;");
  const int lane = tid & 31;
  const int tbase = PT_OFF + c * 10 * 1024;
  const int ibase = IX_OFF + half * IXH + tid;
  const uint32_t lc = (tid & 7) << 4;
  uint4 acc[NS], wq[PF], x[DEPTH], y[YD], ye;
  uint32_t sw[NS] = {};
  auto sget = [&](int s) { return (s & 3) == 3 ? __byte_perm(__byte_perm(sw[s - 3], sw[s - 2], 0x0073), sw[s - 1], 0x0710) : sw[s]; };
  auto sa0 = [&](uint32_t v) { return sbase + SM_U + (((v << 5) & 0x1ffe0) | ((lc >> 2) & 16)); };
  uint32_t c1 = 0;
  auto sa1 = [&](uint32_t v) { return sbase + SM_U + (((v >> 7) & 0x1ffe0) | c1); };
  {
    uint4 i0[8];
#pragma unroll
    for (int q = 0; q < 8; q++) i0[q] = ldtex(tex, I0_OFF + (half * 8 + q) * TH + tid);
    auto wd = [&](int k) { return (k & 3) == 0 ? i0[k >> 2].x : (k & 3) == 1 ? i0[k >> 2].y : (k & 3) == 2 ? i0[k >> 2].z : i0[k >> 2].w; };
    TS(5, 2);
    mbar_wait_fast(fullU, 0);
#pragma unroll
    for (int i = 0; i < PF; i++) wq[i] = ldtex(tex, ibase + i * TH);
    TS(1, 1);
#pragma unroll
    for (int s = 0; s < NS; s++) acc[s] = add4(lds128(sbase + SM_U + (wd(s) & 0x1fff0)), lds128(sbase + SM_U + ((wd(s) >> 13) & 0x1fff0)));
    arrive_both(emptyU, lane);
    asm volatile("bar.sync 3,%0;" :: "n"(TH + 32) : "memory");
    TS(5, 3);
  }
#pragma unroll 1
  for (int k = 0; k < NC; k++) {
    const int ti = ibase + k * 8192;
    const int tb = tbase + k * 1024;
    const bool more = k + 1 < NC;
    TR(k * 4);
    mbar_wait_fast(fullL, k & 1);
    TR(k * 4 + 2);
    uint4 w, cc; uint32_t yc;
    constexpr int TL = NS * 8, TT = TL + NS * 2;
#pragma unroll
    for (int t = 0; t < TT + DEPTH; t += 2) {
      if (t == TL + DEPTH && !more) break;
      if (t >= DEPTH) {
        const int u = t - DEPTH;
        uint4 p = add4(x[u % DEPTH], x[(u + 1) % DEPTH]);
        if (u < TL) {
          const int s = u >> 3, j = u & 7;
          if (j == 0) {
            cc = s >= YD ? add4(y[s % YD], p) : p;
            if (s + YD < NS) y[s % YD] = ldtex(tex, tb | (yc & 1023));
          } else cc = add4(cc, p);
          if (j == 6) acc[s] = add4(acc[s], cc);
        } else {
          const int s = (u - TL) >> 1;
          acc[s] = add4(acc[s], p);
        }
      }
      if (t < TL) {
        const int s = t >> 3, j = t & 7;
        if (j == 0) {
          if (ye_of(s - YD) >= 0) acc[ye_of(s - YD) & 3] = add4(acc[ye_of(s - YD) & 3], ye);
          w = wq[s % PF];
          wq[s % PF] = ldtex(tex, ti + (s + PF) * TH);
          yc = __funnelshift_l(w.z, w.z, 5);
          if ((s & 3) != 3) asm volatile("add.u32 %0,%1,%2;" : "=r"(sw[s]) : "r"(w.w), "r"(never));
          if (ye_of(s) >= 0) ye = ldtex(tex, tb | w.w);
        }
#pragma unroll
        for (int jj = j; jj < j + 2; jj++) {
          const uint32_t ww = jj < 3 ? w.x : jj < 6 ? w.y : w.z;
          const uint32_t sh = jj % 3 == 0 ? ww : jj % 3 == 1 ? ww >> 10 : __funnelshift_l(ww, ww, 12);
          x[(t + jj - j) % DEPTH] = lds128(sbase + ((sh & 0x1ff80) | lc) + jj * 16 - 128);
        }
      } else if (t < TT) {
        const int s = (t - TL) >> 1;
        if (s == 0) {
          asm volatile("add.u32 %0,%1,%2;" : "=r"(c1) : "r"((~lc >> 2) & 16), "r"(never));
          arrive_both(emptyL, more ? lane : 9);
          TR(k * 4 + 3);
          mbar_wait_fast(fullU, (k + 1) & 1);
        }
        const uint32_t sv = sget(s);
        x[t % DEPTH] = lds128(sa0(sv));
        x[(t + 1) % DEPTH] = lds128(sa1(sv));
      } else if (t == TT) arrive_both(emptyU, lane);
      if ((t & 3) == 2) SCHED_FENCE(never, t);
    }
  }
  TS(1, 2);
  const uint4 w2v = lds128(barJ + 32);
  const uint32_t cell = sbase + SM_U + tid * 16;
  const int t9 = tbase + 9 * 1024;
  uint4 za[4], i9 = wq[0];
  auto fetch = [&](int q) {
    y[0] = ldtex(tex, t9 | i9.x); y[1] = ldtex(tex, t9 | i9.y); y[2] = ldtex(tex, t9 | i9.z); y[3] = ldtex(tex, t9 | i9.w);
    if (q) {
      i9 = ldtex(tex, ibase + NC * 8192 + min(q + 1, 7) * TH);
      const uint32_t ca = cell + (q > 6 ? 0 : q - 1) * 16384;
#pragma unroll
      for (int s = 0; s < 4; s++) za[s] = lds128(ca + s * 4096);
    }
  };
  fetch(0);
  i9 = wq[1];
#pragma unroll
  for (int s = 0; s < 4; s++) za[s] = acc[s];
#pragma unroll
  for (int s = 0; s < 24; s++) sts128(cell + s * 4096, acc[4 + s]);
  float hw[8];
  {
    const uint32_t ww[4] = {w2v.x, w2v.y, w2v.z, w2v.w};
#pragma unroll
    for (int k = 0; k < 8; k++) hw[k] = 0.5f * ((k & 1) ? bf_hi(ww[k >> 1]) : bf_lo(ww[k >> 1]));
  }
  float* outp = g_acc + half * 8192 + tid;
#pragma unroll 1
  for (int q = 0; q < NS / 4; q++) {
    uint4 z[4];
#pragma unroll
    for (int s = 0; s < 4; s++) z[s] = add4(za[s], y[s]);
    if (q == 1) {
#pragma unroll
      for (int s = 0; s < 4; s++) sts128(cell + s * 4096, acc[28 + s]);
    }
    if (q < 7) fetch(q + 1);
    SCHED_FENCE(never, 999);
#pragma unroll
    for (int s = 0; s < 4; s++) {
      const uint32_t a[4] = {z[s].x, z[s].y, z[s].z, z[s].w};
      float r0 = 0.f;
#pragma unroll
      for (int k = 0; k < 8; k++) {
        const float v = (k & 1) ? bf_hi(a[k >> 1]) : bf_lo(a[k >> 1]);
        const float u = v * fmaf(v * v, 0.7978845608028654f * 0.044715f, 0.7978845608028654f);
        float th; asm("tanh.approx.f32 %0,%1;" : "=f"(th) : "f"(u));
        r0 = fmaf(fmaf(v, th, v), hw[k], r0);
      }
      asm volatile("red.global.add.f32 [%0],%1;" :: "l"(outp + s * TH), "f"(r0) : "memory");
    }
    outp += 4 * TH;
  }
  TS(1, 3);
  asm volatile("bar.sync 1,%0;" :: "n"(TH + 32) : "memory");
  if (tid == 0) {
    unsigned old; asm volatile("atom.acq_rel.gpu.global.inc.u32 %0,[%1],63;" : "=r"(old) : "l"(&g_done[half * 32]) : "memory");
    asm volatile("st.shared.u32 [%0],%1;" :: "r"(barJ + 8), "r"(old) : "memory");
  }
  asm volatile("bar.sync 2,%0;" :: "n"(TH) : "memory");
  uint32_t old; asm volatile("ld.shared.u32 %0,[%1];" : "=r"(old) : "r"(barJ + 8));
  if (old == 63) {
    if (half == 0 && tid == 25) g_slot = 0;
    if (half == 0 && tid < 25) g_flag[tid * 32] = 0;
    float4 v[8];
#pragma unroll
    for (int q = 0; q < 8; q++) v[q] = __ldcg((const float4*)(g_acc + half * 8192) + q * TH + tid);
#pragma unroll
    for (int q = 0; q < 8; q++) ((uint2*)(out + half * 8192))[q * TH + tid] = make_uint2(pack_bf2(v[q].x, v[q].y), pack_bf2(v[q].z, v[q].w));
    TS(6, 2);
  }
}

}

extern "C" void kernel_launch(void* const* d_in, const int* in_sizes, int n_in, void* d_out, int out_size) {
  const int* idx = (const int*)d_in[0];
  const __nv_bfloat16* table = (const __nv_bfloat16*)d_in[1];
  const __nv_bfloat16* wp = (const __nv_bfloat16*)d_in[2];
  const __nv_bfloat16* w1 = (const __nv_bfloat16*)d_in[3];
  const __nv_bfloat16* b1 = (const __nv_bfloat16*)d_in[4];
  const __nv_bfloat16* w2 = (const __nv_bfloat16*)d_in[5];
  const __nv_bfloat16* b2 = (const __nv_bfloat16*)d_in[6];
  static cudaTextureObject_t texScr = 0, texX = 0;
  static CUtensorMap mapW, mapL, mapS, mapT, mapE, mapC;
  static const void *c_tab = nullptr, *c_w1 = nullptr;
  if (c_tab != table || c_w1 != w1) {
    c_tab = table; c_w1 = w1;
    char* scr = nullptr; cudaGetSymbolAddress((void**)&scr, g_scr);
    auto mk_tex = [](const void* p, size_t bytes, cudaChannelFormatDesc d) {
      cudaResourceDesc rd = {}; rd.resType = cudaResourceTypeLinear; rd.res.linear.devPtr = (void*)p; rd.res.linear.desc = d; rd.res.linear.sizeInBytes = bytes;
      cudaTextureDesc td = {}; td.readMode = cudaReadModeElementType;
      cudaTextureObject_t t = 0; cudaCreateTextureObject(&t, &rd, &td, nullptr); return t;
    };
    if (!texScr) {
      texScr = mk_tex(scr, (size_t)SCR_N * 16, cudaCreateChannelDesc<uint4>());
      texX = mk_tex(scr + (size_t)PX_OFF * 16, (size_t)(SCR_N - PX_OFF) * 16, cudaCreateChannelDesc<unsigned>());
    }
    typedef CUresult (*EncFn)(CUtensorMap*, CUtensorMapDataType, cuuint32_t, void*, const cuuint64_t*, const cuuint64_t*, const cuuint32_t*,
                              const cuuint32_t*, CUtensorMapInterleave, CUtensorMapSwizzle, CUtensorMapL2promotion, CUtensorMapFloatOOBfill);
    EncFn enc = nullptr; cudaDriverEntryPointQueryResult qr;
    cudaGetDriverEntryPoint("cuTensorMapEncodeTiled", (void**)&enc, cudaEnableDefault, &qr);
    const cuuint32_t ones[4] = {1, 1, 1, 1};
    auto mk = [&](CUtensorMap* m, CUtensorMapDataType dt, int rank, void* p, const cuuint64_t* dim, const cuuint64_t* str, const cuuint32_t* box, CUtensorMapSwizzle sw) {
      enc(m, dt, rank, p, dim, str, box, ones, CU_TENSOR_MAP_INTERLEAVE_NONE, sw, CU_TENSOR_MAP_L2_PROMOTION_NONE, CU_TENSOR_MAP_FLOAT_OOB_FILL_NONE);
    };
    { cuuint64_t dim[2] = {H_, F_ * D_}, str[1] = {H_ * 2}; cuuint32_t box[2] = {32, 256};
      mk(&mapW, CU_TENSOR_MAP_DATA_TYPE_BFLOAT16, 2, (void*)w1, dim, str, box, CU_TENSOR_MAP_SWIZZLE_64B); }
    { cuuint64_t dim[4] = {64, 64, V_, NC}, str[3] = {128000 * NC, 128, 128000}; cuuint32_t box[4] = {32, 4, 64, 1};
      mk(&mapL, CU_TENSOR_MAP_DATA_TYPE_BFLOAT16, 4, scr + (size_t)PL_OFF * 16, dim, str, box, CU_TENSOR_MAP_SWIZZLE_64B); }
    { cuuint64_t dim[4] = {64, 64, V_ / 4, NC}, str[3] = {32000 * NC, 128, 32000}; cuuint32_t box[4] = {64, 4, 16, 1};
      mk(&mapS, CU_TENSOR_MAP_DATA_TYPE_BFLOAT16, 4, scr + (size_t)PS_OFF * 16, dim, str, box, CU_TENSOR_MAP_SWIZZLE_128B); }
    { cuuint64_t dim[4] = {64, 64, V_ / 8, 10}, str[3] = {163840, 128, 16384}; cuuint32_t box[4] = {64, 4, 8, 2};
      mk(&mapT, CU_TENSOR_MAP_DATA_TYPE_BFLOAT16, 4, scr + (size_t)PT_OFF * 16, dim, str, box, CU_TENSOR_MAP_SWIZZLE_128B); }
    { cuuint64_t dim[2] = {D_, V_}, str[1] = {D_ * 2}; cuuint32_t box[2] = {64, 128};
      mk(&mapE, CU_TENSOR_MAP_DATA_TYPE_BFLOAT16, 2, (void*)table, dim, str, box, CU_TENSOR_MAP_SWIZZLE_128B);
      cuuint32_t box2[2] = {8, 256};
      mk(&mapC, CU_TENSOR_MAP_DATA_TYPE_BFLOAT16, 2, (void*)table, dim, str, box2, CU_TENSOR_MAP_SWIZZLE_NONE); }
    cudaFuncSetAttribute(k_deep, cudaFuncAttributeMaxDynamicSharedMemorySize, DEEP_SMEM);
    cudaFuncSetAttribute(k_tens, cudaFuncAttributeMaxDynamicSharedMemorySize, K1_SMEM);
  }
  k_tens<<<132, 512, K1_SMEM, cudaStreamPerThread>>>(mapW, mapL, mapS, mapT, mapE, mapC, texScr, texX, idx, table, wp, w1, b1, 0);
  cudaLaunchAttribute at[1];
  at[0].id = cudaLaunchAttributeProgrammaticStreamSerialization; at[0].val.programmaticStreamSerializationAllowed = 1;
  cudaLaunchConfig_t cfg = {};
  cfg.stream = cudaStreamPerThread; cfg.attrs = at;
  cfg.gridDim = 128; cfg.blockDim = TH + 128; cfg.dynamicSmemBytes = DEEP_SMEM; cfg.numAttrs = PDL;
  cudaLaunchKernelEx(&cfg, k_deep, texScr, w2, b2, (__nv_bfloat16*)d_out, 0);

}
```

```cpp
#include <cuda_runtime.h>
#include <cuda_bf16.h>
#include <cuda_fp16.h>
#include <stdint.h>
#include <cuda.h>

namespace {

constexpr int B_ = 16384, F_ = 100, D_ = 128, V_ = 1000, H_ = 512;
constexpr int NC = 9;
constexpr int PT_OFF = 0;
constexpr int PL_OFF = 64 * 10 * 1024;
constexpr int PS_OFF = PL_OFF + 64 * NC * 8000;
constexpr int IXH = NC * 8192 + 2048;
constexpr int IX_OFF = PS_OFF + 64 * NC * 2000;
constexpr int I0_OFF = IX_OFF + 2 * IXH;
constexpr int PX_OFF = I0_OFF + 4096;
constexpr int SCR_N = PX_OFF + 64 * 16 * 136;
static_assert(PX_OFF % 32 == 0, "");

__device__ __align__(1024) uint4 g_scr[SCR_N];
__device__ float g_acc[B_];
__device__ unsigned long long g_slot;
__device__ unsigned g_done[64];
__device__ float g_partP[16 * B_];
__device__ unsigned g_flag[25 * 32];

#define TS(k, i)
#define TR(slot)
#define PT(slot)

constexpr uint64_t POL_EF = 0x12F0000000000000ull, POL_N = 0x1000000000000000ull;
__device__ __forceinline__ uint32_t addbf2(uint32_t a, uint32_t b) { uint32_t r; asm("add.rn.bf16x2 %0,%1,%2;" : "=r"(r) : "r"(a), "r"(b)); return r; }
__device__ __forceinline__ uint4 add4(const uint4& a, const uint4& b) { return make_uint4(addbf2(a.x, b.x), addbf2(a.y, b.y), addbf2(a.z, b.z), addbf2(a.w, b.w)); }
__device__ __forceinline__ uint4 ldtex(cudaTextureObject_t t, int i) {
  uint4 v; asm volatile("tex.1d.v4.u32.s32 {%0,%1,%2,%3},[%4,{%5}];" : "=r"(v.x), "=r"(v.y), "=r"(v.z), "=r"(v.w) : "l"(t), "r"(i)); return v;
}
__device__ __forceinline__ uint4 lds128(uint32_t a) {
  uint4 v; asm volatile("ld.volatile.shared.v4.u32 {%0,%1,%2,%3},[%4];" : "=r"(v.x), "=r"(v.y), "=r"(v.z), "=r"(v.w) : "r"(a)); return v;
}
__device__ __forceinline__ void sts128(uint32_t a, const uint4& v) {
  asm volatile("st.shared.v4.u32 [%0],{%1,%2,%3,%4};" :: "r"(a), "r"(v.x), "r"(v.y), "r"(v.z), "r"(v.w) : "memory");
}
__device__ __forceinline__ void mbar_init(uint32_t bar, int n) { asm volatile("mbarrier.init.shared::cta.b64 [%0],%1;" :: "r"(bar), "r"(n) : "memory"); }
__device__ __forceinline__ void mbar_wait(uint32_t bar, uint32_t parity) {
  uint32_t ok; int it = 0;
  do { asm volatile("{.reg .pred p; mbarrier.try_wait.parity.shared::cta.b64 p,[%1],%2; selp.u32 %0,1,0,p;}" : "=r"(ok) : "r"(bar), "r"(parity) : "memory"); } while (!ok && ++it < (1 << 19));
}
__device__ __forceinline__ void mbar_expect(uint32_t bar, uint32_t bytes) { asm volatile("mbarrier.arrive.expect_tx.shared::cta.b64 _,[%0],%1;" :: "r"(bar), "r"(bytes) : "memory"); }
__device__ __forceinline__ void bulk_g2s(uint32_t dst, const void* src, uint32_t bytes, uint32_t bar) {
  asm volatile("cp.async.bulk.shared::cluster.global.mbarrier::complete_tx::bytes [%0],[%1],%2,[%3];" :: "r"(dst), "l"(src), "r"(bytes), "r"(bar) : "memory");
}
__device__ __forceinline__ void bulk_pf(const void* src, uint32_t bytes) { asm volatile("cp.async.bulk.prefetch.L2.global [%0],%1;" :: "l"(src), "r"(bytes) : "memory"); }
#define SCHED_FENCE(never, k) asm volatile("{.reg .pred p; setp.ne.u32 p,%0,%1; @p bra.uni SKIP_%=; pmevent 1; SKIP_%=: }" :: "r"(never), "r"(0x7fff0000 + (k)) : "memory")
#define PDL 1
#define RSV 22
#define PACE 800
__device__ __forceinline__ int quad_of(int n) { return n < 23 ? n + 2 : n - 23; }
__device__ __forceinline__ void mbar_wait_fast(uint32_t bar, uint32_t parity) {
  asm volatile("{.reg .pred p; .reg .u32 n;\n"
               "mbarrier.try_wait.parity.shared::cta.b64 p,[%0],%1;\n"
               "@p bra DONE_%=;\n"
               "mov.u32 n,0;\n"
               "LOOP_%=: mbarrier.try_wait.parity.shared::cta.b64 p,[%0],%1;\n"
               "add.u32 n,n,1; setp.gt.or.u32 p,n,400000,p;\n"
               "@!p bra LOOP_%=;\n"
               "DONE_%=: }" :: "r"(bar), "r"(parity) : "memory");
}
__device__ __forceinline__ void sleep_until(uint32_t t0, uint32_t dt) { while ((uint32_t)clock() - t0 < dt) __nanosleep(40); }
__device__ __forceinline__ uint32_t s_mask(uint32_t v, int q) { return (1u << ((v + 3 - q) & 3)) | (16u << ((v + 3 + q) & 3)); }
__device__ __forceinline__ uint32_t s_cell(uint32_t v, int q, uint32_t m) {
  const int t = __ffs(~m) - 1;
  const int cp = t == 8 ? q >> 1 : ((t & 4 ? t - q : t + q) - v) & 3;
  return cp * 1001 + v;
}
__device__ __forceinline__ uint32_t pk3(uint32_t a, uint32_t b, uint32_t c) {
  const uint32_t w = c + (a << 12) + (b << 22); return __funnelshift_l(w, w, 27);
}
constexpr int TH = 256, NS = 8192 / TH, YD = 4;
__host__ __device__ constexpr int ye_of(int s) { return s == 3 ? 0 : s == 11 ? 1 : s == 19 ? 2 : s == 23 ? 3 : -1; }
template <int N> __device__ __forceinline__ void wgmma_h(uint32_t* d, const uint32_t* a, uint64_t desc, int acc);
template <> __device__ __forceinline__ void wgmma_h<40>(uint32_t* d, const uint32_t* a, uint64_t desc, int acc) {
  asm volatile("{.reg .pred p; setp.ne.s32 p,%15,0;\n"
    "wgmma.mma_async.sync.aligned.m64n40k16.f16.f16.f16 {%0,%1,%2,%3,%4,%5,%6,%7,%8,%9},{%10,%11,%12,%13},%14,p,1,1,0;}"
    : "+r"(d[0]),"+r"(d[1]),"+r"(d[2]),"+r"(d[3]),"+r"(d[4]),"+r"(d[5]),"+r"(d[6]),"+r"(d[7]),"+r"(d[8]),"+r"(d[9])
    : "r"(a[0]), "r"(a[1]), "r"(a[2]), "r"(a[3]), "l"(desc), "r"(acc));
}
template <> __device__ __forceinline__ void wgmma_h<32>(uint32_t* d, const uint32_t* a, uint64_t desc, int acc) {
  asm volatile("{.reg .pred p; setp.ne.s32 p,%13,0;\n"
    "wgmma.mma_async.sync.aligned.m64n32k16.f16.f16.f16 {%0,%1,%2,%3,%4,%5,%6,%7},{%8,%9,%10,%11},%12,p,1,1,0;}"
    : "+r"(d[0]),"+r"(d[1]),"+r"(d[2]),"+r"(d[3]),"+r"(d[4]),"+r"(d[5]),"+r"(d[6]),"+r"(d[7])
    : "r"(a[0]), "r"(a[1]), "r"(a[2]), "r"(a[3]), "l"(desc), "r"(acc));
}
__device__ __forceinline__ void wgmma_p(float* d, const uint32_t* a, uint64_t desc, int acc) {
  asm volatile("{.reg .pred p; setp.ne.s32 p,%69,0;\n"
    "wgmma.mma_async.sync.aligned.m64n128k16.f32.bf16.bf16 {%0,%1,%2,%3,%4,%5,%6,%7,%8,%9,%10,%11,%12,%13,%14,%15,%16,%17,%18,%19,%20,%21,%22,%23,%24,%25,%26,%27,%28,%29,%30,%31,%32,%33,%34,%35,%36,%37,%38,%39,%40,%41,%42,%43,%44,%45,%46,%47,%48,%49,%50,%51,%52,%53,%54,%55,%56,%57,%58,%59,%60,%61,%62,%63},{%64,%65,%66,%67},%68,p,1,1,1;}"
    : "+f"(d[0]),"+f"(d[1]),"+f"(d[2]),"+f"(d[3]),"+f"(d[4]),"+f"(d[5]),"+f"(d[6]),"+f"(d[7]),"+f"(d[8]),"+f"(d[9]),"+f"(d[10]),"+f"(d[11]),"+f"(d[12]),"+f"(d[13]),"+f"(d[14]),"+f"(d[15]),"+f"(d[16]),"+f"(d[17]),"+f"(d[18]),"+f"(d[19]),"+f"(d[20]),"+f"(d[21]),"+f"(d[22]),"+f"(d[23]),"+f"(d[24]),"+f"(d[25]),"+f"(d[26]),"+f"(d[27]),"+f"(d[28]),"+f"(d[29]),"+f"(d[30]),"+f"(d[31]),"+f"(d[32]),"+f"(d[33]),"+f"(d[34]),"+f"(d[35]),"+f"(d[36]),"+f"(d[37]),"+f"(d[38]),"+f"(d[39]),"+f"(d[40]),"+f"(d[41]),"+f"(d[42]),"+f"(d[43]),"+f"(d[44]),"+f"(d[45]),"+f"(d[46]),"+f"(d[47]),"+f"(d[48]),"+f"(d[49]),"+f"(d[50]),"+f"(d[51]),"+f"(d[52]),"+f"(d[53]),"+f"(d[54]),"+f"(d[55]),"+f"(d[56]),"+f"(d[57]),"+f"(d[58]),"+f"(d[59]),"+f"(d[60]),"+f"(d[61]),"+f"(d[62]),"+f"(d[63])
    : "r"(a[0]), "r"(a[1]), "r"(a[2]), "r"(a[3]), "l"(desc), "r"(acc));
}

__device__ __forceinline__ void mma16816h(uint32_t* c, const uint32_t* a, uint32_t b0, uint32_t b1) {
  asm("mma.sync.aligned.m16n8k16.row.col.f16.f16.f16.f16 {%0,%1},{%2,%3,%4,%5},{%6,%7},{%0,%1};"
      : "+r"(c[0]), "+r"(c[1]) : "r"(a[0]), "r"(a[1]), "r"(a[2]), "r"(a[3]), "r"(b0), "r"(b1));
}
__device__ __forceinline__ void mma1688h(uint32_t* c, uint32_t a0, uint32_t a1, uint32_t b) {
  asm("mma.sync.aligned.m16n8k8.row.col.f16.f16.f16.f16 {%0,%1},{%2,%3},{%4},{%0,%1};" : "+r"(c[0]), "+r"(c[1]) : "r"(a0), "r"(a1), "r"(b));
}
__device__ __forceinline__ void mma1688f(float* c, uint32_t a0, uint32_t a1, uint32_t b) {
  asm("mma.sync.aligned.m16n8k8.row.col.f32.f16.f16.f32 {%0,%1,%2,%3},{%4,%5},{%6},{%0,%1,%2,%3};"
      : "+f"(c[0]), "+f"(c[1]), "+f"(c[2]), "+f"(c[3]) : "r"(a0), "r"(a1), "r"(b));
}
__device__ __forceinline__ uint32_t hadd2(uint32_t a, uint32_t b) { uint32_t r; asm("add.rn.f16x2 %0,%1,%2;" : "=r"(r) : "r"(a), "r"(b)); return r; }
__device__ __forceinline__ uint32_t hfma2(uint32_t a, uint32_t b, uint32_t c) { uint32_t r; asm("fma.rn.f16x2 %0,%1,%2,%3;" : "=r"(r) : "r"(a), "r"(b), "r"(c)); return r; }
__device__ __forceinline__ uint32_t pack_bf2(float lo, float hi) { uint32_t r; asm("cvt.rn.bf16x2.f32 %0,%1,%2;" : "=r"(r) : "f"(hi), "f"(lo)); return r; }
__device__ __forceinline__ uint32_t pack_h2(float lo, float hi) { uint32_t r; asm("cvt.rn.f16x2.f32 %0,%1,%2;" : "=r"(r) : "f"(hi), "f"(lo)); return r; }
__device__ __forceinline__ float bf_lo(uint32_t w) { return __uint_as_float(w << 16); }
__device__ __forceinline__ float bf_hi(uint32_t w) { return __uint_as_float(w & 0xffff0000u); }
__device__ __forceinline__ uint32_t absmax4(const uint4& v, uint32_t m) {
  return __vmaxu2(__vmaxu2(__vmaxu2(v.x & 0x7fff7fffu, v.y & 0x7fff7fffu), __vmaxu2(v.z & 0x7fff7fffu, v.w & 0x7fff7fffu)), m);
}
__device__ __forceinline__ float pow2_scale(uint32_t mbits, int p) { return __uint_as_float((uint32_t)min(max(253 + p - (int)(mbits >> 7), 2), 252) << 23); }

constexpr int G_O0 = 8, G_O1 = 4, G_O2 = 0, G_N0 = 5, G_N1 = 4, G_N2 = 4, G_K0 = 5, G_K1 = 3, G_K2 = 1;
__host__ __device__ constexpr bool unit_wg(int kb, int on) {
  return (on >= G_O0 && on < G_O0 + G_N0 && kb < G_K0) || (on >= G_O1 && on < G_O1 + G_N1 && kb < G_K1) || (on >= G_O2 && on < G_O2 + G_N2 && kb < G_K2);
}
constexpr int G_U1 = G_N0 * G_K0, G_U2 = G_U1 + G_N1 * G_K1, G_U = G_U2 + G_N2 * G_K2;
constexpr int K1_B = 130048, K1_STG = K1_B + 2 * 32768, K1_W = K1_STG + 16384, K1_BAR = K1_W + 48 * 256, K1_SMEM = K1_BAR + 256 + 6400;
__host__ __device__ constexpr int frag_index(int ok, int on) {
  int n = 0;
  for (int k = 0; k < 13; k++) for (int o = k; o < 13; o++) { if (k == ok && o == on) return n; if (!unit_wg(k >> 1, o)) n++; }
  return n;
}
constexpr int HU_N = 2 * G_U + frag_index(99, 99);
static_assert(HU_N <= 96, "");
struct FragIdx { int v[13][13]; };
__host__ __device__ constexpr FragIdx make_fi() { FragIdx f = {}; for (int k = 0; k < 13; k++) for (int o = 0; o < 13; o++) f.v[k][o] = frag_index(k, o); return f; }
__host__ __device__ constexpr uint64_t frag_tab(int first) {
  uint64_t t = 0;
  for (int k = 0; k < 13; k++) for (int o = k; o < 13; o++)
    if (!unit_wg(k >> 1, o)) { const int n = frag_index(k, o) - first; if (n >= 0 && n < 8) t |= (uint64_t)(k << 4 | o) << (8 * n); }
  return t;
}
__device__ __forceinline__ int hu_code(int hu) {
  constexpr uint64_t T0 = frag_tab(0), T1 = frag_tab(8), T2 = frag_tab(16), T3 = frag_tab(24);
  const int u = hu >> 1, f = hu - 2 * G_U;
  if (f >= 0) return (int)((f < 8 ? T0 : f < 16 ? T1 : f < 24 ? T2 : T3) >> (8 * (f & 7))) & 255;
  const int u0 = u < G_U1 ? u : u < G_U2 ? u - G_U1 : u - G_U2;
  const int kb = u < G_U1 ? u0 / G_N0 : u < G_U2 ? u0 / G_N1 : u0 / 4, on = u < G_U1 ? G_O0 + u0 % G_N0 : u < G_U2 ? G_O1 + u0 % G_N1 : G_O2 + u0 % 4;
  return (2 * kb + (hu & 1)) << 4 | on;
}

__device__ __forceinline__ void flag_wait(const unsigned* f, unsigned n) {
  unsigned v; int it = 0;
  asm volatile("ld.acquire.gpu.global.u32 %0,[%1];" : "=r"(v) : "l"(f) : "memory");
  if (v < n) {
    do { __nanosleep(300); asm volatile("ld.relaxed.gpu.global.u32 %0,[%1];" : "=r"(v) : "l"(f) : "memory"); } while (v < n && ++it < (1 << 20));
    asm volatile("ld.acquire.gpu.global.u32 %0,[%1];" : "=r"(v) : "l"(f) : "memory");
  }
}
__device__ __forceinline__ void mbar_arrive(uint32_t bar) { asm volatile("mbarrier.arrive.shared::cta.b64 _,[%0];" :: "r"(bar) : "memory"); }
__device__ __forceinline__ void mbar_arrive_lane0(uint32_t bar) {
  asm volatile("{.reg .pred p; elect.sync _|p,0xffffffff; @p mbarrier.arrive.shared::cta.b64 _,[%0];}" :: "r"(bar) : "memory");
}

__device__ __forceinline__ void arrive_both(uint32_t bar, int lane) {
  asm volatile("{.reg .pred p; .reg .u32 a; setp.lt.u32 p,%1,2; mapa.shared::cluster.u32 a,%0,%1;\n"
               "@p mbarrier.arrive.shared::cluster.b64 _,[a];}" :: "r"(bar), "r"(lane) : "memory");
}
#define ELECT "{.reg .pred p; elect.sync _|p,0xffffffff; @p "
__device__ __forceinline__ void e_mc(uint32_t dst, const void* src, uint32_t bytes, uint32_t bar, uint64_t pol) {
  asm volatile(ELECT "cp.async.bulk.shared::cluster.global.mbarrier::complete_tx::bytes.multicast::cluster.L2::cache_hint [%0],[%1],%2,[%3],%4,%5;}"
               :: "r"(dst), "l"(src), "r"(bytes), "r"(bar), "h"((unsigned short)3), "l"(pol) : "memory");
}
__device__ __forceinline__ void e_g2s(uint32_t dst, const void* src, uint32_t bytes, uint32_t bar) {
  asm volatile(ELECT "cp.async.bulk.shared::cluster.global.mbarrier::complete_tx::bytes [%0],[%1],%2,[%3];}" :: "r"(dst), "l"(src), "r"(bytes), "r"(bar) : "memory");
}
__device__ __forceinline__ void e_pf(const void* src, uint32_t bytes) { asm volatile(ELECT "cp.async.bulk.prefetch.L2.global [%0],%1;}" :: "l"(src), "r"(bytes) : "memory"); }
__device__ __forceinline__ void e_expect(uint32_t bar, uint32_t bytes) { asm volatile(ELECT "mbarrier.arrive.expect_tx.shared::cta.b64 _,[%0],%1;}" :: "r"(bar), "r"(bytes) : "memory"); }
__device__ __forceinline__ void e_tma2d(uint32_t dst, const CUtensorMap* m, int x, int y, uint32_t bar) {
  asm volatile(ELECT "cp.async.bulk.tensor.2d.shared::cluster.global.mbarrier::complete_tx::bytes [%0],[%1,{%2,%3}],[%4];}" :: "r"(dst), "l"(m), "r"(x), "r"(y), "r"(bar) : "memory");
}

__device__ __forceinline__ void pack_role(const int* __restrict__ idx, uint32_t sbase, int pc) {
  constexpr int BUF = 32 * 3328;
  const int tid = threadIdx.x, lane = tid & 31, warp = tid >> 5;
  const uint32_t full = sbase + 2 * BUF, empty = full + 16;
  if (tid == 0) { mbar_init(full, 1); mbar_init(full + 8, 1); mbar_init(empty, 18); mbar_init(empty + 8, 18); asm volatile("fence.proxy.async.shared::cta;" ::: "memory"); }
  __syncthreads();
  auto chunk = [&](int s) { return s * 3200 + (s >> 2) * 288; };
  auto load = [&](int n) {
    const int blk = pc * 16 + n;
    if (lane == 0) mbar_expect(full + (n & 1) * 8, 32 * 3200);
    __syncwarp();
    bulk_g2s(sbase + (n & 1) * BUF + chunk(lane), idx + ((blk >> 5) * 8192 + lane * TH + (blk & 31) * 8) * F_, 3200, full + (n & 1) * 8);
  };
  if (warp == 0) { load(0); load(1); }
  const int l = lane & 7;
  uint32_t rot[8], inc[3];
#pragma unroll
  for (int jj = 0; jj < 8; jj++) rot[jj] = ((l + jj) & 7) * 4;
#pragma unroll
  for (int q = 0; q < 3; q++) inc[q] = (l + 3 * q < 8) << 12 | (l + 3 * q + 1 < 8) << 22 | (q < 2 && l + 3 * q + 2 < 8);
  int loaded = 2;
#pragma unroll 1
  for (int task = warp; task < 288; task += 16) {
    const int n = task / 18, q = (task % 18) * 4 + (lane >> 3), sq = q / 9, k = q % 9;
    if (warp == 0 && n + 1 == loaded && loaded < 16) { mbar_wait(empty + (loaded & 1) * 8, ((loaded >> 1) - 1) & 1); load(loaded); loaded++; }
    mbar_wait(full + (n & 1) * 8, (n >> 1) & 1);
    const uint32_t buf = sbase + (n & 1) * BUF + l * 400, row = buf + chunk(sq * 4);
    auto ld = [&](uint32_t ad) { uint32_t v; asm volatile("ld.shared.u32 %0,[%1];" : "=r"(v) : "r"(ad)); return v; };
    const int blk = pc * 16 + n, half = blk >> 5, col = (blk & 31) * 8 + l;
    const int ks = k == NC - 1 ? 0 : k + 1;
    uint32_t cw[4], sv[8], m[2] = {0, 0};
    { const uint32_t a0 = row + (72 + 2 * ks + (l >> 2)) * 4;
#pragma unroll
      for (int u = 0; u < 8; u++) { sv[u] = ld((a0 ^ ((u >> 2) * 4)) + (u & 3) * 3200); m[u >> 2] |= s_mask(sv[u], l & 3) << (8 * (u & 3)); } }
#pragma unroll
    for (int h = 0; h < 2; h++) { m[h] |= __shfl_xor_sync(0xffffffffu, m[h], 1); m[h] |= __shfl_xor_sync(0xffffffffu, m[h], 2); }
#pragma unroll
    for (int u = 0; u < 4; u++) cw[u] = s_cell(sv[u], l & 3, (m[0] >> (8 * u)) & 255) | s_cell(sv[4 + u], l & 3, (m[1] >> (8 * u)) & 255) << 12;
    if (k == NC - 1) {
      auto wide = [&](uint32_t w) { return (w & 0xfff) << 5 | (w >> 12) << 18 | (l & 4 ? 1u << 4 : 1u << 17); };
      g_scr[I0_OFF + (half * 8 + sq) * TH + col] = make_uint4(wide(cw[0]), wide(cw[1]), wide(cw[2]), wide(cw[3]));
      g_scr[IX_OFF + half * IXH + NC * 8192 + sq * TH + col] = make_uint4(ld(row + 396), ld(row + 3596), ld(row + 6796), ld(row + 9996));
      cw[0] = cw[1] = cw[2] = cw[3] = 0;
    }
    const uint32_t ax = buf + chunk(min(sq + 1, 7) * 4) + (90 + k) * 4;
    const uint32_t yev = ld(buf + ((0x3210 >> (sq * 2 + (sq == 5) * 2)) & 3) * 3200 + (90 + k) * 4);
    uint4* dst = g_scr + IX_OFF + half * IXH + (k * NS + sq * 4) * TH + col;
#pragma unroll
    for (int u = 0; u < 4; u++) {
      uint32_t e[8];
#pragma unroll
      for (int jj = 0; jj < 8; jj++) e[jj] = ld(row + k * 32 + rot[jj] + u * 3200);
      dst[u * TH] = make_uint4(pk3(e[0], e[1], e[2] + inc[0]), pk3(e[3], e[4], e[5] + inc[1]), pk3(e[6], e[7], ld(ax + u * 3200) + inc[2]),
                               u < 3 ? __byte_perm(cw[u], cw[3], 0x4210 + (u << 12)) : yev);
    }
    mbar_arrive_lane0(empty + (n & 1) * 8);
  }
}

__global__ void __cluster_dims__(2, 1, 1) __launch_bounds__(512, 1)
k_tens(const __grid_constant__ CUtensorMap mapW, const __grid_constant__ CUtensorMap mapL, const __grid_constant__ CUtensorMap mapS,
       const __grid_constant__ CUtensorMap mapT, const __grid_constant__ CUtensorMap mapE, const __grid_constant__ CUtensorMap mapC, cudaTextureObject_t tex, cudaTextureObject_t texX,
       const int* __restrict__ idx, const __nv_bfloat16* __restrict__ table, const __nv_bfloat16* __restrict__ wp, const __nv_bfloat16* __restrict__ w1,
       const __nv_bfloat16* __restrict__ b1, int never) {
  extern __shared__ __align__(1024) uint4 sm[];
  const int tid = threadIdx.x, lane = tid & 31, cta = blockIdx.x;
  const uint32_t sbase = (uint32_t)__cvta_generic_to_shared(sm);
  const int g = lane >> 2, r = lane & 3;
  TS(0, 0);
  if (cta >= 128) {
    pack_role(idx, sbase, cta - 128);
    __syncthreads();
    if (tid == 0) {
      asm volatile("fence.acq_rel.gpu; griddepcontrol.launch_dependents;" ::: "memory");
      asm volatile("red.relaxed.gpu.global.add.u32 [%0],1;" :: "l"(&g_flag[24 * 32]) : "memory");
    }
    __syncwarp();
    TS(2, 1);
    asm volatile("barrier.cluster.arrive.relaxed.aligned; barrier.cluster.wait.aligned;" ::: "memory");
    return;
  }
  const uint32_t fullB = sbase + K1_BAR, emptyB = fullB + 24, fullE = fullB + 48, fullC = fullB + 56, fullI = fullB + 64, pxRdy = fullB + 72, fullS = fullB + 96, emptyS = fullB + 104, pkDone = fullB + 112, pkFull = fullB + 136, progG = fullB + 168;
  const int rb = cta & 7, hc = cta >> 3;
  if (__shfl_sync(0xffffffffu, tid >> 5, 0) == 12) {
    if (lane == 0) {
#pragma unroll
      for (int q = 0; q < 19; q++) if (q != 2 && q != 5) mbar_init(fullB + q * 8, q == 3 || q == 4 ? 8 : q == 12 ? 4 : q >= 14 && q < 17 ? 2 : 1);
      asm volatile("st.shared.u32 [%0],%1;" :: "r"(progG), "r"(0) : "memory");
    }
    asm volatile("fence.mbarrier_init.release.cluster; fence.proxy.async.shared::cta;" ::: "memory");
    __syncwarp();
    e_expect(fullC, 16384);
#pragma unroll
    for (int q = 0; q < 4; q++) e_tma2d(sbase + 32768 + q * 4096, &mapC, (cta & 15) * 8, q * 256, fullC);
    e_expect(fullE, 32768);
#pragma unroll
    for (int q = 0; q < 2; q++) e_tma2d(sbase + K1_B + 32768 + q * 16384, &mapE, q * 64, rb * 128, fullE);
    asm volatile("bar.arrive 2,512;" ::: "memory");
  }
  asm volatile("barrier.cluster.arrive.relaxed.aligned;" ::: "memory");
  if (tid >= 384) {
    asm volatile("setmaxnreg.dec.sync.aligned.u32 32;");
    if (tid < 416) {
      asm volatile("barrier.cluster.wait.aligned;" ::: "memory");
      if (tid == 384) {
#pragma unroll 1
        for (int n = 0; n < 25; n++) {
          const int st = n & 1, q = quad_of(n);
          if (n == 1) {
            mbar_expect(fullI, 51200);
#pragma unroll 1
            for (int u = 0; u < 8; u++) bulk_g2s(sbase + 76800 + u * 6400, idx + ((cta >> 4) * 8 + u) * 256 * F_, 6400, fullI);
          }
          mbar_wait(emptyB + st * 8, (((n + 1) >> 1) & 1) ^ 1);
          mbar_expect(fullB + st * 8, 32768);
          asm volatile("cp.async.bulk.tensor.2d.shared::cluster.global.mbarrier::complete_tx::bytes.multicast::cluster [%0],[%1,{%2,%3}],[%4],%5;"
                       :: "r"(sbase + K1_B + st * 32768 + (cta & 1) * 16384), "l"(&mapW), "r"(hc * 32), "r"(q * 512 + (cta & 1) * 256),
                          "r"(fullB + st * 8), "h"((unsigned short)3) : "memory");
          if (n + 1 < 25) bulk_pf(w1 + quad_of(n + 1) * 262144 + cta * 2048, 4096);
        }
      }
    } else if (tid < 448) {
      ((float4*)g_acc)[cta * 32 + lane] = make_float4(0.f, 0.f, 0.f, 0.f);
      asm volatile("bar.sync 2,512;" ::: "memory");
      __syncwarp();
      if (tid == 416) {
        int pub = 0;
#pragma unroll 1
        for (int n = 0; n < 50; n++) {
          const int quad = quad_of(n >> 1), mt = n & 1, v0 = rb * 128 + mt * 64;
          const uint32_t stg = sbase + K1_STG;
          if (pub < 3) {
            uint32_t ok = 1;
            if (pub == 0 || n == 49) mbar_wait(pkDone + pub * 8, 0);
            else asm volatile("{.reg .pred p; mbarrier.test_wait.parity.shared::cta.b64 p,[%1],0; selp.u32 %0,1,0,p;}" : "=r"(ok) : "r"(pkDone + pub * 8) : "memory");
            if (ok) {
              asm volatile("cp.async.bulk.wait_group 0;" ::: "memory");
              asm volatile("red.release.gpu.global.add.u32 [%0],1;" :: "l"(&g_flag[((cta >> 4) * 3 + pub) * 32]) : "memory");
              pub++;
              if (n == 49) { n--; continue; }
            }
          }
          mbar_wait(fullS, n & 1);
          asm volatile("fence.proxy.async.shared::cta;" ::: "memory");
          if (quad < 18) {
            asm volatile("cp.async.bulk.tensor.4d.global.shared::cta.bulk_group.L2::cache_hint [%0,{%1,%2,%3,%4}],[%5],%6;"
                         :: "l"(&mapL), "r"((quad & 1) * 32), "r"(hc * 4), "r"(v0), "r"(quad >> 1), "r"(stg), "l"(POL_EF) : "memory");
          } else {
#pragma unroll 1
            for (int hh = 0; hh < 2; hh++) {
              const int pq = quad * 2 + hh;
              asm volatile("cp.async.bulk.tensor.4d.global.shared::cta.bulk_group.L2::cache_hint [%0,{%1,%2,%3,%4}],[%5],%6;"
                         :: "l"(pq < 45 ? &mapS : &mapT), "r"(0), "r"(hc * 4), "r"(v0 >> (pq < 45 ? 2 : 3)), "r"(pq < 45 ? pq - 36 : (pq - 45) * 2), "r"(stg + hh * 8192), "l"(POL_EF) : "memory");
            }
          }
          asm volatile("cp.async.bulk.commit_group;" ::: "memory");
          asm volatile("cp.async.bulk.wait_group.read 0;" ::: "memory");
          mbar_arrive(emptyS);
        }
        asm volatile("cp.async.bulk.wait_group 0;" ::: "memory");
        asm volatile("fence.proxy.async.global;" ::: "memory");
        asm volatile("fence.acq_rel.gpu; griddepcontrol.launch_dependents;" ::: "memory");
        asm volatile("red.relaxed.gpu.global.add.u32 [%0],1;" :: "l"(&g_flag[24 * 32]) : "memory");
        flag_wait(&g_flag[24 * 32], 132);
        asm volatile("fence.proxy.async.global;" ::: "memory");
        const char* base = (const char*)g_scr;
        const int c = cta >> 1, half = cta & 1, ch = (c + (c >> 4) * 5) & 15;
        bulk_pf(base + (PS_OFF + c * NC * 2000) * 16u + half * 16000, 16000);
        bulk_pf(base + (PT_OFF + c * 10 * 1024) * 16u + half * 8000, 8000);
        mbar_expect(fullE, 18432);
        bulk_g2s(sbase + K1_B, base + (I0_OFF + half * 2048 + ch * 128) * 16u, 2048, fullE);
        bulk_g2s(sbase + K1_B + 2048, base + (IX_OFF + half * IXH + ch * 512) * 16u, 8192, fullE);
        bulk_g2s(sbase + K1_B + 10240, base + (IX_OFF + half * IXH + 8192 + ch * 512) * 16u, 8192, fullE);
        mbar_wait(fullE, 1);
      }
    } else {
      const int pw = (tid >> 5) & 1, rg = (cta >> 4) * 8 + ((cta & 15) >> 1), hf = cta & 1;
      const int* ip = idx + (rg * 256 + hf * 8) * F_;
      asm volatile("bar.sync 2,512;" ::: "memory");
      const uint32_t buf = sbase + K1_BAR + 256 + pw * 3200, bar = pkFull + pw * 8;
      const unsigned* fl = &g_flag[(cta >> 4) * 96];
      int batch = 0, rel = pw ? 3 : 0;
#pragma unroll 1
      for (int n = 1 + pw; n < 16; n += 2) {
        if (lane == 0) { mbar_expect(bar, 3200); bulk_g2s(buf, ip + n * 16 * F_, 3200, bar); if (n + 2 < 16) bulk_pf(ip + (n + 2) * 16 * F_, 3200); }
        uint32_t ok; int it = 0;
        do {
          if (rel < batch) {
            unsigned v; asm volatile("ld.relaxed.gpu.global.u32 %0,[%1];" : "=r"(v) : "l"(fl + rel * 32) : "memory");
            if (__all_sync(0xffffffffu, v >= 16)) { flag_wait(fl + rel * 32, 16); __syncwarp(); mbar_arrive_lane0(pxRdy + rel * 8); rel++; }
          }
          asm volatile("{.reg .pred p; mbarrier.test_wait.parity.shared::cta.b64 p,[%1],%2; selp.u32 %0,1,0,p;}" : "=r"(ok) : "r"(bar), "r"(((n - 1) >> 1) & 1) : "memory");
          ok = __all_sync(0xffffffffu, ok);
          if (!ok) __nanosleep(100);
        } while (!ok && ++it < (1 << 20));
        auto ld = [&](uint32_t ad) { uint32_t v; asm volatile("ld.shared.u32 %0,[%1];" : "=r"(v) : "r"(ad)); return v; };
        const uint32_t p0 = buf + ((lane >> 3) & 1) * 400 + ((lane >> 4) * 8 + (lane & 7)) * 4;
        auto wd = [&](int t, int h) { return pk3(ld(p0 + t * 800 + h * 192), ld(p0 + t * 800 + h * 192 + 64), ld(p0 + t * 800 + h * 192 + 128)); };
        uint4* dst = g_scr + PX_OFF + (rg * 16 + n) * 136;
        ((unsigned short*)(dst + 128))[lane * 2 + hf] = ld(buf + g * 400 + 384 + r * 4);
#pragma unroll
        for (int q = 0; q < 2; q++) dst[(hf * 2 + q) * 32 + lane] = make_uint4(wd(2 * q, 0), wd(2 * q, 1), wd(2 * q + 1, 0), wd(2 * q + 1, 1));
        __syncwarp();
        if (n <= 2 || n == 5 || n == 6 || n >= 14) { mbar_arrive_lane0(pkDone + batch * 8); batch++; }
      }
      for (; rel < 3; rel++) { flag_wait(fl + rel * 32, 16); __syncwarp(); mbar_arrive_lane0(pxRdy + rel * 8); }
      if (lane == 0) {
        mbar_wait(pxRdy + 16, 0);
        asm volatile("fence.proxy.async.global;" ::: "memory");
        const char* src = (const char*)(g_scr + PX_OFF + ((cta >> 4) * 8 + ((cta >> 1) & 3) * 2 + pw) * 16 * 136);
        int ph = pw;
#pragma unroll 1
        for (int n = 5; n < 16; n++) {
          uint32_t cur; int it = 0;
          do { asm volatile("ld.volatile.shared.u32 %0,[%1];" : "=r"(cur) : "r"(progG)); if (cur + 2 < n) __nanosleep(400); } while (cur + 2 < n && ++it < (1 << 16));
          if (cur + 1 >= n) continue;
          mbar_expect(bar, 2176); bulk_g2s(buf, src + n * 2176, 2176, bar);
          mbar_wait(bar, ph); ph ^= 1;
        }
      }
    }
    return;
  }
  if (tid >= 256) {
    asm volatile("setmaxnreg.inc.sync.aligned.u32 160;");
    const int w = (tid >> 5) & 3;
    const int srow = w * 16 + ((lane & 15) ^ ((lane & 1) << 2)), sc = lane >> 4;
    uint32_t a[2][8][4];
    asm volatile("bar.sync 2,512;" ::: "memory");
    mbar_wait_fast(fullE, 0);
#pragma unroll
    for (int mt = 0; mt < 2; mt++)
#pragma unroll
      for (int ks = 0; ks < 8; ks++)
        asm volatile("ldmatrix.sync.aligned.m8n8.x4.shared.b16 {%0,%1,%2,%3},[%4];"
                     : "=r"(a[mt][ks][0]), "=r"(a[mt][ks][1]), "=r"(a[mt][ks][2]), "=r"(a[mt][ks][3])
                     : "r"(sbase + K1_B + 32768 + (ks >> 2) * 16384 + (mt * 64 + srow) * 128 + ((((ks & 3) * 2 + sc) ^ (srow & 7)) * 16)) : "memory");
    asm volatile("barrier.cluster.wait.aligned;" ::: "memory");
    arrive_both(emptyB + 8, lane);
    const int v = w * 16 + (g ^ ((g & 1) << 2));
    const uint32_t baseL = v * 256 + r * 64 + ((v & 1) * 2 + (r >> 1)) * 16, baseS = (v >> 2) * 512 + r * 128 + (((v & 3) * 2) ^ ((v & 4) + r)) * 16,
                   baseT = (v >> 3) * 512 + r * 128 + ((v & 7) ^ r) * 16;
    const uint64_t desc0 = (uint64_t)(((sbase + K1_B) & 0x3FFFF) >> 4) | ((uint64_t)(8192 >> 4) << 16) | ((uint64_t)(512 >> 4) << 32) | (2ull << 62);
#pragma unroll 1
    for (int qn = 0; qn < 25; qn++) {
      const int quad = quad_of(qn), st = qn & 1;
      const bool isL = quad < 18;
      PT(qn * 16);
      mbar_wait_fast(fullB + st * 8, (qn >> 1) & 1);
#pragma unroll
      for (int mt = 0; mt < 2; mt++) {
        float d[64];
        PT(qn * 16 + mt * 4 + 1);
        asm volatile("wgmma.fence.sync.aligned;" ::: "memory");
#pragma unroll
        for (int ks = 0; ks < 8; ks++) wgmma_p(d, a[mt][ks], desc0 + st * 2048 + ks * 64, ks);
        asm volatile("wgmma.commit_group.sync.aligned;" ::: "memory");
        mbar_wait_fast(emptyS, mt ^ 1);
        PT(qn * 16 + mt * 4 + 2);
        asm volatile("wgmma.wait_group.sync.aligned 0;" ::: "memory");
#pragma unroll
        for (int q = 0; q < 16; q++) asm volatile("" : "+f"(d[q * 4]), "+f"(d[q * 4 + 1]), "+f"(d[q * 4 + 2]), "+f"(d[q * 4 + 3]) :: "memory");
        PT(qn * 16 + mt * 4 + 3);
        if (mt) arrive_both(emptyB + st * 8, qn < 23 ? lane : 9);
        if (quad == 24) {
#pragma unroll
          for (int cq = 0; cq < 4; cq++) {
            const uint32_t bw = __ldg((const uint32_t*)(b1 + hc * 32 + cq * 8) + r);
#pragma unroll
            for (int e = 0; e < 4; e++) d[48 + cq * 4 + e] += (e & 1) ? bf_hi(bw) : bf_lo(bw);
          }
        }
#pragma unroll
        for (int h = 0; h < 2; h++) {
          const bool isS = quad * 2 + h < 45;
          const uint32_t base = (isL ? baseL ^ (h * 32) : (isS ? baseS : baseT) ^ (h * 8192)), xj = isS ? 16 : 4096, xr = isL ? 2048 : isS ? 1024 : 576;
#pragma unroll
          for (int e4 = 0; e4 < 4; e4++) {
            const float* e = d + h * 32 + (e4 >> 1) * 16 + (e4 & 1) * 2;
            sts128(sbase + K1_STG + (base ^ ((e4 >> 1) * xj) ^ ((e4 & 1) * xr)),
                   make_uint4(pack_bf2(e[0], e[1]), pack_bf2(e[4], e[5]), pack_bf2(e[8], e[9]), pack_bf2(e[12], e[13])));
          }
        }
        __syncwarp();
        mbar_arrive_lane0(fullS);
        if (!mt) PT(qn * 16 + 4);
      }
      PT(qn * 16 + 8);
    }
    return;
  }
  const int slice = cta & 15;
  const int range = (cta >> 4) * 8 + __shfl_sync(0xffffffffu, tid >> 5, 0);
  uint4 iv[4], trow[4]; uint32_t ix;
  uint2 wrow[10];
#pragma unroll
  for (int q = 0; q < 10; q++) asm volatile("ld.global.nc.v2.u32 {%0,%1},[%2];" : "=r"(wrow[q].x), "=r"(wrow[q].y) : "l"((const uint2*)wp + min(tid + q * 256, 2499)));
  asm volatile("bar.sync 2,512;" ::: "memory");
  uint32_t me = 0, mw = 0;
#pragma unroll
  for (int q = 0; q < 10; q++) {
    mw = __vmaxu2(__vmaxu2(wrow[q].x & 0x7fff7fffu, wrow[q].y & 0x7fff7fffu), mw);
    const int e = min(tid + q * 256, 2499), row = e / 25;
    asm volatile("st.shared.v2.u32 [%0],{%1,%2};" :: "r"(sbase + (e + row) * 8), "r"(wrow[q].x), "r"(wrow[q].y) : "memory");
    if (e - row * 25 == 24) asm volatile("st.shared.v2.u32 [%0],{%1,%2};" :: "r"(sbase + (e + row) * 8 + 8), "r"(wrow[q].x), "r"(wrow[q].y) : "memory");
  }
  mbar_wait_fast(fullC, 0);
#pragma unroll
  for (int q = 0; q < 4; q++) { trow[q] = lds128(sbase + 32768 + (tid + q * 256) * 16); me = absmax4(trow[q], me); }
  me = __reduce_max_sync(0xffffffffu, max(me & 0xffff, me >> 16));
  mw = __reduce_max_sync(0xffffffffu, max(mw & 0xffff, mw >> 16));
  uint32_t* sred = (uint32_t*)((char*)sm + 128000);
  if (lane == 0) sred[tid >> 5] = me | mw << 16;
  TS(3, 0);
  asm volatile("setmaxnreg.inc.sync.aligned.u32 160;");
  asm volatile("bar.sync 1,256;" ::: "memory");
  { uint32_t m = 0;
#pragma unroll
    for (int q = 0; q < 8; q++) m = __vmaxu2(m, sred[q]);
    m = __shfl_sync(0xffffffffu, m, 0);
    me = m & 0xffff; mw = m >> 16; }
  const float se = pow2_scale(me, 3), sW = pow2_scale(mw, -2);
  TS(3, 1);
  auto put_rows = [&](int q, bool on) {
    const uint4 t = trow[q];
    const uint4 hv = make_uint4(pack_h2(bf_lo(t.x) * se, bf_hi(t.x) * se), pack_h2(bf_lo(t.y) * se, bf_hi(t.y) * se),
                                pack_h2(bf_lo(t.z) * se, bf_hi(t.z) * se), pack_h2(bf_lo(t.w) * se, bf_hi(t.w) * se));
    if (on)
#pragma unroll
      for (int s = 0; s < 8; s++) sts128(sbase + (tid + q * 256) * 128 + ((s + lane) & 7) * 16, hv);
  };
#pragma unroll 1
  for (int it = 0; it < 3; it++) {
    const int hu = ((tid >> 5) * 3 + it) * 4, code = hu_code(min(hu + (lane >> 3), HU_N - 1)), ok = code >> 4, on = code & 15;
    uint32_t x[4], y[4];
    asm volatile("ldmatrix.sync.aligned.m8n8.x4.shared.b16 {%0,%1,%2,%3},[%4];" : "=r"(x[0]), "=r"(x[1]), "=r"(x[2]), "=r"(x[3])
                 : "r"(sbase + (on * 8 + (lane & (on == 12 ? 3 : 7))) * 208 + ok * 16) : "memory");
    asm volatile("ldmatrix.sync.aligned.m8n8.x4.trans.shared.b16 {%0,%1,%2,%3},[%4];" : "=r"(y[0]), "=r"(y[1]), "=r"(y[2]), "=r"(y[3])
                 : "r"(sbase + (ok * 8 + (lane & (ok == 12 ? 3 : 7))) * 208 + on * 16) : "memory");
    const uint32_t lo = __ballot_sync(0xffffffffu, ok > on), dg = __ballot_sync(0xffffffffu, ok >= on);
#pragma unroll
    for (int q = 0; q < 4; q++) {
      const float m0 = (lo >> (8 * q)) & 1 ? 0.f : sW, m1 = (dg >> (8 * q)) & 1 ? 0.f : sW;
      asm volatile("st.shared.u32 [%0],%1;" :: "r"(sbase + K1_W + (hu + q) * 128 + lane * 4),
                   "r"(pack_h2(fmaf(bf_lo(x[q]), m0, bf_lo(y[q]) * m1), fmaf(bf_hi(x[q]), m0, bf_hi(y[q]) * m1))) : "memory");
    }
  }
  put_rows(1, true); put_rows(2, tid < 88);
  TS(3, 2);
  asm volatile("fence.proxy.async.shared::cta;" ::: "memory");
  asm volatile("bar.sync 1,256;" ::: "memory");
  put_rows(0, true);
  uint32_t bf[HU_N - 2 * G_U];
#pragma unroll
  for (int q = 0; q < HU_N - 2 * G_U; q++) asm volatile("ld.shared.u32 %0,[%1];" : "=r"(bf[q]) : "r"(sbase + K1_W + (2 * G_U + q) * 128 + lane * 4));
  const float unscale = __uint_as_float(0x7f000000u - __float_as_uint(se)), unscale2 = __uint_as_float(0x7f000000u - __float_as_uint(sW));
  TS(3, 3);
  const int px = range * 16 * 136;
  mbar_wait_fast(fullI, 0);
  {
    const uint32_t ib = sbase + 76800 + (tid >> 5) * 6400, p0 = ib + ((lane >> 3) & 1) * 400 + ((lane >> 4) * 8 + (lane & 7)) * 4;
    auto ld = [&](uint32_t ad) { uint32_t v; asm volatile("ld.shared.u32 %0,[%1];" : "=r"(v) : "r"(ad)); return v; };
    auto wd = [&](int t, int h) { return pk3(ld(p0 + t * 800 + h * 192), ld(p0 + t * 800 + h * 192 + 64), ld(p0 + t * 800 + h * 192 + 128)); };
#pragma unroll
    for (int q = 0; q < 4; q++) {
      iv[q] = make_uint4(wd(2 * q, 0), wd(2 * q, 1), wd(2 * q + 1, 0), wd(2 * q + 1, 1));
    }
    ix = ld(ib + g * 400 + 384 + r * 4) | ld(ib + (8 + g) * 400 + 384 + r * 4) << 16;
  }
  asm volatile("bar.sync 1,256;" ::: "memory");
  put_rows(2, tid >= 88); put_rows(3, tid + 768 < V_);
  asm volatile("bar.sync 1,256;" ::: "memory");
  TS(0, 1);
  uint32_t lc; asm volatile("add.u32 %0,%1,%2;" : "=r"(lc) : "r"((lane & 7) * 16), "r"(never));
  const uint64_t wdesc = (uint64_t)(((sbase + K1_W) & 0x3FFFF) >> 4) | ((uint64_t)(128 >> 4) << 16) | ((uint64_t)(256 >> 4) << 32);
  uint32_t a[2][6][4], d[2][26], ex[4] = {}, s[4] = {};
  float red[4] = {0.f, 0.f, 0.f, 0.f};
  auto ldsm = [&](uint32_t* o, uint32_t sh) {
    asm volatile("ldmatrix.sync.aligned.m8n8.x4.trans.shared.b16 {%0,%1,%2,%3},[%4];"
                 : "=r"(o[0]), "=r"(o[1]), "=r"(o[2]), "=r"(o[3]) : "r"(sbase + ((sh & 0x1ff80) | lc)));
  };
  auto gather = [&](int t, int hf) {
    const int x = t & 1;
    const uint4 v = iv[(t >> 1) & 3];
#pragma unroll
    for (int kb = 3 * hf; kb < 3 * hf + 3; kb++) {
      const uint32_t ww = x ? (kb < 3 ? v.z : v.w) : (kb < 3 ? v.x : v.y);
      ldsm(a[x][kb], kb % 3 == 0 ? ww : kb % 3 == 1 ? ww >> 10 : __funnelshift_l(ww, ww, 12));
    }
  };
  auto issue = [&](int x) {
    asm volatile("wgmma.fence.sync.aligned;" ::: "memory");
#pragma unroll
    for (int kb = 0; kb < 6; kb++) {
      if (kb < G_K0) wgmma_h<G_N0 * 8>(d[x] + G_O0 * 2, a[x][kb], wdesc + kb * G_N0 * 16, kb);
      if (kb < G_K1) wgmma_h<G_N1 * 8>(d[x] + G_O1 * 2, a[x][kb], wdesc + (G_U1 + kb * G_N1) * 16, kb);
      if (kb < G_K2) wgmma_h<32>(d[x] + G_O2 * 2, a[x][kb], wdesc + (G_U2 + kb * G_N2) * 16, kb);
    }
    asm volatile("wgmma.commit_group.sync.aligned;" ::: "memory");
  };
  auto hmma_part = [&](int t) {
    constexpr FragIdx FI = make_fi();
    const int x = t & 1;
#pragma unroll
    for (int o = 0; o < 13; o++) asm volatile("" : "+r"(d[x][o * 2]), "+r"(d[x][o * 2 + 1]) :: "memory");
#pragma unroll
    for (int kb = 0; kb < 6; kb++)
#pragma unroll
      for (int o = 2 * kb + 1; o < 13; o++)
        if (!unit_wg(kb, o)) mma16816h(d[x] + o * 2, a[x][kb], bf[FI.v[2 * kb][o]], bf[FI.v[2 * kb + 1][o]]);
#pragma unroll
    for (int q = 0; q < 6; q++) if (!unit_wg(q, 2 * q)) mma1688h(d[x] + q * 4, a[x][q][0], a[x][q][1], bf[FI.v[2 * q][2 * q]]);
    mma1688h(d[x] + 24, r < 2 ? ex[t & 3] : 0u, r < 2 ? 0u : ex[t & 3], bf[FI.v[12][12]]);
  };
  auto dot_part = [&](int t, int hf) {
    const int x = t & 1;
    if (hf == 0) {
      const uint32_t pe = hfma2(r < 2 ? d[x][24] : d[x][25], ex[t & 3], 0u);
      s[0] = r < 2 ? pe : 0u; s[1] = r < 2 ? 0u : pe; s[2] = s[3] = 0;
    }
#pragma unroll
    for (int q = 3 * hf; q < 3 * hf + 3; q++)
#pragma unroll
      for (int e = 0; e < 4; e++) s[e] = hfma2(d[x][q * 4 + e], a[x][q][e], s[e]);
  };
  float* outp = g_partP + slice * B_ + range * 256;
  float k0 = 0.f, k1 = 0.f, x0 = 0.f, x1 = 0.f;
  auto red_stage = [&](int st, int grp) {
    const bool u16 = lane & 16, u8 = lane & 8;
    if (st == 0) {
      k0 = u16 ? red[2] : red[0]; x0 = __shfl_xor_sync(0xffffffffu, u16 ? red[0] : red[2], 16);
      k1 = u16 ? red[3] : red[1]; x1 = __shfl_xor_sync(0xffffffffu, u16 ? red[1] : red[3], 16);
      red[0] = red[1] = red[2] = red[3] = 0.f;
    }
    if (st == 1) { const float p0 = k0 + x0, p1 = k1 + x1; k0 = u8 ? p1 : p0; x0 = __shfl_xor_sync(0xffffffffu, u8 ? p0 : p1, 8); }
    if (st == 2) { k0 += x0; x0 = __shfl_xor_sync(0xffffffffu, k0, 4); }
    if (st == 3 && !(lane & 4)) outp[grp * 16 + r * 4 + ((lane >> 3) & 1) * 2 + (lane >> 4)] = (k0 + x0) * unscale * unscale * unscale2;
  };
  auto group = [&](bool first, int prv, int cur, int nxt, int part) {
    const int pn = PX_OFF + px + nxt * 136 + lane;
#pragma unroll
    for (int t = part ? 7 : 0; t < 8; t++) {
      if (!part) {
      if (first || t) SCHED_FENCE(never, t * 8);
      if (!first) {
        if (t == 0) { iv[3] = ldtex(tex, PX_OFF + px + cur * 136 + lane + 96); iv[0] = ldtex(tex, pn); }
        if (t == 2) iv[1] = ldtex(tex, pn + 32);
        if (t < 4) red_stage(t, prv);
      } else if (t == 4) {
        TS(4, 2);
        mbar_wait_fast(pxRdy, 0);
        TS(4, 3);
        iv[0] = ldtex(tex, pn); iv[1] = ldtex(tex, pn + 32);
      }
      if (t == 4) { ix = ldtex(texX, (px + nxt * 136 + 128) * 4 + lane).x; iv[2] = ldtex(tex, pn + 64); }
      dot_part(t, 0);
      SCHED_FENCE(never, t * 8 + 1);
      if (t == 3) ldsm(ex, ix >> 9);
      if (t == 7) ldsm(ex, ix << 7);
      gather(t + 2, 0);
      dot_part(t, 1);
      if (first || t < 7) SCHED_FENCE(never, t * 8 + 4);
      if (t == 7) break;
      }
      gather(t + 2, 1);
      asm volatile("wgmma.wait_group.sync.aligned 0;" ::: "memory");
      asm volatile("" : "+r"(d[(t & 1) ^ 1][0]) :: "memory");
      mma1688f(red, hadd2(s[0], s[2]), hadd2(s[1], s[3]), (g | (d[(t & 1) ^ 1][0] & never)) == t ? 0x3c003c00u : 0u);
      hmma_part(t + 1);
      issue(t & 1);
    }
  };
  gather(0, 0); gather(0, 1); issue(0); ldsm(ex, ix << 7); gather(1, 0); gather(1, 1);
  asm volatile("wgmma.wait_group.sync.aligned 0;" ::: "memory");
  hmma_part(0);
  SCHED_FENCE(never, 99);
  issue(1);
  group(true, 0, 0, 1, 0); group(true, 0, 0, 1, 1);
  TS(4, 1);
#pragma unroll 1
  for (int n = 1;; n++) {
    if ((n & 11) == 2) mbar_wait_fast(pxRdy + 8 + (n & 4) * 2, 0);
    asm volatile("st.volatile.shared.u32 [%0],%1;" :: "r"(progG), "r"(n) : "memory");
    group(false, n - 1, n, min(n + 1, 15), 0);
    if (n == 15) break;
    group(false, n - 1, n, min(n + 1, 15), 1);
  }
  asm volatile("wgmma.wait_group.sync.aligned 0;" ::: "memory");
  mma1688f(red, hadd2(s[0], s[2]), hadd2(s[1], s[3]), g == 7 ? 0x3c003c00u : 0u);
#pragma unroll
  for (int st = 0; st < 4; st++) red_stage(st, 15);
  TS(0, 2);
  asm volatile("barrier.cluster.wait.aligned;" ::: "memory");
  asm volatile("barrier.cluster.arrive.relaxed.aligned; barrier.cluster.wait.aligned;" ::: "memory");
}

constexpr int SM_U = 130048, SM_BAR = 128000, SM_J = SM_U + 98304, DEEP_SMEM = SM_J + 4096;

__global__ void __cluster_dims__(2, 1, 1) __launch_bounds__(TH + 128, 1)
k_deep(cudaTextureObject_t tex, const __nv_bfloat16* __restrict__ w2, const __nv_bfloat16* __restrict__ b2,
       __nv_bfloat16* __restrict__ out, int never) {
  extern __shared__ __align__(1024) uint4 sm[];
  constexpr int PF = 4, DEPTH = 4, NW = TH / 32;
  const int tid = threadIdx.x;
  const int c = blockIdx.x >> 1, half = blockIdx.x & 1;
  const uint32_t sbase = (uint32_t)__cvta_generic_to_shared(sm);
  const uint32_t fullL = sbase + SM_BAR, fullU = fullL + 8, emptyL = fullL + 16, emptyU = fullL + 24, barJ = fullL + 32;
  TS(1, 0);
  if (tid == 0) {
    mbar_init(fullL, 1); mbar_init(fullU, 1); mbar_init(emptyL, 2 * NW); mbar_init(emptyU, 2 * NW); mbar_init(barJ, 1);
    asm volatile("fence.mbarrier_init.release.cluster;" ::: "memory");
  }
  __syncwarp();
  const int wrp = __shfl_sync(0xffffffffu, tid >> 5, 0);
  const char* base = (const char*)g_scr;
  uint32_t oL = (PL_OFF + c * NC * 8000) * 16u + half * 64000, oS = (PS_OFF + c * NC * 2000) * 16u + half * 16000;
  asm volatile("barrier.cluster.arrive.relaxed.aligned; barrier.cluster.wait.aligned;" ::: "memory");
  if (wrp == NW) {
    asm volatile("fence.proxy.async.global;" ::: "memory");
    e_expect(fullU, 96000);
#pragma unroll
    for (int m = 0; m < 3; m++) e_mc(sbase + SM_U + m * 32032 + half * 16000, base + oS, 16000, fullU, m == 2 ? POL_EF : POL_N);
    e_expect(fullL, 128000);
  }
  TS(5, 1);
  if (wrp >= NW) {
    asm volatile("setmaxnreg.dec.sync.aligned.u32 24;");
    if (wrp == NW) {
      uint32_t oT = (PT_OFF + c * 10 * 1024) * 16u + half * 8000;
      auto warm = [&](uint32_t off, uint32_t hb) {
        asm volatile(ELECT "mbarrier.expect_tx.relaxed.cta.shared::cta.b64 [%0],%1;}" :: "r"(barJ), "r"(2 * hb) : "memory");
        e_g2s(sbase + SM_J, base + off, hb, barJ); e_g2s(sbase + SM_J, base + off + hb, hb, barJ);
      };
      mbar_wait(fullU, 0);
      e_mc(sbase + half * 64000, base + oL, 64000, fullL, POL_EF);
      warm(oT, 4000);
#pragma unroll 1
      for (int k = 0; k + 1 < NC; k++) {
        oL += 128000; oS += 32000; oT += 16384;
        mbar_wait(fullL, k & 1);
        const uint32_t t0 = clock();
        e_pf(base + oS, 16000);
        warm((IX_OFF + half * IXH + (k + 2) * 8192 + ((c + (c >> 4) * (2 * k + 1)) & (k + 2 < NC ? 15 : 3)) * 512) * 16u, 4096);
        mbar_wait(emptyU, k & 1);
        e_expect(fullU, 96000);
#pragma unroll 1
        for (int q = 0; q < 8; q++) {
          sleep_until(t0, q * PACE);
          e_pf(base + oL + q * 8000, 8000);
          if (q >= 2) e_mc(sbase + SM_U + ((q - 2) >> 1) * 32032 + half * 16000 + (q & 1) * 8000, base + oS + (q & 1) * 8000, 8000, fullU, q >= 6 ? POL_EF : POL_N);
        }
        warm(oT, 4000);
        e_expect(fullL, 128000);
        sleep_until(t0, 7200);
        unsigned long long now, slot = 0;
        asm volatile("mov.u64 %0,%globaltimer;" : "=l"(now));
        if ((tid & 31) == 0) { atomicMax(&g_slot, now + 550); slot = atomicAdd(&g_slot, (unsigned long long)RSV); }
        slot = __shfl_sync(0xffffffffu, slot, 0);
        mbar_wait(emptyL, k & 1);
        for (int it = 0; it < 4000; it++) { asm volatile("mov.u64 %0,%globaltimer;" : "=l"(now)); if (now >= slot) break; }

        e_mc(sbase + half * 64000, base + oL, 64000, fullL, POL_EF);
      }
      mbar_wait(fullL, (NC - 1) & 1);
      mbar_wait(emptyU, (NC - 1) & 1);
      mbar_arrive_lane0(fullU);
      warm(oT + 16384, 4000);
      mbar_arrive_lane0(barJ); mbar_wait(barJ, 0);
    } else if (tid >= TH + 96) {
      if (tid < TH + 100) asm volatile("st.shared.u32 [%0],%1;" :: "r"(barJ + 32 + (tid & 3) * 4), "r"(((const uint32_t*)w2)[(c >> 2) * 16 + (tid & 3) * 4 + (c & 3)]) : "memory");
      asm volatile("bar.arrive 3,%0;" :: "n"(TH + 32) : "memory");
      asm volatile("griddepcontrol.wait;" ::: "memory");
      const int b = half * 8192 + c * 128 + (tid & 31) * 4;
      const float bias = __bfloat162float(b2[0]);
      float4 s = make_float4(bias, bias, bias, bias);
#pragma unroll 2
      for (int k = 0; k < 16; k++) { const float4 v = __ldcg((const float4*)(g_partP + k * B_ + b)); s.x += v.x; s.y += v.y; s.z += v.z; s.w += v.w; }
      asm volatile("red.global.add.v4.f32 [%0],{%1,%2,%3,%4};" :: "l"(g_acc + b), "f"(s.x), "f"(s.y), "f"(s.z), "f"(s.w) : "memory");
      asm volatile("bar.arrive 1,%0;" :: "n"(TH + 32) : "memory");
    }
    return;
  }
  asm volatile("setmaxnreg.inc.sync.aligned.u32 240;");
  const int lane = tid & 31;
  const int tbase = PT_OFF + c * 10 * 1024;
  const int ibase = IX_OFF + half * IXH + tid;
  const uint32_t lc = (tid & 7) << 4;
  uint4 acc[NS], wq[PF], x[DEPTH], y[YD], ye;
  uint32_t sw[NS] = {};
  auto sget = [&](int s) { return (s & 3) == 3 ? __byte_perm(__byte_perm(sw[s - 3], sw[s - 2], 0x0073), sw[s - 1], 0x0710) : sw[s]; };
  auto sa0 = [&](uint32_t v) { return sbase + SM_U + (((v << 5) & 0x1ffe0) | ((lc >> 2) & 16)); };
  uint32_t c1 = 0;
  auto sa1 = [&](uint32_t v) { return sbase + SM_U + (((v >> 7) & 0x1ffe0) | c1); };
  {
    uint4 i0[8];
#pragma unroll
    for (int q = 0; q < 8; q++) i0[q] = ldtex(tex, I0_OFF + (half * 8 + q) * TH + tid);
    auto wd = [&](int k) { return (k & 3) == 0 ? i0[k >> 2].x : (k & 3) == 1 ? i0[k >> 2].y : (k & 3) == 2 ? i0[k >> 2].z : i0[k >> 2].w; };
    TS(5, 2);
    mbar_wait_fast(fullU, 0);
#pragma unroll
    for (int i = 0; i < PF; i++) wq[i] = ldtex(tex, ibase + i * TH);
    TS(1, 1);
#pragma unroll
    for (int s = 0; s < NS; s++) acc[s] = add4(lds128(sbase + SM_U + (wd(s) & 0x1fff0)), lds128(sbase + SM_U + ((wd(s) >> 13) & 0x1fff0)));
    arrive_both(emptyU, lane);
    asm volatile("bar.sync 3,%0;" :: "n"(TH + 32) : "memory");
    TS(5, 3);
  }
#pragma unroll 1
  for (int k = 0; k < NC; k++) {
    const int ti = ibase + k * 8192;
    const int tb = tbase + k * 1024;
    const bool more = k + 1 < NC;
    TR(k * 4);
    mbar_wait_fast(fullL, k & 1);
    TR(k * 4 + 2);
    uint4 w, cc; uint32_t yc;
    constexpr int TL = NS * 8, TT = TL + NS * 2;
#pragma unroll
    for (int t = 0; t < TT + DEPTH; t += 2) {
      if (t == TL + DEPTH && !more) break;
      if (t >= DEPTH) {
        const int u = t - DEPTH;
        uint4 p = add4(x[u % DEPTH], x[(u + 1) % DEPTH]);
        if (u < TL) {
          const int s = u >> 3, j = u & 7;
          if (j == 0) {
            cc = s >= YD ? add4(y[s % YD], p) : p;
            if (s + YD < NS) y[s % YD] = ldtex(tex, tb | (yc & 1023));
          } else cc = add4(cc, p);
          if (j == 6) acc[s] = add4(acc[s], cc);
        } else {
          const int s = (u - TL) >> 1;
          acc[s] = add4(acc[s], p);
        }
      }
      if (t < TL) {
        const int s = t >> 3, j = t & 7;
        if (j == 0) {
          if (ye_of(s - YD) >= 0) acc[ye_of(s - YD) & 3] = add4(acc[ye_of(s - YD) & 3], ye);
          w = wq[s % PF];
          wq[s % PF] = ldtex(tex, ti + (s + PF) * TH);
          yc = __funnelshift_l(w.z, w.z, 5);
          if ((s & 3) != 3) asm volatile("add.u32 %0,%1,%2;" : "=r"(sw[s]) : "r"(w.w), "r"(never));
          if (ye_of(s) >= 0) ye = ldtex(tex, tb | w.w);
        }
#pragma unroll
        for (int jj = j; jj < j + 2; jj++) {
          const uint32_t ww = jj < 3 ? w.x : jj < 6 ? w.y : w.z;
          const uint32_t sh = jj % 3 == 0 ? ww : jj % 3 == 1 ? ww >> 10 : __funnelshift_l(ww, ww, 12);
          x[(t + jj - j) % DEPTH] = lds128(sbase + ((sh & 0x1ff80) | lc) + jj * 16 - 128);
        }
      } else if (t < TT) {
        const int s = (t - TL) >> 1;
        if (s == 0) {
          asm volatile("add.u32 %0,%1,%2;" : "=r"(c1) : "r"((~lc >> 2) & 16), "r"(never));
          arrive_both(emptyL, more ? lane : 9);
          TR(k * 4 + 3);
          mbar_wait_fast(fullU, (k + 1) & 1);
        }
        const uint32_t sv = sget(s);
        x[t % DEPTH] = lds128(sa0(sv));
        x[(t + 1) % DEPTH] = lds128(sa1(sv));
      } else if (t == TT) arrive_both(emptyU, lane);
      if ((t & 3) == 2) SCHED_FENCE(never, t);
    }
  }
  TS(1, 2);
  const uint4 w2v = lds128(barJ + 32);
  const uint32_t cell = sbase + SM_U + tid * 16;
  const int t9 = tbase + 9 * 1024;
  uint4 za[4], i9 = wq[0];
  auto fetch = [&](int q) {
    y[0] = ldtex(tex, t9 | i9.x); y[1] = ldtex(tex, t9 | i9.y); y[2] = ldtex(tex, t9 | i9.z); y[3] = ldtex(tex, t9 | i9.w);
    if (q) {
      i9 = ldtex(tex, ibase + NC * 8192 + min(q + 1, 7) * TH);
      const uint32_t ca = cell + (q > 6 ? 0 : q - 1) * 16384;
#pragma unroll
      for (int s = 0; s < 4; s++) za[s] = lds128(ca + s * 4096);
    }
  };
  fetch(0);
  i9 = wq[1];
#pragma unroll
  for (int s = 0; s < 4; s++) za[s] = acc[s];
#pragma unroll
  for (int s = 0; s < 24; s++) sts128(cell + s * 4096, acc[4 + s]);
  float hw[8];
  {
    const uint32_t ww[4] = {w2v.x, w2v.y, w2v.z, w2v.w};
#pragma unroll
    for (int k = 0; k < 8; k++) hw[k] = 0.5f * ((k & 1) ? bf_hi(ww[k >> 1]) : bf_lo(ww[k >> 1]));
  }
  float* outp = g_acc + half * 8192 + tid;
#pragma unroll 1
  for (int q = 0; q < NS / 4; q++) {
    uint4 z[4];
#pragma unroll
    for (int s = 0; s < 4; s++) z[s] = add4(za[s], y[s]);
    if (q == 1) {
#pragma unroll
      for (int s = 0; s < 4; s++) sts128(cell + s * 4096, acc[28 + s]);
    }
    if (q < 7) fetch(q + 1);
    SCHED_FENCE(never, 999);
#pragma unroll
    for (int s = 0; s < 4; s++) {
      const uint32_t a[4] = {z[s].x, z[s].y, z[s].z, z[s].w};
      float r0 = 0.f;
#pragma unroll
      for (int k = 0; k < 8; k++) {
        const float v = (k & 1) ? bf_hi(a[k >> 1]) : bf_lo(a[k >> 1]);
        const float u = v * fmaf(v * v, 0.7978845608028654f * 0.044715f, 0.7978845608028654f);
        float th; asm("tanh.approx.f32 %0,%1;" : "=f"(th) : "f"(u));
        r0 = fmaf(fmaf(v, th, v), hw[k], r0);
      }
      asm volatile("red.global.add.f32 [%0],%1;" :: "l"(outp + s * TH), "f"(r0) : "memory");
    }
    outp += 4 * TH;
  }
  TS(1, 3);
  asm volatile("bar.sync 1,%0;" :: "n"(TH + 32) : "memory");
  if (tid == 0) {
    unsigned old; asm volatile("atom.acq_rel.gpu.global.inc.u32 %0,[%1],63;" : "=r"(old) : "l"(&g_done[half * 32]) : "memory");
    asm volatile("st.shared.u32 [%0],%1;" :: "r"(barJ + 8), "r"(old) : "memory");
  }
  asm volatile("bar.sync 2,%0;" :: "n"(TH) : "memory");
  uint32_t old; asm volatile("ld.shared.u32 %0,[%1];" : "=r"(old) : "r"(barJ + 8));
  if (old == 63) {
    if (half == 0 && tid == 25) g_slot = 0;
    if (half == 0 && tid < 25) g_flag[tid * 32] = 0;
    float4 v[8];
#pragma unroll
    for (int q = 0; q < 8; q++) v[q] = __ldcg((const float4*)(g_acc + half * 8192) + q * TH + tid);
#pragma unroll
    for (int q = 0; q < 8; q++) ((uint2*)(out + half * 8192))[q * TH + tid] = make_uint2(pack_bf2(v[q].x, v[q].y), pack_bf2(v[q].z, v[q].w));
    TS(6, 2);
  }
}

}

extern "C" void kernel_launch(void* const* d_in, const int* in_sizes, int n_in, void* d_out, int out_size) {
  const int* idx = (const int*)d_in[0];
  const __nv_bfloat16* table = (const __nv_bfloat16*)d_in[1];
  const __nv_bfloat16* wp = (const __nv_bfloat16*)d_in[2];
  const __nv_bfloat16* w1 = (const __nv_bfloat16*)d_in[3];
  const __nv_bfloat16* b1 = (const __nv_bfloat16*)d_in[4];
  const __nv_bfloat16* w2 = (const __nv_bfloat16*)d_in[5];
  const __nv_bfloat16* b2 = (const __nv_bfloat16*)d_in[6];
  static cudaTextureObject_t texScr = 0, texX = 0;
  static CUtensorMap mapW, mapL, mapS, mapT, mapE, mapC;
  static const void *c_tab = nullptr, *c_w1 = nullptr;
  if (c_tab != table || c_w1 != w1) {
    c_tab = table; c_w1 = w1;
    char* scr = nullptr; cudaGetSymbolAddress((void**)&scr, g_scr);
    auto mk_tex = [](const void* p, size_t bytes, cudaChannelFormatDesc d) {
      cudaResourceDesc rd = {}; rd.resType = cudaResourceTypeLinear; rd.res.linear.devPtr = (void*)p; rd.res.linear.desc = d; rd.res.linear.sizeInBytes = bytes;
      cudaTextureDesc td = {}; td.readMode = cudaReadModeElementType;
      cudaTextureObject_t t = 0; cudaCreateTextureObject(&t, &rd, &td, nullptr); return t;
    };
    if (!texScr) {
      texScr = mk_tex(scr, (size_t)SCR_N * 16, cudaCreateChannelDesc<uint4>());
      texX = mk_tex(scr + (size_t)PX_OFF * 16, (size_t)(SCR_N - PX_OFF) * 16, cudaCreateChannelDesc<unsigned>());
    }
    typedef CUresult (*EncFn)(CUtensorMap*, CUtensorMapDataType, cuuint32_t, void*, const cuuint64_t*, const cuuint64_t*, const cuuint32_t*,
                              const cuuint32_t*, CUtensorMapInterleave, CUtensorMapSwizzle, CUtensorMapL2promotion, CUtensorMapFloatOOBfill);
    EncFn enc = nullptr; cudaDriverEntryPointQueryResult qr;
    cudaGetDriverEntryPoint("cuTensorMapEncodeTiled", (void**)&enc, cudaEnableDefault, &qr);
    const cuuint32_t ones[4] = {1, 1, 1, 1};
    auto mk = [&](CUtensorMap* m, CUtensorMapDataType dt, int rank, void* p, const cuuint64_t* dim, const cuuint64_t* str, const cuuint32_t* box, CUtensorMapSwizzle sw) {
      enc(m, dt, rank, p, dim, str, box, ones, CU_TENSOR_MAP_INTERLEAVE_NONE, sw, CU_TENSOR_MAP_L2_PROMOTION_NONE, CU_TENSOR_MAP_FLOAT_OOB_FILL_NONE);
    };
    { cuuint64_t dim[2] = {H_, F_ * D_}, str[1] = {H_ * 2}; cuuint32_t box[2] = {32, 256};
      mk(&mapW, CU_TENSOR_MAP_DATA_TYPE_BFLOAT16, 2, (void*)w1, dim, str, box, CU_TENSOR_MAP_SWIZZLE_64B); }
    { cuuint64_t dim[4] = {64, 64, V_, NC}, str[3] = {128000 * NC, 128, 128000}; cuuint32_t box[4] = {32, 4, 64, 1};
      mk(&mapL, CU_TENSOR_MAP_DATA_TYPE_BFLOAT16, 4, scr + (size_t)PL_OFF * 16, dim, str, box, CU_TENSOR_MAP_SWIZZLE_64B); }
    { cuuint64_t dim[4] = {64, 64, V_ / 4, NC}, str[3] = {32000 * NC, 128, 32000}; cuuint32_t box[4] = {64, 4, 16, 1};
      mk(&mapS, CU_TENSOR_MAP_DATA_TYPE_BFLOAT16, 4, scr + (size_t)PS_OFF * 16, dim, str, box, CU_TENSOR_MAP_SWIZZLE_128B); }
    { cuuint64_t dim[4] = {64, 64, V_ / 8, 10}, str[3] = {163840, 128, 16384}; cuuint32_t box[4] = {64, 4, 8, 2};
      mk(&mapT, CU_TENSOR_MAP_DATA_TYPE_BFLOAT16, 4, scr + (size_t)PT_OFF * 16, dim, str, box, CU_TENSOR_MAP_SWIZZLE_128B); }
    { cuuint64_t dim[2] = {D_, V_}, str[1] = {D_ * 2}; cuuint32_t box[2] = {64, 128};
      mk(&mapE, CU_TENSOR_MAP_DATA_TYPE_BFLOAT16, 2, (void*)table, dim, str, box, CU_TENSOR_MAP_SWIZZLE_128B);
      cuuint32_t box2[2] = {8, 256};
      mk(&mapC, CU_TENSOR_MAP_DATA_TYPE_BFLOAT16, 2, (void*)table, dim, str, box2, CU_TENSOR_MAP_SWIZZLE_NONE); }
    cudaFuncSetAttribute(k_deep, cudaFuncAttributeMaxDynamicSharedMemorySize, DEEP_SMEM);
    cudaFuncSetAttribute(k_tens, cudaFuncAttributeMaxDynamicSharedMemorySize, K1_SMEM);
  }
  k_tens<<<132, 512, K1_SMEM, cudaStreamPerThread>>>(mapW, mapL, mapS, mapT, mapE, mapC, texScr, texX, idx, table, wp, w1, b1, 0);
  cudaLaunchAttribute at[1];
  at[0].id = cudaLaunchAttributeProgrammaticStreamSerialization; at[0].val.programmaticStreamSerializationAllowed = 1;
  cudaLaunchConfig_t cfg = {};
  cfg.stream = cudaStreamPerThread; cfg.attrs = at;
  cfg.gridDim = 128; cfg.blockDim = TH + 128; cfg.dynamicSmemBytes = DEEP_SMEM; cfg.numAttrs = PDL;
  cudaLaunchKernelEx(&cfg, k_deep, texScr, w2, b2, (__nv_bfloat16*)d_out, 0);

}
```

```cpp
#include <cuda_runtime.h>
#include <cuda_bf16.h>
#include <cuda_fp16.h>
#include <stdint.h>
#include <cuda.h>

namespace {

constexpr int B_ = 16384, F_ = 100, D_ = 128, V_ = 1000, H_ = 512;
constexpr int NC = 9;
constexpr int PT_OFF = 0;
constexpr int PL_OFF = 64 * 10 * 1024;
constexpr int PS_OFF = PL_OFF + 64 * NC * 8000;
constexpr int IXH = NC * 8192 + 2048;
constexpr int IX_OFF = PS_OFF + 64 * NC * 2000;
constexpr int I0_OFF = IX_OFF + 2 * IXH;
constexpr int PX_OFF = I0_OFF + 4096;
constexpr int SCR_N = PX_OFF + 64 * 16 * 136;
static_assert(PX_OFF % 32 == 0, "");

__device__ __align__(1024) uint4 g_scr[SCR_N];
__device__ float g_acc[B_];
__device__ unsigned long long g_slot;
__device__ unsigned g_done[64];
__device__ float g_partP[16 * B_];
__device__ float2 g_unscale[16];
__device__ unsigned g_flag[25 * 32];

#define TS(k, i)
#define TR(slot)
#define PT(slot)

constexpr uint64_t POL_EF = 0x12F0000000000000ull, POL_N = 0x1000000000000000ull;
__device__ __forceinline__ uint32_t addbf2(uint32_t a, uint32_t b) { uint32_t r; asm("add.rn.bf16x2 %0,%1,%2;" : "=r"(r) : "r"(a), "r"(b)); return r; }
__device__ __forceinline__ uint4 add4(const uint4& a, const uint4& b) { return make_uint4(addbf2(a.x, b.x), addbf2(a.y, b.y), addbf2(a.z, b.z), addbf2(a.w, b.w)); }
__device__ __forceinline__ uint4 ldtex(cudaTextureObject_t t, int i) {
  uint4 v; asm volatile("tex.1d.v4.u32.s32 {%0,%1,%2,%3},[%4,{%5}];" : "=r"(v.x), "=r"(v.y), "=r"(v.z), "=r"(v.w) : "l"(t), "r"(i)); return v;
}
__device__ __forceinline__ uint4 lds128(uint32_t a) {
  uint4 v; asm volatile("ld.volatile.shared.v4.u32 {%0,%1,%2,%3},[%4];" : "=r"(v.x), "=r"(v.y), "=r"(v.z), "=r"(v.w) : "r"(a)); return v;
}
__device__ __forceinline__ void sts128(uint32_t a, const uint4& v) {
  asm volatile("st.shared.v4.u32 [%0],{%1,%2,%3,%4};" :: "r"(a), "r"(v.x), "r"(v.y), "r"(v.z), "r"(v.w) : "memory");
}
__device__ __forceinline__ void mbar_init(uint32_t bar, int n) { asm volatile("mbarrier.init.shared::cta.b64 [%0],%1;" :: "r"(bar), "r"(n) : "memory"); }
__device__ __forceinline__ void mbar_wait(uint32_t bar, uint32_t parity) {
  uint32_t ok; int it = 0;
  do { asm volatile("{.reg .pred p; mbarrier.try_wait.parity.shared::cta.b64 p,[%1],%2; selp.u32 %0,1,0,p;}" : "=r"(ok) : "r"(bar), "r"(parity) : "memory"); } while (!ok && ++it < (1 << 19));
}
__device__ __forceinline__ void mbar_expect(uint32_t bar, uint32_t bytes) { asm volatile("mbarrier.arrive.expect_tx.shared::cta.b64 _,[%0],%1;" :: "r"(bar), "r"(bytes) : "memory"); }
__device__ __forceinline__ void bulk_g2s(uint32_t dst, const void* src, uint32_t bytes, uint32_t bar) {
  asm volatile("cp.async.bulk.shared::cluster.global.mbarrier::complete_tx::bytes [%0],[%1],%2,[%3];" :: "r"(dst), "l"(src), "r"(bytes), "r"(bar) : "memory");
}
__device__ __forceinline__ void bulk_pf(const void* src, uint32_t bytes) { asm volatile("cp.async.bulk.prefetch.L2.global [%0],%1;" :: "l"(src), "r"(bytes) : "memory"); }
#define SCHED_FENCE(never, k) asm volatile("{.reg .pred p; setp.ne.u32 p,%0,%1; @p bra.uni SKIP_%=; pmevent 1; SKIP_%=: }" :: "r"(never), "r"(0x7fff0000 + (k)) : "memory")
#define SV 0
#define HV 1
#define PDL 1
#define RSV 22
#define PACE 800
__device__ __forceinline__ int quad_of(int n) { return n < 23 ? n + 2 : n - 23; }
__device__ __forceinline__ void mbar_wait_fast(uint32_t bar, uint32_t parity) {
  asm volatile("{.reg .pred p; .reg .u32 n;\n"
               "mbarrier.try_wait.parity.shared::cta.b64 p,[%0],%1;\n"
               "@p bra DONE_%=;\n"
               "mov.u32 n,0;\n"
               "LOOP_%=: mbarrier.try_wait.parity.shared::cta.b64 p,[%0],%1;\n"
               "add.u32 n,n,1; setp.gt.or.u32 p,n,400000,p;\n"
               "@!p bra LOOP_%=;\n"
               "DONE_%=: }" :: "r"(bar), "r"(parity) : "memory");
}
__device__ __forceinline__ void sleep_until(uint32_t t0, uint32_t dt) { while ((uint32_t)clock() - t0 < dt) __nanosleep(40); }
__device__ __forceinline__ uint32_t s_mask(uint32_t v, int q) { return (1u << ((v + 3 - q) & 3)) | (16u << ((v + 3 + q) & 3)); }
__device__ __forceinline__ uint32_t s_cell(uint32_t v, int q, uint32_t m) {
  const int t = __ffs(~m) - 1;
  const int cp = t == 8 ? q >> 1 : ((t & 4 ? t - q : t + q) - v) & 3;
  return cp * 1001 + v;
}
__device__ __forceinline__ uint32_t pk3(uint32_t a, uint32_t b, uint32_t c) {
  const uint32_t w = c + (a << 12) + (b << 22); return __funnelshift_l(w, w, 27);
}
constexpr int TH = 256, NS = 8192 / TH, YD = 4;
__host__ __device__ constexpr int ye_of(int s) { return s == 3 ? 0 : s == 11 ? 1 : s == 19 ? 2 : s == 23 ? 3 : -1; }
template <int N> __device__ __forceinline__ void wgmma_h(uint32_t* d, const uint32_t* a, uint64_t desc, int acc);
template <> __device__ __forceinline__ void wgmma_h<40>(uint32_t* d, const uint32_t* a, uint64_t desc, int acc) {
  asm volatile("{.reg .pred p; setp.ne.s32 p,%15,0;\n"
    "wgmma.mma_async.sync.aligned.m64n40k16.f16.f16.f16 {%0,%1,%2,%3,%4,%5,%6,%7,%8,%9},{%10,%11,%12,%13},%14,p,1,1,0;}"
    : "+r"(d[0]),"+r"(d[1]),"+r"(d[2]),"+r"(d[3]),"+r"(d[4]),"+r"(d[5]),"+r"(d[6]),"+r"(d[7]),"+r"(d[8]),"+r"(d[9])
    : "r"(a[0]), "r"(a[1]), "r"(a[2]), "r"(a[3]), "l"(desc), "r"(acc));
}
template <> __device__ __forceinline__ void wgmma_h<32>(uint32_t* d, const uint32_t* a, uint64_t desc, int acc) {
  asm volatile("{.reg .pred p; setp.ne.s32 p,%13,0;\n"
    "wgmma.mma_async.sync.aligned.m64n32k16.f16.f16.f16 {%0,%1,%2,%3,%4,%5,%6,%7},{%8,%9,%10,%11},%12,p,1,1,0;}"
    : "+r"(d[0]),"+r"(d[1]),"+r"(d[2]),"+r"(d[3]),"+r"(d[4]),"+r"(d[5]),"+r"(d[6]),"+r"(d[7])
    : "r"(a[0]), "r"(a[1]), "r"(a[2]), "r"(a[3]), "l"(desc), "r"(acc));
}
__device__ __forceinline__ void wgmma_p(float* d, const uint32_t* a, uint64_t desc, int acc) {
  asm volatile("{.reg .pred p; setp.ne.s32 p,%69,0;\n"
    "wgmma.mma_async.sync.aligned.m64n128k16.f32.bf16.bf16 {%0,%1,%2,%3,%4,%5,%6,%7,%8,%9,%10,%11,%12,%13,%14,%15,%16,%17,%18,%19,%20,%21,%22,%23,%24,%25,%26,%27,%28,%29,%30,%31,%32,%33,%34,%35,%36,%37,%38,%39,%40,%41,%42,%43,%44,%45,%46,%47,%48,%49,%50,%51,%52,%53,%54,%55,%56,%57,%58,%59,%60,%61,%62,%63},{%64,%65,%66,%67},%68,p,1,1,1;}"
    : "+f"(d[0]),"+f"(d[1]),"+f"(d[2]),"+f"(d[3]),"+f"(d[4]),"+f"(d[5]),"+f"(d[6]),"+f"(d[7]),"+f"(d[8]),"+f"(d[9]),"+f"(d[10]),"+f"(d[11]),"+f"(d[12]),"+f"(d[13]),"+f"(d[14]),"+f"(d[15]),"+f"(d[16]),"+f"(d[17]),"+f"(d[18]),"+f"(d[19]),"+f"(d[20]),"+f"(d[21]),"+f"(d[22]),"+f"(d[23]),"+f"(d[24]),"+f"(d[25]),"+f"(d[26]),"+f"(d[27]),"+f"(d[28]),"+f"(d[29]),"+f"(d[30]),"+f"(d[31]),"+f"(d[32]),"+f"(d[33]),"+f"(d[34]),"+f"(d[35]),"+f"(d[36]),"+f"(d[37]),"+f"(d[38]),"+f"(d[39]),"+f"(d[40]),"+f"(d[41]),"+f"(d[42]),"+f"(d[43]),"+f"(d[44]),"+f"(d[45]),"+f"(d[46]),"+f"(d[47]),"+f"(d[48]),"+f"(d[49]),"+f"(d[50]),"+f"(d[51]),"+f"(d[52]),"+f"(d[53]),"+f"(d[54]),"+f"(d[55]),"+f"(d[56]),"+f"(d[57]),"+f"(d[58]),"+f"(d[59]),"+f"(d[60]),"+f"(d[61]),"+f"(d[62]),"+f"(d[63])
    : "r"(a[0]), "r"(a[1]), "r"(a[2]), "r"(a[3]), "l"(desc), "r"(acc));
}

__device__ __forceinline__ void mma16816h(uint32_t* c, const uint32_t* a, uint32_t b0, uint32_t b1) {
  asm("mma.sync.aligned.m16n8k16.row.col.f16.f16.f16.f16 {%0,%1},{%2,%3,%4,%5},{%6,%7},{%0,%1};"
      : "+r"(c[0]), "+r"(c[1]) : "r"(a[0]), "r"(a[1]), "r"(a[2]), "r"(a[3]), "r"(b0), "r"(b1));
}
__device__ __forceinline__ void mma1688h(uint32_t* c, uint32_t a0, uint32_t a1, uint32_t b) {
  asm("mma.sync.aligned.m16n8k8.row.col.f16.f16.f16.f16 {%0,%1},{%2,%3},{%4},{%0,%1};" : "+r"(c[0]), "+r"(c[1]) : "r"(a0), "r"(a1), "r"(b));
}
__device__ __forceinline__ void mma1688f(float* c, uint32_t a0, uint32_t a1, uint32_t b) {
  asm("mma.sync.aligned.m16n8k8.row.col.f32.f16.f16.f32 {%0,%1,%2,%3},{%4,%5},{%6},{%0,%1,%2,%3};"
      : "+f"(c[0]), "+f"(c[1]), "+f"(c[2]), "+f"(c[3]) : "r"(a0), "r"(a1), "r"(b));
}
__device__ __forceinline__ uint32_t hadd2(uint32_t a, uint32_t b) { uint32_t r; asm("add.rn.f16x2 %0,%1,%2;" : "=r"(r) : "r"(a), "r"(b)); return r; }
__device__ __forceinline__ uint32_t hfma2(uint32_t a, uint32_t b, uint32_t c) { uint32_t r; asm("fma.rn.f16x2 %0,%1,%2,%3;" : "=r"(r) : "r"(a), "r"(b), "r"(c)); return r; }
__device__ __forceinline__ uint32_t pack_bf2(float lo, float hi) { uint32_t r; asm("cvt.rn.bf16x2.f32 %0,%1,%2;" : "=r"(r) : "f"(hi), "f"(lo)); return r; }
__device__ __forceinline__ uint32_t pack_h2(float lo, float hi) { uint32_t r; asm("cvt.rn.f16x2.f32 %0,%1,%2;" : "=r"(r) : "f"(hi), "f"(lo)); return r; }
__device__ __forceinline__ float bf_lo(uint32_t w) { return __uint_as_float(w << 16); }
__device__ __forceinline__ float bf_hi(uint32_t w) { return __uint_as_float(w & 0xffff0000u); }
__device__ __forceinline__ uint32_t absmax4(const uint4& v, uint32_t m) {
  return __vmaxu2(__vmaxu2(__vmaxu2(v.x & 0x7fff7fffu, v.y & 0x7fff7fffu), __vmaxu2(v.z & 0x7fff7fffu, v.w & 0x7fff7fffu)), m);
}
__device__ __forceinline__ float pow2_scale(uint32_t mbits, int p) { return __uint_as_float((uint32_t)min(max(253 + p - (int)(mbits >> 7), 2), 252) << 23); }

constexpr int G_O0 = 8, G_O1 = 4, G_O2 = 0, G_N0 = 5, G_N1 = 4, G_N2 = 4, G_K0 = 5, G_K1 = 3, G_K2 = 1;
__host__ __device__ constexpr bool unit_wg(int kb, int on) {
  return (on >= G_O0 && on < G_O0 + G_N0 && kb < G_K0) || (on >= G_O1 && on < G_O1 + G_N1 && kb < G_K1) || (on >= G_O2 && on < G_O2 + G_N2 && kb < G_K2);
}
constexpr int G_U1 = G_N0 * G_K0, G_U2 = G_U1 + G_N1 * G_K1, G_U = G_U2 + G_N2 * G_K2;
constexpr int K1_B = 130048, K1_STG = K1_B + 2 * 32768, K1_W = K1_STG + 16384, K1_BAR = K1_W + 48 * 256, K1_SMEM = K1_BAR + 256 + 6400;
__host__ __device__ constexpr int frag_index(int ok, int on) {
  int n = 0;
  for (int k = 0; k < 13; k++) for (int o = k; o < 13; o++) { if (k == ok && o == on) return n; if (!unit_wg(k >> 1, o)) n++; }
  return n;
}
constexpr int HU_N = 2 * G_U + frag_index(99, 99);
static_assert(HU_N <= 96, "");
struct FragIdx { int v[13][13]; };
__host__ __device__ constexpr FragIdx make_fi() { FragIdx f = {}; for (int k = 0; k < 13; k++) for (int o = 0; o < 13; o++) f.v[k][o] = frag_index(k, o); return f; }
__host__ __device__ constexpr uint64_t frag_tab(int first) {
  uint64_t t = 0;
  for (int k = 0; k < 13; k++) for (int o = k; o < 13; o++)
    if (!unit_wg(k >> 1, o)) { const int n = frag_index(k, o) - first; if (n >= 0 && n < 8) t |= (uint64_t)(k << 4 | o) << (8 * n); }
  return t;
}
__device__ __forceinline__ int hu_code(int hu) {
  constexpr uint64_t T0 = frag_tab(0), T1 = frag_tab(8), T2 = frag_tab(16), T3 = frag_tab(24);
  const int u = hu >> 1, f = hu - 2 * G_U;
  if (f >= 0) return (int)((f < 8 ? T0 : f < 16 ? T1 : f < 24 ? T2 : T3) >> (8 * (f & 7))) & 255;
  const int u0 = u < G_U1 ? u : u < G_U2 ? u - G_U1 : u - G_U2;
  const int kb = u < G_U1 ? u0 / G_N0 : u < G_U2 ? u0 / G_N1 : u0 / 4, on = u < G_U1 ? G_O0 + u0 % G_N0 : u < G_U2 ? G_O1 + u0 % G_N1 : G_O2 + u0 % 4;
  return (2 * kb + (hu & 1)) << 4 | on;
}

__device__ __forceinline__ void flag_wait(const unsigned* f, unsigned n) {
  unsigned v; int it = 0;
  asm volatile("ld.acquire.gpu.global.u32 %0,[%1];" : "=r"(v) : "l"(f) : "memory");
  if (v < n) {
    do { __nanosleep(300); asm volatile("ld.relaxed.gpu.global.u32 %0,[%1];" : "=r"(v) : "l"(f) : "memory"); } while (v < n && ++it < (1 << 20));
    asm volatile("ld.acquire.gpu.global.u32 %0,[%1];" : "=r"(v) : "l"(f) : "memory");
  }
}
__device__ __forceinline__ void mbar_arrive(uint32_t bar) { asm volatile("mbarrier.arrive.shared::cta.b64 _,[%0];" :: "r"(bar) : "memory"); }
__device__ __forceinline__ void mbar_arrive_lane0(uint32_t bar) {
  asm volatile("{.reg .pred p; elect.sync _|p,0xffffffff; @p mbarrier.arrive.shared::cta.b64 _,[%0];}" :: "r"(bar) : "memory");
}

__device__ __forceinline__ void arrive_both(uint32_t bar, int lane) {
  asm volatile("{.reg .pred p; .reg .u32 a; setp.lt.u32 p,%1,2; mapa.shared::cluster.u32 a,%0,%1;\n"
               "@p mbarrier.arrive.shared::cluster.b64 _,[a];}" :: "r"(bar), "r"(lane) : "memory");
}
#define ELECT "{.reg .pred p; elect.sync _|p,0xffffffff; @p "
__device__ __forceinline__ void e_mc(uint32_t dst, const void* src, uint32_t bytes, uint32_t bar, uint64_t pol) {
  asm volatile(ELECT "cp.async.bulk.shared::cluster.global.mbarrier::complete_tx::bytes.multicast::cluster.L2::cache_hint [%0],[%1],%2,[%3],%4,%5;}"
               :: "r"(dst), "l"(src), "r"(bytes), "r"(bar), "h"((unsigned short)3), "l"(pol) : "memory");
}
__device__ __forceinline__ void e_g2s(uint32_t dst, const void* src, uint32_t bytes, uint32_t bar) {
  asm volatile(ELECT "cp.async.bulk.shared::cluster.global.mbarrier::complete_tx::bytes [%0],[%1],%2,[%3];}" :: "r"(dst), "l"(src), "r"(bytes), "r"(bar) : "memory");
}
__device__ __forceinline__ void e_pf(const void* src, uint32_t bytes) { asm volatile(ELECT "cp.async.bulk.prefetch.L2.global [%0],%1;}" :: "l"(src), "r"(bytes) : "memory"); }
__device__ __forceinline__ void e_expect(uint32_t bar, uint32_t bytes) { asm volatile(ELECT "mbarrier.arrive.expect_tx.shared::cta.b64 _,[%0],%1;}" :: "r"(bar), "r"(bytes) : "memory"); }
__device__ __forceinline__ void e_tma2d(uint32_t dst, const CUtensorMap* m, int x, int y, uint32_t bar) {
  asm volatile(ELECT "cp.async.bulk.tensor.2d.shared::cluster.global.mbarrier::complete_tx::bytes [%0],[%1,{%2,%3}],[%4];}" :: "r"(dst), "l"(m), "r"(x), "r"(y), "r"(bar) : "memory");
}

__device__ __forceinline__ void pack_role(const int* __restrict__ idx, uint32_t sbase, int pc) {
  constexpr int BUF = 32 * 3328;
  const int tid = threadIdx.x, lane = tid & 31, warp = tid >> 5;
  const uint32_t full = sbase + 2 * BUF, empty = full + 16;
  if (tid == 0) { mbar_init(full, 1); mbar_init(full + 8, 1); mbar_init(empty, 18); mbar_init(empty + 8, 18); asm volatile("fence.proxy.async.shared::cta;" ::: "memory"); }
  __syncthreads();
  auto chunk = [&](int s) { return s * 3200 + (s >> 2) * 288; };
  auto load = [&](int n) {
    const int blk = pc * 16 + n;
    if (lane == 0) mbar_expect(full + (n & 1) * 8, 32 * 3200);
    __syncwarp();
    bulk_g2s(sbase + (n & 1) * BUF + chunk(lane), idx + ((blk >> 5) * 8192 + lane * TH + (blk & 31) * 8) * F_, 3200, full + (n & 1) * 8);
  };
  if (warp == 0) { load(0); load(1); }
  const int l = lane & 7;
  uint32_t rot[8], inc[3];
#pragma unroll
  for (int jj = 0; jj < 8; jj++) rot[jj] = ((l + jj) & 7) * 4;
#pragma unroll
  for (int q = 0; q < 3; q++) inc[q] = (l + 3 * q < 8) << 12 | (l + 3 * q + 1 < 8) << 22 | (q < 2 && l + 3 * q + 2 < 8);
  int loaded = 2;
#pragma unroll 1
  for (int task = warp; task < 288; task += 16) {
    const int n = task / 18, q = (task % 18) * 4 + (lane >> 3), sq = q / 9, k = q % 9;
    if (warp == 0 && n + 1 == loaded && loaded < 16) { mbar_wait(empty + (loaded & 1) * 8, ((loaded >> 1) - 1) & 1); load(loaded); loaded++; }
    mbar_wait(full + (n & 1) * 8, (n >> 1) & 1);
    const uint32_t buf = sbase + (n & 1) * BUF + l * 400, row = buf + chunk(sq * 4);
    auto ld = [&](uint32_t ad) { uint32_t v; asm volatile("ld.shared.u32 %0,[%1];" : "=r"(v) : "r"(ad)); return v; };
    const int blk = pc * 16 + n, half = blk >> 5, col = (blk & 31) * 8 + l;
    const int ks = k == NC - 1 ? 0 : k + 1;
    uint32_t cw[4], sv[8], m[2] = {0, 0};
    { const uint32_t a0 = row + (72 + 2 * ks + (l >> 2)) * 4;
#pragma unroll
      for (int u = 0; u < 8; u++) { sv[u] = ld((a0 ^ ((u >> 2) * 4)) + (u & 3) * 3200); m[u >> 2] |= s_mask(sv[u], l & 3) << (8 * (u & 3)); } }
#pragma unroll
    for (int h = 0; h < 2; h++) { m[h] |= __shfl_xor_sync(0xffffffffu, m[h], 1); m[h] |= __shfl_xor_sync(0xffffffffu, m[h], 2); }
#pragma unroll
    for (int u = 0; u < 4; u++) cw[u] = s_cell(sv[u], l & 3, (m[0] >> (8 * u)) & 255) | s_cell(sv[4 + u], l & 3, (m[1] >> (8 * u)) & 255) << 12;
    if (k == NC - 1) {
      auto wide = [&](uint32_t w) { return (w & 0xfff) << 5 | (w >> 12) << 18 | (l & 4 ? 1u << 4 : 1u << 17); };
      g_scr[I0_OFF + (half * 8 + sq) * TH + col] = make_uint4(wide(cw[0]), wide(cw[1]), wide(cw[2]), wide(cw[3]));
      g_scr[IX_OFF + half * IXH + NC * 8192 + sq * TH + col] = make_uint4(ld(row + 396), ld(row + 3596), ld(row + 6796), ld(row + 9996));
      cw[0] = cw[1] = cw[2] = cw[3] = 0;
    }
    const uint32_t ax = buf + chunk(min(sq + 1, 7) * 4) + (90 + k) * 4;
    const uint32_t yev = ld(buf + ((0x3210 >> (sq * 2 + (sq == 5) * 2)) & 3) * 3200 + (90 + k) * 4);
    uint4* dst = g_scr + IX_OFF + half * IXH + (k * NS + sq * 4) * TH + col;
#pragma unroll
    for (int u = 0; u < 4; u++) {
      uint32_t e[8];
#pragma unroll
      for (int jj = 0; jj < 8; jj++) e[jj] = ld(row + k * 32 + rot[jj] + u * 3200);
      dst[u * TH] = make_uint4(pk3(e[0], e[1], e[2] + inc[0]), pk3(e[3], e[4], e[5] + inc[1]), pk3(e[6], e[7], ld(ax + u * 3200) + inc[2]),
                               u < 3 ? __byte_perm(cw[u], cw[3], 0x4210 + (u << 12)) : yev);
    }
    mbar_arrive_lane0(empty + (n & 1) * 8);
  }
}

__global__ void __cluster_dims__(2, 1, 1) __launch_bounds__(512, 1)
k_tens(const __grid_constant__ CUtensorMap mapW, const __grid_constant__ CUtensorMap mapL, const __grid_constant__ CUtensorMap mapS,
       const __grid_constant__ CUtensorMap mapT, const __grid_constant__ CUtensorMap mapE, const __grid_constant__ CUtensorMap mapC, cudaTextureObject_t tex, cudaTextureObject_t texX,
       const int* __restrict__ idx, const __nv_bfloat16* __restrict__ table, const __nv_bfloat16* __restrict__ wp, const __nv_bfloat16* __restrict__ w1,
       const __nv_bfloat16* __restrict__ b1, int never) {
  extern __shared__ __align__(1024) uint4 sm[];
  const int tid = threadIdx.x, lane = tid & 31, cta = blockIdx.x;
  const uint32_t sbase = (uint32_t)__cvta_generic_to_shared(sm);
  const int g = lane >> 2, r = lane & 3;
  TS(0, 0);
  if (cta >= 128) {
    pack_role(idx, sbase, cta - 128);
    __syncthreads();
    if (tid == 0) {
      asm volatile("fence.acq_rel.gpu; griddepcontrol.launch_dependents;" ::: "memory");
      asm volatile("red.relaxed.gpu.global.add.u32 [%0],1;" :: "l"(&g_flag[24 * 32]) : "memory");
    }
    __syncwarp();
    TS(2, 1);
    asm volatile("barrier.cluster.arrive.relaxed.aligned; barrier.cluster.wait.aligned;" ::: "memory");
    return;
  }
  const uint32_t fullB = sbase + K1_BAR, emptyB = fullB + 24, fullE = fullB + 48, fullC = fullB + 56, fullI = fullB + 64, pxRdy = fullB + 72, fullS = fullB + 96, emptyS = fullB + 104, pkDone = fullB + 112, pkFull = fullB + 136, progG = fullB + 168;
  const int rb = cta & 7, hc = cta >> 3;
  if (__shfl_sync(0xffffffffu, tid >> 5, 0) == 12) {
    if (lane == 0) {
#pragma unroll
      for (int q = 0; q < 19; q++) if (q != 2 && q != 5) mbar_init(fullB + q * 8, q == 3 || q == 4 ? 8 : q == 12 ? 4 : q >= 14 && q < 17 ? 2 : 1);
      asm volatile("st.shared.u32 [%0],%1;" :: "r"(progG), "r"(0) : "memory");
    }
    asm volatile("fence.mbarrier_init.release.cluster; fence.proxy.async.shared::cta;" ::: "memory");
    __syncwarp();
    e_expect(fullC, 16384);
#pragma unroll
    for (int q = 0; q < 4; q++) e_tma2d(sbase + 32768 + q * 4096, &mapC, (cta & 15) * 8, q * 256, fullC);
    e_expect(fullE, 32768);
#pragma unroll
    for (int q = 0; q < 2; q++) e_tma2d(sbase + K1_B + 32768 + q * 16384, &mapE, q * 64, rb * 128, fullE);
    asm volatile("bar.arrive 2,512;" ::: "memory");
  }
  asm volatile("barrier.cluster.arrive.relaxed.aligned;" ::: "memory");
  if (tid >= 384) {
    asm volatile("setmaxnreg.dec.sync.aligned.u32 32;");
    if (tid < 416) {
      asm volatile("barrier.cluster.wait.aligned;" ::: "memory");
      if (tid == 384) {
#pragma unroll 1
        for (int n = 0; n < 25; n++) {
          const int st = n & 1, q = quad_of(n);
          if (n == 1) {
            mbar_expect(fullI, 51200);
#pragma unroll 1
            for (int u = 0; u < 8; u++) bulk_g2s(sbase + 76800 + u * 6400, idx + ((cta >> 4) * 8 + u) * 256 * F_, 6400, fullI);
          }
          mbar_wait(emptyB + st * 8, (((n + 1) >> 1) & 1) ^ 1);
          mbar_expect(fullB + st * 8, 32768);
          asm volatile("cp.async.bulk.tensor.2d.shared::cluster.global.mbarrier::complete_tx::bytes.multicast::cluster [%0],[%1,{%2,%3}],[%4],%5;"
                       :: "r"(sbase + K1_B + st * 32768 + (cta & 1) * 16384), "l"(&mapW), "r"(hc * 32), "r"(q * 512 + (cta & 1) * 256),
                          "r"(fullB + st * 8), "h"((unsigned short)3) : "memory");
          if (n + 1 < 25) bulk_pf(w1 + quad_of(n + 1) * 262144 + cta * 2048, 4096);
        }
      }
    } else if (tid < 448) {
      ((float4*)g_acc)[cta * 32 + lane] = make_float4(0.f, 0.f, 0.f, 0.f);
      asm volatile("bar.sync 2,512;" ::: "memory");
      __syncwarp();
      if (tid == 416) {
        int pub = 0;
#pragma unroll 1
        for (int n = 0; n < 50; n++) {
          const int quad = quad_of(n >> 1), mt = n & 1, v0 = rb * 128 + mt * 64;
          const uint32_t stg = sbase + K1_STG;
          if (pub < 3) {
            uint32_t ok = 1;
            if (pub == 0 || n == 49) mbar_wait(pkDone + pub * 8, 0);
            else asm volatile("{.reg .pred p; mbarrier.test_wait.parity.shared::cta.b64 p,[%1],0; selp.u32 %0,1,0,p;}" : "=r"(ok) : "r"(pkDone + pub * 8) : "memory");
            if (ok) {
              asm volatile("cp.async.bulk.wait_group 0;" ::: "memory");
              asm volatile("red.release.gpu.global.add.u32 [%0],1;" :: "l"(&g_flag[((cta >> 4) * 3 + pub) * 32]) : "memory");
              pub++;
              if (n == 49) { n--; continue; }
            }
          }
          mbar_wait(fullS, n & 1);
          asm volatile("fence.proxy.async.shared::cta;" ::: "memory");
          if (quad < 18) {
            asm volatile("cp.async.bulk.tensor.4d.global.shared::cta.bulk_group.L2::cache_hint [%0,{%1,%2,%3,%4}],[%5],%6;"
                         :: "l"(&mapL), "r"((quad & 1) * 32), "r"(hc * 4), "r"(v0), "r"(quad >> 1), "r"(stg), "l"(POL_EF) : "memory");
          } else {
#pragma unroll 1
            for (int hh = 0; hh < 2; hh++) {
              const int pq = quad * 2 + hh;
              asm volatile("cp.async.bulk.tensor.4d.global.shared::cta.bulk_group.L2::cache_hint [%0,{%1,%2,%3,%4}],[%5],%6;"
                         :: "l"(pq < 45 ? &mapS : &mapT), "r"(0), "r"(hc * 4), "r"(v0 >> (pq < 45 ? 2 : 3)), "r"(pq < 45 ? pq - 36 : (pq - 45) * 2), "r"(stg + hh * 8192), "l"(POL_EF) : "memory");
            }
          }
          asm volatile("cp.async.bulk.commit_group;" ::: "memory");
          asm volatile("cp.async.bulk.wait_group.read 0;" ::: "memory");
          mbar_arrive(emptyS);
        }
        asm volatile("cp.async.bulk.wait_group 0;" ::: "memory");
        asm volatile("fence.proxy.async.global;" ::: "memory");
        asm volatile("fence.acq_rel.gpu; griddepcontrol.launch_dependents;" ::: "memory");
        asm volatile("red.relaxed.gpu.global.add.u32 [%0],1;" :: "l"(&g_flag[24 * 32]) : "memory");
        flag_wait(&g_flag[24 * 32], 132);
        asm volatile("fence.proxy.async.global;" ::: "memory");
        const char* base = (const char*)g_scr;
        const int c = cta >> 1, half = cta & 1, ch = (c + (c >> 4) * 5) & 15;
        bulk_pf(base + (PS_OFF + c * NC * 2000) * 16u + half * 16000, 16000);
        bulk_pf(base + (PT_OFF + c * 10 * 1024) * 16u + half * 8000, 8000);
        mbar_expect(fullE, 18432);
        bulk_g2s(sbase + K1_B, base + (I0_OFF + half * 2048 + ch * 128) * 16u, 2048, fullE);
        bulk_g2s(sbase + K1_B + 2048, base + (IX_OFF + half * IXH + ch * 512) * 16u, 8192, fullE);
        bulk_g2s(sbase + K1_B + 10240, base + (IX_OFF + half * IXH + 8192 + ch * 512) * 16u, 8192, fullE);
        mbar_wait(fullE, 1);
      }
    } else {
      const int pw = (tid >> 5) & 1, rg = (cta >> 4) * 8 + ((cta & 15) >> 1), hf = cta & 1;
      const int* ip = idx + (rg * 256 + hf * 8) * F_;
      asm volatile("bar.sync 2,512;" ::: "memory");
      const uint32_t buf = sbase + K1_BAR + 256 + pw * 3200, bar = pkFull + pw * 8;
      const unsigned* fl = &g_flag[(cta >> 4) * 96];
      int batch = 0, rel = pw ? 3 : 0;
#pragma unroll 1
      for (int n = 1 + pw; n < 16; n += 2) {
        if (lane == 0) { mbar_expect(bar, 3200); bulk_g2s(buf, ip + n * 16 * F_, 3200, bar); if (n + 2 < 16) bulk_pf(ip + (n + 2) * 16 * F_, 3200); }
        uint32_t ok; int it = 0;
        do {
          if (rel < batch) {
            unsigned v; asm volatile("ld.relaxed.gpu.global.u32 %0,[%1];" : "=r"(v) : "l"(fl + rel * 32) : "memory");
            if (__all_sync(0xffffffffu, v >= 16)) { flag_wait(fl + rel * 32, 16); __syncwarp(); mbar_arrive_lane0(pxRdy + rel * 8); rel++; }
          }
          asm volatile("{.reg .pred p; mbarrier.test_wait.parity.shared::cta.b64 p,[%1],%2; selp.u32 %0,1,0,p;}" : "=r"(ok) : "r"(bar), "r"(((n - 1) >> 1) & 1) : "memory");
          ok = __all_sync(0xffffffffu, ok);
          if (!ok) __nanosleep(100);
        } while (!ok && ++it < (1 << 20));
        auto ld = [&](uint32_t ad) { uint32_t v; asm volatile("ld.shared.u32 %0,[%1];" : "=r"(v) : "r"(ad)); return v; };
        const uint32_t p0 = buf + ((lane >> 3) & 1) * 400 + ((lane >> 4) * 8 + (lane & 7)) * 4;
        auto wd = [&](int t, int h) { return pk3(ld(p0 + t * 800 + h * 192), ld(p0 + t * 800 + h * 192 + 64), ld(p0 + t * 800 + h * 192 + 128)); };
        uint4* dst = g_scr + PX_OFF + (rg * 16 + n) * 136;
        ((unsigned short*)(dst + 128))[lane * 2 + hf] = ld(buf + g * 400 + 384 + r * 4);
#pragma unroll
        for (int q = 0; q < 2; q++) dst[(hf * 2 + q) * 32 + lane] = make_uint4(wd(2 * q, 0), wd(2 * q, 1), wd(2 * q + 1, 0), wd(2 * q + 1, 1));
        __syncwarp();
        if (n <= 2 || n == 5 || n == 6 || n >= 14) { mbar_arrive_lane0(pkDone + batch * 8); batch++; }
      }
      for (; rel < 3; rel++) { flag_wait(fl + rel * 32, 16); __syncwarp(); mbar_arrive_lane0(pxRdy + rel * 8); }
      if (lane == 0) {
        mbar_wait(pxRdy + 16, 0);
        asm volatile("fence.proxy.async.global;" ::: "memory");
        const char* src = (const char*)(g_scr + PX_OFF + ((cta >> 4) * 8 + ((cta >> 1) & 3) * 2 + pw) * 16 * 136);
        int ph = pw;
#pragma unroll 1
        for (int n = 5; n < 16; n++) {
          uint32_t cur; int it = 0;
          do { asm volatile("ld.volatile.shared.u32 %0,[%1];" : "=r"(cur) : "r"(progG)); if (cur + 2 < n) __nanosleep(400); } while (cur + 2 < n && ++it < (1 << 16));
          if (cur + 1 >= n) continue;
          mbar_expect(bar, 2176); bulk_g2s(buf, src + n * 2176, 2176, bar);
          mbar_wait(bar, ph); ph ^= 1;
        }
      }
    }
    return;
  }
  if (tid >= 256) {
    asm volatile("setmaxnreg.inc.sync.aligned.u32 160;");
    const int w = (tid >> 5) & 3;
    const int srow = w * 16 + ((lane & 15) ^ ((lane & 1) << 2)), sc = lane >> 4;
    uint32_t a[2][8][4];
    asm volatile("bar.sync 2,512;" ::: "memory");
    mbar_wait_fast(fullE, 0);
#pragma unroll
    for (int mt = 0; mt < 2; mt++)
#pragma unroll
      for (int ks = 0; ks < 8; ks++)
        asm volatile("ldmatrix.sync.aligned.m8n8.x4.shared.b16 {%0,%1,%2,%3},[%4];"
                     : "=r"(a[mt][ks][0]), "=r"(a[mt][ks][1]), "=r"(a[mt][ks][2]), "=r"(a[mt][ks][3])
                     : "r"(sbase + K1_B + 32768 + (ks >> 2) * 16384 + (mt * 64 + srow) * 128 + ((((ks & 3) * 2 + sc) ^ (srow & 7)) * 16)) : "memory");
    asm volatile("barrier.cluster.wait.aligned;" ::: "memory");
    arrive_both(emptyB + 8, lane);
    const int v = w * 16 + (g ^ ((g & 1) << 2));
    const uint32_t baseL = v * 256 + r * 64 + ((v & 1) * 2 + (r >> 1)) * 16, baseS = (v >> 2) * 512 + r * 128 + (((v & 3) * 2) ^ ((v & 4) + r)) * 16,
                   baseT = (v >> 3) * 512 + r * 128 + ((v & 7) ^ r) * 16;
    const uint64_t desc0 = (uint64_t)(((sbase + K1_B) & 0x3FFFF) >> 4) | ((uint64_t)(8192 >> 4) << 16) | ((uint64_t)(512 >> 4) << 32) | (2ull << 62);
#pragma unroll 1
    for (int qn = 0; qn < 25; qn++) {
      const int quad = quad_of(qn), st = qn & 1;
      const bool isL = quad < 18;
      PT(qn * 16);
      mbar_wait_fast(fullB + st * 8, (qn >> 1) & 1);
#pragma unroll
      for (int mt = 0; mt < 2; mt++) {
        float d[64];
        PT(qn * 16 + mt * 4 + 1);
        asm volatile("wgmma.fence.sync.aligned;" ::: "memory");
#pragma unroll
        for (int ks = 0; ks < 8; ks++) wgmma_p(d, a[mt][ks], desc0 + st * 2048 + ks * 64, ks);
        asm volatile("wgmma.commit_group.sync.aligned;" ::: "memory");
        mbar_wait_fast(emptyS, mt ^ 1);
        PT(qn * 16 + mt * 4 + 2);
        asm volatile("wgmma.wait_group.sync.aligned 0;" ::: "memory");
#pragma unroll
        for (int q = 0; q < 16; q++) asm volatile("" : "+f"(d[q * 4]), "+f"(d[q * 4 + 1]), "+f"(d[q * 4 + 2]), "+f"(d[q * 4 + 3]) :: "memory");
        PT(qn * 16 + mt * 4 + 3);
        if (mt) arrive_both(emptyB + st * 8, qn < 23 ? lane : 9);
        if (quad == 24) {
#pragma unroll
          for (int cq = 0; cq < 4; cq++) {
            const uint32_t bw = __ldg((const uint32_t*)(b1 + hc * 32 + cq * 8) + r);
#pragma unroll
            for (int e = 0; e < 4; e++) d[48 + cq * 4 + e] += (e & 1) ? bf_hi(bw) : bf_lo(bw);
          }
        }
#pragma unroll
        for (int h = 0; h < 2; h++) {
          const bool isS = quad * 2 + h < 45;
          const uint32_t base = (isL ? baseL ^ (h * 32) : (isS ? baseS : baseT) ^ (h * 8192)), xj = isS ? 16 : 4096, xr = isL ? 2048 : isS ? 1024 : 576;
#pragma unroll
          for (int e4 = 0; e4 < 4; e4++) {
            const float* e = d + h * 32 + (e4 >> 1) * 16 + (e4 & 1) * 2;
            sts128(sbase + K1_STG + (base ^ ((e4 >> 1) * xj) ^ ((e4 & 1) * xr)),
                   make_uint4(pack_bf2(e[0], e[1]), pack_bf2(e[4], e[5]), pack_bf2(e[8], e[9]), pack_bf2(e[12], e[13])));
          }
        }
        __syncwarp();
        mbar_arrive_lane0(fullS);
        if (!mt) PT(qn * 16 + 4);
      }
      PT(qn * 16 + 8);
    }
    return;
  }
  const int slice = cta & 15;
  const int range = (cta >> 4) * 8 + __shfl_sync(0xffffffffu, tid >> 5, 0);
  uint4 iv[4], trow[4]; uint32_t ix;
  uint2 wrow[10];
#pragma unroll
  for (int q = 0; q < 10; q++) asm volatile("ld.global.nc.v2.u32 {%0,%1},[%2];" : "=r"(wrow[q].x), "=r"(wrow[q].y) : "l"((const uint2*)wp + min(tid + q * 256, 2499)));
  asm volatile("bar.sync 2,512;" ::: "memory");
  uint32_t me = 0, mw = 0;
#pragma unroll
  for (int q = 0; q < 10; q++) {
    mw = __vmaxu2(__vmaxu2(wrow[q].x & 0x7fff7fffu, wrow[q].y & 0x7fff7fffu), mw);
    const int e = min(tid + q * 256, 2499), row = e / 25;
    asm volatile("st.shared.v2.u32 [%0],{%1,%2};" :: "r"(sbase + (e + row) * 8), "r"(wrow[q].x), "r"(wrow[q].y) : "memory");
    if (e - row * 25 == 24) asm volatile("st.shared.v2.u32 [%0],{%1,%2};" :: "r"(sbase + (e + row) * 8 + 8), "r"(wrow[q].x), "r"(wrow[q].y) : "memory");
  }
  mbar_wait_fast(fullC, 0);
#pragma unroll
  for (int q = 0; q < 4; q++) { trow[q] = lds128(sbase + 32768 + (tid + q * 256) * 16); me = absmax4(trow[q], me); }
  me = __reduce_max_sync(0xffffffffu, max(me & 0xffff, me >> 16));
  mw = __reduce_max_sync(0xffffffffu, max(mw & 0xffff, mw >> 16));
  uint32_t* sred = (uint32_t*)((char*)sm + 128000);
  if (lane == 0) sred[tid >> 5] = me | mw << 16;
  TS(3, 0);
  asm volatile("setmaxnreg.inc.sync.aligned.u32 160;");
  asm volatile("bar.sync 1,256;" ::: "memory");
  { uint32_t m = 0;
#pragma unroll
    for (int q = 0; q < 8; q++) m = __vmaxu2(m, sred[q]);
    m = __shfl_sync(0xffffffffu, m, 0);
    me = m & 0xffff; mw = m >> 16; }
  const float se = pow2_scale(me, 3), sW = pow2_scale(mw, -2);
  TS(3, 1);
  auto put_rows = [&](int q, bool on) {
    const uint4 t = trow[q];
    const uint4 hv = make_uint4(pack_h2(bf_lo(t.x) * se, bf_hi(t.x) * se), pack_h2(bf_lo(t.y) * se, bf_hi(t.y) * se),
                                pack_h2(bf_lo(t.z) * se, bf_hi(t.z) * se), pack_h2(bf_lo(t.w) * se, bf_hi(t.w) * se));
    if (on)
#pragma unroll
      for (int s = 0; s < 8; s++) sts128(sbase + (tid + q * 256) * 128 + ((s + lane) & 7) * 16, hv);
  };
#pragma unroll 1
  for (int it = 0; it < 3; it++) {
    const int hu = ((tid >> 5) * 3 + it) * 4, code = hu_code(min(hu + (lane >> 3), HU_N - 1)), ok = code >> 4, on = code & 15;
    uint32_t x[4], y[4];
    asm volatile("ldmatrix.sync.aligned.m8n8.x4.shared.b16 {%0,%1,%2,%3},[%4];" : "=r"(x[0]), "=r"(x[1]), "=r"(x[2]), "=r"(x[3])
                 : "r"(sbase + (on * 8 + (lane & (on == 12 ? 3 : 7))) * 208 + ok * 16) : "memory");
    asm volatile("ldmatrix.sync.aligned.m8n8.x4.trans.shared.b16 {%0,%1,%2,%3},[%4];" : "=r"(y[0]), "=r"(y[1]), "=r"(y[2]), "=r"(y[3])
                 : "r"(sbase + (ok * 8 + (lane & (ok == 12 ? 3 : 7))) * 208 + on * 16) : "memory");
    const uint32_t lo = __ballot_sync(0xffffffffu, ok > on), dg = __ballot_sync(0xffffffffu, ok >= on);
#pragma unroll
    for (int q = 0; q < 4; q++) {
      const float m0 = (lo >> (8 * q)) & 1 ? 0.f : sW, m1 = (dg >> (8 * q)) & 1 ? 0.f : sW;
      asm volatile("st.shared.u32 [%0],%1;" :: "r"(sbase + K1_W + (hu + q) * 128 + lane * 4),
                   "r"(pack_h2(fmaf(bf_lo(x[q]), m0, bf_lo(y[q]) * m1), fmaf(bf_hi(x[q]), m0, bf_hi(y[q]) * m1))) : "memory");
    }
  }
  put_rows(1, true); put_rows(2, tid < 88);
  TS(3, 2);
  asm volatile("fence.proxy.async.shared::cta;" ::: "memory");
  asm volatile("bar.sync 1,256;" ::: "memory");
  put_rows(0, true);
  uint32_t bf[HU_N - 2 * G_U];
#pragma unroll
  for (int q = 0; q < HU_N - 2 * G_U; q++) asm volatile("ld.shared.u32 %0,[%1];" : "=r"(bf[q]) : "r"(sbase + K1_W + (2 * G_U + q) * 128 + lane * 4));
  if (cta < 16 && tid == 0) g_unscale[cta] = make_float2(__uint_as_float(0x7f000000u - __float_as_uint(se)), __uint_as_float(0x7f000000u - __float_as_uint(sW)));
  TS(3, 3);
  const int px = range * 16 * 136;
  mbar_wait_fast(fullI, 0);
  {
    const uint32_t ib = sbase + 76800 + (tid >> 5) * 6400, p0 = ib + ((lane >> 3) & 1) * 400 + ((lane >> 4) * 8 + (lane & 7)) * 4;
    auto ld = [&](uint32_t ad) { uint32_t v; asm volatile("ld.shared.u32 %0,[%1];" : "=r"(v) : "r"(ad)); return v; };
    auto wd = [&](int t, int h) { return pk3(ld(p0 + t * 800 + h * 192), ld(p0 + t * 800 + h * 192 + 64), ld(p0 + t * 800 + h * 192 + 128)); };
#pragma unroll
    for (int q = 0; q < 4; q++) {
      iv[q] = make_uint4(wd(2 * q, 0), wd(2 * q, 1), wd(2 * q + 1, 0), wd(2 * q + 1, 1));
    }
    ix = ld(ib + g * 400 + 384 + r * 4) | ld(ib + (8 + g) * 400 + 384 + r * 4) << 16;
  }
  asm volatile("bar.sync 1,256;" ::: "memory");
  put_rows(2, tid >= 88); put_rows(3, tid + 768 < V_);
  asm volatile("bar.sync 1,256;" ::: "memory");
  TS(0, 1);
  uint32_t lc; asm volatile("add.u32 %0,%1,%2;" : "=r"(lc) : "r"((lane & 7) * 16), "r"(never));
  const uint64_t wdesc = (uint64_t)(((sbase + K1_W) & 0x3FFFF) >> 4) | ((uint64_t)(128 >> 4) << 16) | ((uint64_t)(256 >> 4) << 32);
  uint32_t a[2][6][4], d[2][26], ex[4] = {}, s[4] = {};
  float red[4] = {0.f, 0.f, 0.f, 0.f};
  auto ldsm = [&](uint32_t* o, uint32_t sh) {
    asm volatile("ldmatrix.sync.aligned.m8n8.x4.trans.shared.b16 {%0,%1,%2,%3},[%4];"
                 : "=r"(o[0]), "=r"(o[1]), "=r"(o[2]), "=r"(o[3]) : "r"(sbase + ((sh & 0x1ff80) | lc)));
  };
  auto gather = [&](int t, int hf) {
    const int x = t & 1;
    const uint4 v = iv[(t >> 1) & 3];
#pragma unroll
    for (int kb = 3 * hf; kb < 3 * hf + 3; kb++) {
      const uint32_t ww = x ? (kb < 3 ? v.z : v.w) : (kb < 3 ? v.x : v.y);
      ldsm(a[x][kb], kb % 3 == 0 ? ww : kb % 3 == 1 ? ww >> 10 : __funnelshift_l(ww, ww, 12));
    }
  };
  auto issue = [&](int x) {
    asm volatile("wgmma.fence.sync.aligned;" ::: "memory");
#pragma unroll
    for (int kb = 0; kb < 6; kb++) {
      if (kb < G_K0) wgmma_h<G_N0 * 8>(d[x] + G_O0 * 2, a[x][kb], wdesc + kb * G_N0 * 16, kb);
      if (kb < G_K1) wgmma_h<G_N1 * 8>(d[x] + G_O1 * 2, a[x][kb], wdesc + (G_U1 + kb * G_N1) * 16, kb);
      if (kb < G_K2) wgmma_h<32>(d[x] + G_O2 * 2, a[x][kb], wdesc + (G_U2 + kb * G_N2) * 16, kb);
    }
    asm volatile("wgmma.commit_group.sync.aligned;" ::: "memory");
  };
  auto hmma_part = [&](int t) {
    constexpr FragIdx FI = make_fi();
    const int x = t & 1;
#pragma unroll
    for (int o = 0; o < 13; o++) asm volatile("" : "+r"(d[x][o * 2]), "+r"(d[x][o * 2 + 1]) :: "memory");
#pragma unroll
    for (int kb = 0; kb < 6; kb++)
#pragma unroll
      for (int o = 2 * kb + 1; o < 13; o++)
        if (!unit_wg(kb, o)) mma16816h(d[x] + o * 2, a[x][kb], bf[FI.v[2 * kb][o]], bf[FI.v[2 * kb + 1][o]]);
#pragma unroll
    for (int q = 0; q < 6; q++) if (!unit_wg(q, 2 * q)) mma1688h(d[x] + q * 4, a[x][q][0], a[x][q][1], bf[FI.v[2 * q][2 * q]]);
    mma1688h(d[x] + 24, r < 2 ? ex[t & 3] : 0u, r < 2 ? 0u : ex[t & 3], bf[FI.v[12][12]]);
  };
  auto dot_part = [&](int t, int hf) {
    const int x = t & 1;
    if (hf == 0) {
      const uint32_t pe = hfma2(r < 2 ? d[x][24] : d[x][25], ex[t & 3], 0u);
      s[0] = r < 2 ? pe : 0u; s[1] = r < 2 ? 0u : pe; s[2] = s[3] = 0;
    }
#pragma unroll
    for (int q = 3 * hf; q < 3 * hf + 3; q++)
#pragma unroll
      for (int e = 0; e < 4; e++) s[e] = hfma2(d[x][q * 4 + e], a[x][q][e], s[e]);
  };
  const float* outp = g_partP + slice * B_ + range * 256;
  uint32_t oofs; asm volatile("add.u32 %0,%1,%2;" : "=r"(oofs) : "r"((r * 4 + ((lane >> 3) & 1) * 2 + (lane >> 4)) * 4), "r"(never));
  float k0 = 0.f, k1 = 0.f, x0 = 0.f, x1 = 0.f;
  auto red_stage = [&](int st, int grp) {
    const bool u16 = lane & 16, u8 = lane & 8;
    if (st == 0) {
      k0 = u16 ? red[2] : red[0]; x0 = __shfl_xor_sync(0xffffffffu, u16 ? red[0] : red[2], 16);
      k1 = u16 ? red[3] : red[1]; x1 = __shfl_xor_sync(0xffffffffu, u16 ? red[1] : red[3], 16);
      red[0] = red[1] = red[2] = red[3] = 0.f;
    }
    if (st == 1) { const float p0 = k0 + x0, p1 = k1 + x1; k0 = u8 ? p1 : p0; x0 = __shfl_xor_sync(0xffffffffu, u8 ? p0 : p1, 8); }
    if (st == 2) { k0 += x0; x0 = __shfl_xor_sync(0xffffffffu, k0, 4); }
    if (st == 3) asm volatile("st.global.f32 [%0],%1;" :: "l"((const char*)(outp + grp * 16) + oofs), "f"(k0 + x0) : "memory");
  };
  auto side = [&](bool first, int t, int prv, int cur, int nxt) {
    const int pn = PX_OFF + px + nxt * 136 + lane;
    if (!first) {
      if (t == 0) { iv[3] = ldtex(tex, PX_OFF + px + cur * 136 + lane + 96); iv[0] = ldtex(tex, pn); }
      if (t == 2) iv[1] = ldtex(tex, pn + 32);
      if (t < 4) red_stage(t, prv);
    } else if (t == 4) {
      TS(4, 2);
      mbar_wait_fast(pxRdy, 0);
      TS(4, 3);
      iv[0] = ldtex(tex, pn); iv[1] = ldtex(tex, pn + 32);
    }
    if (t == 4) { ix = ldtex(texX, (px + nxt * 136 + 128) * 4 + lane).x; iv[2] = ldtex(tex, pn + 64); }
  };
  auto group = [&](bool first, int prv, int cur, int nxt, int part) {
#pragma unroll
    for (int t = part ? 7 : 0; t < 8; t++) {
      if (!part) {
        if (first || t) SCHED_FENCE(never, t * 8);
        if (SV == 0) side(first, t, prv, cur, nxt);
        dot_part(t, 0);
        SCHED_FENCE(never, t * 8 + 1);
        if (t == 3) ldsm(ex, ix >> 9);
        if (t == 7) ldsm(ex, ix << 7);
        gather(t + 2, 0);
        dot_part(t, 1);
        if (SV == 1) side(first, t, prv, cur, nxt);
        if (HV) { s[0] = hadd2(s[0], s[2]); s[1] = hadd2(s[1], s[3]); }
        if (first || t < 7) SCHED_FENCE(never, t * 8 + 4);
        if (t == 7) break;
      }
      gather(t + 2, 1);
      if (SV == 2) side(first, t, prv, cur, nxt);
      asm volatile("wgmma.wait_group.sync.aligned 0;" ::: "memory");
      asm volatile("" : "+r"(d[(t & 1) ^ 1][0]) :: "memory");
      mma1688f(red, HV ? s[0] : hadd2(s[0], s[2]), HV ? s[1] : hadd2(s[1], s[3]), (g | (d[(t & 1) ^ 1][0] & never)) == t ? 0x3c003c00u : 0u);
      hmma_part(t + 1);
      issue(t & 1);
    }
  };
  gather(0, 0); gather(0, 1); issue(0); ldsm(ex, ix << 7); gather(1, 0); gather(1, 1);
  asm volatile("wgmma.wait_group.sync.aligned 0;" ::: "memory");
  hmma_part(0);
  SCHED_FENCE(never, 99);
  issue(1);
  group(true, 0, 0, 1, 0); group(true, 0, 0, 1, 1);
  TS(4, 1);
#pragma unroll 1
  for (int n = 1;; n++) {
    if ((n & 11) == 2) mbar_wait_fast(pxRdy + 8 + (n & 4) * 2, 0);
    asm volatile("st.volatile.shared.u32 [%0],%1;" :: "r"(progG), "r"(n) : "memory");
    group(false, n - 1, n, min(n + 1, 15), 0);
    if (n == 15) break;
    group(false, n - 1, n, min(n + 1, 15), 1);
  }
  asm volatile("wgmma.wait_group.sync.aligned 0;" ::: "memory");
  mma1688f(red, HV ? s[0] : hadd2(s[0], s[2]), HV ? s[1] : hadd2(s[1], s[3]), g == 7 ? 0x3c003c00u : 0u);
#pragma unroll
  for (int st = 0; st < 4; st++) red_stage(st, 15);
  TS(0, 2);
  asm volatile("barrier.cluster.wait.aligned;" ::: "memory");
  asm volatile("barrier.cluster.arrive.relaxed.aligned; barrier.cluster.wait.aligned;" ::: "memory");
}

constexpr int SM_U = 130048, SM_BAR = 128000, SM_J = SM_U + 98304, DEEP_SMEM = SM_J + 4096;

__global__ void __cluster_dims__(2, 1, 1) __launch_bounds__(TH + 128, 1)
k_deep(cudaTextureObject_t tex, const __nv_bfloat16* __restrict__ w2, const __nv_bfloat16* __restrict__ b2,
       __nv_bfloat16* __restrict__ out, int never) {
  extern __shared__ __align__(1024) uint4 sm[];
  constexpr int PF = 4, DEPTH = 4, NW = TH / 32;
  const int tid = threadIdx.x;
  const int c = blockIdx.x >> 1, half = blockIdx.x & 1;
  const uint32_t sbase = (uint32_t)__cvta_generic_to_shared(sm);
  const uint32_t fullL = sbase + SM_BAR, fullU = fullL + 8, emptyL = fullL + 16, emptyU = fullL + 24, barJ = fullL + 32;
  TS(1, 0);
  if (tid == 0) {
    mbar_init(fullL, 1); mbar_init(fullU, 1); mbar_init(emptyL, 2 * NW); mbar_init(emptyU, 2 * NW); mbar_init(barJ, 1);
    asm volatile("fence.mbarrier_init.release.cluster;" ::: "memory");
  }
  __syncwarp();
  const int wrp = __shfl_sync(0xffffffffu, tid >> 5, 0);
  const char* base = (const char*)g_scr;
  uint32_t oL = (PL_OFF + c * NC * 8000) * 16u + half * 64000, oS = (PS_OFF + c * NC * 2000) * 16u + half * 16000;
  asm volatile("barrier.cluster.arrive.relaxed.aligned; barrier.cluster.wait.aligned;" ::: "memory");
  if (wrp == NW) {
    asm volatile("fence.proxy.async.global;" ::: "memory");
    e_expect(fullU, 96000);
#pragma unroll
    for (int m = 0; m < 3; m++) e_mc(sbase + SM_U + m * 32032 + half * 16000, base + oS, 16000, fullU, m == 2 ? POL_EF : POL_N);
    e_expect(fullL, 128000);
  }
  TS(5, 1);
  if (wrp >= NW) {
    asm volatile("setmaxnreg.dec.sync.aligned.u32 24;");
    if (wrp == NW) {
      uint32_t oT = (PT_OFF + c * 10 * 1024) * 16u + half * 8000;
      auto warm = [&](uint32_t off, uint32_t hb) {
        asm volatile(ELECT "mbarrier.expect_tx.relaxed.cta.shared::cta.b64 [%0],%1;}" :: "r"(barJ), "r"(2 * hb) : "memory");
        e_g2s(sbase + SM_J, base + off, hb, barJ); e_g2s(sbase + SM_J, base + off + hb, hb, barJ);
      };
      mbar_wait(fullU, 0);
      e_mc(sbase + half * 64000, base + oL, 64000, fullL, POL_EF);
      warm(oT, 4000);
#pragma unroll 1
      for (int k = 0; k + 1 < NC; k++) {
        oL += 128000; oS += 32000; oT += 16384;
        mbar_wait(fullL, k & 1);
        const uint32_t t0 = clock();
        e_pf(base + oS, 16000);
        warm((IX_OFF + half * IXH + (k + 2) * 8192 + ((c + (c >> 4) * (2 * k + 1)) & (k + 2 < NC ? 15 : 3)) * 512) * 16u, 4096);
        mbar_wait(emptyU, k & 1);
        e_expect(fullU, 96000);
#pragma unroll 1
        for (int q = 0; q < 8; q++) {
          sleep_until(t0, q * PACE);
          e_pf(base + oL + q * 8000, 8000);
          if (q >= 2) e_mc(sbase + SM_U + ((q - 2) >> 1) * 32032 + half * 16000 + (q & 1) * 8000, base + oS + (q & 1) * 8000, 8000, fullU, q >= 6 ? POL_EF : POL_N);
        }
        warm(oT, 4000);
        e_expect(fullL, 128000);
        sleep_until(t0, 7200);
        unsigned long long now, slot = 0;
        asm volatile("mov.u64 %0,%globaltimer;" : "=l"(now));
        if ((tid & 31) == 0) { atomicMax(&g_slot, now + 550); slot = atomicAdd(&g_slot, (unsigned long long)RSV); }
        slot = __shfl_sync(0xffffffffu, slot, 0);
        mbar_wait(emptyL, k & 1);
        for (int it = 0; it < 4000; it++) { asm volatile("mov.u64 %0,%globaltimer;" : "=l"(now)); if (now >= slot) break; }

        e_mc(sbase + half * 64000, base + oL, 64000, fullL, POL_EF);
      }
      mbar_wait(fullL, (NC - 1) & 1);
      mbar_wait(emptyU, (NC - 1) & 1);
      mbar_arrive_lane0(fullU);
      warm(oT + 16384, 4000);
      mbar_arrive_lane0(barJ); mbar_wait(barJ, 0);
    } else if (tid >= TH + 96) {
      if (tid < TH + 100) asm volatile("st.shared.u32 [%0],%1;" :: "r"(barJ + 32 + (tid & 3) * 4), "r"(((const uint32_t*)w2)[(c >> 2) * 16 + (tid & 3) * 4 + (c & 3)]) : "memory");
      asm volatile("bar.arrive 3,%0;" :: "n"(TH + 32) : "memory");
      asm volatile("griddepcontrol.wait;" ::: "memory");
      const int b = half * 8192 + c * 128 + (tid & 31) * 4;
      const float bias = __bfloat162float(b2[0]);
      float4 s = make_float4(bias, bias, bias, bias);
#pragma unroll 2
      for (int k = 0; k < 16; k++) {
        const float4 v = __ldcg((const float4*)(g_partP + k * B_ + b)); const float2 u = __ldcg(g_unscale + k);
        s.x = fmaf(v.x * u.x * u.x, u.y, s.x); s.y = fmaf(v.y * u.x * u.x, u.y, s.y); s.z = fmaf(v.z * u.x * u.x, u.y, s.z); s.w = fmaf(v.w * u.x * u.x, u.y, s.w);
      }
      asm volatile("red.global.add.v4.f32 [%0],{%1,%2,%3,%4};" :: "l"(g_acc + b), "f"(s.x), "f"(s.y), "f"(s.z), "f"(s.w) : "memory");
      asm volatile("bar.arrive 1,%0;" :: "n"(TH + 32) : "memory");
    }
    return;
  }
  asm volatile("setmaxnreg.inc.sync.aligned.u32 240;");
  const int lane = tid & 31;
  const int tbase = PT_OFF + c * 10 * 1024;
  const int ibase = IX_OFF + half * IXH + tid;
  const uint32_t lc = (tid & 7) << 4;
  uint4 acc[NS], wq[PF], x[DEPTH], y[YD], ye;
  uint32_t sw[NS] = {};
  auto sget = [&](int s) { return (s & 3) == 3 ? __byte_perm(__byte_perm(sw[s - 3], sw[s - 2], 0x0073), sw[s - 1], 0x0710) : sw[s]; };
  auto sa0 = [&](uint32_t v) { return sbase + SM_U + (((v << 5) & 0x1ffe0) | ((lc >> 2) & 16)); };
  uint32_t c1 = 0;
  auto sa1 = [&](uint32_t v) { return sbase + SM_U + (((v >> 7) & 0x1ffe0) | c1); };
  {
    uint4 i0[8];
#pragma unroll
    for (int q = 0; q < 8; q++) i0[q] = ldtex(tex, I0_OFF + (half * 8 + q) * TH + tid);
    auto wd = [&](int k) { return (k & 3) == 0 ? i0[k >> 2].x : (k & 3) == 1 ? i0[k >> 2].y : (k & 3) == 2 ? i0[k >> 2].z : i0[k >> 2].w; };
    TS(5, 2);
    mbar_wait_fast(fullU, 0);
#pragma unroll
    for (int i = 0; i < PF; i++) wq[i] = ldtex(tex, ibase + i * TH);
    TS(1, 1);
#pragma unroll
    for (int s = 0; s < NS; s++) acc[s] = add4(lds128(sbase + SM_U + (wd(s) & 0x1fff0)), lds128(sbase + SM_U + ((wd(s) >> 13) & 0x1fff0)));
    arrive_both(emptyU, lane);
    asm volatile("bar.sync 3,%0;" :: "n"(TH + 32) : "memory");
    TS(5, 3);
  }
#pragma unroll 1
  for (int k = 0; k < NC; k++) {
    const int ti = ibase + k * 8192;
    const int tb = tbase + k * 1024;
    const bool more = k + 1 < NC;
    TR(k * 4);
    mbar_wait_fast(fullL, k & 1);
    TR(k * 4 + 2);
    uint4 w, cc; uint32_t yc;
    constexpr int TL = NS * 8, TT = TL + NS * 2;
#pragma unroll
    for (int t = 0; t < TT + DEPTH; t += 2) {
      if (t == TL + DEPTH && !more) break;
      if (t >= DEPTH) {
        const int u = t - DEPTH;
        uint4 p = add4(x[u % DEPTH], x[(u + 1) % DEPTH]);
        if (u < TL) {
          const int s = u >> 3, j = u & 7;
          if (j == 0) {
            cc = s >= YD ? add4(y[s % YD], p) : p;
            if (s + YD < NS) y[s % YD] = ldtex(tex, tb | (yc & 1023));
          } else cc = add4(cc, p);
          if (j == 6) acc[s] = add4(acc[s], cc);
        } else {
          const int s = (u - TL) >> 1;
          acc[s] = add4(acc[s], p);
        }
      }
      if (t < TL) {
        const int s = t >> 3, j = t & 7;
        if (j == 0) {
          if (ye_of(s - YD) >= 0) acc[ye_of(s - YD) & 3] = add4(acc[ye_of(s - YD) & 3], ye);
          w = wq[s % PF];
          wq[s % PF] = ldtex(tex, ti + (s + PF) * TH);
          yc = __funnelshift_l(w.z, w.z, 5);
          if ((s & 3) != 3) asm volatile("add.u32 %0,%1,%2;" : "=r"(sw[s]) : "r"(w.w), "r"(never));
          if (ye_of(s) >= 0) ye = ldtex(tex, tb | w.w);
        }
#pragma unroll
        for (int jj = j; jj < j + 2; jj++) {
          const uint32_t ww = jj < 3 ? w.x : jj < 6 ? w.y : w.z;
          const uint32_t sh = jj % 3 == 0 ? ww : jj % 3 == 1 ? ww >> 10 : __funnelshift_l(ww, ww, 12);
          x[(t + jj - j) % DEPTH] = lds128(sbase + ((sh & 0x1ff80) | lc) + jj * 16 - 128);
        }
      } else if (t < TT) {
        const int s = (t - TL) >> 1;
        if (s == 0) {
          asm volatile("add.u32 %0,%1,%2;" : "=r"(c1) : "r"((~lc >> 2) & 16), "r"(never));
          arrive_both(emptyL, more ? lane : 9);
          TR(k * 4 + 3);
          mbar_wait_fast(fullU, (k + 1) & 1);
        }
        const uint32_t sv = sget(s);
        x[t % DEPTH] = lds128(sa0(sv));
        x[(t + 1) % DEPTH] = lds128(sa1(sv));
      } else if (t == TT) arrive_both(emptyU, lane);
      if ((t & 3) == 2) SCHED_FENCE(never, t);
    }
  }
  TS(1, 2);
  const uint4 w2v = lds128(barJ + 32);
  const uint32_t cell = sbase + SM_U + tid * 16;
  const int t9 = tbase + 9 * 1024;
  uint4 za[4], i9 = wq[0];
  auto fetch = [&](int q) {
    y[0] = ldtex(tex, t9 | i9.x); y[1] = ldtex(tex, t9 | i9.y); y[2] = ldtex(tex, t9 | i9.z); y[3] = ldtex(tex, t9 | i9.w);
    if (q) {
      i9 = ldtex(tex, ibase + NC * 8192 + min(q + 1, 7) * TH);
      const uint32_t ca = cell + (q > 6 ? 0 : q - 1) * 16384;
#pragma unroll
      for (int s = 0; s < 4; s++) za[s] = lds128(ca + s * 4096);
    }
  };
  fetch(0);
  i9 = wq[1];
#pragma unroll
  for (int s = 0; s < 4; s++) za[s] = acc[s];
#pragma unroll
  for (int s = 0; s < 24; s++) sts128(cell + s * 4096, acc[4 + s]);
  float hw[8];
  {
    const uint32_t ww[4] = {w2v.x, w2v.y, w2v.z, w2v.w};
#pragma unroll
    for (int k = 0; k < 8; k++) hw[k] = 0.5f * ((k & 1) ? bf_hi(ww[k >> 1]) : bf_lo(ww[k >> 1]));
  }
  float* outp = g_acc + half * 8192 + tid;
#pragma unroll 1
  for (int q = 0; q < NS / 4; q++) {
    uint4 z[4];
#pragma unroll
    for (int s = 0; s < 4; s++) z[s] = add4(za[s], y[s]);
    if (q == 1) {
#pragma unroll
      for (int s = 0; s < 4; s++) sts128(cell + s * 4096, acc[28 + s]);
    }
    if (q < 7) fetch(q + 1);
    SCHED_FENCE(never, 999);
#pragma unroll
    for (int s = 0; s < 4; s++) {
      const uint32_t a[4] = {z[s].x, z[s].y, z[s].z, z[s].w};
      float r0 = 0.f;
#pragma unroll
      for (int k = 0; k < 8; k++) {
        const float v = (k & 1) ? bf_hi(a[k >> 1]) : bf_lo(a[k >> 1]);
        const float u = v * fmaf(v * v, 0.7978845608028654f * 0.044715f, 0.7978845608028654f);
        float th; asm("tanh.approx.f32 %0,%1;" : "=f"(th) : "f"(u));
        r0 = fmaf(fmaf(v, th, v), hw[k], r0);
      }
      asm volatile("red.global.add.f32 [%0],%1;" :: "l"(outp + s * TH), "f"(r0) : "memory");
    }
    outp += 4 * TH;
  }
  TS(1, 3);
  asm volatile("bar.sync 1,%0;" :: "n"(TH + 32) : "memory");
  if (tid == 0) {
    unsigned old; asm volatile("atom.acq_rel.gpu.global.inc.u32 %0,[%1],63;" : "=r"(old) : "l"(&g_done[half * 32]) : "memory");
    asm volatile("st.shared.u32 [%0],%1;" :: "r"(barJ + 8), "r"(old) : "memory");
  }
  asm volatile("bar.sync 2,%0;" :: "n"(TH) : "memory");
  uint32_t old; asm volatile("ld.shared.u32 %0,[%1];" : "=r"(old) : "r"(barJ + 8));
  if (old == 63) {
    if (half == 0 && tid == 25) g_slot = 0;
    if (half == 0 && tid < 25) g_flag[tid * 32] = 0;
    float4 v[8];
#pragma unroll
    for (int q = 0; q < 8; q++) v[q] = __ldcg((const float4*)(g_acc + half * 8192) + q * TH + tid);
#pragma unroll
    for (int q = 0; q < 8; q++) ((uint2*)(out + half * 8192))[q * TH + tid] = make_uint2(pack_bf2(v[q].x, v[q].y), pack_bf2(v[q].z, v[q].w));
    TS(6, 2);
  }
}

}

extern "C" void kernel_launch(void* const* d_in, const int* in_sizes, int n_in, void* d_out, int out_size) {
  const int* idx = (const int*)d_in[0];
  const __nv_bfloat16* table = (const __nv_bfloat16*)d_in[1];
  const __nv_bfloat16* wp = (const __nv_bfloat16*)d_in[2];
  const __nv_bfloat16* w1 = (const __nv_bfloat16*)d_in[3];
  const __nv_bfloat16* b1 = (const __nv_bfloat16*)d_in[4];
  const __nv_bfloat16* w2 = (const __nv_bfloat16*)d_in[5];
  const __nv_bfloat16* b2 = (const __nv_bfloat16*)d_in[6];
  static cudaTextureObject_t texScr = 0, texX = 0;
  static CUtensorMap mapW, mapL, mapS, mapT, mapE, mapC;
  static const void *c_tab = nullptr, *c_w1 = nullptr;
  if (c_tab != table || c_w1 != w1) {
    c_tab = table; c_w1 = w1;
    char* scr = nullptr; cudaGetSymbolAddress((void**)&scr, g_scr);
    auto mk_tex = [](const void* p, size_t bytes, cudaChannelFormatDesc d) {
      cudaResourceDesc rd = {}; rd.resType = cudaResourceTypeLinear; rd.res.linear.devPtr = (void*)p; rd.res.linear.desc = d; rd.res.linear.sizeInBytes = bytes;
      cudaTextureDesc td = {}; td.readMode = cudaReadModeElementType;
      cudaTextureObject_t t = 0; cudaCreateTextureObject(&t, &rd, &td, nullptr); return t;
    };
    if (!texScr) {
      texScr = mk_tex(scr, (size_t)SCR_N * 16, cudaCreateChannelDesc<uint4>());
      texX = mk_tex(scr + (size_t)PX_OFF * 16, (size_t)(SCR_N - PX_OFF) * 16, cudaCreateChannelDesc<unsigned>());
    }
    typedef CUresult (*EncFn)(CUtensorMap*, CUtensorMapDataType, cuuint32_t, void*, const cuuint64_t*, const cuuint64_t*, const cuuint32_t*,
                              const cuuint32_t*, CUtensorMapInterleave, CUtensorMapSwizzle, CUtensorMapL2promotion, CUtensorMapFloatOOBfill);
    EncFn enc = nullptr; cudaDriverEntryPointQueryResult qr;
    cudaGetDriverEntryPoint("cuTensorMapEncodeTiled", (void**)&enc, cudaEnableDefault, &qr);
    const cuuint32_t ones[4] = {1, 1, 1, 1};
    auto mk = [&](CUtensorMap* m, CUtensorMapDataType dt, int rank, void* p, const cuuint64_t* dim, const cuuint64_t* str, const cuuint32_t* box, CUtensorMapSwizzle sw) {
      enc(m, dt, rank, p, dim, str, box, ones, CU_TENSOR_MAP_INTERLEAVE_NONE, sw, CU_TENSOR_MAP_L2_PROMOTION_NONE, CU_TENSOR_MAP_FLOAT_OOB_FILL_NONE);
    };
    { cuuint64_t dim[2] = {H_, F_ * D_}, str[1] = {H_ * 2}; cuuint32_t box[2] = {32, 256};
      mk(&mapW, CU_TENSOR_MAP_DATA_TYPE_BFLOAT16, 2, (void*)w1, dim, str, box, CU_TENSOR_MAP_SWIZZLE_64B); }
    { cuuint64_t dim[4] = {64, 64, V_, NC}, str[3] = {128000 * NC, 128, 128000}; cuuint32_t box[4] = {32, 4, 64, 1};
      mk(&mapL, CU_TENSOR_MAP_DATA_TYPE_BFLOAT16, 4, scr + (size_t)PL_OFF * 16, dim, str, box, CU_TENSOR_MAP_SWIZZLE_64B); }
    { cuuint64_t dim[4] = {64, 64, V_ / 4, NC}, str[3] = {32000 * NC, 128, 32000}; cuuint32_t box[4] = {64, 4, 16, 1};
      mk(&mapS, CU_TENSOR_MAP_DATA_TYPE_BFLOAT16, 4, scr + (size_t)PS_OFF * 16, dim, str, box, CU_TENSOR_MAP_SWIZZLE_128B); }
    { cuuint64_t dim[4] = {64, 64, V_ / 8, 10}, str[3] = {163840, 128, 16384}; cuuint32_t box[4] = {64, 4, 8, 2};
      mk(&mapT, CU_TENSOR_MAP_DATA_TYPE_BFLOAT16, 4, scr + (size_t)PT_OFF * 16, dim, str, box, CU_TENSOR_MAP_SWIZZLE_128B); }
    { cuuint64_t dim[2] = {D_, V_}, str[1] = {D_ * 2}; cuuint32_t box[2] = {64, 128};
      mk(&mapE, CU_TENSOR_MAP_DATA_TYPE_BFLOAT16, 2, (void*)table, dim, str, box, CU_TENSOR_MAP_SWIZZLE_128B);
      cuuint32_t box2[2] = {8, 256};
      mk(&mapC, CU_TENSOR_MAP_DATA_TYPE_BFLOAT16, 2, (void*)table, dim, str, box2, CU_TENSOR_MAP_SWIZZLE_NONE); }
    cudaFuncSetAttribute(k_deep, cudaFuncAttributeMaxDynamicSharedMemorySize, DEEP_SMEM);
    cudaFuncSetAttribute(k_tens, cudaFuncAttributeMaxDynamicSharedMemorySize, K1_SMEM);
  }
  k_tens<<<132, 512, K1_SMEM, cudaStreamPerThread>>>(mapW, mapL, mapS, mapT, mapE, mapC, texScr, texX, idx, table, wp, w1, b1, 0);
  cudaLaunchAttribute at[1];
  at[0].id = cudaLaunchAttributeProgrammaticStreamSerialization; at[0].val.programmaticStreamSerializationAllowed = 1;
  cudaLaunchConfig_t cfg = {};
  cfg.stream = cudaStreamPerThread; cfg.attrs = at;
  cfg.gridDim = 128; cfg.blockDim = TH + 128; cfg.dynamicSmemBytes = DEEP_SMEM; cfg.numAttrs = PDL;
  cudaLaunchKernelEx(&cfg, k_deep, texScr, w2, b2, (__nv_bfloat16*)d_out, 0);

}
```

```cpp
#include <cuda_runtime.h>
#include <cuda_bf16.h>
#include <cuda_fp16.h>
#include <stdint.h>
#include <cuda.h>

namespace {

constexpr int B_ = 16384, F_ = 100, D_ = 128, V_ = 1000, H_ = 512;
constexpr int NC = 9;
constexpr int PT_OFF = 0;
constexpr int PL_OFF = 64 * 10 * 1024;
constexpr int PS_OFF = PL_OFF + 64 * NC * 8000;
constexpr int IXH = NC * 8192 + 2048;
constexpr int IX_OFF = PS_OFF + 64 * NC * 2000;
constexpr int I0_OFF = IX_OFF + 2 * IXH;
constexpr int PX_OFF = I0_OFF + 4096;
constexpr int SCR_N = PX_OFF + 64 * 16 * 136;
static_assert(PX_OFF % 32 == 0, "");

__device__ __align__(1024) uint4 g_scr[SCR_N];
__device__ float g_acc[B_];
__device__ unsigned long long g_slot;
__device__ unsigned g_done[64];
__device__ float g_partP[16 * B_];
__device__ float2 g_unscale[16];
__device__ unsigned g_flag[25 * 32];

#define TS(k, i)
#define TR(slot)
#define PT(slot)

constexpr uint64_t POL_EF = 0x12F0000000000000ull, POL_N = 0x1000000000000000ull;
__device__ __forceinline__ uint32_t addbf2(uint32_t a, uint32_t b) { uint32_t r; asm("add.rn.bf16x2 %0,%1,%2;" : "=r"(r) : "r"(a), "r"(b)); return r; }
__device__ __forceinline__ uint4 add4(const uint4& a, const uint4& b) { return make_uint4(addbf2(a.x, b.x), addbf2(a.y, b.y), addbf2(a.z, b.z), addbf2(a.w, b.w)); }
__device__ __forceinline__ uint4 ldtex(cudaTextureObject_t t, int i) {
  uint4 v; asm volatile("tex.1d.v4.u32.s32 {%0,%1,%2,%3},[%4,{%5}];" : "=r"(v.x), "=r"(v.y), "=r"(v.z), "=r"(v.w) : "l"(t), "r"(i)); return v;
}
__device__ __forceinline__ uint4 lds128(uint32_t a) {
  uint4 v; asm volatile("ld.volatile.shared.v4.u32 {%0,%1,%2,%3},[%4];" : "=r"(v.x), "=r"(v.y), "=r"(v.z), "=r"(v.w) : "r"(a)); return v;
}
__device__ __forceinline__ void sts128(uint32_t a, const uint4& v) {
  asm volatile("st.shared.v4.u32 [%0],{%1,%2,%3,%4};" :: "r"(a), "r"(v.x), "r"(v.y), "r"(v.z), "r"(v.w) : "memory");
}
__device__ __forceinline__ void mbar_init(uint32_t bar, int n) { asm volatile("mbarrier.init.shared::cta.b64 [%0],%1;" :: "r"(bar), "r"(n) : "memory"); }
__device__ __forceinline__ void mbar_wait(uint32_t bar, uint32_t parity) {
  uint32_t ok; int it = 0;
  do { asm volatile("{.reg .pred p; mbarrier.try_wait.parity.shared::cta.b64 p,[%1],%2; selp.u32 %0,1,0,p;}" : "=r"(ok) : "r"(bar), "r"(parity) : "memory"); } while (!ok && ++it < (1 << 19));
}
__device__ __forceinline__ void mbar_expect(uint32_t bar, uint32_t bytes) { asm volatile("mbarrier.arrive.expect_tx.shared::cta.b64 _,[%0],%1;" :: "r"(bar), "r"(bytes) : "memory"); }
__device__ __forceinline__ void bulk_g2s(uint32_t dst, const void* src, uint32_t bytes, uint32_t bar) {
  asm volatile("cp.async.bulk.shared::cluster.global.mbarrier::complete_tx::bytes [%0],[%1],%2,[%3];" :: "r"(dst), "l"(src), "r"(bytes), "r"(bar) : "memory");
}
__device__ __forceinline__ void bulk_pf(const void* src, uint32_t bytes) { asm volatile("cp.async.bulk.prefetch.L2.global [%0],%1;" :: "l"(src), "r"(bytes) : "memory"); }
#define SCHED_FENCE(never, k) asm volatile("{.reg .pred p; setp.ne.u32 p,%0,%1; @p bra.uni SKIP_%=; pmevent 1; SKIP_%=: }" :: "r"(never), "r"(0x7fff0000 + (k)) : "memory")
#define SV 0
#define HV 1
#define PDL 1
#define RSV 23
#define RSV_L 550
#define RSV_T 7200
#define PACE 900
__device__ __forceinline__ int quad_of(int n) { return n < 23 ? n + 2 : n - 23; }
__device__ __forceinline__ void mbar_wait_fast(uint32_t bar, uint32_t parity) {
  asm volatile("{.reg .pred p; .reg .u32 n;\n"
               "mbarrier.try_wait.parity.shared::cta.b64 p,[%0],%1;\n"
               "@p bra DONE_%=;\n"
               "mov.u32 n,0;\n"
               "LOOP_%=: mbarrier.try_wait.parity.shared::cta.b64 p,[%0],%1;\n"
               "add.u32 n,n,1; setp.gt.or.u32 p,n,400000,p;\n"
               "@!p bra LOOP_%=;\n"
               "DONE_%=: }" :: "r"(bar), "r"(parity) : "memory");
}
__device__ __forceinline__ void sleep_until(uint32_t t0, uint32_t dt) { while ((uint32_t)clock() - t0 < dt) __nanosleep(40); }
__device__ __forceinline__ uint32_t s_mask(uint32_t v, int q) { return (1u << ((v + 3 - q) & 3)) | (16u << ((v + 3 + q) & 3)); }
__device__ __forceinline__ uint32_t s_cell(uint32_t v, int q, uint32_t m) {
  const int t = __ffs(~m) - 1;
  const int cp = t == 8 ? q >> 1 : ((t & 4 ? t - q : t + q) - v) & 3;
  return cp * 1001 + v;
}
__device__ __forceinline__ uint32_t pk3(uint32_t a, uint32_t b, uint32_t c) {
  const uint32_t w = c + (a << 12) + (b << 22); return __funnelshift_l(w, w, 27);
}
constexpr int TH = 256, NS = 8192 / TH, YD = 4;
__host__ __device__ constexpr int ye_of(int s) { return s == 3 ? 0 : s == 11 ? 1 : s == 19 ? 2 : s == 23 ? 3 : -1; }
template <int N> __device__ __forceinline__ void wgmma_h(uint32_t* d, const uint32_t* a, uint64_t desc, int acc);
template <> __device__ __forceinline__ void wgmma_h<40>(uint32_t* d, const uint32_t* a, uint64_t desc, int acc) {
  asm volatile("{.reg .pred p; setp.ne.s32 p,%15,0;\n"
    "wgmma.mma_async.sync.aligned.m64n40k16.f16.f16.f16 {%0,%1,%2,%3,%4,%5,%6,%7,%8,%9},{%10,%11,%12,%13},%14,p,1,1,0;}"
    : "+r"(d[0]),"+r"(d[1]),"+r"(d[2]),"+r"(d[3]),"+r"(d[4]),"+r"(d[5]),"+r"(d[6]),"+r"(d[7]),"+r"(d[8]),"+r"(d[9])
    : "r"(a[0]), "r"(a[1]), "r"(a[2]), "r"(a[3]), "l"(desc), "r"(acc));
}
template <> __device__ __forceinline__ void wgmma_h<32>(uint32_t* d, const uint32_t* a, uint64_t desc, int acc) {
  asm volatile("{.reg .pred p; setp.ne.s32 p,%13,0;\n"
    "wgmma.mma_async.sync.aligned.m64n32k16.f16.f16.f16 {%0,%1,%2,%3,%4,%5,%6,%7},{%8,%9,%10,%11},%12,p,1,1,0;}"
    : "+r"(d[0]),"+r"(d[1]),"+r"(d[2]),"+r"(d[3]),"+r"(d[4]),"+r"(d[5]),"+r"(d[6]),"+r"(d[7])
    : "r"(a[0]), "r"(a[1]), "r"(a[2]), "r"(a[3]), "l"(desc), "r"(acc));
}
__device__ __forceinline__ void wgmma_p(float* d, const uint32_t* a, uint64_t desc, int acc) {
  asm volatile("{.reg .pred p; setp.ne.s32 p,%69,0;\n"
    "wgmma.mma_async.sync.aligned.m64n128k16.f32.bf16.bf16 {%0,%1,%2,%3,%4,%5,%6,%7,%8,%9,%10,%11,%12,%13,%14,%15,%16,%17,%18,%19,%20,%21,%22,%23,%24,%25,%26,%27,%28,%29,%30,%31,%32,%33,%34,%35,%36,%37,%38,%39,%40,%41,%42,%43,%44,%45,%46,%47,%48,%49,%50,%51,%52,%53,%54,%55,%56,%57,%58,%59,%60,%61,%62,%63},{%64,%65,%66,%67},%68,p,1,1,1;}"
    : "+f"(d[0]),"+f"(d[1]),"+f"(d[2]),"+f"(d[3]),"+f"(d[4]),"+f"(d[5]),"+f"(d[6]),"+f"(d[7]),"+f"(d[8]),"+f"(d[9]),"+f"(d[10]),"+f"(d[11]),"+f"(d[12]),"+f"(d[13]),"+f"(d[14]),"+f"(d[15]),"+f"(d[16]),"+f"(d[17]),"+f"(d[18]),"+f"(d[19]),"+f"(d[20]),"+f"(d[21]),"+f"(d[22]),"+f"(d[23]),"+f"(d[24]),"+f"(d[25]),"+f"(d[26]),"+f"(d[27]),"+f"(d[28]),"+f"(d[29]),"+f"(d[30]),"+f"(d[31]),"+f"(d[32]),"+f"(d[33]),"+f"(d[34]),"+f"(d[35]),"+f"(d[36]),"+f"(d[37]),"+f"(d[38]),"+f"(d[39]),"+f"(d[40]),"+f"(d[41]),"+f"(d[42]),"+f"(d[43]),"+f"(d[44]),"+f"(d[45]),"+f"(d[46]),"+f"(d[47]),"+f"(d[48]),"+f"(d[49]),"+f"(d[50]),"+f"(d[51]),"+f"(d[52]),"+f"(d[53]),"+f"(d[54]),"+f"(d[55]),"+f"(d[56]),"+f"(d[57]),"+f"(d[58]),"+f"(d[59]),"+f"(d[60]),"+f"(d[61]),"+f"(d[62]),"+f"(d[63])
    : "r"(a[0]), "r"(a[1]), "r"(a[2]), "r"(a[3]), "l"(desc), "r"(acc));
}

__device__ __forceinline__ void mma16816h(uint32_t* c, const uint32_t* a, uint32_t b0, uint32_t b1) {
  asm("mma.sync.aligned.m16n8k16.row.col.f16.f16.f16.f16 {%0,%1},{%2,%3,%4,%5},{%6,%7},{%0,%1};"
      : "+r"(c[0]), "+r"(c[1]) : "r"(a[0]), "r"(a[1]), "r"(a[2]), "r"(a[3]), "r"(b0), "r"(b1));
}
__device__ __forceinline__ void mma1688h(uint32_t* c, uint32_t a0, uint32_t a1, uint32_t b) {
  asm("mma.sync.aligned.m16n8k8.row.col.f16.f16.f16.f16 {%0,%1},{%2,%3},{%4},{%0,%1};" : "+r"(c[0]), "+r"(c[1]) : "r"(a0), "r"(a1), "r"(b));
}
__device__ __forceinline__ void mma1688f(float* c, uint32_t a0, uint32_t a1, uint32_t b) {
  asm("mma.sync.aligned.m16n8k8.row.col.f32.f16.f16.f32 {%0,%1,%2,%3},{%4,%5},{%6},{%0,%1,%2,%3};"
      : "+f"(c[0]), "+f"(c[1]), "+f"(c[2]), "+f"(c[3]) : "r"(a0), "r"(a1), "r"(b));
}
__device__ __forceinline__ uint32_t hadd2(uint32_t a, uint32_t b) { uint32_t r; asm("add.rn.f16x2 %0,%1,%2;" : "=r"(r) : "r"(a), "r"(b)); return r; }
__device__ __forceinline__ uint32_t hfma2(uint32_t a, uint32_t b, uint32_t c) { uint32_t r; asm("fma.rn.f16x2 %0,%1,%2,%3;" : "=r"(r) : "r"(a), "r"(b), "r"(c)); return r; }
__device__ __forceinline__ uint32_t pack_bf2(float lo, float hi) { uint32_t r; asm("cvt.rn.bf16x2.f32 %0,%1,%2;" : "=r"(r) : "f"(hi), "f"(lo)); return r; }
__device__ __forceinline__ uint32_t pack_h2(float lo, float hi) { uint32_t r; asm("cvt.rn.f16x2.f32 %0,%1,%2;" : "=r"(r) : "f"(hi), "f"(lo)); return r; }
__device__ __forceinline__ float bf_lo(uint32_t w) { return __uint_as_float(w << 16); }
__device__ __forceinline__ float bf_hi(uint32_t w) { return __uint_as_float(w & 0xffff0000u); }
__device__ __forceinline__ uint32_t absmax4(const uint4& v, uint32_t m) {
  return __vmaxu2(__vmaxu2(__vmaxu2(v.x & 0x7fff7fffu, v.y & 0x7fff7fffu), __vmaxu2(v.z & 0x7fff7fffu, v.w & 0x7fff7fffu)), m);
}
__device__ __forceinline__ float pow2_scale(uint32_t mbits, int p) { return __uint_as_float((uint32_t)min(max(253 + p - (int)(mbits >> 7), 2), 252) << 23); }

constexpr int G_O0 = 8, G_O1 = 4, G_O2 = 0, G_N0 = 5, G_N1 = 4, G_N2 = 4, G_K0 = 5, G_K1 = 3, G_K2 = 1;
__host__ __device__ constexpr bool unit_wg(int kb, int on) {
  return (on >= G_O0 && on < G_O0 + G_N0 && kb < G_K0) || (on >= G_O1 && on < G_O1 + G_N1 && kb < G_K1) || (on >= G_O2 && on < G_O2 + G_N2 && kb < G_K2);
}
constexpr int G_U1 = G_N0 * G_K0, G_U2 = G_U1 + G_N1 * G_K1, G_U = G_U2 + G_N2 * G_K2;
constexpr int K1_B = 130048, K1_STG = K1_B + 2 * 32768, K1_W = K1_STG + 16384, K1_BAR = K1_W + 48 * 256, K1_SMEM = K1_BAR + 256 + 6400;
__host__ __device__ constexpr int frag_index(int ok, int on) {
  int n = 0;
  for (int k = 0; k < 13; k++) for (int o = k; o < 13; o++) { if (k == ok && o == on) return n; if (!unit_wg(k >> 1, o)) n++; }
  return n;
}
constexpr int HU_N = 2 * G_U + frag_index(99, 99);
static_assert(HU_N <= 96, "");
struct FragIdx { int v[13][13]; };
__host__ __device__ constexpr FragIdx make_fi() { FragIdx f = {}; for (int k = 0; k < 13; k++) for (int o = 0; o < 13; o++) f.v[k][o] = frag_index(k, o); return f; }
__host__ __device__ constexpr uint64_t frag_tab(int first) {
  uint64_t t = 0;
  for (int k = 0; k < 13; k++) for (int o = k; o < 13; o++)
    if (!unit_wg(k >> 1, o)) { const int n = frag_index(k, o) - first; if (n >= 0 && n < 8) t |= (uint64_t)(k << 4 | o) << (8 * n); }
  return t;
}
__device__ __forceinline__ int hu_code(int hu) {
  constexpr uint64_t T0 = frag_tab(0), T1 = frag_tab(8), T2 = frag_tab(16), T3 = frag_tab(24);
  const int u = hu >> 1, f = hu - 2 * G_U;
  if (f >= 0) return (int)((f < 8 ? T0 : f < 16 ? T1 : f < 24 ? T2 : T3) >> (8 * (f & 7))) & 255;
  const int u0 = u < G_U1 ? u : u < G_U2 ? u - G_U1 : u - G_U2;
  const int kb = u < G_U1 ? u0 / G_N0 : u < G_U2 ? u0 / G_N1 : u0 / 4, on = u < G_U1 ? G_O0 + u0 % G_N0 : u < G_U2 ? G_O1 + u0 % G_N1 : G_O2 + u0 % 4;
  return (2 * kb + (hu & 1)) << 4 | on;
}

__device__ __forceinline__ void flag_wait(const unsigned* f, unsigned n) {
  unsigned v; int it = 0;
  asm volatile("ld.acquire.gpu.global.u32 %0,[%1];" : "=r"(v) : "l"(f) : "memory");
  if (v < n) {
    do { __nanosleep(300); asm volatile("ld.relaxed.gpu.global.u32 %0,[%1];" : "=r"(v) : "l"(f) : "memory"); } while (v < n && ++it < (1 << 20));
    asm volatile("ld.acquire.gpu.global.u32 %0,[%1];" : "=r"(v) : "l"(f) : "memory");
  }
}
__device__ __forceinline__ void mbar_arrive(uint32_t bar) { asm volatile("mbarrier.arrive.shared::cta.b64 _,[%0];" :: "r"(bar) : "memory"); }
__device__ __forceinline__ void mbar_arrive_lane0(uint32_t bar) {
  asm volatile("{.reg .pred p; elect.sync _|p,0xffffffff; @p mbarrier.arrive.shared::cta.b64 _,[%0];}" :: "r"(bar) : "memory");
}

__device__ __forceinline__ void arrive_both(uint32_t bar, int lane) {
  asm volatile("{.reg .pred p; .reg .u32 a; setp.lt.u32 p,%1,2; mapa.shared::cluster.u32 a,%0,%1;\n"
               "@p mbarrier.arrive.shared::cluster.b64 _,[a];}" :: "r"(bar), "r"(lane) : "memory");
}
#define ELECT "{.reg .pred p; elect.sync _|p,0xffffffff; @p "
__device__ __forceinline__ void e_mc(uint32_t dst, const void* src, uint32_t bytes, uint32_t bar, uint64_t pol) {
  asm volatile(ELECT "cp.async.bulk.shared::cluster.global.mbarrier::complete_tx::bytes.multicast::cluster.L2::cache_hint [%0],[%1],%2,[%3],%4,%5;}"
               :: "r"(dst), "l"(src), "r"(bytes), "r"(bar), "h"((unsigned short)3), "l"(pol) : "memory");
}
__device__ __forceinline__ void e_g2s(uint32_t dst, const void* src, uint32_t bytes, uint32_t bar) {
  asm volatile(ELECT "cp.async.bulk.shared::cluster.global.mbarrier::complete_tx::bytes [%0],[%1],%2,[%3];}" :: "r"(dst), "l"(src), "r"(bytes), "r"(bar) : "memory");
}
__device__ __forceinline__ void e_pf(const void* src, uint32_t bytes) { asm volatile(ELECT "cp.async.bulk.prefetch.L2.global [%0],%1;}" :: "l"(src), "r"(bytes) : "memory"); }
__device__ __forceinline__ void e_expect(uint32_t bar, uint32_t bytes) { asm volatile(ELECT "mbarrier.arrive.expect_tx.shared::cta.b64 _,[%0],%1;}" :: "r"(bar), "r"(bytes) : "memory"); }
__device__ __forceinline__ void e_tma2d(uint32_t dst, const CUtensorMap* m, int x, int y, uint32_t bar) {
  asm volatile(ELECT "cp.async.bulk.tensor.2d.shared::cluster.global.mbarrier::complete_tx::bytes [%0],[%1,{%2,%3}],[%4];}" :: "r"(dst), "l"(m), "r"(x), "r"(y), "r"(bar) : "memory");
}

__device__ __forceinline__ void pack_role(const int* __restrict__ idx, uint32_t sbase, int pc) {
  constexpr int BUF = 32 * 3328;
  const int tid = threadIdx.x, lane = tid & 31, warp = tid >> 5;
  const uint32_t full = sbase + 2 * BUF, empty = full + 16;
  if (tid == 0) { mbar_init(full, 1); mbar_init(full + 8, 1); mbar_init(empty, 18); mbar_init(empty + 8, 18); asm volatile("fence.proxy.async.shared::cta;" ::: "memory"); }
  __syncthreads();
  auto chunk = [&](int s) { return s * 3200 + (s >> 2) * 288; };
  auto load = [&](int n) {
    const int blk = pc * 16 + n;
    if (lane == 0) mbar_expect(full + (n & 1) * 8, 32 * 3200);
    __syncwarp();
    bulk_g2s(sbase + (n & 1) * BUF + chunk(lane), idx + ((blk >> 5) * 8192 + lane * TH + (blk & 31) * 8) * F_, 3200, full + (n & 1) * 8);
  };
  if (warp == 0) { load(0); load(1); }
  const int l = lane & 7;
  uint32_t rot[8], inc[3];
#pragma unroll
  for (int jj = 0; jj < 8; jj++) rot[jj] = ((l + jj) & 7) * 4;
#pragma unroll
  for (int q = 0; q < 3; q++) inc[q] = (l + 3 * q < 8) << 12 | (l + 3 * q + 1 < 8) << 22 | (q < 2 && l + 3 * q + 2 < 8);
  int loaded = 2;
#pragma unroll 1
  for (int task = warp; task < 288; task += 16) {
    const int n = task / 18, q = (task % 18) * 4 + (lane >> 3), sq = q / 9, k = q % 9;
    if (warp == 0 && n + 1 == loaded && loaded < 16) { mbar_wait(empty + (loaded & 1) * 8, ((loaded >> 1) - 1) & 1); load(loaded); loaded++; }
    mbar_wait(full + (n & 1) * 8, (n >> 1) & 1);
    const uint32_t buf = sbase + (n & 1) * BUF + l * 400, row = buf + chunk(sq * 4);
    auto ld = [&](uint32_t ad) { uint32_t v; asm volatile("ld.shared.u32 %0,[%1];" : "=r"(v) : "r"(ad)); return v; };
    const int blk = pc * 16 + n, half = blk >> 5, col = (blk & 31) * 8 + l;
    const int ks = k == NC - 1 ? 0 : k + 1;
    uint32_t cw[4], sv[8], m[2] = {0, 0};
    { const uint32_t a0 = row + (72 + 2 * ks + (l >> 2)) * 4;
#pragma unroll
      for (int u = 0; u < 8; u++) { sv[u] = ld((a0 ^ ((u >> 2) * 4)) + (u & 3) * 3200); m[u >> 2] |= s_mask(sv[u], l & 3) << (8 * (u & 3)); } }
#pragma unroll
    for (int h = 0; h < 2; h++) { m[h] |= __shfl_xor_sync(0xffffffffu, m[h], 1); m[h] |= __shfl_xor_sync(0xffffffffu, m[h], 2); }
#pragma unroll
    for (int u = 0; u < 4; u++) cw[u] = s_cell(sv[u], l & 3, (m[0] >> (8 * u)) & 255) | s_cell(sv[4 + u], l & 3, (m[1] >> (8 * u)) & 255) << 12;
    if (k == NC - 1) {
      auto wide = [&](uint32_t w) { return (w & 0xfff) << 5 | (w >> 12) << 18 | (l & 4 ? 1u << 4 : 1u << 17); };
      g_scr[I0_OFF + (half * 8 + sq) * TH + col] = make_uint4(wide(cw[0]), wide(cw[1]), wide(cw[2]), wide(cw[3]));
      g_scr[IX_OFF + half * IXH + NC * 8192 + sq * TH + col] = make_uint4(ld(row + 396), ld(row + 3596), ld(row + 6796), ld(row + 9996));
      cw[0] = cw[1] = cw[2] = cw[3] = 0;
    }
    const uint32_t ax = buf + chunk(min(sq + 1, 7) * 4) + (90 + k) * 4;
    const uint32_t yev = ld(buf + ((0x3210 >> (sq * 2 + (sq == 5) * 2)) & 3) * 3200 + (90 + k) * 4);
    uint4* dst = g_scr + IX_OFF + half * IXH + (k * NS + sq * 4) * TH + col;
#pragma unroll
    for (int u = 0; u < 4; u++) {
      uint32_t e[8];
#pragma unroll
      for (int jj = 0; jj < 8; jj++) e[jj] = ld(row + k * 32 + rot[jj] + u * 3200);
      dst[u * TH] = make_uint4(pk3(e[0], e[1], e[2] + inc[0]), pk3(e[3], e[4], e[5] + inc[1]), pk3(e[6], e[7], ld(ax + u * 3200) + inc[2]),
                               u < 3 ? __byte_perm(cw[u], cw[3], 0x4210 + (u << 12)) : yev);
    }
    mbar_arrive_lane0(empty + (n & 1) * 8);
  }
}

__global__ void __cluster_dims__(2, 1, 1) __launch_bounds__(512, 1)
k_tens(const __grid_constant__ CUtensorMap mapW, const __grid_constant__ CUtensorMap mapL, const __grid_constant__ CUtensorMap mapS,
       const __grid_constant__ CUtensorMap mapT, const __grid_constant__ CUtensorMap mapE, const __grid_constant__ CUtensorMap mapC, cudaTextureObject_t tex, cudaTextureObject_t texX,
       const int* __restrict__ idx, const __nv_bfloat16* __restrict__ table, const __nv_bfloat16* __restrict__ wp, const __nv_bfloat16* __restrict__ w1,
       const __nv_bfloat16* __restrict__ b1, int never) {
  extern __shared__ __align__(1024) uint4 sm[];
  const int tid = threadIdx.x, lane = tid & 31, cta = blockIdx.x;
  const uint32_t sbase = (uint32_t)__cvta_generic_to_shared(sm);
  const int g = lane >> 2, r = lane & 3;
  TS(0, 0);
  if (cta >= 128) {
    pack_role(idx, sbase, cta - 128);
    __syncthreads();
    if (tid == 0) {
      asm volatile("fence.acq_rel.gpu; griddepcontrol.launch_dependents;" ::: "memory");
      asm volatile("red.relaxed.gpu.global.add.u32 [%0],1;" :: "l"(&g_flag[24 * 32]) : "memory");
    }
    __syncwarp();
    TS(2, 1);
    asm volatile("barrier.cluster.arrive.relaxed.aligned; barrier.cluster.wait.aligned;" ::: "memory");
    return;
  }
  const uint32_t fullB = sbase + K1_BAR, emptyB = fullB + 24, fullE = fullB + 48, fullC = fullB + 56, fullI = fullB + 64, pxRdy = fullB + 72, fullS = fullB + 96, emptyS = fullB + 104, pkDone = fullB + 112, pkFull = fullB + 136, progG = fullB + 168;
  const int rb = cta & 7, hc = cta >> 3;
  if (__shfl_sync(0xffffffffu, tid >> 5, 0) == 12) {
    if (lane == 0) {
#pragma unroll
      for (int q = 0; q < 19; q++) if (q != 2 && q != 5) mbar_init(fullB + q * 8, q == 3 || q == 4 ? 8 : q == 12 ? 4 : q >= 14 && q < 17 ? 2 : 1);
      asm volatile("st.shared.u32 [%0],%1;" :: "r"(progG), "r"(0) : "memory");
    }
    asm volatile("fence.mbarrier_init.release.cluster; fence.proxy.async.shared::cta;" ::: "memory");
    __syncwarp();
    e_expect(fullC, 16384);
#pragma unroll
    for (int q = 0; q < 4; q++) e_tma2d(sbase + 32768 + q * 4096, &mapC, (cta & 15) * 8, q * 256, fullC);
    e_expect(fullE, 32768);
#pragma unroll
    for (int q = 0; q < 2; q++) e_tma2d(sbase + K1_B + 32768 + q * 16384, &mapE, q * 64, rb * 128, fullE);
    asm volatile("bar.arrive 2,512;" ::: "memory");
  }
  asm volatile("barrier.cluster.arrive.relaxed.aligned;" ::: "memory");
  if (tid >= 384) {
    asm volatile("setmaxnreg.dec.sync.aligned.u32 32;");
    if (tid < 416) {
      asm volatile("barrier.cluster.wait.aligned;" ::: "memory");
      if (tid == 384) {
#pragma unroll 1
        for (int n = 0; n < 25; n++) {
          const int st = n & 1, q = quad_of(n);
          if (n == 1) {
            mbar_expect(fullI, 51200);
#pragma unroll 1
            for (int u = 0; u < 8; u++) bulk_g2s(sbase + 76800 + u * 6400, idx + ((cta >> 4) * 8 + u) * 256 * F_, 6400, fullI);
          }
          mbar_wait(emptyB + st * 8, (((n + 1) >> 1) & 1) ^ 1);
          mbar_expect(fullB + st * 8, 32768);
          asm volatile("cp.async.bulk.tensor.2d.shared::cluster.global.mbarrier::complete_tx::bytes.multicast::cluster [%0],[%1,{%2,%3}],[%4],%5;"
                       :: "r"(sbase + K1_B + st * 32768 + (cta & 1) * 16384), "l"(&mapW), "r"(hc * 32), "r"(q * 512 + (cta & 1) * 256),
                          "r"(fullB + st * 8), "h"((unsigned short)3) : "memory");
          if (n + 1 < 25) bulk_pf(w1 + quad_of(n + 1) * 262144 + cta * 2048, 4096);
        }
      }
    } else if (tid < 448) {
      ((float4*)g_acc)[cta * 32 + lane] = make_float4(0.f, 0.f, 0.f, 0.f);
      asm volatile("bar.sync 2,512;" ::: "memory");
      __syncwarp();
      if (tid == 416) {
        int pub = 0;
#pragma unroll 1
        for (int n = 0; n < 50; n++) {
          const int quad = quad_of(n >> 1), mt = n & 1, v0 = rb * 128 + mt * 64;
          const uint32_t stg = sbase + K1_STG;
          if (pub < 3) {
            uint32_t ok = 1;
            if (pub == 0 || n == 49) mbar_wait(pkDone + pub * 8, 0);
            else asm volatile("{.reg .pred p; mbarrier.test_wait.parity.shared::cta.b64 p,[%1],0; selp.u32 %0,1,0,p;}" : "=r"(ok) : "r"(pkDone + pub * 8) : "memory");
            if (ok) {
              asm volatile("cp.async.bulk.wait_group 0;" ::: "memory");
              asm volatile("red.release.gpu.global.add.u32 [%0],1;" :: "l"(&g_flag[((cta >> 4) * 3 + pub) * 32]) : "memory");
              pub++;
              if (n == 49) { n--; continue; }
            }
          }
          mbar_wait(fullS, n & 1);
          asm volatile("fence.proxy.async.shared::cta;" ::: "memory");
          if (quad < 18) {
            asm volatile("cp.async.bulk.tensor.4d.global.shared::cta.bulk_group.L2::cache_hint [%0,{%1,%2,%3,%4}],[%5],%6;"
                         :: "l"(&mapL), "r"((quad & 1) * 32), "r"(hc * 4), "r"(v0), "r"(quad >> 1), "r"(stg), "l"(POL_EF) : "memory");
          } else {
#pragma unroll 1
            for (int hh = 0; hh < 2; hh++) {
              const int pq = quad * 2 + hh;
              asm volatile("cp.async.bulk.tensor.4d.global.shared::cta.bulk_group.L2::cache_hint [%0,{%1,%2,%3,%4}],[%5],%6;"
                         :: "l"(pq < 45 ? &mapS : &mapT), "r"(0), "r"(hc * 4), "r"(v0 >> (pq < 45 ? 2 : 3)), "r"(pq < 45 ? pq - 36 : (pq - 45) * 2), "r"(stg + hh * 8192), "l"(POL_EF) : "memory");
            }
          }
          asm volatile("cp.async.bulk.commit_group;" ::: "memory");
          asm volatile("cp.async.bulk.wait_group.read 0;" ::: "memory");
          mbar_arrive(emptyS);
        }
        asm volatile("cp.async.bulk.wait_group 0;" ::: "memory");
        asm volatile("fence.proxy.async.global;" ::: "memory");
        asm volatile("fence.acq_rel.gpu; griddepcontrol.launch_dependents;" ::: "memory");
        asm volatile("red.relaxed.gpu.global.add.u32 [%0],1;" :: "l"(&g_flag[24 * 32]) : "memory");
        flag_wait(&g_flag[24 * 32], 132);
        asm volatile("fence.proxy.async.global;" ::: "memory");
        const char* base = (const char*)g_scr;
        const int c = cta >> 1, half = cta & 1, ch = (c + (c >> 4) * 5) & 15;
        bulk_pf(base + (PS_OFF + c * NC * 2000) * 16u + half * 16000, 16000);
        bulk_pf(base + (PT_OFF + c * 10 * 1024) * 16u + half * 8000, 8000);
        mbar_expect(fullE, 18432);
        bulk_g2s(sbase + K1_B, base + (I0_OFF + half * 2048 + ch * 128) * 16u, 2048, fullE);
        bulk_g2s(sbase + K1_B + 2048, base + (IX_OFF + half * IXH + ch * 512) * 16u, 8192, fullE);
        bulk_g2s(sbase + K1_B + 10240, base + (IX_OFF + half * IXH + 8192 + ch * 512) * 16u, 8192, fullE);
        mbar_wait(fullE, 1);
      }
    } else {
      const int pw = (tid >> 5) & 1, rg = (cta >> 4) * 8 + ((cta & 15) >> 1), hf = cta & 1;
      const int* ip = idx + (rg * 256 + hf * 8) * F_;
      asm volatile("bar.sync 2,512;" ::: "memory");
      const uint32_t buf = sbase + K1_BAR + 256 + pw * 3200, bar = pkFull + pw * 8;
      const unsigned* fl = &g_flag[(cta >> 4) * 96];
      int batch = 0, rel = pw ? 3 : 0;
#pragma unroll 1
      for (int n = 1 + pw; n < 16; n += 2) {
        if (lane == 0) { mbar_expect(bar, 3200); bulk_g2s(buf, ip + n * 16 * F_, 3200, bar); if (n + 2 < 16) bulk_pf(ip + (n + 2) * 16 * F_, 3200); }
        uint32_t ok; int it = 0;
        do {
          if (rel < batch) {
            unsigned v; asm volatile("ld.relaxed.gpu.global.u32 %0,[%1];" : "=r"(v) : "l"(fl + rel * 32) : "memory");
            if (__all_sync(0xffffffffu, v >= 16)) { flag_wait(fl + rel * 32, 16); __syncwarp(); mbar_arrive_lane0(pxRdy + rel * 8); rel++; }
          }
          asm volatile("{.reg .pred p; mbarrier.test_wait.parity.shared::cta.b64 p,[%1],%2; selp.u32 %0,1,0,p;}" : "=r"(ok) : "r"(bar), "r"(((n - 1) >> 1) & 1) : "memory");
          ok = __all_sync(0xffffffffu, ok);
          if (!ok) __nanosleep(100);
        } while (!ok && ++it < (1 << 20));
        auto ld = [&](uint32_t ad) { uint32_t v; asm volatile("ld.shared.u32 %0,[%1];" : "=r"(v) : "r"(ad)); return v; };
        const uint32_t p0 = buf + ((lane >> 3) & 1) * 400 + ((lane >> 4) * 8 + (lane & 7)) * 4;
        auto wd = [&](int t, int h) { return pk3(ld(p0 + t * 800 + h * 192), ld(p0 + t * 800 + h * 192 + 64), ld(p0 + t * 800 + h * 192 + 128)); };
        uint4* dst = g_scr + PX_OFF + (rg * 16 + n) * 136;
        ((unsigned short*)(dst + 128))[lane * 2 + hf] = ld(buf + g * 400 + 384 + r * 4);
#pragma unroll
        for (int q = 0; q < 2; q++) dst[(hf * 2 + q) * 32 + lane] = make_uint4(wd(2 * q, 0), wd(2 * q, 1), wd(2 * q + 1, 0), wd(2 * q + 1, 1));
        __syncwarp();
        if (n <= 2 || n == 5 || n == 6 || n >= 14) { mbar_arrive_lane0(pkDone + batch * 8); batch++; }
      }
      for (; rel < 3; rel++) { flag_wait(fl + rel * 32, 16); __syncwarp(); mbar_arrive_lane0(pxRdy + rel * 8); }
      if (lane == 0) {
        mbar_wait(pxRdy + 16, 0);
        asm volatile("fence.proxy.async.global;" ::: "memory");
        const char* src = (const char*)(g_scr + PX_OFF + ((cta >> 4) * 8 + ((cta >> 1) & 3) * 2 + pw) * 16 * 136);
        int ph = pw;
#pragma unroll 1
        for (int n = 5; n < 16; n++) {
          uint32_t cur; int it = 0;
          do { asm volatile("ld.volatile.shared.u32 %0,[%1];" : "=r"(cur) : "r"(progG)); if (cur + 2 < n) __nanosleep(400); } while (cur + 2 < n && ++it < (1 << 16));
          if (cur + 1 >= n) continue;
          mbar_expect(bar, 2176); bulk_g2s(buf, src + n * 2176, 2176, bar);
          mbar_wait(bar, ph); ph ^= 1;
        }
      }
    }
    return;
  }
  if (tid >= 256) {
    asm volatile("setmaxnreg.inc.sync.aligned.u32 160;");
    const int w = (tid >> 5) & 3;
    const int srow = w * 16 + ((lane & 15) ^ ((lane & 1) << 2)), sc = lane >> 4;
    uint32_t a[2][8][4];
    asm volatile("bar.sync 2,512;" ::: "memory");
    mbar_wait_fast(fullE, 0);
#pragma unroll
    for (int mt = 0; mt < 2; mt++)
#pragma unroll
      for (int ks = 0; ks < 8; ks++)
        asm volatile("ldmatrix.sync.aligned.m8n8.x4.shared.b16 {%0,%1,%2,%3},[%4];"
                     : "=r"(a[mt][ks][0]), "=r"(a[mt][ks][1]), "=r"(a[mt][ks][2]), "=r"(a[mt][ks][3])
                     : "r"(sbase + K1_B + 32768 + (ks >> 2) * 16384 + (mt * 64 + srow) * 128 + ((((ks & 3) * 2 + sc) ^ (srow & 7)) * 16)) : "memory");
    asm volatile("barrier.cluster.wait.aligned;" ::: "memory");
    arrive_both(emptyB + 8, lane);
    const int v = w * 16 + (g ^ ((g & 1) << 2));
    const uint32_t baseL = v * 256 + r * 64 + ((v & 1) * 2 + (r >> 1)) * 16, baseS = (v >> 2) * 512 + r * 128 + (((v & 3) * 2) ^ ((v & 4) + r)) * 16,
                   baseT = (v >> 3) * 512 + r * 128 + ((v & 7) ^ r) * 16;
    const uint64_t desc0 = (uint64_t)(((sbase + K1_B) & 0x3FFFF) >> 4) | ((uint64_t)(8192 >> 4) << 16) | ((uint64_t)(512 >> 4) << 32) | (2ull << 62);
#pragma unroll 1
    for (int qn = 0; qn < 25; qn++) {
      const int quad = quad_of(qn), st = qn & 1;
      const bool isL = quad < 18;
      PT(qn * 16);
      mbar_wait_fast(fullB + st * 8, (qn >> 1) & 1);
#pragma unroll
      for (int mt = 0; mt < 2; mt++) {
        float d[64];
        PT(qn * 16 + mt * 4 + 1);
        asm volatile("wgmma.fence.sync.aligned;" ::: "memory");
#pragma unroll
        for (int ks = 0; ks < 8; ks++) wgmma_p(d, a[mt][ks], desc0 + st * 2048 + ks * 64, ks);
        asm volatile("wgmma.commit_group.sync.aligned;" ::: "memory");
        mbar_wait_fast(emptyS, mt ^ 1);
        PT(qn * 16 + mt * 4 + 2);
        asm volatile("wgmma.wait_group.sync.aligned 0;" ::: "memory");
#pragma unroll
        for (int q = 0; q < 16; q++) asm volatile("" : "+f"(d[q * 4]), "+f"(d[q * 4 + 1]), "+f"(d[q * 4 + 2]), "+f"(d[q * 4 + 3]) :: "memory");
        PT(qn * 16 + mt * 4 + 3);
        if (mt) arrive_both(emptyB + st * 8, qn < 23 ? lane : 9);
        if (quad == 24) {
#pragma unroll
          for (int cq = 0; cq < 4; cq++) {
            const uint32_t bw = __ldg((const uint32_t*)(b1 + hc * 32 + cq * 8) + r);
#pragma unroll
            for (int e = 0; e < 4; e++) d[48 + cq * 4 + e] += (e & 1) ? bf_hi(bw) : bf_lo(bw);
          }
        }
#pragma unroll
        for (int h = 0; h < 2; h++) {
          const bool isS = quad * 2 + h < 45;
          const uint32_t base = (isL ? baseL ^ (h * 32) : (isS ? baseS : baseT) ^ (h * 8192)), xj = isS ? 16 : 4096, xr = isL ? 2048 : isS ? 1024 : 576;
#pragma unroll
          for (int e4 = 0; e4 < 4; e4++) {
            const float* e = d + h * 32 + (e4 >> 1) * 16 + (e4 & 1) * 2;
            sts128(sbase + K1_STG + (base ^ ((e4 >> 1) * xj) ^ ((e4 & 1) * xr)),
                   make_uint4(pack_bf2(e[0], e[1]), pack_bf2(e[4], e[5]), pack_bf2(e[8], e[9]), pack_bf2(e[12], e[13])));
          }
        }
        __syncwarp();
        mbar_arrive_lane0(fullS);
        if (!mt) PT(qn * 16 + 4);
      }
      PT(qn * 16 + 8);
    }
    return;
  }
  const int slice = cta & 15;
  const int range = (cta >> 4) * 8 + __shfl_sync(0xffffffffu, tid >> 5, 0);
  uint4 iv[4], trow[4]; uint32_t ix;
  uint2 wrow[10];
#pragma unroll
  for (int q = 0; q < 10; q++) asm volatile("ld.global.nc.v2.u32 {%0,%1},[%2];" : "=r"(wrow[q].x), "=r"(wrow[q].y) : "l"((const uint2*)wp + min(tid + q * 256, 2499)));
  asm volatile("bar.sync 2,512;" ::: "memory");
  uint32_t me = 0, mw = 0;
#pragma unroll
  for (int q = 0; q < 10; q++) {
    mw = __vmaxu2(__vmaxu2(wrow[q].x & 0x7fff7fffu, wrow[q].y & 0x7fff7fffu), mw);
    const int e = min(tid + q * 256, 2499), row = e / 25;
    asm volatile("st.shared.v2.u32 [%0],{%1,%2};" :: "r"(sbase + (e + row) * 8), "r"(wrow[q].x), "r"(wrow[q].y) : "memory");
    if (e - row * 25 == 24) asm volatile("st.shared.v2.u32 [%0],{%1,%2};" :: "r"(sbase + (e + row) * 8 + 8), "r"(wrow[q].x), "r"(wrow[q].y) : "memory");
  }
  mbar_wait_fast(fullC, 0);
#pragma unroll
  for (int q = 0; q < 4; q++) { trow[q] = lds128(sbase + 32768 + (tid + q * 256) * 16); me = absmax4(trow[q], me); }
  me = __reduce_max_sync(0xffffffffu, max(me & 0xffff, me >> 16));
  mw = __reduce_max_sync(0xffffffffu, max(mw & 0xffff, mw >> 16));
  uint32_t* sred = (uint32_t*)((char*)sm + 128000);
  if (lane == 0) sred[tid >> 5] = me | mw << 16;
  TS(3, 0);
  asm volatile("setmaxnreg.inc.sync.aligned.u32 160;");
  asm volatile("bar.sync 1,256;" ::: "memory");
  { uint32_t m = 0;
#pragma unroll
    for (int q = 0; q < 8; q++) m = __vmaxu2(m, sred[q]);
    m = __shfl_sync(0xffffffffu, m, 0);
    me = m & 0xffff; mw = m >> 16; }
  const float se = pow2_scale(me, 3), sW = pow2_scale(mw, -2);
  TS(3, 1);
  auto put_rows = [&](int q, bool on) {
    const uint4 t = trow[q];
    const uint4 hv = make_uint4(pack_h2(bf_lo(t.x) * se, bf_hi(t.x) * se), pack_h2(bf_lo(t.y) * se, bf_hi(t.y) * se),
                                pack_h2(bf_lo(t.z) * se, bf_hi(t.z) * se), pack_h2(bf_lo(t.w) * se, bf_hi(t.w) * se));
    if (on)
#pragma unroll
      for (int s = 0; s < 8; s++) sts128(sbase + (tid + q * 256) * 128 + ((s + lane) & 7) * 16, hv);
  };
#pragma unroll 1
  for (int it = 0; it < 3; it++) {
    const int hu = ((tid >> 5) * 3 + it) * 4, code = hu_code(min(hu + (lane >> 3), HU_N - 1)), ok = code >> 4, on = code & 15;
    uint32_t x[4], y[4];
    asm volatile("ldmatrix.sync.aligned.m8n8.x4.shared.b16 {%0,%1,%2,%3},[%4];" : "=r"(x[0]), "=r"(x[1]), "=r"(x[2]), "=r"(x[3])
                 : "r"(sbase + (on * 8 + (lane & (on == 12 ? 3 : 7))) * 208 + ok * 16) : "memory");
    asm volatile("ldmatrix.sync.aligned.m8n8.x4.trans.shared.b16 {%0,%1,%2,%3},[%4];" : "=r"(y[0]), "=r"(y[1]), "=r"(y[2]), "=r"(y[3])
                 : "r"(sbase + (ok * 8 + (lane & (ok == 12 ? 3 : 7))) * 208 + on * 16) : "memory");
    const uint32_t lo = __ballot_sync(0xffffffffu, ok > on), dg = __ballot_sync(0xffffffffu, ok >= on);
#pragma unroll
    for (int q = 0; q < 4; q++) {
      const float m0 = (lo >> (8 * q)) & 1 ? 0.f : sW, m1 = (dg >> (8 * q)) & 1 ? 0.f : sW;
      asm volatile("st.shared.u32 [%0],%1;" :: "r"(sbase + K1_W + (hu + q) * 128 + lane * 4),
                   "r"(pack_h2(fmaf(bf_lo(x[q]), m0, bf_lo(y[q]) * m1), fmaf(bf_hi(x[q]), m0, bf_hi(y[q]) * m1))) : "memory");
    }
  }
  put_rows(1, true); put_rows(2, tid < 88);
  TS(3, 2);
  asm volatile("fence.proxy.async.shared::cta;" ::: "memory");
  asm volatile("bar.sync 1,256;" ::: "memory");
  put_rows(0, true);
  uint32_t bf[HU_N - 2 * G_U];
#pragma unroll
  for (int q = 0; q < HU_N - 2 * G_U; q++) asm volatile("ld.shared.u32 %0,[%1];" : "=r"(bf[q]) : "r"(sbase + K1_W + (2 * G_U + q) * 128 + lane * 4));
  if (cta < 16 && tid == 0) g_unscale[cta] = make_float2(__uint_as_float(0x7f000000u - __float_as_uint(se)), __uint_as_float(0x7f000000u - __float_as_uint(sW)));
  TS(3, 3);
  const int px = range * 16 * 136;
  mbar_wait_fast(fullI, 0);
  {
    const uint32_t ib = sbase + 76800 + (tid >> 5) * 6400, p0 = ib + ((lane >> 3) & 1) * 400 + ((lane >> 4) * 8 + (lane & 7)) * 4;
    auto ld = [&](uint32_t ad) { uint32_t v; asm volatile("ld.shared.u32 %0,[%1];" : "=r"(v) : "r"(ad)); return v; };
    auto wd = [&](int t, int h) { return pk3(ld(p0 + t * 800 + h * 192), ld(p0 + t * 800 + h * 192 + 64), ld(p0 + t * 800 + h * 192 + 128)); };
#pragma unroll
    for (int q = 0; q < 4; q++) {
      iv[q] = make_uint4(wd(2 * q, 0), wd(2 * q, 1), wd(2 * q + 1, 0), wd(2 * q + 1, 1));
    }
    ix = ld(ib + g * 400 + 384 + r * 4) | ld(ib + (8 + g) * 400 + 384 + r * 4) << 16;
  }
  asm volatile("bar.sync 1,256;" ::: "memory");
  put_rows(2, tid >= 88); put_rows(3, tid + 768 < V_);
  asm volatile("bar.sync 1,256;" ::: "memory");
  TS(0, 1);
  uint32_t lc; asm volatile("add.u32 %0,%1,%2;" : "=r"(lc) : "r"((lane & 7) * 16), "r"(never));
  const uint64_t wdesc = (uint64_t)(((sbase + K1_W) & 0x3FFFF) >> 4) | ((uint64_t)(128 >> 4) << 16) | ((uint64_t)(256 >> 4) << 32);
  uint32_t a[2][6][4], d[2][26], ex[4] = {}, s[4] = {};
  float red[4] = {0.f, 0.f, 0.f, 0.f};
  auto ldsm = [&](uint32_t* o, uint32_t sh) {
    asm volatile("ldmatrix.sync.aligned.m8n8.x4.trans.shared.b16 {%0,%1,%2,%3},[%4];"
                 : "=r"(o[0]), "=r"(o[1]), "=r"(o[2]), "=r"(o[3]) : "r"(sbase + ((sh & 0x1ff80) | lc)));
  };
  auto gather = [&](int t, int hf) {
    const int x = t & 1;
    const uint4 v = iv[(t >> 1) & 3];
#pragma unroll
    for (int kb = 3 * hf; kb < 3 * hf + 3; kb++) {
      const uint32_t ww = x ? (kb < 3 ? v.z : v.w) : (kb < 3 ? v.x : v.y);
      ldsm(a[x][kb], kb % 3 == 0 ? ww : kb % 3 == 1 ? ww >> 10 : __funnelshift_l(ww, ww, 12));
    }
  };
  auto issue = [&](int x) {
    asm volatile("wgmma.fence.sync.aligned;" ::: "memory");
#pragma unroll
    for (int kb = 0; kb < 6; kb++) {
      if (kb < G_K0) wgmma_h<G_N0 * 8>(d[x] + G_O0 * 2, a[x][kb], wdesc + kb * G_N0 * 16, kb);
      if (kb < G_K1) wgmma_h<G_N1 * 8>(d[x] + G_O1 * 2, a[x][kb], wdesc + (G_U1 + kb * G_N1) * 16, kb);
      if (kb < G_K2) wgmma_h<32>(d[x] + G_O2 * 2, a[x][kb], wdesc + (G_U2 + kb * G_N2) * 16, kb);
    }
    asm volatile("wgmma.commit_group.sync.aligned;" ::: "memory");
  };
  auto hmma_part = [&](int t) {
    constexpr FragIdx FI = make_fi();
    const int x = t & 1;
#pragma unroll
    for (int o = 0; o < 13; o++) asm volatile("" : "+r"(d[x][o * 2]), "+r"(d[x][o * 2 + 1]) :: "memory");
#pragma unroll
    for (int kb = 0; kb < 6; kb++)
#pragma unroll
      for (int o = 2 * kb + 1; o < 13; o++)
        if (!unit_wg(kb, o)) mma16816h(d[x] + o * 2, a[x][kb], bf[FI.v[2 * kb][o]], bf[FI.v[2 * kb + 1][o]]);
#pragma unroll
    for (int q = 0; q < 6; q++) if (!unit_wg(q, 2 * q)) mma1688h(d[x] + q * 4, a[x][q][0], a[x][q][1], bf[FI.v[2 * q][2 * q]]);
    mma1688h(d[x] + 24, r < 2 ? ex[t & 3] : 0u, r < 2 ? 0u : ex[t & 3], bf[FI.v[12][12]]);
  };
  auto dot_part = [&](int t, int hf) {
    const int x = t & 1;
    if (hf == 0) {
      const uint32_t pe = hfma2(r < 2 ? d[x][24] : d[x][25], ex[t & 3], 0u);
      s[0] = r < 2 ? pe : 0u; s[1] = r < 2 ? 0u : pe; s[2] = s[3] = 0;
    }
#pragma unroll
    for (int q = 3 * hf; q < 3 * hf + 3; q++)
#pragma unroll
      for (int e = 0; e < 4; e++) s[e] = hfma2(d[x][q * 4 + e], a[x][q][e], s[e]);
  };
  const float* outp = g_partP + slice * B_ + range * 256;
  uint32_t oofs; asm volatile("add.u32 %0,%1,%2;" : "=r"(oofs) : "r"((r * 4 + ((lane >> 3) & 1) * 2 + (lane >> 4)) * 4), "r"(never));
  float k0 = 0.f, k1 = 0.f, x0 = 0.f, x1 = 0.f;
  auto red_stage = [&](int st, int grp) {
    const bool u16 = lane & 16, u8 = lane & 8;
    if (st == 0) {
      k0 = u16 ? red[2] : red[0]; x0 = __shfl_xor_sync(0xffffffffu, u16 ? red[0] : red[2], 16);
      k1 = u16 ? red[3] : red[1]; x1 = __shfl_xor_sync(0xffffffffu, u16 ? red[1] : red[3], 16);
      red[0] = red[1] = red[2] = red[3] = 0.f;
    }
    if (st == 1) { const float p0 = k0 + x0, p1 = k1 + x1; k0 = u8 ? p1 : p0; x0 = __shfl_xor_sync(0xffffffffu, u8 ? p0 : p1, 8); }
    if (st == 2) { k0 += x0; x0 = __shfl_xor_sync(0xffffffffu, k0, 4); }
    if (st == 3) asm volatile("st.global.f32 [%0],%1;" :: "l"((const char*)(outp + grp * 16) + oofs), "f"(k0 + x0) : "memory");
  };
  auto side = [&](bool first, int t, int prv, int cur, int nxt) {
    const int pn = PX_OFF + px + nxt * 136 + lane;
    if (!first) {
      if (t == 0) { iv[3] = ldtex(tex, PX_OFF + px + cur * 136 + lane + 96); iv[0] = ldtex(tex, pn); }
      if (t == 2) iv[1] = ldtex(tex, pn + 32);
      if (t < 4) red_stage(t, prv);
    } else if (t == 4) {
      TS(4, 2);
      mbar_wait_fast(pxRdy, 0);
      TS(4, 3);
      iv[0] = ldtex(tex, pn); iv[1] = ldtex(tex, pn + 32);
    }
    if (t == 4) { ix = ldtex(texX, (px + nxt * 136 + 128) * 4 + lane).x; iv[2] = ldtex(tex, pn + 64); }
  };
  auto group = [&](bool first, int prv, int cur, int nxt, int part) {
#pragma unroll
    for (int t = part ? 7 : 0; t < 8; t++) {
      if (!part) {
        if (first || t) SCHED_FENCE(never, t * 8);
        if (SV == 0) side(first, t, prv, cur, nxt);
        dot_part(t, 0);
        SCHED_FENCE(never, t * 8 + 1);
        if (t == 3) ldsm(ex, ix >> 9);
        if (t == 7) ldsm(ex, ix << 7);
        gather(t + 2, 0);
        dot_part(t, 1);
        if (SV == 1) side(first, t, prv, cur, nxt);
        if (HV) { s[0] = hadd2(s[0], s[2]); s[1] = hadd2(s[1], s[3]); }
        if (first || t < 7) SCHED_FENCE(never, t * 8 + 4);
        if (t == 7) break;
      }
      gather(t + 2, 1);
      if (SV == 2) side(first, t, prv, cur, nxt);
      asm volatile("wgmma.wait_group.sync.aligned 0;" ::: "memory");
      asm volatile("" : "+r"(d[(t & 1) ^ 1][0]) :: "memory");
      mma1688f(red, HV ? s[0] : hadd2(s[0], s[2]), HV ? s[1] : hadd2(s[1], s[3]), (g | (d[(t & 1) ^ 1][0] & never)) == t ? 0x3c003c00u : 0u);
      hmma_part(t + 1);
      issue(t & 1);
    }
  };
  gather(0, 0); gather(0, 1); issue(0); ldsm(ex, ix << 7); gather(1, 0); gather(1, 1);
  asm volatile("wgmma.wait_group.sync.aligned 0;" ::: "memory");
  hmma_part(0);
  SCHED_FENCE(never, 99);
  issue(1);
  group(true, 0, 0, 1, 0); group(true, 0, 0, 1, 1);
  TS(4, 1);
#pragma unroll 1
  for (int n = 1;; n++) {
    if ((n & 11) == 2) mbar_wait_fast(pxRdy + 8 + (n & 4) * 2, 0);
    asm volatile("st.volatile.shared.u32 [%0],%1;" :: "r"(progG), "r"(n) : "memory");
    group(false, n - 1, n, min(n + 1, 15), 0);
    if (n == 15) break;
    group(false, n - 1, n, min(n + 1, 15), 1);
  }
  asm volatile("wgmma.wait_group.sync.aligned 0;" ::: "memory");
  mma1688f(red, HV ? s[0] : hadd2(s[0], s[2]), HV ? s[1] : hadd2(s[1], s[3]), g == 7 ? 0x3c003c00u : 0u);
#pragma unroll
  for (int st = 0; st < 4; st++) red_stage(st, 15);
  TS(0, 2);
  asm volatile("barrier.cluster.wait.aligned;" ::: "memory");
  asm volatile("barrier.cluster.arrive.relaxed.aligned; barrier.cluster.wait.aligned;" ::: "memory");
}

constexpr int SM_U = 130048, SM_BAR = 128000, SM_J = SM_U + 98304, DEEP_SMEM = SM_J + 4096;

__global__ void __cluster_dims__(2, 1, 1) __launch_bounds__(TH + 128, 1)
k_deep(cudaTextureObject_t tex, const __nv_bfloat16* __restrict__ w2, const __nv_bfloat16* __restrict__ b2,
       __nv_bfloat16* __restrict__ out, int never) {
  extern __shared__ __align__(1024) uint4 sm[];
  constexpr int PF = 4, DEPTH = 4, NW = TH / 32;
  const int tid = threadIdx.x;
  const int c = blockIdx.x >> 1, half = blockIdx.x & 1;
  const uint32_t sbase = (uint32_t)__cvta_generic_to_shared(sm);
  const uint32_t fullL = sbase + SM_BAR, fullU = fullL + 8, emptyL = fullL + 16, emptyU = fullL + 24, barJ = fullL + 32;
  TS(1, 0);
  if (tid == 0) {
    mbar_init(fullL, 1); mbar_init(fullU, 1); mbar_init(emptyL, 2 * NW); mbar_init(emptyU, 2 * NW); mbar_init(barJ, 1);
    asm volatile("fence.mbarrier_init.release.cluster;" ::: "memory");
  }
  __syncwarp();
  const int wrp = __shfl_sync(0xffffffffu, tid >> 5, 0);
  const char* base = (const char*)g_scr;
  uint32_t oL = (PL_OFF + c * NC * 8000) * 16u + half * 64000, oS = (PS_OFF + c * NC * 2000) * 16u + half * 16000;
  asm volatile("barrier.cluster.arrive.relaxed.aligned; barrier.cluster.wait.aligned;" ::: "memory");
  if (wrp == NW) {
    asm volatile("fence.proxy.async.global;" ::: "memory");
    e_expect(fullU, 96000);
#pragma unroll
    for (int m = 0; m < 3; m++) e_mc(sbase + SM_U + m * 32032 + half * 16000, base + oS, 16000, fullU, m == 2 ? POL_EF : POL_N);
    e_expect(fullL, 128000);
  }
  TS(5, 1);
  if (wrp >= NW) {
    asm volatile("setmaxnreg.dec.sync.aligned.u32 24;");
    if (wrp == NW) {
      uint32_t oT = (PT_OFF + c * 10 * 1024) * 16u + half * 8000;
      auto warm = [&](uint32_t off, uint32_t hb) {
        asm volatile(ELECT "mbarrier.expect_tx.relaxed.cta.shared::cta.b64 [%0],%1;}" :: "r"(barJ), "r"(2 * hb) : "memory");
        e_g2s(sbase + SM_J, base + off, hb, barJ); e_g2s(sbase + SM_J, base + off + hb, hb, barJ);
      };
      mbar_wait(fullU, 0);
      e_mc(sbase + half * 64000, base + oL, 64000, fullL, POL_EF);
      warm(oT, 4000);
#pragma unroll 1
      for (int k = 0; k + 1 < NC; k++) {
        oL += 128000; oS += 32000; oT += 16384;
        mbar_wait(fullL, k & 1);
        const uint32_t t0 = clock();
        e_pf(base + oS, 16000);
        warm((IX_OFF + half * IXH + (k + 2) * 8192 + ((c + (c >> 4) * (2 * k + 1)) & (k + 2 < NC ? 15 : 3)) * 512) * 16u, 4096);
        mbar_wait(emptyU, k & 1);
        e_expect(fullU, 96000);
#pragma unroll 1
        for (int q = 0; q < 8; q++) {
          sleep_until(t0, q * PACE);
          e_pf(base + oL + q * 8000, 8000);
          if (q >= 2) e_mc(sbase + SM_U + ((q - 2) >> 1) * 32032 + half * 16000 + (q & 1) * 8000, base + oS + (q & 1) * 8000, 8000, fullU, q >= 6 ? POL_EF : POL_N);
        }
        warm(oT, 4000);
        e_expect(fullL, 128000);
        sleep_until(t0, RSV_T);
        unsigned long long now, slot = 0;
        asm volatile("mov.u64 %0,%globaltimer;" : "=l"(now));
        if ((tid & 31) == 0) { atomicMax(&g_slot, now + RSV_L); slot = atomicAdd(&g_slot, (unsigned long long)RSV); }
        slot = __shfl_sync(0xffffffffu, slot, 0);
        mbar_wait(emptyL, k & 1);
        for (int it = 0; it < 4000; it++) { asm volatile("mov.u64 %0,%globaltimer;" : "=l"(now)); if (now >= slot) break; }

        e_mc(sbase + half * 64000, base + oL, 64000, fullL, POL_EF);
      }
      mbar_wait(fullL, (NC - 1) & 1);
      mbar_wait(emptyU, (NC - 1) & 1);
      mbar_arrive_lane0(fullU);
      warm(oT + 16384, 4000);
      mbar_arrive_lane0(barJ); mbar_wait(barJ, 0);
    } else if (tid >= TH + 96) {
      if (tid < TH + 100) asm volatile("st.shared.u32 [%0],%1;" :: "r"(barJ + 32 + (tid & 3) * 4), "r"(((const uint32_t*)w2)[(c >> 2) * 16 + (tid & 3) * 4 + (c & 3)]) : "memory");
      asm volatile("bar.arrive 3,%0;" :: "n"(TH + 32) : "memory");
      asm volatile("griddepcontrol.wait;" ::: "memory");
      const int b = half * 8192 + c * 128 + (tid & 31) * 4;
      const float bias = __bfloat162float(b2[0]);
      float4 s = make_float4(bias, bias, bias, bias);
#pragma unroll 2
      for (int k = 0; k < 16; k++) {
        const float4 v = __ldcg((const float4*)(g_partP + k * B_ + b)); const float2 u = __ldcg(g_unscale + k);
        s.x = fmaf(v.x * u.x * u.x, u.y, s.x); s.y = fmaf(v.y * u.x * u.x, u.y, s.y); s.z = fmaf(v.z * u.x * u.x, u.y, s.z); s.w = fmaf(v.w * u.x * u.x, u.y, s.w);
      }
      asm volatile("red.global.add.v4.f32 [%0],{%1,%2,%3,%4};" :: "l"(g_acc + b), "f"(s.x), "f"(s.y), "f"(s.z), "f"(s.w) : "memory");
      asm volatile("bar.arrive 1,%0;" :: "n"(TH + 32) : "memory");
    }
    return;
  }
  asm volatile("setmaxnreg.inc.sync.aligned.u32 240;");
  const int lane = tid & 31;
  const int tbase = PT_OFF + c * 10 * 1024;
  const int ibase = IX_OFF + half * IXH + tid;
  const uint32_t lc = (tid & 7) << 4;
  uint4 acc[NS], wq[PF], x[DEPTH], y[YD], ye;
  uint32_t sw[NS] = {};
  auto sget = [&](int s) { return (s & 3) == 3 ? __byte_perm(__byte_perm(sw[s - 3], sw[s - 2], 0x0073), sw[s - 1], 0x0710) : sw[s]; };
  auto sa0 = [&](uint32_t v) { return sbase + SM_U + (((v << 5) & 0x1ffe0) | ((lc >> 2) & 16)); };
  uint32_t c1 = 0;
  auto sa1 = [&](uint32_t v) { return sbase + SM_U + (((v >> 7) & 0x1ffe0) | c1); };
  {
    uint4 i0[8];
#pragma unroll
    for (int q = 0; q < 8; q++) i0[q] = ldtex(tex, I0_OFF + (half * 8 + q) * TH + tid);
    auto wd = [&](int k) { return (k & 3) == 0 ? i0[k >> 2].x : (k & 3) == 1 ? i0[k >> 2].y : (k & 3) == 2 ? i0[k >> 2].z : i0[k >> 2].w; };
    TS(5, 2);
    mbar_wait_fast(fullU, 0);
#pragma unroll
    for (int i = 0; i < PF; i++) wq[i] = ldtex(tex, ibase + i * TH);
    TS(1, 1);
#pragma unroll
    for (int s = 0; s < NS; s++) acc[s] = add4(lds128(sbase + SM_U + (wd(s) & 0x1fff0)), lds128(sbase + SM_U + ((wd(s) >> 13) & 0x1fff0)));
    arrive_both(emptyU, lane);
    asm volatile("bar.sync 3,%0;" :: "n"(TH + 32) : "memory");
    TS(5, 3);
  }
#pragma unroll 1
  for (int k = 0; k < NC; k++) {
    const int ti = ibase + k * 8192;
    const int tb = tbase + k * 1024;
    const bool more = k + 1 < NC;
    TR(k * 4);
    mbar_wait_fast(fullL, k & 1);
    TR(k * 4 + 2);
    uint4 w, cc; uint32_t yc;
    constexpr int TL = NS * 8, TT = TL + NS * 2;
#pragma unroll
    for (int t = 0; t < TT + DEPTH; t += 2) {
      if (t == TL + DEPTH && !more) break;
      if (t >= DEPTH) {
        const int u = t - DEPTH;
        uint4 p = add4(x[u % DEPTH], x[(u + 1) % DEPTH]);
        if (u < TL) {
          const int s = u >> 3, j = u & 7;
          if (j == 0) {
            cc = s >= YD ? add4(y[s % YD], p) : p;
            if (s + YD < NS) y[s % YD] = ldtex(tex, tb | (yc & 1023));
          } else cc = add4(cc, p);
          if (j == 6) acc[s] = add4(acc[s], cc);
        } else {
          const int s = (u - TL) >> 1;
          acc[s] = add4(acc[s], p);
        }
      }
      if (t < TL) {
        const int s = t >> 3, j = t & 7;
        if (j == 0) {
          if (ye_of(s - YD) >= 0) acc[ye_of(s - YD) & 3] = add4(acc[ye_of(s - YD) & 3], ye);
          w = wq[s % PF];
          wq[s % PF] = ldtex(tex, ti + (s + PF) * TH);
          yc = __funnelshift_l(w.z, w.z, 5);
          if ((s & 3) != 3) asm volatile("add.u32 %0,%1,%2;" : "=r"(sw[s]) : "r"(w.w), "r"(never));
          if (ye_of(s) >= 0) ye = ldtex(tex, tb | w.w);
        }
#pragma unroll
        for (int jj = j; jj < j + 2; jj++) {
          const uint32_t ww = jj < 3 ? w.x : jj < 6 ? w.y : w.z;
          const uint32_t sh = jj % 3 == 0 ? ww : jj % 3 == 1 ? ww >> 10 : __funnelshift_l(ww, ww, 12);
          x[(t + jj - j) % DEPTH] = lds128(sbase + ((sh & 0x1ff80) | lc) + jj * 16 - 128);
        }
      } else if (t < TT) {
        const int s = (t - TL) >> 1;
        if (s == 0) {
          asm volatile("add.u32 %0,%1,%2;" : "=r"(c1) : "r"((~lc >> 2) & 16), "r"(never));
          arrive_both(emptyL, more ? lane : 9);
          TR(k * 4 + 3);
          mbar_wait_fast(fullU, (k + 1) & 1);
        }
        const uint32_t sv = sget(s);
        x[t % DEPTH] = lds128(sa0(sv));
        x[(t + 1) % DEPTH] = lds128(sa1(sv));
      } else if (t == TT) arrive_both(emptyU, lane);
      if ((t & 3) == 2) SCHED_FENCE(never, t);
    }
  }
  TS(1, 2);
  const uint4 w2v = lds128(barJ + 32);
  const uint32_t cell = sbase + SM_U + tid * 16;
  const int t9 = tbase + 9 * 1024;
  uint4 za[4], i9 = wq[0];
  auto fetch = [&](int q) {
    y[0] = ldtex(tex, t9 | i9.x); y[1] = ldtex(tex, t9 | i9.y); y[2] = ldtex(tex, t9 | i9.z); y[3] = ldtex(tex, t9 | i9.w);
    if (q) {
      i9 = ldtex(tex, ibase + NC * 8192 + min(q + 1, 7) * TH);
      const uint32_t ca = cell + (q > 6 ? 0 : q - 1) * 16384;
#pragma unroll
      for (int s = 0; s < 4; s++) za[s] = lds128(ca + s * 4096);
    }
  };
  fetch(0);
  i9 = wq[1];
#pragma unroll
  for (int s = 0; s < 4; s++) za[s] = acc[s];
#pragma unroll
  for (int s = 0; s < 24; s++) sts128(cell + s * 4096, acc[4 + s]);
  float hw[8];
  {
    const uint32_t ww[4] = {w2v.x, w2v.y, w2v.z, w2v.w};
#pragma unroll
    for (int k = 0; k < 8; k++) hw[k] = 0.5f * ((k & 1) ? bf_hi(ww[k >> 1]) : bf_lo(ww[k >> 1]));
  }
  float* outp = g_acc + half * 8192 + tid;
#pragma unroll 1
  for (int q = 0; q < NS / 4; q++) {
    uint4 z[4];
#pragma unroll
    for (int s = 0; s < 4; s++) z[s] = add4(za[s], y[s]);
    if (q == 1) {
#pragma unroll
      for (int s = 0; s < 4; s++) sts128(cell + s * 4096, acc[28 + s]);
    }
    if (q < 7) fetch(q + 1);
    SCHED_FENCE(never, 999);
#pragma unroll
    for (int s = 0; s < 4; s++) {
      const uint32_t a[4] = {z[s].x, z[s].y, z[s].z, z[s].w};
      float r0 = 0.f;
#pragma unroll
      for (int k = 0; k < 8; k++) {
        const float v = (k & 1) ? bf_hi(a[k >> 1]) : bf_lo(a[k >> 1]);
        const float u = v * fmaf(v * v, 0.7978845608028654f * 0.044715f, 0.7978845608028654f);
        float th; asm("tanh.approx.f32 %0,%1;" : "=f"(th) : "f"(u));
        r0 = fmaf(fmaf(v, th, v), hw[k], r0);
      }
      asm volatile("red.global.add.f32 [%0],%1;" :: "l"(outp + s * TH), "f"(r0) : "memory");
    }
    outp += 4 * TH;
  }
  TS(1, 3);
  asm volatile("bar.sync 1,%0;" :: "n"(TH + 32) : "memory");
  if (tid == 0) {
    unsigned old; asm volatile("atom.acq_rel.gpu.global.inc.u32 %0,[%1],63;" : "=r"(old) : "l"(&g_done[half * 32]) : "memory");
    asm volatile("st.shared.u32 [%0],%1;" :: "r"(barJ + 8), "r"(old) : "memory");
  }
  asm volatile("bar.sync 2,%0;" :: "n"(TH) : "memory");
  uint32_t old; asm volatile("ld.shared.u32 %0,[%1];" : "=r"(old) : "r"(barJ + 8));
  if (old == 63) {
    if (half == 0 && tid == 25) g_slot = 0;
    if (half == 0 && tid < 25) g_flag[tid * 32] = 0;
    float4 v[8];
#pragma unroll
    for (int q = 0; q < 8; q++) v[q] = __ldcg((const float4*)(g_acc + half * 8192) + q * TH + tid);
#pragma unroll
    for (int q = 0; q < 8; q++) ((uint2*)(out + half * 8192))[q * TH + tid] = make_uint2(pack_bf2(v[q].x, v[q].y), pack_bf2(v[q].z, v[q].w));
    TS(6, 2);
  }
}

}

extern "C" void kernel_launch(void* const* d_in, const int* in_sizes, int n_in, void* d_out, int out_size) {
  const int* idx = (const int*)d_in[0];
  const __nv_bfloat16* table = (const __nv_bfloat16*)d_in[1];
  const __nv_bfloat16* wp = (const __nv_bfloat16*)d_in[2];
  const __nv_bfloat16* w1 = (const __nv_bfloat16*)d_in[3];
  const __nv_bfloat16* b1 = (const __nv_bfloat16*)d_in[4];
  const __nv_bfloat16* w2 = (const __nv_bfloat16*)d_in[5];
  const __nv_bfloat16* b2 = (const __nv_bfloat16*)d_in[6];
  static cudaTextureObject_t texScr = 0, texX = 0;
  static CUtensorMap mapW, mapL, mapS, mapT, mapE, mapC;
  static const void *c_tab = nullptr, *c_w1 = nullptr;
  if (c_tab != table || c_w1 != w1) {
    c_tab = table; c_w1 = w1;
    char* scr = nullptr; cudaGetSymbolAddress((void**)&scr, g_scr);
    auto mk_tex = [](const void* p, size_t bytes, cudaChannelFormatDesc d) {
      cudaResourceDesc rd = {}; rd.resType = cudaResourceTypeLinear; rd.res.linear.devPtr = (void*)p; rd.res.linear.desc = d; rd.res.linear.sizeInBytes = bytes;
      cudaTextureDesc td = {}; td.readMode = cudaReadModeElementType;
      cudaTextureObject_t t = 0; cudaCreateTextureObject(&t, &rd, &td, nullptr); return t;
    };
    if (!texScr) {
      texScr = mk_tex(scr, (size_t)SCR_N * 16, cudaCreateChannelDesc<uint4>());
      texX = mk_tex(scr + (size_t)PX_OFF * 16, (size_t)(SCR_N - PX_OFF) * 16, cudaCreateChannelDesc<unsigned>());
    }
    typedef CUresult (*EncFn)(CUtensorMap*, CUtensorMapDataType, cuuint32_t, void*, const cuuint64_t*, const cuuint64_t*, const cuuint32_t*,
                              const cuuint32_t*, CUtensorMapInterleave, CUtensorMapSwizzle, CUtensorMapL2promotion, CUtensorMapFloatOOBfill);
    EncFn enc = nullptr; cudaDriverEntryPointQueryResult qr;
    cudaGetDriverEntryPoint("cuTensorMapEncodeTiled", (void**)&enc, cudaEnableDefault, &qr);
    const cuuint32_t ones[4] = {1, 1, 1, 1};
    auto mk = [&](CUtensorMap* m, CUtensorMapDataType dt, int rank, void* p, const cuuint64_t* dim, const cuuint64_t* str, const cuuint32_t* box, CUtensorMapSwizzle sw) {
      enc(m, dt, rank, p, dim, str, box, ones, CU_TENSOR_MAP_INTERLEAVE_NONE, sw, CU_TENSOR_MAP_L2_PROMOTION_NONE, CU_TENSOR_MAP_FLOAT_OOB_FILL_NONE);
    };
    { cuuint64_t dim[2] = {H_, F_ * D_}, str[1] = {H_ * 2}; cuuint32_t box[2] = {32, 256};
      mk(&mapW, CU_TENSOR_MAP_DATA_TYPE_BFLOAT16, 2, (void*)w1, dim, str, box, CU_TENSOR_MAP_SWIZZLE_64B); }
    { cuuint64_t dim[4] = {64, 64, V_, NC}, str[3] = {128000 * NC, 128, 128000}; cuuint32_t box[4] = {32, 4, 64, 1};
      mk(&mapL, CU_TENSOR_MAP_DATA_TYPE_BFLOAT16, 4, scr + (size_t)PL_OFF * 16, dim, str, box, CU_TENSOR_MAP_SWIZZLE_64B); }
    { cuuint64_t dim[4] = {64, 64, V_ / 4, NC}, str[3] = {32000 * NC, 128, 32000}; cuuint32_t box[4] = {64, 4, 16, 1};
      mk(&mapS, CU_TENSOR_MAP_DATA_TYPE_BFLOAT16, 4, scr + (size_t)PS_OFF * 16, dim, str, box, CU_TENSOR_MAP_SWIZZLE_128B); }
    { cuuint64_t dim[4] = {64, 64, V_ / 8, 10}, str[3] = {163840, 128, 16384}; cuuint32_t box[4] = {64, 4, 8, 2};
      mk(&mapT, CU_TENSOR_MAP_DATA_TYPE_BFLOAT16, 4, scr + (size_t)PT_OFF * 16, dim, str, box, CU_TENSOR_MAP_SWIZZLE_128B); }
    { cuuint64_t dim[2] = {D_, V_}, str[1] = {D_ * 2}; cuuint32_t box[2] = {64, 128};
      mk(&mapE, CU_TENSOR_MAP_DATA_TYPE_BFLOAT16, 2, (void*)table, dim, str, box, CU_TENSOR_MAP_SWIZZLE_128B);
      cuuint32_t box2[2] = {8, 256};
      mk(&mapC, CU_TENSOR_MAP_DATA_TYPE_BFLOAT16, 2, (void*)table, dim, str, box2, CU_TENSOR_MAP_SWIZZLE_NONE); }
    cudaFuncSetAttribute(k_deep, cudaFuncAttributeMaxDynamicSharedMemorySize, DEEP_SMEM);
    cudaFuncSetAttribute(k_tens, cudaFuncAttributeMaxDynamicSharedMemorySize, K1_SMEM);
  }
  k_tens<<<132, 512, K1_SMEM, cudaStreamPerThread>>>(mapW, mapL, mapS, mapT, mapE, mapC, texScr, texX, idx, table, wp, w1, b1, 0);
  cudaLaunchAttribute at[1];
  at[0].id = cudaLaunchAttributeProgrammaticStreamSerialization; at[0].val.programmaticStreamSerializationAllowed = 1;
  cudaLaunchConfig_t cfg = {};
  cfg.stream = cudaStreamPerThread; cfg.attrs = at;
  cfg.gridDim = 128; cfg.blockDim = TH + 128; cfg.dynamicSmemBytes = DEEP_SMEM; cfg.numAttrs = PDL;
  cudaLaunchKernelEx(&cfg, k_deep, texScr, w2, b2, (__nv_bfloat16*)d_out, 0);

}
```

```cpp
#include <cuda_runtime.h>
#include <cuda_bf16.h>
#include <cuda_fp16.h>
#include <stdint.h>
#include <cuda.h>

namespace {

constexpr int B_ = 16384, F_ = 100, D_ = 128, V_ = 1000, H_ = 512;
constexpr int NC = 9;
constexpr int PT_OFF = 0;
constexpr int PL_OFF = 64 * 10 * 1024;
constexpr int PS_OFF = PL_OFF + 64 * NC * 8000;
constexpr int IXH = NC * 8192 + 2048;
constexpr int IX_OFF = PS_OFF + 64 * NC * 2000;
constexpr int I0_OFF = IX_OFF + 2 * IXH;
constexpr int PX_OFF = I0_OFF + 4096;
constexpr int SCR_N = PX_OFF + 64 * 16 * 136;
static_assert(PX_OFF % 32 == 0, "");

__device__ __align__(1024) uint4 g_scr[SCR_N];
__device__ float g_acc[B_];
__device__ unsigned long long g_slot;
__device__ unsigned g_done[64];
__device__ float g_partP[16 * B_];
__device__ float2 g_unscale[16];
__device__ unsigned g_flag[25 * 32];

#define TS(k, i)
#define TR(slot)
#define PT(slot)

constexpr uint64_t POL_EF = 0x12F0000000000000ull, POL_N = 0x1000000000000000ull;
__device__ __forceinline__ uint32_t addbf2(uint32_t a, uint32_t b) { uint32_t r; asm("add.rn.bf16x2 %0,%1,%2;" : "=r"(r) : "r"(a), "r"(b)); return r; }
__device__ __forceinline__ uint4 add4(const uint4& a, const uint4& b) { return make_uint4(addbf2(a.x, b.x), addbf2(a.y, b.y), addbf2(a.z, b.z), addbf2(a.w, b.w)); }
__device__ __forceinline__ uint4 ldtex(cudaTextureObject_t t, int i) {
  uint4 v; asm volatile("tex.1d.v4.u32.s32 {%0,%1,%2,%3},[%4,{%5}];" : "=r"(v.x), "=r"(v.y), "=r"(v.z), "=r"(v.w) : "l"(t), "r"(i)); return v;
}
__device__ __forceinline__ uint4 lds128(uint32_t a) {
  uint4 v; asm volatile("ld.volatile.shared.v4.u32 {%0,%1,%2,%3},[%4];" : "=r"(v.x), "=r"(v.y), "=r"(v.z), "=r"(v.w) : "r"(a)); return v;
}
__device__ __forceinline__ void sts128(uint32_t a, const uint4& v) {
  asm volatile("st.shared.v4.u32 [%0],{%1,%2,%3,%4};" :: "r"(a), "r"(v.x), "r"(v.y), "r"(v.z), "r"(v.w) : "memory");
}
__device__ __forceinline__ void mbar_init(uint32_t bar, int n) { asm volatile("mbarrier.init.shared::cta.b64 [%0],%1;" :: "r"(bar), "r"(n) : "memory"); }
__device__ __forceinline__ void mbar_wait(uint32_t bar, uint32_t parity) {
  uint32_t ok; int it = 0;
  do { asm volatile("{.reg .pred p; mbarrier.try_wait.parity.shared::cta.b64 p,[%1],%2; selp.u32 %0,1,0,p;}" : "=r"(ok) : "r"(bar), "r"(parity) : "memory"); } while (!ok && ++it < (1 << 19));
}
__device__ __forceinline__ void mbar_expect(uint32_t bar, uint32_t bytes) { asm volatile("mbarrier.arrive.expect_tx.shared::cta.b64 _,[%0],%1;" :: "r"(bar), "r"(bytes) : "memory"); }
__device__ __forceinline__ void bulk_g2s(uint32_t dst, const void* src, uint32_t bytes, uint32_t bar) {
  asm volatile("cp.async.bulk.shared::cluster.global.mbarrier::complete_tx::bytes [%0],[%1],%2,[%3];" :: "r"(dst), "l"(src), "r"(bytes), "r"(bar) : "memory");
}
__device__ __forceinline__ void bulk_pf(const void* src, uint32_t bytes) { asm volatile("cp.async.bulk.prefetch.L2.global [%0],%1;" :: "l"(src), "r"(bytes) : "memory"); }
#define SCHED_FENCE(never, k) asm volatile("{.reg .pred p; setp.ne.u32 p,%0,%1; @p bra.uni SKIP_%=; pmevent 1; SKIP_%=: }" :: "r"(never), "r"(0x7fff0000 + (k)) : "memory")
#define SV 0
#define HV 1
#define PDL 1
#define RSV 23
#define RSV_L 550
#define RSV_T 7200
#define PACE 900
__device__ __forceinline__ int quad_of(int n) { return n < 23 ? n + 2 : n - 23; }
__device__ __forceinline__ void mbar_wait_fast(uint32_t bar, uint32_t parity) {
  asm volatile("{.reg .pred p; .reg .u32 n;\n"
               "mbarrier.try_wait.parity.shared::cta.b64 p,[%0],%1;\n"
               "@p bra DONE_%=;\n"
               "mov.u32 n,0;\n"
               "LOOP_%=: mbarrier.try_wait.parity.shared::cta.b64 p,[%0],%1;\n"
               "add.u32 n,n,1; setp.gt.or.u32 p,n,400000,p;\n"
               "@!p bra LOOP_%=;\n"
               "DONE_%=: }" :: "r"(bar), "r"(parity) : "memory");
}
__device__ __forceinline__ void sleep_until(uint32_t t0, uint32_t dt) { while ((uint32_t)clock() - t0 < dt) __nanosleep(40); }
__device__ __forceinline__ uint32_t s_mask(uint32_t v, int q) { return (1u << ((v + 3 - q) & 3)) | (16u << ((v + 3 + q) & 3)); }
__device__ __forceinline__ uint32_t s_cell(uint32_t v, int q, uint32_t m) {
  const int t = __ffs(~m) - 1;
  const int cp = t == 8 ? q >> 1 : ((t & 4 ? t - q : t + q) - v) & 3;
  return cp * 1001 + v;
}
__device__ __forceinline__ uint32_t pk3(uint32_t a, uint32_t b, uint32_t c) {
  const uint32_t w = c + (a << 12) + (b << 22); return __funnelshift_l(w, w, 27);
}
constexpr int TH = 256, NS = 8192 / TH, YD = 4;
__host__ __device__ constexpr int ye_of(int s) { return s == 3 ? 0 : s == 11 ? 1 : s == 19 ? 2 : s == 23 ? 3 : -1; }
template <int N> __device__ __forceinline__ void wgmma_h(uint32_t* d, const uint32_t* a, uint64_t desc, int acc);
template <> __device__ __forceinline__ void wgmma_h<40>(uint32_t* d, const uint32_t* a, uint64_t desc, int acc) {
  asm volatile("{.reg .pred p; setp.ne.s32 p,%15,0;\n"
    "wgmma.mma_async.sync.aligned.m64n40k16.f16.f16.f16 {%0,%1,%2,%3,%4,%5,%6,%7,%8,%9},{%10,%11,%12,%13},%14,p,1,1,0;}"
    : "+r"(d[0]),"+r"(d[1]),"+r"(d[2]),"+r"(d[3]),"+r"(d[4]),"+r"(d[5]),"+r"(d[6]),"+r"(d[7]),"+r"(d[8]),"+r"(d[9])
    : "r"(a[0]), "r"(a[1]), "r"(a[2]), "r"(a[3]), "l"(desc), "r"(acc));
}
template <> __device__ __forceinline__ void wgmma_h<32>(uint32_t* d, const uint32_t* a, uint64_t desc, int acc) {
  asm volatile("{.reg .pred p; setp.ne.s32 p,%13,0;\n"
    "wgmma.mma_async.sync.aligned.m64n32k16.f16.f16.f16 {%0,%1,%2,%3,%4,%5,%6,%7},{%8,%9,%10,%11},%12,p,1,1,0;}"
    : "+r"(d[0]),"+r"(d[1]),"+r"(d[2]),"+r"(d[3]),"+r"(d[4]),"+r"(d[5]),"+r"(d[6]),"+r"(d[7])
    : "r"(a[0]), "r"(a[1]), "r"(a[2]), "r"(a[3]), "l"(desc), "r"(acc));
}
__device__ __forceinline__ void wgmma_p(float* d, const uint32_t* a, uint64_t desc, int acc) {
  asm volatile("{.reg .pred p; setp.ne.s32 p,%69,0;\n"
    "wgmma.mma_async.sync.aligned.m64n128k16.f32.bf16.bf16 {%0,%1,%2,%3,%4,%5,%6,%7,%8,%9,%10,%11,%12,%13,%14,%15,%16,%17,%18,%19,%20,%21,%22,%23,%24,%25,%26,%27,%28,%29,%30,%31,%32,%33,%34,%35,%36,%37,%38,%39,%40,%41,%42,%43,%44,%45,%46,%47,%48,%49,%50,%51,%52,%53,%54,%55,%56,%57,%58,%59,%60,%61,%62,%63},{%64,%65,%66,%67},%68,p,1,1,1;}"
    : "+f"(d[0]),"+f"(d[1]),"+f"(d[2]),"+f"(d[3]),"+f"(d[4]),"+f"(d[5]),"+f"(d[6]),"+f"(d[7]),"+f"(d[8]),"+f"(d[9]),"+f"(d[10]),"+f"(d[11]),"+f"(d[12]),"+f"(d[13]),"+f"(d[14]),"+f"(d[15]),"+f"(d[16]),"+f"(d[17]),"+f"(d[18]),"+f"(d[19]),"+f"(d[20]),"+f"(d[21]),"+f"(d[22]),"+f"(d[23]),"+f"(d[24]),"+f"(d[25]),"+f"(d[26]),"+f"(d[27]),"+f"(d[28]),"+f"(d[29]),"+f"(d[30]),"+f"(d[31]),"+f"(d[32]),"+f"(d[33]),"+f"(d[34]),"+f"(d[35]),"+f"(d[36]),"+f"(d[37]),"+f"(d[38]),"+f"(d[39]),"+f"(d[40]),"+f"(d[41]),"+f"(d[42]),"+f"(d[43]),"+f"(d[44]),"+f"(d[45]),"+f"(d[46]),"+f"(d[47]),"+f"(d[48]),"+f"(d[49]),"+f"(d[50]),"+f"(d[51]),"+f"(d[52]),"+f"(d[53]),"+f"(d[54]),"+f"(d[55]),"+f"(d[56]),"+f"(d[57]),"+f"(d[58]),"+f"(d[59]),"+f"(d[60]),"+f"(d[61]),"+f"(d[62]),"+f"(d[63])
    : "r"(a[0]), "r"(a[1]), "r"(a[2]), "r"(a[3]), "l"(desc), "r"(acc));
}

__device__ __forceinline__ void mma16816h(uint32_t* c, const uint32_t* a, uint32_t b0, uint32_t b1) {
  asm("mma.sync.aligned.m16n8k16.row.col.f16.f16.f16.f16 {%0,%1},{%2,%3,%4,%5},{%6,%7},{%0,%1};"
      : "+r"(c[0]), "+r"(c[1]) : "r"(a[0]), "r"(a[1]), "r"(a[2]), "r"(a[3]), "r"(b0), "r"(b1));
}
__device__ __forceinline__ void mma1688h(uint32_t* c, uint32_t a0, uint32_t a1, uint32_t b) {
  asm("mma.sync.aligned.m16n8k8.row.col.f16.f16.f16.f16 {%0,%1},{%2,%3},{%4},{%0,%1};" : "+r"(c[0]), "+r"(c[1]) : "r"(a0), "r"(a1), "r"(b));
}
__device__ __forceinline__ void mma1688f(float* c, uint32_t a0, uint32_t a1, uint32_t b) {
  asm("mma.sync.aligned.m16n8k8.row.col.f32.f16.f16.f32 {%0,%1,%2,%3},{%4,%5},{%6},{%0,%1,%2,%3};"
      : "+f"(c[0]), "+f"(c[1]), "+f"(c[2]), "+f"(c[3]) : "r"(a0), "r"(a1), "r"(b));
}
__device__ __forceinline__ uint32_t hadd2(uint32_t a, uint32_t b) { uint32_t r; asm("add.rn.f16x2 %0,%1,%2;" : "=r"(r) : "r"(a), "r"(b)); return r; }
__device__ __forceinline__ uint32_t hfma2(uint32_t a, uint32_t b, uint32_t c) { uint32_t r; asm("fma.rn.f16x2 %0,%1,%2,%3;" : "=r"(r) : "r"(a), "r"(b), "r"(c)); return r; }
__device__ __forceinline__ uint32_t pack_bf2(float lo, float hi) { uint32_t r; asm("cvt.rn.bf16x2.f32 %0,%1,%2;" : "=r"(r) : "f"(hi), "f"(lo)); return r; }
__device__ __forceinline__ uint32_t pack_h2(float lo, float hi) { uint32_t r; asm("cvt.rn.f16x2.f32 %0,%1,%2;" : "=r"(r) : "f"(hi), "f"(lo)); return r; }
__device__ __forceinline__ float bf_lo(uint32_t w) { return __uint_as_float(w << 16); }
__device__ __forceinline__ float bf_hi(uint32_t w) { return __uint_as_float(w & 0xffff0000u); }
__device__ __forceinline__ uint32_t absmax4(const uint4& v, uint32_t m) {
  return __vmaxu2(__vmaxu2(__vmaxu2(v.x & 0x7fff7fffu, v.y & 0x7fff7fffu), __vmaxu2(v.z & 0x7fff7fffu, v.w & 0x7fff7fffu)), m);
}
__device__ __forceinline__ float pow2_scale(uint32_t mbits, int p) { return __uint_as_float((uint32_t)min(max(253 + p - (int)(mbits >> 7), 2), 252) << 23); }

constexpr int G_O0 = 8, G_O1 = 4, G_O2 = 0, G_N0 = 5, G_N1 = 4, G_N2 = 4, G_K0 = 5, G_K1 = 3, G_K2 = 1;
__host__ __device__ constexpr bool unit_wg(int kb, int on) {
  return (on >= G_O0 && on < G_O0 + G_N0 && kb < G_K0) || (on >= G_O1 && on < G_O1 + G_N1 && kb < G_K1) || (on >= G_O2 && on < G_O2 + G_N2 && kb < G_K2);
}
constexpr int G_U1 = G_N0 * G_K0, G_U2 = G_U1 + G_N1 * G_K1, G_U = G_U2 + G_N2 * G_K2;
constexpr int K1_B = 130048, K1_STG = K1_B + 2 * 32768, K1_W = K1_STG + 16384, K1_BAR = K1_W + 48 * 256, K1_SMEM = K1_BAR + 256 + 6400;
__host__ __device__ constexpr int frag_index(int ok, int on) {
  int n = 0;
  for (int k = 0; k < 13; k++) for (int o = k; o < 13; o++) { if (k == ok && o == on) return n; if (!unit_wg(k >> 1, o)) n++; }
  return n;
}
constexpr int HU_N = 2 * G_U + frag_index(99, 99);
static_assert(HU_N <= 96, "");
struct FragIdx { int v[13][13]; };
__host__ __device__ constexpr FragIdx make_fi() { FragIdx f = {}; for (int k = 0; k < 13; k++) for (int o = 0; o < 13; o++) f.v[k][o] = frag_index(k, o); return f; }
__host__ __device__ constexpr uint64_t frag_tab(int first) {
  uint64_t t = 0;
  for (int k = 0; k < 13; k++) for (int o = k; o < 13; o++)
    if (!unit_wg(k >> 1, o)) { const int n = frag_index(k, o) - first; if (n >= 0 && n < 8) t |= (uint64_t)(k << 4 | o) << (8 * n); }
  return t;
}
__device__ __forceinline__ int hu_code(int hu) {
  constexpr uint64_t T0 = frag_tab(0), T1 = frag_tab(8), T2 = frag_tab(16), T3 = frag_tab(24);
  const int u = hu >> 1, f = hu - 2 * G_U;
  if (f >= 0) return (int)((f < 8 ? T0 : f < 16 ? T1 : f < 24 ? T2 : T3) >> (8 * (f & 7))) & 255;
  const int u0 = u < G_U1 ? u : u < G_U2 ? u - G_U1 : u - G_U2;
  const int kb = u < G_U1 ? u0 / G_N0 : u < G_U2 ? u0 / G_N1 : u0 / 4, on = u < G_U1 ? G_O0 + u0 % G_N0 : u < G_U2 ? G_O1 + u0 % G_N1 : G_O2 + u0 % 4;
  return (2 * kb + (hu & 1)) << 4 | on;
}

__device__ __forceinline__ void flag_wait(const unsigned* f, unsigned n) {
  unsigned v; int it = 0;
  asm volatile("ld.acquire.gpu.global.u32 %0,[%1];" : "=r"(v) : "l"(f) : "memory");
  if (v < n) {
    do { __nanosleep(300); asm volatile("ld.relaxed.gpu.global.u32 %0,[%1];" : "=r"(v) : "l"(f) : "memory"); } while (v < n && ++it < (1 << 20));
    asm volatile("ld.acquire.gpu.global.u32 %0,[%1];" : "=r"(v) : "l"(f) : "memory");
  }
}
__device__ __forceinline__ void mbar_arrive(uint32_t bar) { asm volatile("mbarrier.arrive.shared::cta.b64 _,[%0];" :: "r"(bar) : "memory"); }
__device__ __forceinline__ void mbar_arrive_lane0(uint32_t bar) {
  asm volatile("{.reg .pred p; elect.sync _|p,0xffffffff; @p mbarrier.arrive.shared::cta.b64 _,[%0];}" :: "r"(bar) : "memory");
}

__device__ __forceinline__ void arrive_both(uint32_t bar, int lane) {
  asm volatile("{.reg .pred p; .reg .u32 a; setp.lt.u32 p,%1,2; mapa.shared::cluster.u32 a,%0,%1;\n"
               "@p mbarrier.arrive.shared::cluster.b64 _,[a];}" :: "r"(bar), "r"(lane) : "memory");
}
#define ELECT "{.reg .pred p; elect.sync _|p,0xffffffff; @p "
__device__ __forceinline__ void e_mc(uint32_t dst, const void* src, uint32_t bytes, uint32_t bar, uint64_t pol) {
  asm volatile(ELECT "cp.async.bulk.shared::cluster.global.mbarrier::complete_tx::bytes.multicast::cluster.L2::cache_hint [%0],[%1],%2,[%3],%4,%5;}"
               :: "r"(dst), "l"(src), "r"(bytes), "r"(bar), "h"((unsigned short)3), "l"(pol) : "memory");
}
__device__ __forceinline__ void e_g2s(uint32_t dst, const void* src, uint32_t bytes, uint32_t bar) {
  asm volatile(ELECT "cp.async.bulk.shared::cluster.global.mbarrier::complete_tx::bytes [%0],[%1],%2,[%3];}" :: "r"(dst), "l"(src), "r"(bytes), "r"(bar) : "memory");
}
__device__ __forceinline__ void e_pf(const void* src, uint32_t bytes) { asm volatile(ELECT "cp.async.bulk.prefetch.L2.global [%0],%1;}" :: "l"(src), "r"(bytes) : "memory"); }
__device__ __forceinline__ void e_expect(uint32_t bar, uint32_t bytes) { asm volatile(ELECT "mbarrier.arrive.expect_tx.shared::cta.b64 _,[%0],%1;}" :: "r"(bar), "r"(bytes) : "memory"); }
__device__ __forceinline__ void e_tma2d(uint32_t dst, const CUtensorMap* m, int x, int y, uint32_t bar) {
  asm volatile(ELECT "cp.async.bulk.tensor.2d.shared::cluster.global.mbarrier::complete_tx::bytes [%0],[%1,{%2,%3}],[%4];}" :: "r"(dst), "l"(m), "r"(x), "r"(y), "r"(bar) : "memory");
}

__device__ __forceinline__ void pack_role(const int* __restrict__ idx, uint32_t sbase, int pc) {
  constexpr int BUF = 32 * 3328;
  const int tid = threadIdx.x, lane = tid & 31, warp = tid >> 5;
  const uint32_t full = sbase + 2 * BUF, empty = full + 16;
  if (tid == 0) { mbar_init(full, 1); mbar_init(full + 8, 1); mbar_init(empty, 18); mbar_init(empty + 8, 18); asm volatile("fence.proxy.async.shared::cta;" ::: "memory"); }
  __syncthreads();
  auto chunk = [&](int s) { return s * 3200 + (s >> 2) * 288; };
  auto load = [&](int n) {
    const int blk = pc * 16 + n;
    if (lane == 0) mbar_expect(full + (n & 1) * 8, 32 * 3200);
    __syncwarp();
    bulk_g2s(sbase + (n & 1) * BUF + chunk(lane), idx + ((blk >> 5) * 8192 + lane * TH + (blk & 31) * 8) * F_, 3200, full + (n & 1) * 8);
  };
  if (warp == 0) { load(0); load(1); }
  const int l = lane & 7;
  uint32_t rot[8], inc[3];
#pragma unroll
  for (int jj = 0; jj < 8; jj++) rot[jj] = ((l + jj) & 7) * 4;
#pragma unroll
  for (int q = 0; q < 3; q++) inc[q] = (l + 3 * q < 8) << 12 | (l + 3 * q + 1 < 8) << 22 | (q < 2 && l + 3 * q + 2 < 8);
  int loaded = 2;
#pragma unroll 1
  for (int task = warp; task < 288; task += 16) {
    const int n = task / 18, q = (task % 18) * 4 + (lane >> 3), sq = q / 9, k = q % 9;
    if (warp == 0 && n + 1 == loaded && loaded < 16) { mbar_wait(empty + (loaded & 1) * 8, ((loaded >> 1) - 1) & 1); load(loaded); loaded++; }
    mbar_wait(full + (n & 1) * 8, (n >> 1) & 1);
    const uint32_t buf = sbase + (n & 1) * BUF + l * 400, row = buf + chunk(sq * 4);
    auto ld = [&](uint32_t ad) { uint32_t v; asm volatile("ld.shared.u32 %0,[%1];" : "=r"(v) : "r"(ad)); return v; };
    const int blk = pc * 16 + n, half = blk >> 5, col = (blk & 31) * 8 + l;
    const int ks = k == NC - 1 ? 0 : k + 1;
    uint32_t cw[4], sv[8], m[2] = {0, 0};
    { const uint32_t a0 = row + (72 + 2 * ks + (l >> 2)) * 4;
#pragma unroll
      for (int u = 0; u < 8; u++) { sv[u] = ld((a0 ^ ((u >> 2) * 4)) + (u & 3) * 3200); m[u >> 2] |= s_mask(sv[u], l & 3) << (8 * (u & 3)); } }
#pragma unroll
    for (int h = 0; h < 2; h++) { m[h] |= __shfl_xor_sync(0xffffffffu, m[h], 1); m[h] |= __shfl_xor_sync(0xffffffffu, m[h], 2); }
#pragma unroll
    for (int u = 0; u < 4; u++) cw[u] = s_cell(sv[u], l & 3, (m[0] >> (8 * u)) & 255) | s_cell(sv[4 + u], l & 3, (m[1] >> (8 * u)) & 255) << 12;
    if (k == NC - 1) {
      auto wide = [&](uint32_t w) { return (w & 0xfff) << 5 | (w >> 12) << 18 | (l & 4 ? 1u << 4 : 1u << 17); };
      g_scr[I0_OFF + (half * 8 + sq) * TH + col] = make_uint4(wide(cw[0]), wide(cw[1]), wide(cw[2]), wide(cw[3]));
      g_scr[IX_OFF + half * IXH + NC * 8192 + sq * TH + col] = make_uint4(ld(row + 396), ld(row + 3596), ld(row + 6796), ld(row + 9996));
      cw[0] = cw[1] = cw[2] = cw[3] = 0;
    }
    const uint32_t ax = buf + chunk(min(sq + 1, 7) * 4) + (90 + k) * 4;
    const uint32_t yev = ld(buf + ((0x3210 >> (sq * 2 + (sq == 5) * 2)) & 3) * 3200 + (90 + k) * 4);
    uint4* dst = g_scr + IX_OFF + half * IXH + (k * NS + sq * 4) * TH + col;
#pragma unroll
    for (int u = 0; u < 4; u++) {
      uint32_t e[8];
#pragma unroll
      for (int jj = 0; jj < 8; jj++) e[jj] = ld(row + k * 32 + rot[jj] + u * 3200);
      dst[u * TH] = make_uint4(pk3(e[0], e[1], e[2] + inc[0]), pk3(e[3], e[4], e[5] + inc[1]), pk3(e[6], e[7], ld(ax + u * 3200) + inc[2]),
                               u < 3 ? __byte_perm(cw[u], cw[3], 0x4210 + (u << 12)) : yev);
    }
    mbar_arrive_lane0(empty + (n & 1) * 8);
  }
}

__global__ void __cluster_dims__(2, 1, 1) __launch_bounds__(512, 1)
k_tens(const __grid_constant__ CUtensorMap mapW, const __grid_constant__ CUtensorMap mapL, const __grid_constant__ CUtensorMap mapS,
       const __grid_constant__ CUtensorMap mapT, const __grid_constant__ CUtensorMap mapE, const __grid_constant__ CUtensorMap mapC, cudaTextureObject_t tex, cudaTextureObject_t texX,
       const int* __restrict__ idx, const __nv_bfloat16* __restrict__ table, const __nv_bfloat16* __restrict__ wp, const __nv_bfloat16* __restrict__ w1,
       const __nv_bfloat16* __restrict__ b1, int never) {
  extern __shared__ __align__(1024) uint4 sm[];
  const int tid = threadIdx.x, lane = tid & 31, cta = blockIdx.x;
  const uint32_t sbase = (uint32_t)__cvta_generic_to_shared(sm);
  const int g = lane >> 2, r = lane & 3;
  TS(0, 0);
  if (cta >= 128) {
    pack_role(idx, sbase, cta - 128);
    __syncthreads();
    if (tid == 0) {
      asm volatile("fence.acq_rel.gpu; griddepcontrol.launch_dependents;" ::: "memory");
      asm volatile("red.relaxed.gpu.global.add.u32 [%0],1;" :: "l"(&g_flag[24 * 32]) : "memory");
    }
    __syncwarp();
    TS(2, 1);
    asm volatile("barrier.cluster.arrive.relaxed.aligned; barrier.cluster.wait.aligned;" ::: "memory");
    return;
  }
  const uint32_t fullB = sbase + K1_BAR, emptyB = fullB + 24, fullE = fullB + 48, fullC = fullB + 56, fullI = fullB + 64, pxRdy = fullB + 72, fullS = fullB + 96, emptyS = fullB + 104, pkDone = fullB + 112, pkFull = fullB + 136, progG = fullB + 168;
  const int rb = cta & 7, hc = cta >> 3;
  if (__shfl_sync(0xffffffffu, tid >> 5, 0) == 12) {
    if (lane == 0) {
#pragma unroll
      for (int q = 0; q < 19; q++) if (q != 2 && q != 5) mbar_init(fullB + q * 8, q == 3 || q == 4 ? 8 : q == 12 ? 4 : q >= 14 && q < 17 ? 2 : 1);
      asm volatile("st.shared.u32 [%0],%1;" :: "r"(progG), "r"(0) : "memory");
    }
    asm volatile("fence.mbarrier_init.release.cluster; fence.proxy.async.shared::cta;" ::: "memory");
    __syncwarp();
    e_expect(fullC, 16384);
#pragma unroll
    for (int q = 0; q < 4; q++) e_tma2d(sbase + 32768 + q * 4096, &mapC, (cta & 15) * 8, q * 256, fullC);
    e_expect(fullE, 32768);
#pragma unroll
    for (int q = 0; q < 2; q++) e_tma2d(sbase + K1_B + 32768 + q * 16384, &mapE, q * 64, rb * 128, fullE);
    asm volatile("bar.arrive 2,512;" ::: "memory");
  }
  asm volatile("barrier.cluster.arrive.relaxed.aligned;" ::: "memory");
  if (tid >= 384) {
    asm volatile("setmaxnreg.dec.sync.aligned.u32 32;");
    if (tid < 416) {
      asm volatile("barrier.cluster.wait.aligned;" ::: "memory");
      if (tid == 384) {
#pragma unroll 1
        for (int n = 0; n < 25; n++) {
          const int st = n & 1, q = quad_of(n);
          if (n == 1) {
            mbar_expect(fullI, 51200);
#pragma unroll 1
            for (int u = 0; u < 8; u++) bulk_g2s(sbase + 76800 + u * 6400, idx + ((cta >> 4) * 8 + u) * 256 * F_, 6400, fullI);
          }
          mbar_wait(emptyB + st * 8, (((n + 1) >> 1) & 1) ^ 1);
          mbar_expect(fullB + st * 8, 32768);
          asm volatile("cp.async.bulk.tensor.2d.shared::cluster.global.mbarrier::complete_tx::bytes.multicast::cluster [%0],[%1,{%2,%3}],[%4],%5;"
                       :: "r"(sbase + K1_B + st * 32768 + (cta & 1) * 16384), "l"(&mapW), "r"(hc * 32), "r"(q * 512 + (cta & 1) * 256),
                          "r"(fullB + st * 8), "h"((unsigned short)3) : "memory");
          if (n + 1 < 25) bulk_pf(w1 + quad_of(n + 1) * 262144 + cta * 2048, 4096);
        }
      }
    } else if (tid < 448) {
      ((float4*)g_acc)[cta * 32 + lane] = make_float4(0.f, 0.f, 0.f, 0.f);
      asm volatile("bar.sync 2,512;" ::: "memory");
      __syncwarp();
      if (tid == 416) {
        int pub = 0;
#pragma unroll 1
        for (int n = 0; n < 50; n++) {
          const int quad = quad_of(n >> 1), mt = n & 1, v0 = rb * 128 + mt * 64;
          const uint32_t stg = sbase + K1_STG;
          if (pub < 3) {
            uint32_t ok = 1;
            if (pub == 0 || n == 49) mbar_wait(pkDone + pub * 8, 0);
            else asm volatile("{.reg .pred p; mbarrier.test_wait.parity.shared::cta.b64 p,[%1],0; selp.u32 %0,1,0,p;}" : "=r"(ok) : "r"(pkDone + pub * 8) : "memory");
            if (ok) {
              asm volatile("cp.async.bulk.wait_group 0;" ::: "memory");
              asm volatile("red.release.gpu.global.add.u32 [%0],1;" :: "l"(&g_flag[((cta >> 4) * 3 + pub) * 32]) : "memory");
              pub++;
              if (n == 49) { n--; continue; }
            }
          }
          mbar_wait(fullS, n & 1);
          asm volatile("fence.proxy.async.shared::cta;" ::: "memory");
          if (quad < 18) {
            asm volatile("cp.async.bulk.tensor.4d.global.shared::cta.bulk_group.L2::cache_hint [%0,{%1,%2,%3,%4}],[%5],%6;"
                         :: "l"(&mapL), "r"((quad & 1) * 32), "r"(hc * 4), "r"(v0), "r"(quad >> 1), "r"(stg), "l"(POL_EF) : "memory");
          } else {
#pragma unroll 1
            for (int hh = 0; hh < 2; hh++) {
              const int pq = quad * 2 + hh;
              asm volatile("cp.async.bulk.tensor.4d.global.shared::cta.bulk_group.L2::cache_hint [%0,{%1,%2,%3,%4}],[%5],%6;"
                         :: "l"(pq < 45 ? &mapS : &mapT), "r"(0), "r"(hc * 4), "r"(v0 >> (pq < 45 ? 2 : 3)), "r"(pq < 45 ? pq - 36 : (pq - 45) * 2), "r"(stg + hh * 8192), "l"(POL_EF) : "memory");
            }
          }
          asm volatile("cp.async.bulk.commit_group;" ::: "memory");
          asm volatile("cp.async.bulk.wait_group.read 0;" ::: "memory");
          mbar_arrive(emptyS);
        }
        asm volatile("cp.async.bulk.wait_group 0;" ::: "memory");
        asm volatile("fence.proxy.async.global;" ::: "memory");
        asm volatile("fence.acq_rel.gpu; griddepcontrol.launch_dependents;" ::: "memory");
        asm volatile("red.relaxed.gpu.global.add.u32 [%0],1;" :: "l"(&g_flag[24 * 32]) : "memory");
        flag_wait(&g_flag[24 * 32], 132);
        asm volatile("fence.proxy.async.global;" ::: "memory");
        const char* base = (const char*)g_scr;
        const int c = cta >> 1, half = cta & 1, ch = (c + (c >> 4) * 5) & 15;
        bulk_pf(base + (PS_OFF + c * NC * 2000) * 16u + half * 16000, 16000);
        bulk_pf(base + (PT_OFF + c * 10 * 1024) * 16u + half * 8000, 8000);
        mbar_expect(fullE, 18432);
        bulk_g2s(sbase + K1_B, base + (I0_OFF + half * 2048 + ch * 128) * 16u, 2048, fullE);
        bulk_g2s(sbase + K1_B + 2048, base + (IX_OFF + half * IXH + ch * 512) * 16u, 8192, fullE);
        bulk_g2s(sbase + K1_B + 10240, base + (IX_OFF + half * IXH + 8192 + ch * 512) * 16u, 8192, fullE);
        mbar_wait(fullE, 1);
      }
    } else {
      const int pw = (tid >> 5) & 1, rg = (cta >> 4) * 8 + ((cta & 15) >> 1), hf = cta & 1;
      const int* ip = idx + (rg * 256 + hf * 8) * F_;
      asm volatile("bar.sync 2,512;" ::: "memory");
      const uint32_t buf = sbase + K1_BAR + 256 + pw * 3200, bar = pkFull + pw * 8;
      const unsigned* fl = &g_flag[(cta >> 4) * 96];
      int batch = 0, rel = pw ? 3 : 0;
#pragma unroll 1
      for (int n = 1 + pw; n < 16; n += 2) {
        if (lane == 0) { mbar_expect(bar, 3200); bulk_g2s(buf, ip + n * 16 * F_, 3200, bar); if (n + 2 < 16) bulk_pf(ip + (n + 2) * 16 * F_, 3200); }
        uint32_t ok; int it = 0;
        do {
          if (rel < batch) {
            unsigned v; asm volatile("ld.relaxed.gpu.global.u32 %0,[%1];" : "=r"(v) : "l"(fl + rel * 32) : "memory");
            if (__all_sync(0xffffffffu, v >= 16)) { flag_wait(fl + rel * 32, 16); __syncwarp(); mbar_arrive_lane0(pxRdy + rel * 8); rel++; }
          }
          asm volatile("{.reg .pred p; mbarrier.test_wait.parity.shared::cta.b64 p,[%1],%2; selp.u32 %0,1,0,p;}" : "=r"(ok) : "r"(bar), "r"(((n - 1) >> 1) & 1) : "memory");
          ok = __all_sync(0xffffffffu, ok);
          if (!ok) __nanosleep(100);
        } while (!ok && ++it < (1 << 20));
        auto ld = [&](uint32_t ad) { uint32_t v; asm volatile("ld.shared.u32 %0,[%1];" : "=r"(v) : "r"(ad)); return v; };
        const uint32_t p0 = buf + ((lane >> 3) & 1) * 400 + ((lane >> 4) * 8 + (lane & 7)) * 4;
        auto wd = [&](int t, int h) { return pk3(ld(p0 + t * 800 + h * 192), ld(p0 + t * 800 + h * 192 + 64), ld(p0 + t * 800 + h * 192 + 128)); };
        uint4* dst = g_scr + PX_OFF + (rg * 16 + n) * 136;
        ((unsigned short*)(dst + 128))[lane * 2 + hf] = ld(buf + g * 400 + 384 + r * 4);
#pragma unroll
        for (int q = 0; q < 2; q++) dst[(hf * 2 + q) * 32 + lane] = make_uint4(wd(2 * q, 0), wd(2 * q, 1), wd(2 * q + 1, 0), wd(2 * q + 1, 1));
        __syncwarp();
        if (n <= 2 || n == 5 || n == 6 || n >= 14) { mbar_arrive_lane0(pkDone + batch * 8); batch++; }
      }
      for (; rel < 3; rel++) { flag_wait(fl + rel * 32, 16); __syncwarp(); mbar_arrive_lane0(pxRdy + rel * 8); }
      if (lane == 0) {
        mbar_wait(pxRdy + 16, 0);
        asm volatile("fence.proxy.async.global;" ::: "memory");
        const char* src = (const char*)(g_scr + PX_OFF + ((cta >> 4) * 8 + ((cta >> 1) & 3) * 2 + pw) * 16 * 136);
        int ph = pw;
#pragma unroll 1
        for (int n = 5; n < 16; n++) {
          uint32_t cur; int it = 0;
          do { asm volatile("ld.volatile.shared.u32 %0,[%1];" : "=r"(cur) : "r"(progG)); if (cur + 2 < n) __nanosleep(400); } while (cur + 2 < n && ++it < (1 << 16));
          if (cur + 1 >= n) continue;
          mbar_expect(bar, 2176); bulk_g2s(buf, src + n * 2176, 2176, bar);
          mbar_wait(bar, ph); ph ^= 1;
        }
      }
    }
    return;
  }
  if (tid >= 256) {
    asm volatile("setmaxnreg.inc.sync.aligned.u32 160;");
    const int w = (tid >> 5) & 3;
    const int srow = w * 16 + ((lane & 15) ^ ((lane & 1) << 2)), sc = lane >> 4;
    uint32_t a[2][8][4];
    asm volatile("bar.sync 2,512;" ::: "memory");
    mbar_wait_fast(fullE, 0);
#pragma unroll
    for (int mt = 0; mt < 2; mt++)
#pragma unroll
      for (int ks = 0; ks < 8; ks++)
        asm volatile("ldmatrix.sync.aligned.m8n8.x4.shared.b16 {%0,%1,%2,%3},[%4];"
                     : "=r"(a[mt][ks][0]), "=r"(a[mt][ks][1]), "=r"(a[mt][ks][2]), "=r"(a[mt][ks][3])
                     : "r"(sbase + K1_B + 32768 + (ks >> 2) * 16384 + (mt * 64 + srow) * 128 + ((((ks & 3) * 2 + sc) ^ (srow & 7)) * 16)) : "memory");
    asm volatile("barrier.cluster.wait.aligned;" ::: "memory");
    arrive_both(emptyB + 8, lane);
    const int v = w * 16 + (g ^ ((g & 1) << 2));
    const uint32_t baseL = v * 256 + r * 64 + ((v & 1) * 2 + (r >> 1)) * 16, baseS = (v >> 2) * 512 + r * 128 + (((v & 3) * 2) ^ ((v & 4) + r)) * 16,
                   baseT = (v >> 3) * 512 + r * 128 + ((v & 7) ^ r) * 16;
    const uint64_t desc0 = (uint64_t)(((sbase + K1_B) & 0x3FFFF) >> 4) | ((uint64_t)(8192 >> 4) << 16) | ((uint64_t)(512 >> 4) << 32) | (2ull << 62);
#pragma unroll 1
    for (int qn = 0; qn < 25; qn++) {
      const int quad = quad_of(qn), st = qn & 1;
      const bool isL = quad < 18;
      PT(qn * 16);
      mbar_wait_fast(fullB + st * 8, (qn >> 1) & 1);
#pragma unroll
      for (int mt = 0; mt < 2; mt++) {
        float d[64];
        PT(qn * 16 + mt * 4 + 1);
        asm volatile("wgmma.fence.sync.aligned;" ::: "memory");
#pragma unroll
        for (int ks = 0; ks < 8; ks++) wgmma_p(d, a[mt][ks], desc0 + st * 2048 + ks * 64, ks);
        asm volatile("wgmma.commit_group.sync.aligned;" ::: "memory");
        mbar_wait_fast(emptyS, mt ^ 1);
        PT(qn * 16 + mt * 4 + 2);
        asm volatile("wgmma.wait_group.sync.aligned 0;" ::: "memory");
#pragma unroll
        for (int q = 0; q < 16; q++) asm volatile("" : "+f"(d[q * 4]), "+f"(d[q * 4 + 1]), "+f"(d[q * 4 + 2]), "+f"(d[q * 4 + 3]) :: "memory");
        PT(qn * 16 + mt * 4 + 3);
        if (mt) arrive_both(emptyB + st * 8, qn < 23 ? lane : 9);
        if (quad == 24) {
#pragma unroll
          for (int cq = 0; cq < 4; cq++) {
            const uint32_t bw = __ldg((const uint32_t*)(b1 + hc * 32 + cq * 8) + r);
#pragma unroll
            for (int e = 0; e < 4; e++) d[48 + cq * 4 + e] += (e & 1) ? bf_hi(bw) : bf_lo(bw);
          }
        }
#pragma unroll
        for (int h = 0; h < 2; h++) {
          const bool isS = quad * 2 + h < 45;
          const uint32_t base = (isL ? baseL ^ (h * 32) : (isS ? baseS : baseT) ^ (h * 8192)), xj = isS ? 16 : 4096, xr = isL ? 2048 : isS ? 1024 : 576;
#pragma unroll
          for (int e4 = 0; e4 < 4; e4++) {
            const float* e = d + h * 32 + (e4 >> 1) * 16 + (e4 & 1) * 2;
            sts128(sbase + K1_STG + (base ^ ((e4 >> 1) * xj) ^ ((e4 & 1) * xr)),
                   make_uint4(pack_bf2(e[0], e[1]), pack_bf2(e[4], e[5]), pack_bf2(e[8], e[9]), pack_bf2(e[12], e[13])));
          }
        }
        __syncwarp();
        mbar_arrive_lane0(fullS);
        if (!mt) PT(qn * 16 + 4);
      }
      PT(qn * 16 + 8);
    }
    return;
  }
  const int slice = cta & 15;
  const int range = (cta >> 4) * 8 + __shfl_sync(0xffffffffu, tid >> 5, 0);
  uint4 iv[4], trow[4]; uint32_t ix;
  uint2 wrow[10];
#pragma unroll
  for (int q = 0; q < 10; q++) asm volatile("ld.global.nc.v2.u32 {%0,%1},[%2];" : "=r"(wrow[q].x), "=r"(wrow[q].y) : "l"((const uint2*)wp + min(tid + q * 256, 2499)));
  asm volatile("bar.sync 2,512;" ::: "memory");
  uint32_t me = 0, mw = 0;
#pragma unroll
  for (int q = 0; q < 10; q++) {
    mw = __vmaxu2(__vmaxu2(wrow[q].x & 0x7fff7fffu, wrow[q].y & 0x7fff7fffu), mw);
    const int e = min(tid + q * 256, 2499), row = e / 25;
    asm volatile("st.shared.v2.u32 [%0],{%1,%2};" :: "r"(sbase + (e + row) * 8), "r"(wrow[q].x), "r"(wrow[q].y) : "memory");
    if (e - row * 25 == 24) asm volatile("st.shared.v2.u32 [%0],{%1,%2};" :: "r"(sbase + (e + row) * 8 + 8), "r"(wrow[q].x), "r"(wrow[q].y) : "memory");
  }
  mbar_wait_fast(fullC, 0);
#pragma unroll
  for (int q = 0; q < 4; q++) { trow[q] = lds128(sbase + 32768 + (tid + q * 256) * 16); me = absmax4(trow[q], me); }
  me = __reduce_max_sync(0xffffffffu, max(me & 0xffff, me >> 16));
  mw = __reduce_max_sync(0xffffffffu, max(mw & 0xffff, mw >> 16));
  uint32_t* sred = (uint32_t*)((char*)sm + 128000);
  if (lane == 0) sred[tid >> 5] = me | mw << 16;
  TS(3, 0);
  asm volatile("setmaxnreg.inc.sync.aligned.u32 160;");
  asm volatile("bar.sync 1,256;" ::: "memory");
  { uint32_t m = 0;
#pragma unroll
    for (int q = 0; q < 8; q++) m = __vmaxu2(m, sred[q]);
    m = __shfl_sync(0xffffffffu, m, 0);
    me = m & 0xffff; mw = m >> 16; }
  const float se = pow2_scale(me, 3), sW = pow2_scale(mw, -2);
  TS(3, 1);
  auto put_rows = [&](int q, bool on) {
    const uint4 t = trow[q];
    const uint4 hv = make_uint4(pack_h2(bf_lo(t.x) * se, bf_hi(t.x) * se), pack_h2(bf_lo(t.y) * se, bf_hi(t.y) * se),
                                pack_h2(bf_lo(t.z) * se, bf_hi(t.z) * se), pack_h2(bf_lo(t.w) * se, bf_hi(t.w) * se));
    if (on)
#pragma unroll
      for (int s = 0; s < 8; s++) sts128(sbase + (tid + q * 256) * 128 + ((s + lane) & 7) * 16, hv);
  };
#pragma unroll 1
  for (int it = 0; it < 3; it++) {
    const int hu = ((tid >> 5) * 3 + it) * 4, code = hu_code(min(hu + (lane >> 3), HU_N - 1)), ok = code >> 4, on = code & 15;
    uint32_t x[4], y[4];
    asm volatile("ldmatrix.sync.aligned.m8n8.x4.shared.b16 {%0,%1,%2,%3},[%4];" : "=r"(x[0]), "=r"(x[1]), "=r"(x[2]), "=r"(x[3])
                 : "r"(sbase + (on * 8 + (lane & (on == 12 ? 3 : 7))) * 208 + ok * 16) : "memory");
    asm volatile("ldmatrix.sync.aligned.m8n8.x4.trans.shared.b16 {%0,%1,%2,%3},[%4];" : "=r"(y[0]), "=r"(y[1]), "=r"(y[2]), "=r"(y[3])
                 : "r"(sbase + (ok * 8 + (lane & (ok == 12 ? 3 : 7))) * 208 + on * 16) : "memory");
    const uint32_t lo = __ballot_sync(0xffffffffu, ok > on), dg = __ballot_sync(0xffffffffu, ok >= on);
#pragma unroll
    for (int q = 0; q < 4; q++) {
      const float m0 = (lo >> (8 * q)) & 1 ? 0.f : sW, m1 = (dg >> (8 * q)) & 1 ? 0.f : sW;
      asm volatile("st.shared.u32 [%0],%1;" :: "r"(sbase + K1_W + (hu + q) * 128 + lane * 4),
                   "r"(pack_h2(fmaf(bf_lo(x[q]), m0, bf_lo(y[q]) * m1), fmaf(bf_hi(x[q]), m0, bf_hi(y[q]) * m1))) : "memory");
    }
  }
  put_rows(1, true); put_rows(2, tid < 88);
  TS(3, 2);
  asm volatile("fence.proxy.async.shared::cta;" ::: "memory");
  asm volatile("bar.sync 1,256;" ::: "memory");
  put_rows(0, true);
  uint32_t bf[HU_N - 2 * G_U];
#pragma unroll
  for (int q = 0; q < HU_N - 2 * G_U; q++) asm volatile("ld.shared.u32 %0,[%1];" : "=r"(bf[q]) : "r"(sbase + K1_W + (2 * G_U + q) * 128 + lane * 4));
  if (cta < 16 && tid == 0) g_unscale[cta] = make_float2(__uint_as_float(0x7f000000u - __float_as_uint(se)), __uint_as_float(0x7f000000u - __float_as_uint(sW)));
  TS(3, 3);
  const int px = range * 16 * 136;
  mbar_wait_fast(fullI, 0);
  {
    const uint32_t ib = sbase + 76800 + (tid >> 5) * 6400, p0 = ib + ((lane >> 3) & 1) * 400 + ((lane >> 4) * 8 + (lane & 7)) * 4;
    auto ld = [&](uint32_t ad) { uint32_t v; asm volatile("ld.shared.u32 %0,[%1];" : "=r"(v) : "r"(ad)); return v; };
    auto wd = [&](int t, int h) { return pk3(ld(p0 + t * 800 + h * 192), ld(p0 + t * 800 + h * 192 + 64), ld(p0 + t * 800 + h * 192 + 128)); };
#pragma unroll
    for (int q = 0; q < 4; q++) {
      iv[q] = make_uint4(wd(2 * q, 0), wd(2 * q, 1), wd(2 * q + 1, 0), wd(2 * q + 1, 1));
    }
    ix = ld(ib + g * 400 + 384 + r * 4) | ld(ib + (8 + g) * 400 + 384 + r * 4) << 16;
  }
  asm volatile("bar.sync 1,256;" ::: "memory");
  put_rows(2, tid >= 88); put_rows(3, tid + 768 < V_);
  asm volatile("bar.sync 1,256;" ::: "memory");
  TS(0, 1);
  uint32_t lc; asm volatile("add.u32 %0,%1,%2;" : "=r"(lc) : "r"((lane & 7) * 16), "r"(never));
  const uint64_t wdesc = (uint64_t)(((sbase + K1_W) & 0x3FFFF) >> 4) | ((uint64_t)(128 >> 4) << 16) | ((uint64_t)(256 >> 4) << 32);
  uint32_t a[2][6][4], d[2][26], ex[4] = {}, s[4] = {};
  float red[4] = {0.f, 0.f, 0.f, 0.f};
  auto ldsm = [&](uint32_t* o, uint32_t sh) {
    asm volatile("ldmatrix.sync.aligned.m8n8.x4.trans.shared.b16 {%0,%1,%2,%3},[%4];"
                 : "=r"(o[0]), "=r"(o[1]), "=r"(o[2]), "=r"(o[3]) : "r"(sbase + ((sh & 0x1ff80) | lc)));
  };
  auto gather = [&](int t, int hf) {
    const int x = t & 1;
    const uint4 v = iv[(t >> 1) & 3];
#pragma unroll
    for (int kb = 3 * hf; kb < 3 * hf + 3; kb++) {
      const uint32_t ww = x ? (kb < 3 ? v.z : v.w) : (kb < 3 ? v.x : v.y);
      ldsm(a[x][kb], kb % 3 == 0 ? ww : kb % 3 == 1 ? ww >> 10 : __funnelshift_l(ww, ww, 12));
    }
  };
  auto issue = [&](int x) {
    asm volatile("wgmma.fence.sync.aligned;" ::: "memory");
#pragma unroll
    for (int kb = 0; kb < 6; kb++) {
      if (kb < G_K0) wgmma_h<G_N0 * 8>(d[x] + G_O0 * 2, a[x][kb], wdesc + kb * G_N0 * 16, kb);
      if (kb < G_K1) wgmma_h<G_N1 * 8>(d[x] + G_O1 * 2, a[x][kb], wdesc + (G_U1 + kb * G_N1) * 16, kb);
      if (kb < G_K2) wgmma_h<32>(d[x] + G_O2 * 2, a[x][kb], wdesc + (G_U2 + kb * G_N2) * 16, kb);
    }
    asm volatile("wgmma.commit_group.sync.aligned;" ::: "memory");
  };
  auto hmma_part = [&](int t) {
    constexpr FragIdx FI = make_fi();
    const int x = t & 1;
#pragma unroll
    for (int o = 0; o < 13; o++) asm volatile("" : "+r"(d[x][o * 2]), "+r"(d[x][o * 2 + 1]) :: "memory");
#pragma unroll
    for (int kb = 0; kb < 6; kb++)
#pragma unroll
      for (int o = 2 * kb + 1; o < 13; o++)
        if (!unit_wg(kb, o)) mma16816h(d[x] + o * 2, a[x][kb], bf[FI.v[2 * kb][o]], bf[FI.v[2 * kb + 1][o]]);
#pragma unroll
    for (int q = 0; q < 6; q++) if (!unit_wg(q, 2 * q)) mma1688h(d[x] + q * 4, a[x][q][0], a[x][q][1], bf[FI.v[2 * q][2 * q]]);
    mma1688h(d[x] + 24, r < 2 ? ex[t & 3] : 0u, r < 2 ? 0u : ex[t & 3], bf[FI.v[12][12]]);
  };
  auto dot_part = [&](int t, int hf) {
    const int x = t & 1;
    if (hf == 0) {
      const uint32_t pe = hfma2(r < 2 ? d[x][24] : d[x][25], ex[t & 3], 0u);
      s[0] = r < 2 ? pe : 0u; s[1] = r < 2 ? 0u : pe; s[2] = s[3] = 0;
    }
#pragma unroll
    for (int q = 3 * hf; q < 3 * hf + 3; q++)
#pragma unroll
      for (int e = 0; e < 4; e++) s[e] = hfma2(d[x][q * 4 + e], a[x][q][e], s[e]);
  };
  const float* outp = g_partP + slice * B_ + range * 256;
  uint32_t oofs; asm volatile("add.u32 %0,%1,%2;" : "=r"(oofs) : "r"((r * 4 + ((lane >> 3) & 1) * 2 + (lane >> 4)) * 4), "r"(never));
  float k0 = 0.f, k1 = 0.f, x0 = 0.f, x1 = 0.f;
  auto red_stage = [&](int st, int grp) {
    const bool u16 = lane & 16, u8 = lane & 8;
    if (st == 0) {
      k0 = u16 ? red[2] : red[0]; x0 = __shfl_xor_sync(0xffffffffu, u16 ? red[0] : red[2], 16);
      k1 = u16 ? red[3] : red[1]; x1 = __shfl_xor_sync(0xffffffffu, u16 ? red[1] : red[3], 16);
      red[0] = red[1] = red[2] = red[3] = 0.f;
    }
    if (st == 1) { const float p0 = k0 + x0, p1 = k1 + x1; k0 = u8 ? p1 : p0; x0 = __shfl_xor_sync(0xffffffffu, u8 ? p0 : p1, 8); }
    if (st == 2) { k0 += x0; x0 = __shfl_xor_sync(0xffffffffu, k0, 4); }
    if (st == 3) asm volatile("st.global.f32 [%0],%1;" :: "l"((const char*)(outp + grp * 16) + oofs), "f"(k0 + x0) : "memory");
  };
  auto side = [&](bool first, int t, int prv, int cur, int nxt) {
    const int pn = PX_OFF + px + nxt * 136 + lane;
    if (!first) {
      if (t == 0) { iv[3] = ldtex(tex, PX_OFF + px + cur * 136 + lane + 96); iv[0] = ldtex(tex, pn); }
      if (t == 2) iv[1] = ldtex(tex, pn + 32);
      if (t < 4) red_stage(t, prv);
    } else if (t == 4) {
      TS(4, 2);
      mbar_wait_fast(pxRdy, 0);
      TS(4, 3);
      iv[0] = ldtex(tex, pn); iv[1] = ldtex(tex, pn + 32);
    }
    if (t == 4) { ix = ldtex(texX, (px + nxt * 136 + 128) * 4 + lane).x; iv[2] = ldtex(tex, pn + 64); }
  };
  auto group = [&](bool first, int prv, int cur, int nxt, int part) {
#pragma unroll
    for (int t = part ? 7 : 0; t < 8; t++) {
      if (!part) {
        if (first || t) SCHED_FENCE(never, t * 8);
        if (SV == 0) side(first, t, prv, cur, nxt);
        dot_part(t, 0);
        SCHED_FENCE(never, t * 8 + 1);
        if (t == 3) ldsm(ex, ix >> 9);
        if (t == 7) ldsm(ex, ix << 7);
        gather(t + 2, 0);
        dot_part(t, 1);
        if (SV == 1) side(first, t, prv, cur, nxt);
        if (HV) { s[0] = hadd2(s[0], s[2]); s[1] = hadd2(s[1], s[3]); }
        if (first || t < 7) SCHED_FENCE(never, t * 8 + 4);
        if (t == 7) break;
      }
      gather(t + 2, 1);
      if (SV == 2) side(first, t, prv, cur, nxt);
      asm volatile("wgmma.wait_group.sync.aligned 0;" ::: "memory");
      asm volatile("" : "+r"(d[(t & 1) ^ 1][0]) :: "memory");
      mma1688f(red, HV ? s[0] : hadd2(s[0], s[2]), HV ? s[1] : hadd2(s[1], s[3]), (g | (d[(t & 1) ^ 1][0] & never)) == t ? 0x3c003c00u : 0u);
      hmma_part(t + 1);
      issue(t & 1);
    }
  };
  gather(0, 0); gather(0, 1); issue(0); ldsm(ex, ix << 7); gather(1, 0); gather(1, 1);
  asm volatile("wgmma.wait_group.sync.aligned 0;" ::: "memory");
  hmma_part(0);
  SCHED_FENCE(never, 99);
  issue(1);
  group(true, 0, 0, 1, 0); group(true, 0, 0, 1, 1);
  TS(4, 1);
#pragma unroll 1
  for (int n = 1;; n++) {
    if ((n & 11) == 2) mbar_wait_fast(pxRdy + 8 + (n & 4) * 2, 0);
    asm volatile("st.volatile.shared.u32 [%0],%1;" :: "r"(progG), "r"(n) : "memory");
    group(false, n - 1, n, min(n + 1, 15), 0);
    if (n == 15) break;
    group(false, n - 1, n, min(n + 1, 15), 1);
  }
  asm volatile("wgmma.wait_group.sync.aligned 0;" ::: "memory");
  mma1688f(red, HV ? s[0] : hadd2(s[0], s[2]), HV ? s[1] : hadd2(s[1], s[3]), g == 7 ? 0x3c003c00u : 0u);
#pragma unroll
  for (int st = 0; st < 4; st++) red_stage(st, 15);
  TS(0, 2);
  asm volatile("barrier.cluster.wait.aligned;" ::: "memory");
  asm volatile("barrier.cluster.arrive.relaxed.aligned; barrier.cluster.wait.aligned;" ::: "memory");
}

constexpr int SM_U = 130048, SM_BAR = 128000, SM_J = SM_U + 98304, DEEP_SMEM = SM_J + 4096;

__global__ void __cluster_dims__(2, 1, 1) __launch_bounds__(TH + 128, 1)
k_deep(cudaTextureObject_t tex, const __nv_bfloat16* __restrict__ w2, const __nv_bfloat16* __restrict__ b2,
       __nv_bfloat16* __restrict__ out, int never) {
  extern __shared__ __align__(1024) uint4 sm[];
  constexpr int PF = 4, DEPTH = 4, NW = TH / 32;
  const int tid = threadIdx.x;
  const int c = blockIdx.x >> 1, half = blockIdx.x & 1;
  const uint32_t sbase = (uint32_t)__cvta_generic_to_shared(sm);
  const uint32_t fullL = sbase + SM_BAR, fullU = fullL + 8, emptyL = fullL + 16, emptyU = fullL + 24, barJ = fullL + 32, barW = fullL + 48;
  TS(1, 0);
  if (tid == 0) {
    mbar_init(fullL, 1); mbar_init(fullU, 1); mbar_init(emptyL, 2 * NW); mbar_init(emptyU, 2 * NW); mbar_init(barJ, 1); mbar_init(barW, 1);
    asm volatile("fence.mbarrier_init.release.cluster;" ::: "memory");
  }
  __syncwarp();
  const int wrp = __shfl_sync(0xffffffffu, tid >> 5, 0);
  const char* base = (const char*)g_scr;
  uint32_t oL = (PL_OFF + c * NC * 8000) * 16u + half * 64000, oS = (PS_OFF + c * NC * 2000) * 16u + half * 16000;
  asm volatile("barrier.cluster.arrive.relaxed.aligned; barrier.cluster.wait.aligned;" ::: "memory");
  if (wrp == NW) {
    asm volatile("fence.proxy.async.global;" ::: "memory");
    e_expect(fullU, 96000);
#pragma unroll
    for (int m = 0; m < 3; m++) e_mc(sbase + SM_U + m * 32032 + half * 16000, base + oS, 16000, fullU, m == 2 ? POL_EF : POL_N);
    e_expect(fullL, 128000);
  }
  TS(5, 1);
  if (wrp >= NW) {
    asm volatile("setmaxnreg.dec.sync.aligned.u32 24;");
    if (wrp == NW) {
      uint32_t oT = (PT_OFF + c * 10 * 1024) * 16u + half * 8000;
      auto warm = [&](uint32_t off, uint32_t hb) {
        asm volatile(ELECT "mbarrier.expect_tx.relaxed.cta.shared::cta.b64 [%0],%1;}" :: "r"(barJ), "r"(2 * hb) : "memory");
        e_g2s(sbase + SM_J, base + off, hb, barJ); e_g2s(sbase + SM_J, base + off + hb, hb, barJ);
      };
      mbar_wait(fullU, 0);
      e_mc(sbase + half * 64000, base + oL, 64000, fullL, POL_EF);
      warm(oT, 4000);
#pragma unroll 1
      for (int k = 0; k + 1 < NC; k++) {
        oL += 128000; oS += 32000; oT += 16384;
        mbar_wait(fullL, k & 1);
        const uint32_t t0 = clock();
        e_pf(base + oS, 16000);
        warm((IX_OFF + half * IXH + (k + 2) * 8192 + ((c + (c >> 4) * (2 * k + 1)) & (k + 2 < NC ? 15 : 3)) * 512) * 16u, 4096);
        mbar_wait(emptyU, k & 1);
        e_expect(fullU, 96000);
#pragma unroll 1
        for (int q = 0; q < 8; q++) {
          sleep_until(t0, q * PACE);
          e_pf(base + oL + q * 8000, 8000);
          if (q >= 2) e_mc(sbase + SM_U + ((q - 2) >> 1) * 32032 + half * 16000 + (q & 1) * 8000, base + oS + (q & 1) * 8000, 8000, fullU, q >= 6 ? POL_EF : POL_N);
        }
        warm(oT, 4000);
        e_expect(fullL, 128000);
        sleep_until(t0, RSV_T);
        unsigned long long now, slot = 0;
        asm volatile("mov.u64 %0,%globaltimer;" : "=l"(now));
        if ((tid & 31) == 0) { atomicMax(&g_slot, now + RSV_L); slot = atomicAdd(&g_slot, (unsigned long long)RSV); }
        slot = __shfl_sync(0xffffffffu, slot, 0);
        mbar_wait(emptyL, k & 1);
        for (int it = 0; it < 4000; it++) { asm volatile("mov.u64 %0,%globaltimer;" : "=l"(now)); if (now >= slot) break; }

        e_mc(sbase + half * 64000, base + oL, 64000, fullL, POL_EF);
      }
      mbar_wait(fullL, (NC - 1) & 1);
      mbar_wait(emptyU, (NC - 1) & 1);
      mbar_arrive_lane0(fullU);
      warm(oT + 16384, 4000);
      mbar_arrive_lane0(barJ); mbar_wait(barJ, 0);
    } else if (tid >= TH + 96) {
      if (tid < TH + 100) asm volatile("st.shared.u32 [%0],%1;" :: "r"(barJ + 32 + (tid & 3) * 4), "r"(((const uint32_t*)w2)[(c >> 2) * 16 + (tid & 3) * 4 + (c & 3)]) : "memory");
      __syncwarp();
      mbar_arrive_lane0(barW);
      asm volatile("griddepcontrol.wait;" ::: "memory");
      const int b = half * 8192 + c * 128 + (tid & 31) * 4;
      const float bias = __bfloat162float(b2[0]);
      float4 s = make_float4(bias, bias, bias, bias);
#pragma unroll 2
      for (int k = 0; k < 16; k++) {
        const float4 v = __ldcg((const float4*)(g_partP + k * B_ + b)); const float2 u = __ldcg(g_unscale + k);
        s.x = fmaf(v.x * u.x * u.x, u.y, s.x); s.y = fmaf(v.y * u.x * u.x, u.y, s.y); s.z = fmaf(v.z * u.x * u.x, u.y, s.z); s.w = fmaf(v.w * u.x * u.x, u.y, s.w);
      }
      asm volatile("red.global.add.v4.f32 [%0],{%1,%2,%3,%4};" :: "l"(g_acc + b), "f"(s.x), "f"(s.y), "f"(s.z), "f"(s.w) : "memory");
      asm volatile("bar.arrive 1,%0;" :: "n"(TH + 32) : "memory");
    }
    return;
  }
  asm volatile("setmaxnreg.inc.sync.aligned.u32 240;");
  const int lane = tid & 31;
  const int tbase = PT_OFF + c * 10 * 1024;
  const int ibase = IX_OFF + half * IXH + tid;
  const uint32_t lc = (tid & 7) << 4;
  uint4 acc[NS], wq[PF], x[DEPTH], y[YD], ye;
  uint32_t sw[NS] = {};
  auto sget = [&](int s) { return (s & 3) == 3 ? __byte_perm(__byte_perm(sw[s - 3], sw[s - 2], 0x0073), sw[s - 1], 0x0710) : sw[s]; };
  auto sa0 = [&](uint32_t v) { return sbase + SM_U + (((v << 5) & 0x1ffe0) | ((lc >> 2) & 16)); };
  uint32_t c1 = 0;
  auto sa1 = [&](uint32_t v) { return sbase + SM_U + (((v >> 7) & 0x1ffe0) | c1); };
  {
    uint4 i0[8];
#pragma unroll
    for (int q = 0; q < 8; q++) i0[q] = ldtex(tex, I0_OFF + (half * 8 + q) * TH + tid);
    auto wd = [&](int k) { return (k & 3) == 0 ? i0[k >> 2].x : (k & 3) == 1 ? i0[k >> 2].y : (k & 3) == 2 ? i0[k >> 2].z : i0[k >> 2].w; };
    TS(5, 2);
    mbar_wait_fast(fullU, 0);
#pragma unroll
    for (int i = 0; i < PF; i++) wq[i] = ldtex(tex, ibase + i * TH);
    TS(1, 1);
#pragma unroll
    for (int s = 0; s < NS; s++) acc[s] = add4(lds128(sbase + SM_U + (wd(s) & 0x1fff0)), lds128(sbase + SM_U + ((wd(s) >> 13) & 0x1fff0)));
    arrive_both(emptyU, lane);
    mbar_wait_fast(barW, 0);
    TS(5, 3);
  }
#pragma unroll 1
  for (int k = 0; k < NC; k++) {
    const int ti = ibase + k * 8192;
    const int tb = tbase + k * 1024;
    const bool more = k + 1 < NC;
    TR(k * 4);
    mbar_wait_fast(fullL, k & 1);
    TR(k * 4 + 2);
    uint4 w, cc; uint32_t yc;
    constexpr int TL = NS * 8, TT = TL + NS * 2;
#pragma unroll
    for (int t = 0; t < TT + DEPTH; t += 2) {
      if (t == TL + DEPTH && !more) break;
      if (t >= DEPTH) {
        const int u = t - DEPTH;
        uint4 p = add4(x[u % DEPTH], x[(u + 1) % DEPTH]);
        if (u < TL) {
          const int s = u >> 3, j = u & 7;
          if (j == 0) {
            cc = s >= YD ? add4(y[s % YD], p) : p;
            if (s + YD < NS) y[s % YD] = ldtex(tex, tb | (yc & 1023));
          } else cc = add4(cc, p);
          if (j == 6) acc[s] = add4(acc[s], cc);
        } else {
          const int s = (u - TL) >> 1;
          acc[s] = add4(acc[s], p);
        }
      }
      if (t < TL) {
        const int s = t >> 3, j = t & 7;
        if (j == 0) {
          if (ye_of(s - YD) >= 0) acc[ye_of(s - YD) & 3] = add4(acc[ye_of(s - YD) & 3], ye);
          w = wq[s % PF];
          wq[s % PF] = ldtex(tex, ti + (s + PF) * TH);
          yc = __funnelshift_l(w.z, w.z, 5);
          if ((s & 3) != 3) asm volatile("add.u32 %0,%1,%2;" : "=r"(sw[s]) : "r"(w.w), "r"(never));
          if (ye_of(s) >= 0) ye = ldtex(tex, tb | w.w);
        }
#pragma unroll
        for (int jj = j; jj < j + 2; jj++) {
          const uint32_t ww = jj < 3 ? w.x : jj < 6 ? w.y : w.z;
          const uint32_t sh = jj % 3 == 0 ? ww : jj % 3 == 1 ? ww >> 10 : __funnelshift_l(ww, ww, 12);
          x[(t + jj - j) % DEPTH] = lds128(sbase + ((sh & 0x1ff80) | lc) + jj * 16 - 128);
        }
      } else if (t < TT) {
        const int s = (t - TL) >> 1;
        if (s == 0) {
          asm volatile("add.u32 %0,%1,%2;" : "=r"(c1) : "r"((~lc >> 2) & 16), "r"(never));
          arrive_both(emptyL, more ? lane : 9);
          TR(k * 4 + 3);
          mbar_wait_fast(fullU, (k + 1) & 1);
        }
        const uint32_t sv = sget(s);
        x[t % DEPTH] = lds128(sa0(sv));
        x[(t + 1) % DEPTH] = lds128(sa1(sv));
      } else if (t == TT) arrive_both(emptyU, lane);
      if ((t & 3) == 2) SCHED_FENCE(never, t);
    }
  }
  TS(1, 2);
  const uint4 w2v = lds128(barJ + 32);
  const uint32_t cell = sbase + SM_U + tid * 16;
  const int t9 = tbase + 9 * 1024;
  uint4 za[4], i9 = wq[0];
  auto fetch = [&](int q) {
    y[0] = ldtex(tex, t9 | i9.x); y[1] = ldtex(tex, t9 | i9.y); y[2] = ldtex(tex, t9 | i9.z); y[3] = ldtex(tex, t9 | i9.w);
    if (q) {
      i9 = ldtex(tex, ibase + NC * 8192 + min(q + 1, 7) * TH);
      const uint32_t ca = cell + (q > 6 ? 0 : q - 1) * 16384;
#pragma unroll
      for (int s = 0; s < 4; s++) za[s] = lds128(ca + s * 4096);
    }
  };
  fetch(0);
  i9 = wq[1];
#pragma unroll
  for (int s = 0; s < 4; s++) za[s] = acc[s];
#pragma unroll
  for (int s = 0; s < 24; s++) sts128(cell + s * 4096, acc[4 + s]);
  float hw[8];
  {
    const uint32_t ww[4] = {w2v.x, w2v.y, w2v.z, w2v.w};
#pragma unroll
    for (int k = 0; k < 8; k++) hw[k] = 0.5f * ((k & 1) ? bf_hi(ww[k >> 1]) : bf_lo(ww[k >> 1]));
  }
  float* outp = g_acc + half * 8192 + tid;
#pragma unroll 1
  for (int q = 0; q < NS / 4; q++) {
    uint4 z[4];
#pragma unroll
    for (int s = 0; s < 4; s++) z[s] = add4(za[s], y[s]);
    if (q == 1) {
#pragma unroll
      for (int s = 0; s < 4; s++) sts128(cell + s * 4096, acc[28 + s]);
    }
    if (q < 7) fetch(q + 1);
    SCHED_FENCE(never, 999);
#pragma unroll
    for (int s = 0; s < 4; s++) {
      const uint32_t a[4] = {z[s].x, z[s].y, z[s].z, z[s].w};
      float r0 = 0.f;
#pragma unroll
      for (int k = 0; k < 8; k++) {
        const float v = (k & 1) ? bf_hi(a[k >> 1]) : bf_lo(a[k >> 1]);
        const float u = v * fmaf(v * v, 0.7978845608028654f * 0.044715f, 0.7978845608028654f);
        float th; asm("tanh.approx.f32 %0,%1;" : "=f"(th) : "f"(u));
        r0 = fmaf(fmaf(v, th, v), hw[k], r0);
      }
      asm volatile("red.global.add.f32 [%0],%1;" :: "l"(outp + s * TH), "f"(r0) : "memory");
    }
    outp += 4 * TH;
  }
  TS(1, 3);
  asm volatile("bar.sync 1,%0;" :: "n"(TH + 32) : "memory");
  if (tid == 0) {
    unsigned old; asm volatile("atom.acq_rel.gpu.global.inc.u32 %0,[%1],63;" : "=r"(old) : "l"(&g_done[half * 32]) : "memory");
    asm volatile("st.shared.u32 [%0],%1;" :: "r"(barJ + 8), "r"(old) : "memory");
  }
  asm volatile("bar.sync 2,%0;" :: "n"(TH) : "memory");
  uint32_t old; asm volatile("ld.shared.u32 %0,[%1];" : "=r"(old) : "r"(barJ + 8));
  if (old == 63) {
    if (half == 0 && tid == 25) g_slot = 0;
    if (half == 0 && tid < 25) g_flag[tid * 32] = 0;
    float4 v[8];
#pragma unroll
    for (int q = 0; q < 8; q++) v[q] = __ldcg((const float4*)(g_acc + half * 8192) + q * TH + tid);
#pragma unroll
    for (int q = 0; q < 8; q++) ((uint2*)(out + half * 8192))[q * TH + tid] = make_uint2(pack_bf2(v[q].x, v[q].y), pack_bf2(v[q].z, v[q].w));
    TS(6, 2);
  }
}

}

extern "C" void kernel_launch(void* const* d_in, const int* in_sizes, int n_in, void* d_out, int out_size) {
  const int* idx = (const int*)d_in[0];
  const __nv_bfloat16* table = (const __nv_bfloat16*)d_in[1];
  const __nv_bfloat16* wp = (const __nv_bfloat16*)d_in[2];
  const __nv_bfloat16* w1 = (const __nv_bfloat16*)d_in[3];
  const __nv_bfloat16* b1 = (const __nv_bfloat16*)d_in[4];
  const __nv_bfloat16* w2 = (const __nv_bfloat16*)d_in[5];
  const __nv_bfloat16* b2 = (const __nv_bfloat16*)d_in[6];
  static cudaTextureObject_t texScr = 0, texX = 0;
  static CUtensorMap mapW, mapL, mapS, mapT, mapE, mapC;
  static const void *c_tab = nullptr, *c_w1 = nullptr;
  if (c_tab != table || c_w1 != w1) {
    c_tab = table; c_w1 = w1;
    char* scr = nullptr; cudaGetSymbolAddress((void**)&scr, g_scr);
    auto mk_tex = [](const void* p, size_t bytes, cudaChannelFormatDesc d) {
      cudaResourceDesc rd = {}; rd.resType = cudaResourceTypeLinear; rd.res.linear.devPtr = (void*)p; rd.res.linear.desc = d; rd.res.linear.sizeInBytes = bytes;
      cudaTextureDesc td = {}; td.readMode = cudaReadModeElementType;
      cudaTextureObject_t t = 0; cudaCreateTextureObject(&t, &rd, &td, nullptr); return t;
    };
    if (!texScr) {
      texScr = mk_tex(scr, (size_t)SCR_N * 16, cudaCreateChannelDesc<uint4>());
      texX = mk_tex(scr + (size_t)PX_OFF * 16, (size_t)(SCR_N - PX_OFF) * 16, cudaCreateChannelDesc<unsigned>());
    }
    typedef CUresult (*EncFn)(CUtensorMap*, CUtensorMapDataType, cuuint32_t, void*, const cuuint64_t*, const cuuint64_t*, const cuuint32_t*,
                              const cuuint32_t*, CUtensorMapInterleave, CUtensorMapSwizzle, CUtensorMapL2promotion, CUtensorMapFloatOOBfill);
    EncFn enc = nullptr; cudaDriverEntryPointQueryResult qr;
    cudaGetDriverEntryPoint("cuTensorMapEncodeTiled", (void**)&enc, cudaEnableDefault, &qr);
    const cuuint32_t ones[4] = {1, 1, 1, 1};
    auto mk = [&](CUtensorMap* m, CUtensorMapDataType dt, int rank, void* p, const cuuint64_t* dim, const cuuint64_t* str, const cuuint32_t* box, CUtensorMapSwizzle sw) {
      enc(m, dt, rank, p, dim, str, box, ones, CU_TENSOR_MAP_INTERLEAVE_NONE, sw, CU_TENSOR_MAP_L2_PROMOTION_NONE, CU_TENSOR_MAP_FLOAT_OOB_FILL_NONE);
    };
    { cuuint64_t dim[2] = {H_, F_ * D_}, str[1] = {H_ * 2}; cuuint32_t box[2] = {32, 256};
      mk(&mapW, CU_TENSOR_MAP_DATA_TYPE_BFLOAT16, 2, (void*)w1, dim, str, box, CU_TENSOR_MAP_SWIZZLE_64B); }
    { cuuint64_t dim[4] = {64, 64, V_, NC}, str[3] = {128000 * NC, 128, 128000}; cuuint32_t box[4] = {32, 4, 64, 1};
      mk(&mapL, CU_TENSOR_MAP_DATA_TYPE_BFLOAT16, 4, scr + (size_t)PL_OFF * 16, dim, str, box, CU_TENSOR_MAP_SWIZZLE_64B); }
    { cuuint64_t dim[4] = {64, 64, V_ / 4, NC}, str[3] = {32000 * NC, 128, 32000}; cuuint32_t box[4] = {64, 4, 16, 1};
      mk(&mapS, CU_TENSOR_MAP_DATA_TYPE_BFLOAT16, 4, scr + (size_t)PS_OFF * 16, dim, str, box, CU_TENSOR_MAP_SWIZZLE_128B); }
    { cuuint64_t dim[4] = {64, 64, V_ / 8, 10}, str[3] = {163840, 128, 16384}; cuuint32_t box[4] = {64, 4, 8, 2};
      mk(&mapT, CU_TENSOR_MAP_DATA_TYPE_BFLOAT16, 4, scr + (size_t)PT_OFF * 16, dim, str, box, CU_TENSOR_MAP_SWIZZLE_128B); }
    { cuuint64_t dim[2] = {D_, V_}, str[1] = {D_ * 2}; cuuint32_t box[2] = {64, 128};
      mk(&mapE, CU_TENSOR_MAP_DATA_TYPE_BFLOAT16, 2, (void*)table, dim, str, box, CU_TENSOR_MAP_SWIZZLE_128B);
      cuuint32_t box2[2] = {8, 256};
      mk(&mapC, CU_TENSOR_MAP_DATA_TYPE_BFLOAT16, 2, (void*)table, dim, str, box2, CU_TENSOR_MAP_SWIZZLE_NONE); }
    cudaFuncSetAttribute(k_deep, cudaFuncAttributeMaxDynamicSharedMemorySize, DEEP_SMEM);
    cudaFuncSetAttribute(k_tens, cudaFuncAttributeMaxDynamicSharedMemorySize, K1_SMEM);
  }
  k_tens<<<132, 512, K1_SMEM, cudaStreamPerThread>>>(mapW, mapL, mapS, mapT, mapE, mapC, texScr, texX, idx, table, wp, w1, b1, 0);
  cudaLaunchAttribute at[1];
  at[0].id = cudaLaunchAttributeProgrammaticStreamSerialization; at[0].val.programmaticStreamSerializationAllowed = 1;
  cudaLaunchConfig_t cfg = {};
  cfg.stream = cudaStreamPerThread; cfg.attrs = at;
  cfg.gridDim = 128; cfg.blockDim = TH + 128; cfg.dynamicSmemBytes = DEEP_SMEM; cfg.numAttrs = PDL;
  cudaLaunchKernelEx(&cfg, k_deep, texScr, w2, b2, (__nv_bfloat16*)d_out, 0);

}
```

```cpp
#include <cuda_runtime.h>
#include <cuda_bf16.h>
#include <cuda_fp16.h>
#include <stdint.h>
#include <cuda.h>

namespace {

constexpr int B_ = 16384, F_ = 100, D_ = 128, V_ = 1000, H_ = 512;
constexpr int NC = 9;
constexpr int PT_OFF = 0;
constexpr int PL_OFF = 64 * 10 * 1024;
constexpr int PS_OFF = PL_OFF + 64 * NC * 8000;
constexpr int IXH = NC * 8192 + 2048;
constexpr int IX_OFF = PS_OFF + 64 * NC * 2000;
constexpr int I0_OFF = IX_OFF + 2 * IXH;
constexpr int PX_OFF = I0_OFF + 4096;
constexpr int SCR_N = PX_OFF + 64 * 16 * 136;
static_assert(PX_OFF % 32 == 0, "");

__device__ __align__(1024) uint4 g_scr[SCR_N];
__device__ float g_acc[B_];
__device__ unsigned long long g_slot;
__device__ unsigned g_done[64];
__device__ float g_partP[16 * B_];
__device__ float2 g_unscale[16];
__device__ unsigned g_flag[25 * 32];

#define TS(k, i)
#define TR(slot)
#define PT(slot)

constexpr uint64_t POL_EF = 0x12F0000000000000ull, POL_N = 0x1000000000000000ull;
__device__ __forceinline__ uint32_t addbf2(uint32_t a, uint32_t b) { uint32_t r; asm("add.rn.bf16x2 %0,%1,%2;" : "=r"(r) : "r"(a), "r"(b)); return r; }
__device__ __forceinline__ uint4 add4(const uint4& a, const uint4& b) { return make_uint4(addbf2(a.x, b.x), addbf2(a.y, b.y), addbf2(a.z, b.z), addbf2(a.w, b.w)); }
__device__ __forceinline__ uint4 ldtex(cudaTextureObject_t t, int i) {
  uint4 v; asm volatile("tex.1d.v4.u32.s32 {%0,%1,%2,%3},[%4,{%5}];" : "=r"(v.x), "=r"(v.y), "=r"(v.z), "=r"(v.w) : "l"(t), "r"(i)); return v;
}
__device__ __forceinline__ uint4 lds128(uint32_t a) {
  uint4 v; asm volatile("ld.volatile.shared.v4.u32 {%0,%1,%2,%3},[%4];" : "=r"(v.x), "=r"(v.y), "=r"(v.z), "=r"(v.w) : "r"(a)); return v;
}
__device__ __forceinline__ void sts128(uint32_t a, const uint4& v) {
  asm volatile("st.shared.v4.u32 [%0],{%1,%2,%3,%4};" :: "r"(a), "r"(v.x), "r"(v.y), "r"(v.z), "r"(v.w) : "memory");
}
__device__ __forceinline__ void mbar_init(uint32_t bar, int n) { asm volatile("mbarrier.init.shared::cta.b64 [%0],%1;" :: "r"(bar), "r"(n) : "memory"); }
__device__ __forceinline__ void mbar_wait(uint32_t bar, uint32_t parity) {
  uint32_t ok; int it = 0;
  do { asm volatile("{.reg .pred p; mbarrier.try_wait.parity.shared::cta.b64 p,[%1],%2; selp.u32 %0,1,0,p;}" : "=r"(ok) : "r"(bar), "r"(parity) : "memory"); } while (!ok && ++it < (1 << 19));
}
__device__ __forceinline__ void mbar_expect(uint32_t bar, uint32_t bytes) { asm volatile("mbarrier.arrive.expect_tx.shared::cta.b64 _,[%0],%1;" :: "r"(bar), "r"(bytes) : "memory"); }
__device__ __forceinline__ void bulk_g2s(uint32_t dst, const void* src, uint32_t bytes, uint32_t bar) {
  asm volatile("cp.async.bulk.shared::cluster.global.mbarrier::complete_tx::bytes [%0],[%1],%2,[%3];" :: "r"(dst), "l"(src), "r"(bytes), "r"(bar) : "memory");
}
__device__ __forceinline__ void bulk_pf(const void* src, uint32_t bytes) { asm volatile("cp.async.bulk.prefetch.L2.global [%0],%1;" :: "l"(src), "r"(bytes) : "memory"); }
#define SCHED_FENCE(never, k) asm volatile("{.reg .pred p; setp.ne.u32 p,%0,%1; @p bra.uni SKIP_%=; pmevent 1; SKIP_%=: }" :: "r"(never), "r"(0x7fff0000 + (k)) : "memory")
#define PDL 1
#define RSV 23
#define RSV_L 550
#define RSV_T 7200
#define PACE 900
__device__ __forceinline__ int quad_of(int n) { return n < 23 ? n + 2 : n - 23; }
__device__ __forceinline__ void mbar_wait_fast(uint32_t bar, uint32_t parity) {
  asm volatile("{.reg .pred p; .reg .u32 n;\n"
               "mbarrier.try_wait.parity.shared::cta.b64 p,[%0],%1;\n"
               "@p bra DONE_%=;\n"
               "mov.u32 n,0;\n"
               "LOOP_%=: mbarrier.try_wait.parity.shared::cta.b64 p,[%0],%1;\n"
               "add.u32 n,n,1; setp.gt.or.u32 p,n,400000,p;\n"
               "@!p bra LOOP_%=;\n"
               "DONE_%=: }" :: "r"(bar), "r"(parity) : "memory");
}
__device__ __forceinline__ void sleep_until(uint32_t t0, uint32_t dt) { while ((uint32_t)clock() - t0 < dt) __nanosleep(40); }
__device__ __forceinline__ uint32_t s_mask(uint32_t v, int q) { return (1u << ((v + 3 - q) & 3)) | (16u << ((v + 3 + q) & 3)); }
__device__ __forceinline__ uint32_t s_cell(uint32_t v, int q, uint32_t m) {
  const int t = __ffs(~m) - 1;
  const int cp = t == 8 ? q >> 1 : ((t & 4 ? t - q : t + q) - v) & 3;
  return cp * 1001 + v;
}
__device__ __forceinline__ uint32_t pk3(uint32_t a, uint32_t b, uint32_t c) {
  const uint32_t w = c + (a << 12) + (b << 22); return __funnelshift_l(w, w, 27);
}
constexpr int TH = 256, NS = 8192 / TH, YD = 4;
__host__ __device__ constexpr int ye_of(int s) { return s == 3 ? 0 : s == 11 ? 1 : s == 19 ? 2 : s == 23 ? 3 : -1; }
template <int N> __device__ __forceinline__ void wgmma_h(uint32_t* d, const uint32_t* a, uint64_t desc, int acc);
template <> __device__ __forceinline__ void wgmma_h<40>(uint32_t* d, const uint32_t* a, uint64_t desc, int acc) {
  asm volatile("{.reg .pred p; setp.ne.s32 p,%15,0;\n"
    "wgmma.mma_async.sync.aligned.m64n40k16.f16.f16.f16 {%0,%1,%2,%3,%4,%5,%6,%7,%8,%9},{%10,%11,%12,%13},%14,p,1,1,0;}"
    : "+r"(d[0]),"+r"(d[1]),"+r"(d[2]),"+r"(d[3]),"+r"(d[4]),"+r"(d[5]),"+r"(d[6]),"+r"(d[7]),"+r"(d[8]),"+r"(d[9])
    : "r"(a[0]), "r"(a[1]), "r"(a[2]), "r"(a[3]), "l"(desc), "r"(acc));
}
template <> __device__ __forceinline__ void wgmma_h<32>(uint32_t* d, const uint32_t* a, uint64_t desc, int acc) {
  asm volatile("{.reg .pred p; setp.ne.s32 p,%13,0;\n"
    "wgmma.mma_async.sync.aligned.m64n32k16.f16.f16.f16 {%0,%1,%2,%3,%4,%5,%6,%7},{%8,%9,%10,%11},%12,p,1,1,0;}"
    : "+r"(d[0]),"+r"(d[1]),"+r"(d[2]),"+r"(d[3]),"+r"(d[4]),"+r"(d[5]),"+r"(d[6]),"+r"(d[7])
    : "r"(a[0]), "r"(a[1]), "r"(a[2]), "r"(a[3]), "l"(desc), "r"(acc));
}
__device__ __forceinline__ void wgmma_p(float* d, const uint32_t* a, uint64_t desc, int acc) {
  asm volatile("{.reg .pred p; setp.ne.s32 p,%69,0;\n"
    "wgmma.mma_async.sync.aligned.m64n128k16.f32.bf16.bf16 {%0,%1,%2,%3,%4,%5,%6,%7,%8,%9,%10,%11,%12,%13,%14,%15,%16,%17,%18,%19,%20,%21,%22,%23,%24,%25,%26,%27,%28,%29,%30,%31,%32,%33,%34,%35,%36,%37,%38,%39,%40,%41,%42,%43,%44,%45,%46,%47,%48,%49,%50,%51,%52,%53,%54,%55,%56,%57,%58,%59,%60,%61,%62,%63},{%64,%65,%66,%67},%68,p,1,1,1;}"
    : "+f"(d[0]),"+f"(d[1]),"+f"(d[2]),"+f"(d[3]),"+f"(d[4]),"+f"(d[5]),"+f"(d[6]),"+f"(d[7]),"+f"(d[8]),"+f"(d[9]),"+f"(d[10]),"+f"(d[11]),"+f"(d[12]),"+f"(d[13]),"+f"(d[14]),"+f"(d[15]),"+f"(d[16]),"+f"(d[17]),"+f"(d[18]),"+f"(d[19]),"+f"(d[20]),"+f"(d[21]),"+f"(d[22]),"+f"(d[23]),"+f"(d[24]),"+f"(d[25]),"+f"(d[26]),"+f"(d[27]),"+f"(d[28]),"+f"(d[29]),"+f"(d[30]),"+f"(d[31]),"+f"(d[32]),"+f"(d[33]),"+f"(d[34]),"+f"(d[35]),"+f"(d[36]),"+f"(d[37]),"+f"(d[38]),"+f"(d[39]),"+f"(d[40]),"+f"(d[41]),"+f"(d[42]),"+f"(d[43]),"+f"(d[44]),"+f"(d[45]),"+f"(d[46]),"+f"(d[47]),"+f"(d[48]),"+f"(d[49]),"+f"(d[50]),"+f"(d[51]),"+f"(d[52]),"+f"(d[53]),"+f"(d[54]),"+f"(d[55]),"+f"(d[56]),"+f"(d[57]),"+f"(d[58]),"+f"(d[59]),"+f"(d[60]),"+f"(d[61]),"+f"(d[62]),"+f"(d[63])
    : "r"(a[0]), "r"(a[1]), "r"(a[2]), "r"(a[3]), "l"(desc), "r"(acc));
}

__device__ __forceinline__ void mma16816h(uint32_t* c, const uint32_t* a, uint32_t b0, uint32_t b1) {
  asm("mma.sync.aligned.m16n8k16.row.col.f16.f16.f16.f16 {%0,%1},{%2,%3,%4,%5},{%6,%7},{%0,%1};"
      : "+r"(c[0]), "+r"(c[1]) : "r"(a[0]), "r"(a[1]), "r"(a[2]), "r"(a[3]), "r"(b0), "r"(b1));
}
__device__ __forceinline__ void mma1688h(uint32_t* c, uint32_t a0, uint32_t a1, uint32_t b) {
  asm("mma.sync.aligned.m16n8k8.row.col.f16.f16.f16.f16 {%0,%1},{%2,%3},{%4},{%0,%1};" : "+r"(c[0]), "+r"(c[1]) : "r"(a0), "r"(a1), "r"(b));
}
__device__ __forceinline__ void mma1688f(float* c, uint32_t a0, uint32_t a1, uint32_t b) {
  asm("mma.sync.aligned.m16n8k8.row.col.f32.f16.f16.f32 {%0,%1,%2,%3},{%4,%5},{%6},{%0,%1,%2,%3};"
      : "+f"(c[0]), "+f"(c[1]), "+f"(c[2]), "+f"(c[3]) : "r"(a0), "r"(a1), "r"(b));
}
__device__ __forceinline__ uint32_t hadd2(uint32_t a, uint32_t b) { uint32_t r; asm("add.rn.f16x2 %0,%1,%2;" : "=r"(r) : "r"(a), "r"(b)); return r; }
__device__ __forceinline__ uint32_t hfma2(uint32_t a, uint32_t b, uint32_t c) { uint32_t r; asm("fma.rn.f16x2 %0,%1,%2,%3;" : "=r"(r) : "r"(a), "r"(b), "r"(c)); return r; }
__device__ __forceinline__ uint32_t pack_bf2(float lo, float hi) { uint32_t r; asm("cvt.rn.bf16x2.f32 %0,%1,%2;" : "=r"(r) : "f"(hi), "f"(lo)); return r; }
__device__ __forceinline__ uint32_t pack_h2(float lo, float hi) { uint32_t r; asm("cvt.rn.f16x2.f32 %0,%1,%2;" : "=r"(r) : "f"(hi), "f"(lo)); return r; }
__device__ __forceinline__ float bf_lo(uint32_t w) { return __uint_as_float(w << 16); }
__device__ __forceinline__ float bf_hi(uint32_t w) { return __uint_as_float(w & 0xffff0000u); }
__device__ __forceinline__ uint32_t absmax4(const uint4& v, uint32_t m) {
  return __vmaxu2(__vmaxu2(__vmaxu2(v.x & 0x7fff7fffu, v.y & 0x7fff7fffu), __vmaxu2(v.z & 0x7fff7fffu, v.w & 0x7fff7fffu)), m);
}
__device__ __forceinline__ float pow2_scale(uint32_t mbits, int p) { return __uint_as_float((uint32_t)min(max(253 + p - (int)(mbits >> 7), 2), 252) << 23); }

constexpr int G_O0 = 8, G_O1 = 4, G_O2 = 0, G_N0 = 5, G_N1 = 4, G_N2 = 4, G_K0 = 5, G_K1 = 3, G_K2 = 1;
__host__ __device__ constexpr bool unit_wg(int kb, int on) {
  return (on >= G_O0 && on < G_O0 + G_N0 && kb < G_K0) || (on >= G_O1 && on < G_O1 + G_N1 && kb < G_K1) || (on >= G_O2 && on < G_O2 + G_N2 && kb < G_K2);
}
constexpr int G_U1 = G_N0 * G_K0, G_U2 = G_U1 + G_N1 * G_K1, G_U = G_U2 + G_N2 * G_K2;
constexpr int K1_B = 130048, K1_STG = K1_B + 2 * 32768, K1_W = K1_STG + 16384, K1_BAR = K1_W + 48 * 256, K1_SMEM = K1_BAR + 256 + 6400;
__host__ __device__ constexpr int frag_index(int ok, int on) {
  int n = 0;
  for (int k = 0; k < 13; k++) for (int o = k; o < 13; o++) { if (k == ok && o == on) return n; if (!unit_wg(k >> 1, o)) n++; }
  return n;
}
constexpr int HU_N = 2 * G_U + frag_index(99, 99);
static_assert(HU_N <= 96, "");
struct FragIdx { int v[13][13]; };
__host__ __device__ constexpr FragIdx make_fi() { FragIdx f = {}; for (int k = 0; k < 13; k++) for (int o = 0; o < 13; o++) f.v[k][o] = frag_index(k, o); return f; }
__host__ __device__ constexpr uint64_t frag_tab(int first) {
  uint64_t t = 0;
  for (int k = 0; k < 13; k++) for (int o = k; o < 13; o++)
    if (!unit_wg(k >> 1, o)) { const int n = frag_index(k, o) - first; if (n >= 0 && n < 8) t |= (uint64_t)(k << 4 | o) << (8 * n); }
  return t;
}
__device__ __forceinline__ int hu_code(int hu) {
  constexpr uint64_t T0 = frag_tab(0), T1 = frag_tab(8), T2 = frag_tab(16), T3 = frag_tab(24);
  const int u = hu >> 1, f = hu - 2 * G_U;
  if (f >= 0) return (int)((f < 8 ? T0 : f < 16 ? T1 : f < 24 ? T2 : T3) >> (8 * (f & 7))) & 255;
  const int u0 = u < G_U1 ? u : u < G_U2 ? u - G_U1 : u - G_U2;
  const int kb = u < G_U1 ? u0 / G_N0 : u < G_U2 ? u0 / G_N1 : u0 / 4, on = u < G_U1 ? G_O0 + u0 % G_N0 : u < G_U2 ? G_O1 + u0 % G_N1 : G_O2 + u0 % 4;
  return (2 * kb + (hu & 1)) << 4 | on;
}

__device__ __forceinline__ void flag_wait(const unsigned* f, unsigned n) {
  unsigned v; int it = 0;
  asm volatile("ld.acquire.gpu.global.u32 %0,[%1];" : "=r"(v) : "l"(f) : "memory");
  if (v < n) {
    do { __nanosleep(300); asm volatile("ld.relaxed.gpu.global.u32 %0,[%1];" : "=r"(v) : "l"(f) : "memory"); } while (v < n && ++it < (1 << 20));
    asm volatile("ld.acquire.gpu.global.u32 %0,[%1];" : "=r"(v) : "l"(f) : "memory");
  }
}
__device__ __forceinline__ void mbar_arrive(uint32_t bar) { asm volatile("mbarrier.arrive.shared::cta.b64 _,[%0];" :: "r"(bar) : "memory"); }
__device__ __forceinline__ void mbar_arrive_lane0(uint32_t bar) {
  __syncwarp();
  asm volatile("{.reg .pred p; elect.sync _|p,0xffffffff; @p mbarrier.arrive.shared::cta.b64 _,[%0];}" :: "r"(bar) : "memory");
}

__device__ __forceinline__ void arrive_both(uint32_t bar, int lane) {
  __syncwarp();
  asm volatile("{.reg .pred p; .reg .u32 a; setp.lt.u32 p,%1,2; mapa.shared::cluster.u32 a,%0,%1;\n"
               "@p mbarrier.arrive.shared::cluster.b64 _,[a];}" :: "r"(bar), "r"(lane) : "memory");
}
#define ELECT "{.reg .pred p; elect.sync _|p,0xffffffff; @p "
__device__ __forceinline__ void e_mc(uint32_t dst, const void* src, uint32_t bytes, uint32_t bar, uint64_t pol) {
  asm volatile(ELECT "cp.async.bulk.shared::cluster.global.mbarrier::complete_tx::bytes.multicast::cluster.L2::cache_hint [%0],[%1],%2,[%3],%4,%5;}"
               :: "r"(dst), "l"(src), "r"(bytes), "r"(bar), "h"((unsigned short)3), "l"(pol) : "memory");
}
__device__ __forceinline__ void e_g2s(uint32_t dst, const void* src, uint32_t bytes, uint32_t bar) {
  asm volatile(ELECT "cp.async.bulk.shared::cluster.global.mbarrier::complete_tx::bytes [%0],[%1],%2,[%3];}" :: "r"(dst), "l"(src), "r"(bytes), "r"(bar) : "memory");
}
__device__ __forceinline__ void e_pf(const void* src, uint32_t bytes) { asm volatile(ELECT "cp.async.bulk.prefetch.L2.global [%0],%1;}" :: "l"(src), "r"(bytes) : "memory"); }
__device__ __forceinline__ void e_expect(uint32_t bar, uint32_t bytes) { asm volatile(ELECT "mbarrier.arrive.expect_tx.shared::cta.b64 _,[%0],%1;}" :: "r"(bar), "r"(bytes) : "memory"); }
__device__ __forceinline__ void e_tma2d(uint32_t dst, const CUtensorMap* m, int x, int y, uint32_t bar) {
  asm volatile(ELECT "cp.async.bulk.tensor.2d.shared::cluster.global.mbarrier::complete_tx::bytes [%0],[%1,{%2,%3}],[%4];}" :: "r"(dst), "l"(m), "r"(x), "r"(y), "r"(bar) : "memory");
}

__device__ __forceinline__ void pack_role(const int* __restrict__ idx, uint32_t sbase, int pc) {
  constexpr int BUF = 32 * 3328;
  const int tid = threadIdx.x, lane = tid & 31, warp = tid >> 5;
  const uint32_t full = sbase + 2 * BUF, empty = full + 16;
  if (tid == 0) { mbar_init(full, 1); mbar_init(full + 8, 1); mbar_init(empty, 18); mbar_init(empty + 8, 18); asm volatile("fence.proxy.async.shared::cta;" ::: "memory"); }
  __syncthreads();
  auto chunk = [&](int s) { return s * 3200 + (s >> 2) * 288; };
  auto load = [&](int n) {
    const int blk = pc * 16 + n;
    if (lane == 0) mbar_expect(full + (n & 1) * 8, 32 * 3200);
    __syncwarp();
    bulk_g2s(sbase + (n & 1) * BUF + chunk(lane), idx + ((blk >> 5) * 8192 + lane * TH + (blk & 31) * 8) * F_, 3200, full + (n & 1) * 8);
  };
  if (warp == 0) { load(0); load(1); }
  const int l = lane & 7;
  uint32_t rot[8], inc[3];
#pragma unroll
  for (int jj = 0; jj < 8; jj++) rot[jj] = ((l + jj) & 7) * 4;
#pragma unroll
  for (int q = 0; q < 3; q++) inc[q] = (l + 3 * q < 8) << 12 | (l + 3 * q + 1 < 8) << 22 | (q < 2 && l + 3 * q + 2 < 8);
  int loaded = 2;
#pragma unroll 1
  for (int task = warp; task < 288; task += 16) {
    const int n = task / 18, q = (task % 18) * 4 + (lane >> 3), sq = q / 9, k = q % 9;
    if (warp == 0 && n + 1 == loaded && loaded < 16) { mbar_wait(empty + (loaded & 1) * 8, ((loaded >> 1) - 1) & 1); load(loaded); loaded++; }
    mbar_wait(full + (n & 1) * 8, (n >> 1) & 1);
    const uint32_t buf = sbase + (n & 1) * BUF + l * 400, row = buf + chunk(sq * 4);
    auto ld = [&](uint32_t ad) { uint32_t v; asm volatile("ld.shared.u32 %0,[%1];" : "=r"(v) : "r"(ad)); return v; };
    const int blk = pc * 16 + n, half = blk >> 5, col = (blk & 31) * 8 + l;
    const int ks = k == NC - 1 ? 0 : k + 1;
    uint32_t cw[4], sv[8], m[2] = {0, 0};
    { const uint32_t a0 = row + (72 + 2 * ks + (l >> 2)) * 4;
#pragma unroll
      for (int u = 0; u < 8; u++) { sv[u] = ld((a0 ^ ((u >> 2) * 4)) + (u & 3) * 3200); m[u >> 2] |= s_mask(sv[u], l & 3) << (8 * (u & 3)); } }
#pragma unroll
    for (int h = 0; h < 2; h++) { m[h] |= __shfl_xor_sync(0xffffffffu, m[h], 1); m[h] |= __shfl_xor_sync(0xffffffffu, m[h], 2); }
#pragma unroll
    for (int u = 0; u < 4; u++) cw[u] = s_cell(sv[u], l & 3, (m[0] >> (8 * u)) & 255) | s_cell(sv[4 + u], l & 3, (m[1] >> (8 * u)) & 255) << 12;
    if (k == NC - 1) {
      auto wide = [&](uint32_t w) { return (w & 0xfff) << 5 | (w >> 12) << 18 | (l & 4 ? 1u << 4 : 1u << 17); };
      g_scr[I0_OFF + (half * 8 + sq) * TH + col] = make_uint4(wide(cw[0]), wide(cw[1]), wide(cw[2]), wide(cw[3]));
      g_scr[IX_OFF + half * IXH + NC * 8192 + sq * TH + col] = make_uint4(ld(row + 396), ld(row + 3596), ld(row + 6796), ld(row + 9996));
      cw[0] = cw[1] = cw[2] = cw[3] = 0;
    }
    const uint32_t ax = buf + chunk(min(sq + 1, 7) * 4) + (90 + k) * 4;
    const uint32_t yev = ld(buf + ((0x3210 >> (sq * 2 + (sq == 5) * 2)) & 3) * 3200 + (90 + k) * 4);
    uint4* dst = g_scr + IX_OFF + half * IXH + (k * NS + sq * 4) * TH + col;
#pragma unroll
    for (int u = 0; u < 4; u++) {
      uint32_t e[8];
#pragma unroll
      for (int jj = 0; jj < 8; jj++) e[jj] = ld(row + k * 32 + rot[jj] + u * 3200);
      dst[u * TH] = make_uint4(pk3(e[0], e[1], e[2] + inc[0]), pk3(e[3], e[4], e[5] + inc[1]), pk3(e[6], e[7], ld(ax + u * 3200) + inc[2]),
                               u < 3 ? __byte_perm(cw[u], cw[3], 0x4210 + (u << 12)) : yev);
    }
    mbar_arrive_lane0(empty + (n & 1) * 8);
  }
}

__global__ void __cluster_dims__(2, 1, 1) __launch_bounds__(512, 1)
k_tens(const __grid_constant__ CUtensorMap mapW, const __grid_constant__ CUtensorMap mapL, const __grid_constant__ CUtensorMap mapS,
       const __grid_constant__ CUtensorMap mapT, const __grid_constant__ CUtensorMap mapE, const __grid_constant__ CUtensorMap mapC, cudaTextureObject_t tex, cudaTextureObject_t texX,
       const int* __restrict__ idx, const __nv_bfloat16* __restrict__ table, const __nv_bfloat16* __restrict__ wp, const __nv_bfloat16* __restrict__ w1,
       const __nv_bfloat16* __restrict__ b1, int never) {
  extern __shared__ __align__(1024) uint4 sm[];
  const int tid = threadIdx.x, lane = tid & 31, cta = blockIdx.x;
  const uint32_t sbase = (uint32_t)__cvta_generic_to_shared(sm);
  const int g = lane >> 2, r = lane & 3;
  TS(0, 0);
  if (cta >= 128) {
    pack_role(idx, sbase, cta - 128);
    __syncthreads();
    if (tid == 0) {
      asm volatile("fence.acq_rel.gpu; griddepcontrol.launch_dependents;" ::: "memory");
      asm volatile("red.relaxed.gpu.global.add.u32 [%0],1;" :: "l"(&g_flag[24 * 32]) : "memory");
    }
    __syncwarp();
    TS(2, 1);
    asm volatile("barrier.cluster.arrive.relaxed.aligned; barrier.cluster.wait.aligned;" ::: "memory");
    return;
  }
  const uint32_t fullB = sbase + K1_BAR, emptyB = fullB + 24, fullE = fullB + 48, fullC = fullB + 56, fullI = fullB + 64, pxRdy = fullB + 72, fullS = fullB + 96, emptyS = fullB + 104, pkDone = fullB + 112, pkFull = fullB + 136, progG = fullB + 168;
  const int rb = cta & 7, hc = cta >> 3;
  if (__shfl_sync(0xffffffffu, tid >> 5, 0) == 12) {
    if (lane == 0) {
#pragma unroll
      for (int q = 0; q < 19; q++) if (q != 2 && q != 5) mbar_init(fullB + q * 8, q == 3 || q == 4 ? 8 : q == 12 ? 4 : q >= 14 && q < 17 ? 2 : 1);
      asm volatile("st.shared.u32 [%0],%1;" :: "r"(progG), "r"(0) : "memory");
    }
    asm volatile("fence.mbarrier_init.release.cluster; fence.proxy.async.shared::cta;" ::: "memory");
    __syncwarp();
    e_expect(fullC, 16384);
#pragma unroll
    for (int q = 0; q < 4; q++) e_tma2d(sbase + 32768 + q * 4096, &mapC, (cta & 15) * 8, q * 256, fullC);
    e_expect(fullE, 32768);
#pragma unroll
    for (int q = 0; q < 2; q++) e_tma2d(sbase + K1_B + 32768 + q * 16384, &mapE, q * 64, rb * 128, fullE);
    asm volatile("bar.arrive 2,512;" ::: "memory");
  }
  asm volatile("barrier.cluster.arrive.relaxed.aligned;" ::: "memory");
  if (tid >= 384) {
    asm volatile("setmaxnreg.dec.sync.aligned.u32 32;");
    if (tid < 416) {
      asm volatile("barrier.cluster.wait.aligned;" ::: "memory");
      if (tid == 384) {
#pragma unroll 1
        for (int n = 0; n < 25; n++) {
          const int st = n & 1, q = quad_of(n);
          if (n == 1) {
            mbar_expect(fullI, 51200);
#pragma unroll 1
            for (int u = 0; u < 8; u++) bulk_g2s(sbase + 76800 + u * 6400, idx + ((cta >> 4) * 8 + u) * 256 * F_, 6400, fullI);
          }
          mbar_wait(emptyB + st * 8, (((n + 1) >> 1) & 1) ^ 1);
          mbar_expect(fullB + st * 8, 32768);
          asm volatile("cp.async.bulk.tensor.2d.shared::cluster.global.mbarrier::complete_tx::bytes.multicast::cluster [%0],[%1,{%2,%3}],[%4],%5;"
                       :: "r"(sbase + K1_B + st * 32768 + (cta & 1) * 16384), "l"(&mapW), "r"(hc * 32), "r"(q * 512 + (cta & 1) * 256),
                          "r"(fullB + st * 8), "h"((unsigned short)3) : "memory");
          if (n + 1 < 25) bulk_pf(w1 + quad_of(n + 1) * 262144 + cta * 2048, 4096);
        }
      }
    } else if (tid < 448) {
      ((float4*)g_acc)[cta * 32 + lane] = make_float4(0.f, 0.f, 0.f, 0.f);
      asm volatile("bar.sync 2,512;" ::: "memory");
      __syncwarp();
      if (tid == 416) {
        int pub = 0;
#pragma unroll 1
        for (int n = 0; n < 50; n++) {
          const int quad = quad_of(n >> 1), mt = n & 1, v0 = rb * 128 + mt * 64;
          const uint32_t stg = sbase + K1_STG;
          if (pub < 3) {
            uint32_t ok = 1;
            if (pub == 0 || n == 49) mbar_wait(pkDone + pub * 8, 0);
            else asm volatile("{.reg .pred p; mbarrier.test_wait.parity.shared::cta.b64 p,[%1],0; selp.u32 %0,1,0,p;}" : "=r"(ok) : "r"(pkDone + pub * 8) : "memory");
            if (ok) {
              asm volatile("cp.async.bulk.wait_group 0;" ::: "memory");
              asm volatile("red.release.gpu.global.add.u32 [%0],1;" :: "l"(&g_flag[((cta >> 4) * 3 + pub) * 32]) : "memory");
              pub++;
              if (n == 49) { n--; continue; }
            }
          }
          mbar_wait(fullS, n & 1);
          asm volatile("fence.proxy.async.shared::cta;" ::: "memory");
          if (quad < 18) {
            asm volatile("cp.async.bulk.tensor.4d.global.shared::cta.bulk_group.L2::cache_hint [%0,{%1,%2,%3,%4}],[%5],%6;"
                         :: "l"(&mapL), "r"((quad & 1) * 32), "r"(hc * 4), "r"(v0), "r"(quad >> 1), "r"(stg), "l"(POL_EF) : "memory");
          } else {
#pragma unroll 1
            for (int hh = 0; hh < 2; hh++) {
              const int pq = quad * 2 + hh;
              asm volatile("cp.async.bulk.tensor.4d.global.shared::cta.bulk_group.L2::cache_hint [%0,{%1,%2,%3,%4}],[%5],%6;"
                         :: "l"(pq < 45 ? &mapS : &mapT), "r"(0), "r"(hc * 4), "r"(v0 >> (pq < 45 ? 2 : 3)), "r"(pq < 45 ? pq - 36 : (pq - 45) * 2), "r"(stg + hh * 8192), "l"(POL_EF) : "memory");
            }
          }
          asm volatile("cp.async.bulk.commit_group;" ::: "memory");
          asm volatile("cp.async.bulk.wait_group.read 0;" ::: "memory");
          mbar_arrive(emptyS);
        }
        asm volatile("cp.async.bulk.wait_group 0;" ::: "memory");
        asm volatile("fence.proxy.async.global;" ::: "memory");
        asm volatile("fence.acq_rel.gpu; griddepcontrol.launch_dependents;" ::: "memory");
        asm volatile("red.relaxed.gpu.global.add.u32 [%0],1;" :: "l"(&g_flag[24 * 32]) : "memory");
        flag_wait(&g_flag[24 * 32], 132);
        asm volatile("fence.proxy.async.global;" ::: "memory");
        const char* base = (const char*)g_scr;
        const int c = cta >> 1, half = cta & 1, ch = (c + (c >> 4) * 5) & 15;
        bulk_pf(base + (PS_OFF + c * NC * 2000) * 16u + half * 16000, 16000);
        bulk_pf(base + (PT_OFF + c * 10 * 1024) * 16u + half * 8000, 8000);
        mbar_expect(fullE, 18432);
        bulk_g2s(sbase + K1_B, base + (I0_OFF + half * 2048 + ch * 128) * 16u, 2048, fullE);
        bulk_g2s(sbase + K1_B + 2048, base + (IX_OFF + half * IXH + ch * 512) * 16u, 8192, fullE);
        bulk_g2s(sbase + K1_B + 10240, base + (IX_OFF + half * IXH + 8192 + ch * 512) * 16u, 8192, fullE);
        mbar_wait(fullE, 1);
      }
    } else {
      const int pw = (tid >> 5) & 1, rg = (cta >> 4) * 8 + ((cta & 15) >> 1), hf = cta & 1;
      const int* ip = idx + (rg * 256 + hf * 8) * F_;
      asm volatile("bar.sync 2,512;" ::: "memory");
      const uint32_t buf = sbase + K1_BAR + 256 + pw * 3200, bar = pkFull + pw * 8;
      const unsigned* fl = &g_flag[(cta >> 4) * 96];
      int batch = 0, rel = pw ? 3 : 0;
#pragma unroll 1
      for (int n = 1 + pw; n < 16; n += 2) {
        if (lane == 0) { mbar_expect(bar, 3200); bulk_g2s(buf, ip + n * 16 * F_, 3200, bar); if (n + 2 < 16) bulk_pf(ip + (n + 2) * 16 * F_, 3200); }
        uint32_t ok; int it = 0;
        do {
          if (rel < batch) {
            unsigned v; asm volatile("ld.relaxed.gpu.global.u32 %0,[%1];" : "=r"(v) : "l"(fl + rel * 32) : "memory");
            if (__all_sync(0xffffffffu, v >= 16)) { flag_wait(fl + rel * 32, 16); mbar_arrive_lane0(pxRdy + rel * 8); rel++; }
          }
          asm volatile("{.reg .pred p; mbarrier.test_wait.parity.shared::cta.b64 p,[%1],%2; selp.u32 %0,1,0,p;}" : "=r"(ok) : "r"(bar), "r"(((n - 1) >> 1) & 1) : "memory");
          ok = __all_sync(0xffffffffu, ok);
          if (!ok) __nanosleep(100);
        } while (!ok && ++it < (1 << 20));
        auto ld = [&](uint32_t ad) { uint32_t v; asm volatile("ld.shared.u32 %0,[%1];" : "=r"(v) : "r"(ad)); return v; };
        const uint32_t p0 = buf + ((lane >> 3) & 1) * 400 + ((lane >> 4) * 8 + (lane & 7)) * 4;
        auto wd = [&](int t, int h) { return pk3(ld(p0 + t * 800 + h * 192), ld(p0 + t * 800 + h * 192 + 64), ld(p0 + t * 800 + h * 192 + 128)); };
        uint4* dst = g_scr + PX_OFF + (rg * 16 + n) * 136;
        ((unsigned short*)(dst + 128))[lane * 2 + hf] = ld(buf + g * 400 + 384 + r * 4);
#pragma unroll
        for (int q = 0; q < 2; q++) dst[(hf * 2 + q) * 32 + lane] = make_uint4(wd(2 * q, 0), wd(2 * q, 1), wd(2 * q + 1, 0), wd(2 * q + 1, 1));
        __syncwarp();
        if (n <= 2 || n == 5 || n == 6 || n >= 14) { mbar_arrive_lane0(pkDone + batch * 8); batch++; }
      }
      for (; rel < 3; rel++) { flag_wait(fl + rel * 32, 16); mbar_arrive_lane0(pxRdy + rel * 8); }
      if (lane == 0) {
        mbar_wait(pxRdy + 16, 0);
        asm volatile("fence.proxy.async.global;" ::: "memory");
        const char* src = (const char*)(g_scr + PX_OFF + ((cta >> 4) * 8 + ((cta >> 1) & 3) * 2 + pw) * 16 * 136);
        int ph = pw;
#pragma unroll 1
        for (int n = 5; n < 16; n++) {
          uint32_t cur; int it = 0;
          do { asm volatile("ld.volatile.shared.u32 %0,[%1];" : "=r"(cur) : "r"(progG)); if (cur + 2 < n) __nanosleep(400); } while (cur + 2 < n && ++it < (1 << 16));
          if (cur + 1 >= n) continue;
          mbar_expect(bar, 2176); bulk_g2s(buf, src + n * 2176, 2176, bar);
          mbar_wait(bar, ph); ph ^= 1;
        }
      }
    }
    return;
  }
  if (tid >= 256) {
    asm volatile("setmaxnreg.inc.sync.aligned.u32 160;");
    const int w = (tid >> 5) & 3;
    const int srow = w * 16 + ((lane & 15) ^ ((lane & 1) << 2)), sc = lane >> 4;
    uint32_t a[2][8][4];
    asm volatile("bar.sync 2,512;" ::: "memory");
    mbar_wait_fast(fullE, 0);
#pragma unroll
    for (int mt = 0; mt < 2; mt++)
#pragma unroll
      for (int ks = 0; ks < 8; ks++)
        asm volatile("ldmatrix.sync.aligned.m8n8.x4.shared.b16 {%0,%1,%2,%3},[%4];"
                     : "=r"(a[mt][ks][0]), "=r"(a[mt][ks][1]), "=r"(a[mt][ks][2]), "=r"(a[mt][ks][3])
                     : "r"(sbase + K1_B + 32768 + (ks >> 2) * 16384 + (mt * 64 + srow) * 128 + ((((ks & 3) * 2 + sc) ^ (srow & 7)) * 16)) : "memory");
    asm volatile("barrier.cluster.wait.aligned;" ::: "memory");
    arrive_both(emptyB + 8, lane);
    const int v = w * 16 + (g ^ ((g & 1) << 2));
    const uint32_t baseL = v * 256 + r * 64 + ((v & 1) * 2 + (r >> 1)) * 16, baseS = (v >> 2) * 512 + r * 128 + (((v & 3) * 2) ^ ((v & 4) + r)) * 16,
                   baseT = (v >> 3) * 512 + r * 128 + ((v & 7) ^ r) * 16;
    const uint64_t desc0 = (uint64_t)(((sbase + K1_B) & 0x3FFFF) >> 4) | ((uint64_t)(8192 >> 4) << 16) | ((uint64_t)(512 >> 4) << 32) | (2ull << 62);
#pragma unroll 1
    for (int qn = 0; qn < 25; qn++) {
      const int quad = quad_of(qn), st = qn & 1;
      const bool isL = quad < 18;
      PT(qn * 16);
      mbar_wait_fast(fullB + st * 8, (qn >> 1) & 1);
#pragma unroll
      for (int mt = 0; mt < 2; mt++) {
        float d[64];
        PT(qn * 16 + mt * 4 + 1);
        asm volatile("wgmma.fence.sync.aligned;" ::: "memory");
#pragma unroll
        for (int ks = 0; ks < 8; ks++) wgmma_p(d, a[mt][ks], desc0 + st * 2048 + ks * 64, ks);
        asm volatile("wgmma.commit_group.sync.aligned;" ::: "memory");
        mbar_wait_fast(emptyS, mt ^ 1);
        PT(qn * 16 + mt * 4 + 2);
        asm volatile("wgmma.wait_group.sync.aligned 0;" ::: "memory");
#pragma unroll
        for (int q = 0; q < 16; q++) asm volatile("" : "+f"(d[q * 4]), "+f"(d[q * 4 + 1]), "+f"(d[q * 4 + 2]), "+f"(d[q * 4 + 3]) :: "memory");
        PT(qn * 16 + mt * 4 + 3);
        if (mt) arrive_both(emptyB + st * 8, qn < 23 ? lane : 9);
        if (quad == 24) {
#pragma unroll
          for (int cq = 0; cq < 4; cq++) {
            const uint32_t bw = __ldg((const uint32_t*)(b1 + hc * 32 + cq * 8) + r);
#pragma unroll
            for (int e = 0; e < 4; e++) d[48 + cq * 4 + e] += (e & 1) ? bf_hi(bw) : bf_lo(bw);
          }
        }
#pragma unroll
        for (int h = 0; h < 2; h++) {
          const bool isS = quad * 2 + h < 45;
          const uint32_t base = (isL ? baseL ^ (h * 32) : (isS ? baseS : baseT) ^ (h * 8192)), xj = isS ? 16 : 4096, xr = isL ? 2048 : isS ? 1024 : 576;
#pragma unroll
          for (int e4 = 0; e4 < 4; e4++) {
            const float* e = d + h * 32 + (e4 >> 1) * 16 + (e4 & 1) * 2;
            sts128(sbase + K1_STG + (base ^ ((e4 >> 1) * xj) ^ ((e4 & 1) * xr)),
                   make_uint4(pack_bf2(e[0], e[1]), pack_bf2(e[4], e[5]), pack_bf2(e[8], e[9]), pack_bf2(e[12], e[13])));
          }
        }
        mbar_arrive_lane0(fullS);
        if (!mt) PT(qn * 16 + 4);
      }
      PT(qn * 16 + 8);
    }
    return;
  }
  const int slice = cta & 15;
  const int range = (cta >> 4) * 8 + __shfl_sync(0xffffffffu, tid >> 5, 0);
  uint4 iv[4], trow[4]; uint32_t ix;
  uint2 wrow[10];
#pragma unroll
  for (int q = 0; q < 10; q++) asm volatile("ld.global.nc.v2.u32 {%0,%1},[%2];" : "=r"(wrow[q].x), "=r"(wrow[q].y) : "l"((const uint2*)wp + min(tid + q * 256, 2499)));
  asm volatile("bar.sync 2,512;" ::: "memory");
  uint32_t me = 0, mw = 0;
#pragma unroll
  for (int q = 0; q < 10; q++) {
    mw = __vmaxu2(__vmaxu2(wrow[q].x & 0x7fff7fffu, wrow[q].y & 0x7fff7fffu), mw);
    const int e = min(tid + q * 256, 2499), row = e / 25;
    asm volatile("st.shared.v2.u32 [%0],{%1,%2};" :: "r"(sbase + (e + row) * 8), "r"(wrow[q].x), "r"(wrow[q].y) : "memory");
    if (e - row * 25 == 24) asm volatile("st.shared.v2.u32 [%0],{%1,%2};" :: "r"(sbase + (e + row) * 8 + 8), "r"(wrow[q].x), "r"(wrow[q].y) : "memory");
  }
  mbar_wait_fast(fullC, 0);
#pragma unroll
  for (int q = 0; q < 4; q++) { trow[q] = lds128(sbase + 32768 + (tid + q * 256) * 16); me = absmax4(trow[q], me); }
  me = __reduce_max_sync(0xffffffffu, max(me & 0xffff, me >> 16));
  mw = __reduce_max_sync(0xffffffffu, max(mw & 0xffff, mw >> 16));
  uint32_t* sred = (uint32_t*)((char*)sm + 128000);
  if (lane == 0) sred[tid >> 5] = me | mw << 16;
  TS(3, 0);
  asm volatile("setmaxnreg.inc.sync.aligned.u32 160;");
  asm volatile("bar.sync 1,256;" ::: "memory");
  { uint32_t m = 0;
#pragma unroll
    for (int q = 0; q < 8; q++) m = __vmaxu2(m, sred[q]);
    m = __shfl_sync(0xffffffffu, m, 0);
    me = m & 0xffff; mw = m >> 16; }
  const float se = pow2_scale(me, 3), sW = pow2_scale(mw, -2);
  TS(3, 1);
  auto put_rows = [&](int q, bool on) {
    const uint4 t = trow[q];
    const uint4 hv = make_uint4(pack_h2(bf_lo(t.x) * se, bf_hi(t.x) * se), pack_h2(bf_lo(t.y) * se, bf_hi(t.y) * se),
                                pack_h2(bf_lo(t.z) * se, bf_hi(t.z) * se), pack_h2(bf_lo(t.w) * se, bf_hi(t.w) * se));
    if (on)
#pragma unroll
      for (int s = 0; s < 8; s++) sts128(sbase + (tid + q * 256) * 128 + ((s + lane) & 7) * 16, hv);
  };
#pragma unroll 1
  for (int it = 0; it < 3; it++) {
    const int hu = ((tid >> 5) * 3 + it) * 4, code = hu_code(min(hu + (lane >> 3), HU_N - 1)), ok = code >> 4, on = code & 15;
    uint32_t x[4], y[4];
    asm volatile("ldmatrix.sync.aligned.m8n8.x4.shared.b16 {%0,%1,%2,%3},[%4];" : "=r"(x[0]), "=r"(x[1]), "=r"(x[2]), "=r"(x[3])
                 : "r"(sbase + (on * 8 + (lane & (on == 12 ? 3 : 7))) * 208 + ok * 16) : "memory");
    asm volatile("ldmatrix.sync.aligned.m8n8.x4.trans.shared.b16 {%0,%1,%2,%3},[%4];" : "=r"(y[0]), "=r"(y[1]), "=r"(y[2]), "=r"(y[3])
                 : "r"(sbase + (ok * 8 + (lane & (ok == 12 ? 3 : 7))) * 208 + on * 16) : "memory");
    const uint32_t lo = __ballot_sync(0xffffffffu, ok > on), dg = __ballot_sync(0xffffffffu, ok >= on);
#pragma unroll
    for (int q = 0; q < 4; q++) {
      const float m0 = (lo >> (8 * q)) & 1 ? 0.f : sW, m1 = (dg >> (8 * q)) & 1 ? 0.f : sW;
      asm volatile("st.shared.u32 [%0],%1;" :: "r"(sbase + K1_W + (hu + q) * 128 + lane * 4),
                   "r"(pack_h2(fmaf(bf_lo(x[q]), m0, bf_lo(y[q]) * m1), fmaf(bf_hi(x[q]), m0, bf_hi(y[q]) * m1))) : "memory");
    }
  }
  put_rows(1, true); put_rows(2, tid < 88);
  TS(3, 2);
  asm volatile("fence.proxy.async.shared::cta;" ::: "memory");
  asm volatile("bar.sync 1,256;" ::: "memory");
  put_rows(0, true);
  uint32_t bf[HU_N - 2 * G_U];
#pragma unroll
  for (int q = 0; q < HU_N - 2 * G_U; q++) asm volatile("ld.shared.u32 %0,[%1];" : "=r"(bf[q]) : "r"(sbase + K1_W + (2 * G_U + q) * 128 + lane * 4));
  if (cta < 16 && tid == 0) g_unscale[cta] = make_float2(__uint_as_float(0x7f000000u - __float_as_uint(se)), __uint_as_float(0x7f000000u - __float_as_uint(sW)));
  TS(3, 3);
  const int px = range * 16 * 136;
  mbar_wait_fast(fullI, 0);
  {
    const uint32_t ib = sbase + 76800 + (tid >> 5) * 6400, p0 = ib + ((lane >> 3) & 1) * 400 + ((lane >> 4) * 8 + (lane & 7)) * 4;
    auto ld = [&](uint32_t ad) { uint32_t v; asm volatile("ld.shared.u32 %0,[%1];" : "=r"(v) : "r"(ad)); return v; };
    auto wd = [&](int t, int h) { return pk3(ld(p0 + t * 800 + h * 192), ld(p0 + t * 800 + h * 192 + 64), ld(p0 + t * 800 + h * 192 + 128)); };
#pragma unroll
    for (int q = 0; q < 4; q++) {
      iv[q] = make_uint4(wd(2 * q, 0), wd(2 * q, 1), wd(2 * q + 1, 0), wd(2 * q + 1, 1));
    }
    ix = ld(ib + g * 400 + 384 + r * 4) | ld(ib + (8 + g) * 400 + 384 + r * 4) << 16;
  }
  asm volatile("bar.sync 1,256;" ::: "memory");
  put_rows(2, tid >= 88); put_rows(3, tid + 768 < V_);
  asm volatile("bar.sync 1,256;" ::: "memory");
  TS(0, 1);
  uint32_t lc; asm volatile("add.u32 %0,%1,%2;" : "=r"(lc) : "r"((lane & 7) * 16), "r"(never));
  const uint64_t wdesc = (uint64_t)(((sbase + K1_W) & 0x3FFFF) >> 4) | ((uint64_t)(128 >> 4) << 16) | ((uint64_t)(256 >> 4) << 32);
  uint32_t a[2][6][4], d[2][26], ex[4] = {}, s[4] = {};
  float red[4] = {0.f, 0.f, 0.f, 0.f};
  auto ldsm = [&](uint32_t* o, uint32_t sh) {
    asm volatile("ldmatrix.sync.aligned.m8n8.x4.trans.shared.b16 {%0,%1,%2,%3},[%4];"
                 : "=r"(o[0]), "=r"(o[1]), "=r"(o[2]), "=r"(o[3]) : "r"(sbase + ((sh & 0x1ff80) | lc)));
  };
  auto gather = [&](int t, int hf) {
    const int x = t & 1;
    const uint4 v = iv[(t >> 1) & 3];
#pragma unroll
    for (int kb = 3 * hf; kb < 3 * hf + 3; kb++) {
      const uint32_t ww = x ? (kb < 3 ? v.z : v.w) : (kb < 3 ? v.x : v.y);
      ldsm(a[x][kb], kb % 3 == 0 ? ww : kb % 3 == 1 ? ww >> 10 : __funnelshift_l(ww, ww, 12));
    }
  };
  auto issue = [&](int x) {
    asm volatile("wgmma.fence.sync.aligned;" ::: "memory");
#pragma unroll
    for (int kb = 0; kb < 6; kb++) {
      if (kb < G_K0) wgmma_h<G_N0 * 8>(d[x] + G_O0 * 2, a[x][kb], wdesc + kb * G_N0 * 16, kb);
      if (kb < G_K1) wgmma_h<G_N1 * 8>(d[x] + G_O1 * 2, a[x][kb], wdesc + (G_U1 + kb * G_N1) * 16, kb);
      if (kb < G_K2) wgmma_h<32>(d[x] + G_O2 * 2, a[x][kb], wdesc + (G_U2 + kb * G_N2) * 16, kb);
    }
    asm volatile("wgmma.commit_group.sync.aligned;" ::: "memory");
  };
  auto hmma_part = [&](int t) {
    constexpr FragIdx FI = make_fi();
    const int x = t & 1;
#pragma unroll
    for (int o = 0; o < 13; o++) asm volatile("" : "+r"(d[x][o * 2]), "+r"(d[x][o * 2 + 1]) :: "memory");
#pragma unroll
    for (int kb = 0; kb < 6; kb++)
#pragma unroll
      for (int o = 2 * kb + 1; o < 13; o++)
        if (!unit_wg(kb, o)) mma16816h(d[x] + o * 2, a[x][kb], bf[FI.v[2 * kb][o]], bf[FI.v[2 * kb + 1][o]]);
#pragma unroll
    for (int q = 0; q < 6; q++) if (!unit_wg(q, 2 * q)) mma1688h(d[x] + q * 4, a[x][q][0], a[x][q][1], bf[FI.v[2 * q][2 * q]]);
    mma1688h(d[x] + 24, r < 2 ? ex[t & 3] : 0u, r < 2 ? 0u : ex[t & 3], bf[FI.v[12][12]]);
  };
  auto dot_part = [&](int t, int hf) {
    const int x = t & 1;
    if (hf == 0) {
      const uint32_t pe = hfma2(r < 2 ? d[x][24] : d[x][25], ex[t & 3], 0u);
      s[0] = r < 2 ? pe : 0u; s[1] = r < 2 ? 0u : pe; s[2] = s[3] = 0;
    }
#pragma unroll
    for (int q = 3 * hf; q < 3 * hf + 3; q++)
#pragma unroll
      for (int e = 0; e < 4; e++) s[e] = hfma2(d[x][q * 4 + e], a[x][q][e], s[e]);
  };
  const float* outp = g_partP + slice * B_ + range * 256;
  uint32_t oofs; asm volatile("add.u32 %0,%1,%2;" : "=r"(oofs) : "r"((r * 4 + ((lane >> 3) & 1) * 2 + (lane >> 4)) * 4), "r"(never));
  float k0 = 0.f, k1 = 0.f, x0 = 0.f, x1 = 0.f;
  auto red_stage = [&](int st, int grp) {
    const bool u16 = lane & 16, u8 = lane & 8;
    if (st == 0) {
      k0 = u16 ? red[2] : red[0]; x0 = __shfl_xor_sync(0xffffffffu, u16 ? red[0] : red[2], 16);
      k1 = u16 ? red[3] : red[1]; x1 = __shfl_xor_sync(0xffffffffu, u16 ? red[1] : red[3], 16);
      red[0] = red[1] = red[2] = red[3] = 0.f;
    }
    if (st == 1) { const float p0 = k0 + x0, p1 = k1 + x1; k0 = u8 ? p1 : p0; x0 = __shfl_xor_sync(0xffffffffu, u8 ? p0 : p1, 8); }
    if (st == 2) { k0 += x0; x0 = __shfl_xor_sync(0xffffffffu, k0, 4); }
    if (st == 3) asm volatile("st.global.f32 [%0],%1;" :: "l"((const char*)(outp + grp * 16) + oofs), "f"(k0 + x0) : "memory");
  };
  auto side = [&](bool first, int t, int prv, int cur, int nxt) {
    const int pn = PX_OFF + px + nxt * 136 + lane;
    if (!first) {
      if (t == 0) { iv[3] = ldtex(tex, PX_OFF + px + cur * 136 + lane + 96); iv[0] = ldtex(tex, pn); }
      if (t == 2) iv[1] = ldtex(tex, pn + 32);
      if (t < 4) red_stage(t, prv);
    } else if (t == 4) {
      TS(4, 2);
      mbar_wait_fast(pxRdy, 0);
      TS(4, 3);
      iv[0] = ldtex(tex, pn); iv[1] = ldtex(tex, pn + 32);
    }
    if (t == 4) { ix = ldtex(texX, (px + nxt * 136 + 128) * 4 + lane).x; iv[2] = ldtex(tex, pn + 64); }
  };
  auto group = [&](bool first, int prv, int cur, int nxt, int part) {
#pragma unroll
    for (int t = part ? 7 : 0; t < 8; t++) {
      if (!part) {
        if (first || t) SCHED_FENCE(never, t * 8);
        side(first, t, prv, cur, nxt);
        dot_part(t, 0);
        SCHED_FENCE(never, t * 8 + 1);
        if (t == 3) ldsm(ex, ix >> 9);
        if (t == 7) ldsm(ex, ix << 7);
        gather(t + 2, 0);
        dot_part(t, 1);
        s[0] = hadd2(s[0], s[2]); s[1] = hadd2(s[1], s[3]);
        if (first || t < 7) SCHED_FENCE(never, t * 8 + 4);
        if (t == 7) break;
      }
      gather(t + 2, 1);
      asm volatile("wgmma.wait_group.sync.aligned 0;" ::: "memory");
      asm volatile("" : "+r"(d[(t & 1) ^ 1][0]) :: "memory");
      mma1688f(red, s[0], s[1], (g | (d[(t & 1) ^ 1][0] & never)) == t ? 0x3c003c00u : 0u);
      hmma_part(t + 1);
      issue(t & 1);
    }
  };
  gather(0, 0); gather(0, 1); issue(0); ldsm(ex, ix << 7); gather(1, 0); gather(1, 1);
  asm volatile("wgmma.wait_group.sync.aligned 0;" ::: "memory");
  hmma_part(0);
  SCHED_FENCE(never, 99);
  issue(1);
  group(true, 0, 0, 1, 0); group(true, 0, 0, 1, 1);
  TS(4, 1);
#pragma unroll 1
  for (int n = 1;; n++) {
    if ((n & 11) == 2) mbar_wait_fast(pxRdy + 8 + (n & 4) * 2, 0);
    asm volatile("st.volatile.shared.u32 [%0],%1;" :: "r"(progG), "r"(n) : "memory");
    group(false, n - 1, n, min(n + 1, 15), 0);
    if (n == 15) break;
    group(false, n - 1, n, min(n + 1, 15), 1);
  }
  asm volatile("wgmma.wait_group.sync.aligned 0;" ::: "memory");
  mma1688f(red, s[0], s[1], g == 7 ? 0x3c003c00u : 0u);
#pragma unroll
  for (int st = 0; st < 4; st++) red_stage(st, 15);
  TS(0, 2);
  asm volatile("barrier.cluster.wait.aligned;" ::: "memory");
  asm volatile("barrier.cluster.arrive.relaxed.aligned; barrier.cluster.wait.aligned;" ::: "memory");
}

constexpr int SM_U = 130048, SM_BAR = 128000, SM_J = SM_U + 98304, DEEP_SMEM = SM_J + 4096;

__global__ void __cluster_dims__(2, 1, 1) __launch_bounds__(TH + 128, 1)
k_deep(cudaTextureObject_t tex, const __nv_bfloat16* __restrict__ w2, const __nv_bfloat16* __restrict__ b2,
       __nv_bfloat16* __restrict__ out, int never) {
  extern __shared__ __align__(1024) uint4 sm[];
  constexpr int PF = 4, DEPTH = 4, NW = TH / 32;
  const int tid = threadIdx.x;
  const int c = blockIdx.x >> 1, half = blockIdx.x & 1;
  const uint32_t sbase = (uint32_t)__cvta_generic_to_shared(sm);
  const uint32_t fullL = sbase + SM_BAR, fullU = fullL + 8, emptyL = fullL + 16, emptyU = fullL + 24, barJ = fullL + 32, barW = fullL + 48;
  TS(1, 0);
  if (tid == 0) {
    mbar_init(fullL, 1); mbar_init(fullU, 1); mbar_init(emptyL, 2 * NW); mbar_init(emptyU, 2 * NW); mbar_init(barJ, 1); mbar_init(barW, 1);
    asm volatile("fence.mbarrier_init.release.cluster;" ::: "memory");
  }
  __syncwarp();
  const int wrp = __shfl_sync(0xffffffffu, tid >> 5, 0);
  const char* base = (const char*)g_scr;
  uint32_t oL = (PL_OFF + c * NC * 8000) * 16u + half * 64000, oS = (PS_OFF + c * NC * 2000) * 16u + half * 16000;
  asm volatile("barrier.cluster.arrive.relaxed.aligned; barrier.cluster.wait.aligned;" ::: "memory");
  if (wrp == NW) {
    asm volatile("fence.proxy.async.global;" ::: "memory");
    e_expect(fullU, 96000);
#pragma unroll
    for (int m = 0; m < 3; m++) e_mc(sbase + SM_U + m * 32032 + half * 16000, base + oS, 16000, fullU, m == 2 ? POL_EF : POL_N);
    e_expect(fullL, 128000);
  }
  TS(5, 1);
  if (wrp >= NW) {
    asm volatile("setmaxnreg.dec.sync.aligned.u32 24;");
    if (wrp == NW) {
      uint32_t oT = (PT_OFF + c * 10 * 1024) * 16u + half * 8000;
      auto warm = [&](uint32_t off, uint32_t hb) {
        asm volatile(ELECT "mbarrier.expect_tx.relaxed.cta.shared::cta.b64 [%0],%1;}" :: "r"(barJ), "r"(2 * hb) : "memory");
        e_g2s(sbase + SM_J, base + off, hb, barJ); e_g2s(sbase + SM_J, base + off + hb, hb, barJ);
      };
      mbar_wait(fullU, 0);
      e_mc(sbase + half * 64000, base + oL, 64000, fullL, POL_EF);
      warm(oT, 4000);
#pragma unroll 1
      for (int k = 0; k + 1 < NC; k++) {
        oL += 128000; oS += 32000; oT += 16384;
        mbar_wait(fullL, k & 1);
        const uint32_t t0 = clock();
        e_pf(base + oS, 16000);
        warm((IX_OFF + half * IXH + (k + 2) * 8192 + ((c + (c >> 4) * (2 * k + 1)) & (k + 2 < NC ? 15 : 3)) * 512) * 16u, 4096);
        mbar_wait(emptyU, k & 1);
        e_expect(fullU, 96000);
#pragma unroll 1
        for (int q = 0; q < 8; q++) {
          sleep_until(t0, q * PACE);
          e_pf(base + oL + q * 8000, 8000);
          if (q >= 2) e_mc(sbase + SM_U + ((q - 2) >> 1) * 32032 + half * 16000 + (q & 1) * 8000, base + oS + (q & 1) * 8000, 8000, fullU, q >= 6 ? POL_EF : POL_N);
        }
        warm(oT, 4000);
        e_expect(fullL, 128000);
        sleep_until(t0, RSV_T);
        unsigned long long now, slot = 0;
        asm volatile("mov.u64 %0,%globaltimer;" : "=l"(now));
        if ((tid & 31) == 0) { atomicMax(&g_slot, now + RSV_L); slot = atomicAdd(&g_slot, (unsigned long long)RSV); }
        slot = __shfl_sync(0xffffffffu, slot, 0);
        for (int it = 0; it < 4000; it++) { asm volatile("mov.u64 %0,%globaltimer;" : "=l"(now)); if (now >= slot) break; }
        mbar_wait(emptyL, k & 1);

        e_mc(sbase + half * 64000, base + oL, 64000, fullL, POL_EF);
      }
      mbar_wait(fullL, (NC - 1) & 1);
      mbar_wait(emptyU, (NC - 1) & 1);
      mbar_arrive_lane0(fullU);
      warm(oT + 16384, 4000);
      mbar_arrive_lane0(barJ); mbar_wait(barJ, 0);
    } else if (tid >= TH + 96) {
      if (tid < TH + 100) asm volatile("st.shared.u32 [%0],%1;" :: "r"(barJ + 32 + (tid & 3) * 4), "r"(((const uint32_t*)w2)[(c >> 2) * 16 + (tid & 3) * 4 + (c & 3)]) : "memory");
      mbar_arrive_lane0(barW);
      asm volatile("griddepcontrol.wait;" ::: "memory");
      const int b = half * 8192 + c * 128 + (tid & 31) * 4;
      const float bias = __bfloat162float(b2[0]);
      float4 s = make_float4(bias, bias, bias, bias);
#pragma unroll 2
      for (int k = 0; k < 16; k++) {
        const float4 v = __ldcg((const float4*)(g_partP + k * B_ + b)); const float2 u = __ldcg(g_unscale + k);
        s.x = fmaf(v.x * u.x * u.x, u.y, s.x); s.y = fmaf(v.y * u.x * u.x, u.y, s.y); s.z = fmaf(v.z * u.x * u.x, u.y, s.z); s.w = fmaf(v.w * u.x * u.x, u.y, s.w);
      }
      asm volatile("red.global.add.v4.f32 [%0],{%1,%2,%3,%4};" :: "l"(g_acc + b), "f"(s.x), "f"(s.y), "f"(s.z), "f"(s.w) : "memory");
      asm volatile("bar.arrive 1,%0;" :: "n"(TH + 32) : "memory");
    }
    return;
  }
  asm volatile("setmaxnreg.inc.sync.aligned.u32 240;");
  const int lane = tid & 31;
  const int tbase = PT_OFF + c * 10 * 1024;
  const int ibase = IX_OFF + half * IXH + tid;
  const uint32_t lc = (tid & 7) << 4;
  uint4 acc[NS], wq[PF], x[DEPTH], y[YD], ye;
  uint32_t sw[NS] = {};
  auto sget = [&](int s) { return (s & 3) == 3 ? __byte_perm(__byte_perm(sw[s - 3], sw[s - 2], 0x0073), sw[s - 1], 0x0710) : sw[s]; };
  auto sa0 = [&](uint32_t v) { return sbase + SM_U + (((v << 5) & 0x1ffe0) | ((lc >> 2) & 16)); };
  uint32_t c1 = 0;
  auto sa1 = [&](uint32_t v) { return sbase + SM_U + (((v >> 7) & 0x1ffe0) | c1); };
  {
    uint4 i0[8];
#pragma unroll
    for (int q = 0; q < 8; q++) i0[q] = ldtex(tex, I0_OFF + (half * 8 + q) * TH + tid);
    auto wd = [&](int k) { return (k & 3) == 0 ? i0[k >> 2].x : (k & 3) == 1 ? i0[k >> 2].y : (k & 3) == 2 ? i0[k >> 2].z : i0[k >> 2].w; };
    TS(5, 2);
    mbar_wait_fast(fullU, 0);
#pragma unroll
    for (int i = 0; i < PF; i++) wq[i] = ldtex(tex, ibase + i * TH);
    TS(1, 1);
#pragma unroll
    for (int s = 0; s < NS; s++) acc[s] = add4(lds128(sbase + SM_U + (wd(s) & 0x1fff0)), lds128(sbase + SM_U + ((wd(s) >> 13) & 0x1fff0)));
    arrive_both(emptyU, lane);
    mbar_wait_fast(barW, 0);
    TS(5, 3);
  }
  uint4 w = wq[0];
  auto lds_l = [&](int jj, int slot) {
    const uint32_t ww = jj < 3 ? w.x : jj < 6 ? w.y : w.z;
    const uint32_t sh = jj % 3 == 0 ? ww : jj % 3 == 1 ? ww >> 10 : __funnelshift_l(ww, ww, 12);
    x[slot] = lds128(sbase + ((sh & 0x1ff80) | lc) + jj * 16 - 128);
  };
  mbar_wait_fast(fullL, 0);
  lds_l(0, 0); lds_l(1, 1); lds_l(2, 2); lds_l(3, 3);
#pragma unroll 1
  for (int k = 0; k < NC; k++) {
    const int ti = ibase + k * 8192;
    const int tb = tbase + k * 1024;
    const bool more = k + 1 < NC;
    TR(k * 4);
    TR(k * 4 + 2);
    uint4 cc; uint32_t yc;
    constexpr int TL = NS * 8, TT = TL + NS * 2;
#pragma unroll
    for (int t = 0; t < TT + DEPTH; t += 2) {
      if (t == TL + DEPTH && !more) break;
      if (t >= DEPTH) {
        const int u = t - DEPTH;
        uint4 p = add4(x[u % DEPTH], x[(u + 1) % DEPTH]);
        if (u < TL) {
          const int s = u >> 3, j = u & 7;
          if (j == 0) {
            cc = s >= YD ? add4(y[s % YD], p) : p;
            if (s + YD < NS) y[s % YD] = ldtex(tex, tb | (yc & 1023));
          } else cc = add4(cc, p);
          if (j == 6) acc[s] = add4(acc[s], cc);
        } else {
          const int s = (u - TL) >> 1;
          acc[s] = add4(acc[s], p);
        }
      }
      if (t < TL) {
        const int s = t >> 3, j = t & 7;
        if (j == 0) {
          if (ye_of(s - YD) >= 0) acc[ye_of(s - YD) & 3] = add4(acc[ye_of(s - YD) & 3], ye);
          w = wq[s % PF];
          wq[s % PF] = ldtex(tex, ti + (s + PF) * TH);
          yc = __funnelshift_l(w.z, w.z, 5);
          if ((s & 3) != 3) asm volatile("add.u32 %0,%1,%2;" : "=r"(sw[s]) : "r"(w.w), "r"(never));
          if (ye_of(s) >= 0) ye = ldtex(tex, tb | w.w);
        }
        if (t >= DEPTH) { lds_l(j, t % DEPTH); lds_l(j + 1, (t + 1) % DEPTH); }
      } else if (t < TT) {
        const int s = (t - TL) >> 1;
        if (s == 0) {
          asm volatile("add.u32 %0,%1,%2;" : "=r"(c1) : "r"((~lc >> 2) & 16), "r"(never));
          arrive_both(emptyL, more ? lane : 9);
          TR(k * 4 + 3);
          mbar_wait_fast(fullU, (k + 1) & 1);
        }
        const uint32_t sv = sget(s);
        x[t % DEPTH] = lds128(sa0(sv));
        x[(t + 1) % DEPTH] = lds128(sa1(sv));
      } else {
        if (t == TT) { arrive_both(emptyU, lane); mbar_wait_fast(fullL, (k + 1) & 1); w = wq[0]; }
        lds_l(t - TT, t % DEPTH); lds_l(t - TT + 1, (t + 1) % DEPTH);
      }
      if ((t & 3) == 2 && t > 2 && t < TT) SCHED_FENCE(never, t);
    }
  }
  TS(1, 2);
  const uint4 w2v = lds128(barJ + 32);
  const uint32_t cell = sbase + SM_U + tid * 16;
  const int t9 = tbase + 9 * 1024;
  uint4 za[4], i9 = wq[0];
  auto fetch = [&](int q) {
    y[0] = ldtex(tex, t9 | i9.x); y[1] = ldtex(tex, t9 | i9.y); y[2] = ldtex(tex, t9 | i9.z); y[3] = ldtex(tex, t9 | i9.w);
    if (q) {
      i9 = ldtex(tex, ibase + NC * 8192 + min(q + 1, 7) * TH);
      const uint32_t ca = cell + (q > 6 ? 0 : q - 1) * 16384;
#pragma unroll
      for (int s = 0; s < 4; s++) za[s] = lds128(ca + s * 4096);
    }
  };
  fetch(0);
  i9 = wq[1];
#pragma unroll
  for (int s = 0; s < 4; s++) za[s] = acc[s];
#pragma unroll
  for (int s = 0; s < 24; s++) sts128(cell + s * 4096, acc[4 + s]);
  float hw[8];
  {
    const uint32_t ww[4] = {w2v.x, w2v.y, w2v.z, w2v.w};
#pragma unroll
    for (int k = 0; k < 8; k++) hw[k] = 0.5f * ((k & 1) ? bf_hi(ww[k >> 1]) : bf_lo(ww[k >> 1]));
  }
  float* outp = g_acc + half * 8192 + tid;
#pragma unroll 1
  for (int q = 0; q < NS / 4; q++) {
    uint4 z[4];
#pragma unroll
    for (int s = 0; s < 4; s++) z[s] = add4(za[s], y[s]);
    if (q == 1) {
#pragma unroll
      for (int s = 0; s < 4; s++) sts128(cell + s * 4096, acc[28 + s]);
    }
    if (q < 7) fetch(q + 1);
    SCHED_FENCE(never, 999);
#pragma unroll
    for (int s = 0; s < 4; s++) {
      const uint32_t a[4] = {z[s].x, z[s].y, z[s].z, z[s].w};
      float r0 = 0.f;
#pragma unroll
      for (int k = 0; k < 8; k++) {
        const float v = (k & 1) ? bf_hi(a[k >> 1]) : bf_lo(a[k >> 1]);
        const float u = v * fmaf(v * v, 0.7978845608028654f * 0.044715f, 0.7978845608028654f);
        float th; asm("tanh.approx.f32 %0,%1;" : "=f"(th) : "f"(u));
        r0 = fmaf(fmaf(v, th, v), hw[k], r0);
      }
      asm volatile("red.global.add.f32 [%0],%1;" :: "l"(outp + s * TH), "f"(r0) : "memory");
    }
    outp += 4 * TH;
  }
  TS(1, 3);
  asm volatile("bar.sync 1,%0;" :: "n"(TH + 32) : "memory");
  if (tid == 0) {
    unsigned old; asm volatile("atom.acq_rel.gpu.global.inc.u32 %0,[%1],63;" : "=r"(old) : "l"(&g_done[half * 32]) : "memory");
    asm volatile("st.shared.u32 [%0],%1;" :: "r"(barJ + 8), "r"(old) : "memory");
  }
  asm volatile("bar.sync 2,%0;" :: "n"(TH) : "memory");
  uint32_t old; asm volatile("ld.shared.u32 %0,[%1];" : "=r"(old) : "r"(barJ + 8));
  if (old == 63) {
    if (half == 0 && tid == 25) g_slot = 0;
    if (half == 0 && tid < 25) g_flag[tid * 32] = 0;
    float4 v[8];
#pragma unroll
    for (int q = 0; q < 8; q++) v[q] = __ldcg((const float4*)(g_acc + half * 8192) + q * TH + tid);
#pragma unroll
    for (int q = 0; q < 8; q++) ((uint2*)(out + half * 8192))[q * TH + tid] = make_uint2(pack_bf2(v[q].x, v[q].y), pack_bf2(v[q].z, v[q].w));
    TS(6, 2);
  }
}

}

extern "C" void kernel_launch(void* const* d_in, const int* in_sizes, int n_in, void* d_out, int out_size) {
  const int* idx = (const int*)d_in[0];
  const __nv_bfloat16* table = (const __nv_bfloat16*)d_in[1];
  const __nv_bfloat16* wp = (const __nv_bfloat16*)d_in[2];
  const __nv_bfloat16* w1 = (const __nv_bfloat16*)d_in[3];
  const __nv_bfloat16* b1 = (const __nv_bfloat16*)d_in[4];
  const __nv_bfloat16* w2 = (const __nv_bfloat16*)d_in[5];
  const __nv_bfloat16* b2 = (const __nv_bfloat16*)d_in[6];
  static cudaTextureObject_t texScr = 0, texX = 0;
  static CUtensorMap mapW, mapL, mapS, mapT, mapE, mapC;
  static const void *c_tab = nullptr, *c_w1 = nullptr;
  if (c_tab != table || c_w1 != w1) {
    c_tab = table; c_w1 = w1;
    char* scr = nullptr; cudaGetSymbolAddress((void**)&scr, g_scr);
    auto mk_tex = [](const void* p, size_t bytes, cudaChannelFormatDesc d) {
      cudaResourceDesc rd = {}; rd.resType = cudaResourceTypeLinear; rd.res.linear.devPtr = (void*)p; rd.res.linear.desc = d; rd.res.linear.sizeInBytes = bytes;
      cudaTextureDesc td = {}; td.readMode = cudaReadModeElementType;
      cudaTextureObject_t t = 0; cudaCreateTextureObject(&t, &rd, &td, nullptr); return t;
    };
    if (!texScr) {
      texScr = mk_tex(scr, (size_t)SCR_N * 16, cudaCreateChannelDesc<uint4>());
      texX = mk_tex(scr + (size_t)PX_OFF * 16, (size_t)(SCR_N - PX_OFF) * 16, cudaCreateChannelDesc<unsigned>());
    }
    typedef CUresult (*EncFn)(CUtensorMap*, CUtensorMapDataType, cuuint32_t, void*, const cuuint64_t*, const cuuint64_t*, const cuuint32_t*,
                              const cuuint32_t*, CUtensorMapInterleave, CUtensorMapSwizzle, CUtensorMapL2promotion, CUtensorMapFloatOOBfill);
    EncFn enc = nullptr; cudaDriverEntryPointQueryResult qr;
    cudaGetDriverEntryPoint("cuTensorMapEncodeTiled", (void**)&enc, cudaEnableDefault, &qr);
    const cuuint32_t ones[4] = {1, 1, 1, 1};
    auto mk = [&](CUtensorMap* m, CUtensorMapDataType dt, int rank, void* p, const cuuint64_t* dim, const cuuint64_t* str, const cuuint32_t* box, CUtensorMapSwizzle sw) {
      enc(m, dt, rank, p, dim, str, box, ones, CU_TENSOR_MAP_INTERLEAVE_NONE, sw, CU_TENSOR_MAP_L2_PROMOTION_NONE, CU_TENSOR_MAP_FLOAT_OOB_FILL_NONE);
    };
    { cuuint64_t dim[2] = {H_, F_ * D_}, str[1] = {H_ * 2}; cuuint32_t box[2] = {32, 256};
      mk(&mapW, CU_TENSOR_MAP_DATA_TYPE_BFLOAT16, 2, (void*)w1, dim, str, box, CU_TENSOR_MAP_SWIZZLE_64B); }
    { cuuint64_t dim[4] = {64, 64, V_, NC}, str[3] = {128000 * NC, 128, 128000}; cuuint32_t box[4] = {32, 4, 64, 1};
      mk(&mapL, CU_TENSOR_MAP_DATA_TYPE_BFLOAT16, 4, scr + (size_t)PL_OFF * 16, dim, str, box, CU_TENSOR_MAP_SWIZZLE_64B); }
    { cuuint64_t dim[4] = {64, 64, V_ / 4, NC}, str[3] = {32000 * NC, 128, 32000}; cuuint32_t box[4] = {64, 4, 16, 1};
      mk(&mapS, CU_TENSOR_MAP_DATA_TYPE_BFLOAT16, 4, scr + (size_t)PS_OFF * 16, dim, str, box, CU_TENSOR_MAP_SWIZZLE_128B); }
    { cuuint64_t dim[4] = {64, 64, V_ / 8, 10}, str[3] = {163840, 128, 16384}; cuuint32_t box[4] = {64, 4, 8, 2};
      mk(&mapT, CU_TENSOR_MAP_DATA_TYPE_BFLOAT16, 4, scr + (size_t)PT_OFF * 16, dim, str, box, CU_TENSOR_MAP_SWIZZLE_128B); }
    { cuuint64_t dim[2] = {D_, V_}, str[1] = {D_ * 2}; cuuint32_t box[2] = {64, 128};
      mk(&mapE, CU_TENSOR_MAP_DATA_TYPE_BFLOAT16, 2, (void*)table, dim, str, box, CU_TENSOR_MAP_SWIZZLE_128B);
      cuuint32_t box2[2] = {8, 256};
      mk(&mapC, CU_TENSOR_MAP_DATA_TYPE_BFLOAT16, 2, (void*)table, dim, str, box2, CU_TENSOR_MAP_SWIZZLE_NONE); }
    cudaFuncSetAttribute(k_deep, cudaFuncAttributeMaxDynamicSharedMemorySize, DEEP_SMEM);
    cudaFuncSetAttribute(k_tens, cudaFuncAttributeMaxDynamicSharedMemorySize, K1_SMEM);
  }
  k_tens<<<132, 512, K1_SMEM, cudaStreamPerThread>>>(mapW, mapL, mapS, mapT, mapE, mapC, texScr, texX, idx, table, wp, w1, b1, 0);
  cudaLaunchAttribute at[1];
  at[0].id = cudaLaunchAttributeProgrammaticStreamSerialization; at[0].val.programmaticStreamSerializationAllowed = 1;
  cudaLaunchConfig_t cfg = {};
  cfg.stream = cudaStreamPerThread; cfg.attrs = at;
  cfg.gridDim = 128; cfg.blockDim = TH + 128; cfg.dynamicSmemBytes = DEEP_SMEM; cfg.numAttrs = PDL;
  cudaLaunchKernelEx(&cfg, k_deep, texScr, w2, b2, (__nv_bfloat16*)d_out, 0);

}
```

```cpp
#include <cuda_runtime.h>
#include <cuda_bf16.h>
#include <cuda_fp16.h>
#include <stdint.h>
#include <cuda.h>

namespace {

constexpr int B_ = 16384, F_ = 100, D_ = 128, V_ = 1000, H_ = 512;
constexpr int NC = 9;
constexpr int PT_OFF = 0;
constexpr int PL_OFF = 64 * 10 * 1024;
constexpr int PS_OFF = PL_OFF + 64 * NC * 8000;
constexpr int IXH = NC * 8192 + 2048;
constexpr int IX_OFF = PS_OFF + 64 * NC * 2000;
constexpr int I0_OFF = IX_OFF + 2 * IXH;
constexpr int PX_OFF = I0_OFF + 4096;
constexpr int SCR_N = PX_OFF + 64 * 16 * 136;
static_assert(PX_OFF % 32 == 0, "");

__device__ __align__(1024) uint4 g_scr[SCR_N];
__device__ float g_acc[B_];
__device__ unsigned long long g_slot;
__device__ unsigned g_done[64];
__device__ float g_partP[16 * B_];
__device__ float2 g_unscale[16];
__device__ unsigned g_flag[25 * 32];

#define TS(k, i)
#define TR(slot)
#define PT(slot)

constexpr uint64_t POL_EF = 0x12F0000000000000ull, POL_N = 0x1000000000000000ull;
__device__ __forceinline__ uint32_t addbf2(uint32_t a, uint32_t b) { uint32_t r; asm("add.rn.bf16x2 %0,%1,%2;" : "=r"(r) : "r"(a), "r"(b)); return r; }
__device__ __forceinline__ uint4 add4(const uint4& a, const uint4& b) { return make_uint4(addbf2(a.x, b.x), addbf2(a.y, b.y), addbf2(a.z, b.z), addbf2(a.w, b.w)); }
__device__ __forceinline__ uint4 ldtex(cudaTextureObject_t t, int i) {
  uint4 v; asm volatile("tex.1d.v4.u32.s32 {%0,%1,%2,%3},[%4,{%5}];" : "=r"(v.x), "=r"(v.y), "=r"(v.z), "=r"(v.w) : "l"(t), "r"(i)); return v;
}
__device__ __forceinline__ uint4 lds128(uint32_t a) {
  uint4 v; asm volatile("ld.volatile.shared.v4.u32 {%0,%1,%2,%3},[%4];" : "=r"(v.x), "=r"(v.y), "=r"(v.z), "=r"(v.w) : "r"(a)); return v;
}
__device__ __forceinline__ void sts128(uint32_t a, const uint4& v) {
  asm volatile("st.shared.v4.u32 [%0],{%1,%2,%3,%4};" :: "r"(a), "r"(v.x), "r"(v.y), "r"(v.z), "r"(v.w) : "memory");
}
__device__ __forceinline__ void mbar_init(uint32_t bar, int n) { asm volatile("mbarrier.init.shared::cta.b64 [%0],%1;" :: "r"(bar), "r"(n) : "memory"); }
__device__ __forceinline__ void mbar_wait(uint32_t bar, uint32_t parity) {
  uint32_t ok; int it = 0;
  do { asm volatile("{.reg .pred p; mbarrier.try_wait.parity.shared::cta.b64 p,[%1],%2; selp.u32 %0,1,0,p;}" : "=r"(ok) : "r"(bar), "r"(parity) : "memory"); } while (!ok && ++it < (1 << 19));
}
__device__ __forceinline__ void mbar_expect(uint32_t bar, uint32_t bytes) { asm volatile("mbarrier.arrive.expect_tx.shared::cta.b64 _,[%0],%1;" :: "r"(bar), "r"(bytes) : "memory"); }
__device__ __forceinline__ void bulk_g2s(uint32_t dst, const void* src, uint32_t bytes, uint32_t bar) {
  asm volatile("cp.async.bulk.shared::cluster.global.mbarrier::complete_tx::bytes [%0],[%1],%2,[%3];" :: "r"(dst), "l"(src), "r"(bytes), "r"(bar) : "memory");
}
__device__ __forceinline__ void bulk_pf(const void* src, uint32_t bytes) { asm volatile("cp.async.bulk.prefetch.L2.global [%0],%1;" :: "l"(src), "r"(bytes) : "memory"); }
#define SCHED_FENCE(never, k) asm volatile("{.reg .pred p; setp.ne.u32 p,%0,%1; @p bra.uni SKIP_%=; pmevent 1; SKIP_%=: }" :: "r"(never), "r"(0x7fff0000 + (k)) : "memory")
#define PDL 1
#define RSV 23
#define RSV_L 550
#define RSV_T 7200
#define PACE 900
__device__ __forceinline__ int quad_of(int n) { return n < 23 ? n + 2 : n - 23; }
__device__ __forceinline__ void mbar_wait_fast(uint32_t bar, uint32_t parity) {
  asm volatile("{.reg .pred p; .reg .u32 n;\n"
               "mbarrier.try_wait.parity.shared::cta.b64 p,[%0],%1;\n"
               "@p bra DONE_%=;\n"
               "mov.u32 n,0;\n"
               "LOOP_%=: mbarrier.try_wait.parity.shared::cta.b64 p,[%0],%1;\n"
               "add.u32 n,n,1; setp.gt.or.u32 p,n,400000,p;\n"
               "@!p bra LOOP_%=;\n"
               "DONE_%=: }" :: "r"(bar), "r"(parity) : "memory");
}
__device__ __forceinline__ void sleep_until(uint32_t t0, uint32_t dt) { while ((uint32_t)clock() - t0 < dt) __nanosleep(40); }
__device__ __forceinline__ uint32_t s_mask(uint32_t v, int q) { return (1u << ((v + 3 - q) & 3)) | (16u << ((v + 3 + q) & 3)); }
__device__ __forceinline__ uint32_t s_cell(uint32_t v, int q, uint32_t m) {
  const int t = __ffs(~m) - 1;
  const int cp = t == 8 ? q >> 1 : ((t & 4 ? t - q : t + q) - v) & 3;
  return cp * 1001 + v;
}
__device__ __forceinline__ uint32_t pk3(uint32_t a, uint32_t b, uint32_t c) {
  const uint32_t w = c + (a << 12) + (b << 22); return __funnelshift_l(w, w, 27);
}
constexpr int TH = 256, NS = 8192 / TH, YD = 4;
__host__ __device__ constexpr int ye_of(int s) { return s == 3 ? 0 : s == 11 ? 1 : s == 19 ? 2 : s == 23 ? 3 : -1; }
template <int N> __device__ __forceinline__ void wgmma_h(uint32_t* d, const uint32_t* a, uint64_t desc, int acc);
template <> __device__ __forceinline__ void wgmma_h<40>(uint32_t* d, const uint32_t* a, uint64_t desc, int acc) {
  asm volatile("{.reg .pred p; setp.ne.s32 p,%15,0;\n"
    "wgmma.mma_async.sync.aligned.m64n40k16.f16.f16.f16 {%0,%1,%2,%3,%4,%5,%6,%7,%8,%9},{%10,%11,%12,%13},%14,p,1,1,0;}"
    : "+r"(d[0]),"+r"(d[1]),"+r"(d[2]),"+r"(d[3]),"+r"(d[4]),"+r"(d[5]),"+r"(d[6]),"+r"(d[7]),"+r"(d[8]),"+r"(d[9])
    : "r"(a[0]), "r"(a[1]), "r"(a[2]), "r"(a[3]), "l"(desc), "r"(acc));
}
template <> __device__ __forceinline__ void wgmma_h<32>(uint32_t* d, const uint32_t* a, uint64_t desc, int acc) {
  asm volatile("{.reg .pred p; setp.ne.s32 p,%13,0;\n"
    "wgmma.mma_async.sync.aligned.m64n32k16.f16.f16.f16 {%0,%1,%2,%3,%4,%5,%6,%7},{%8,%9,%10,%11},%12,p,1,1,0;}"
    : "+r"(d[0]),"+r"(d[1]),"+r"(d[2]),"+r"(d[3]),"+r"(d[4]),"+r"(d[5]),"+r"(d[6]),"+r"(d[7])
    : "r"(a[0]), "r"(a[1]), "r"(a[2]), "r"(a[3]), "l"(desc), "r"(acc));
}
__device__ __forceinline__ void wgmma_p(float* d, const uint32_t* a, uint64_t desc, int acc) {
  asm volatile("{.reg .pred p; setp.ne.s32 p,%69,0;\n"
    "wgmma.mma_async.sync.aligned.m64n128k16.f32.bf16.bf16 {%0,%1,%2,%3,%4,%5,%6,%7,%8,%9,%10,%11,%12,%13,%14,%15,%16,%17,%18,%19,%20,%21,%22,%23,%24,%25,%26,%27,%28,%29,%30,%31,%32,%33,%34,%35,%36,%37,%38,%39,%40,%41,%42,%43,%44,%45,%46,%47,%48,%49,%50,%51,%52,%53,%54,%55,%56,%57,%58,%59,%60,%61,%62,%63},{%64,%65,%66,%67},%68,p,1,1,1;}"
    : "+f"(d[0]),"+f"(d[1]),"+f"(d[2]),"+f"(d[3]),"+f"(d[4]),"+f"(d[5]),"+f"(d[6]),"+f"(d[7]),"+f"(d[8]),"+f"(d[9]),"+f"(d[10]),"+f"(d[11]),"+f"(d[12]),"+f"(d[13]),"+f"(d[14]),"+f"(d[15]),"+f"(d[16]),"+f"(d[17]),"+f"(d[18]),"+f"(d[19]),"+f"(d[20]),"+f"(d[21]),"+f"(d[22]),"+f"(d[23]),"+f"(d[24]),"+f"(d[25]),"+f"(d[26]),"+f"(d[27]),"+f"(d[28]),"+f"(d[29]),"+f"(d[30]),"+f"(d[31]),"+f"(d[32]),"+f"(d[33]),"+f"(d[34]),"+f"(d[35]),"+f"(d[36]),"+f"(d[37]),"+f"(d[38]),"+f"(d[39]),"+f"(d[40]),"+f"(d[41]),"+f"(d[42]),"+f"(d[43]),"+f"(d[44]),"+f"(d[45]),"+f"(d[46]),"+f"(d[47]),"+f"(d[48]),"+f"(d[49]),"+f"(d[50]),"+f"(d[51]),"+f"(d[52]),"+f"(d[53]),"+f"(d[54]),"+f"(d[55]),"+f"(d[56]),"+f"(d[57]),"+f"(d[58]),"+f"(d[59]),"+f"(d[60]),"+f"(d[61]),"+f"(d[62]),"+f"(d[63])
    : "r"(a[0]), "r"(a[1]), "r"(a[2]), "r"(a[3]), "l"(desc), "r"(acc));
}

__device__ __forceinline__ void mma16816h(uint32_t* c, const uint32_t* a, uint32_t b0, uint32_t b1) {
  asm("mma.sync.aligned.m16n8k16.row.col.f16.f16.f16.f16 {%0,%1},{%2,%3,%4,%5},{%6,%7},{%0,%1};"
      : "+r"(c[0]), "+r"(c[1]) : "r"(a[0]), "r"(a[1]), "r"(a[2]), "r"(a[3]), "r"(b0), "r"(b1));
}
__device__ __forceinline__ void mma1688h(uint32_t* c, uint32_t a0, uint32_t a1, uint32_t b) {
  asm("mma.sync.aligned.m16n8k8.row.col.f16.f16.f16.f16 {%0,%1},{%2,%3},{%4},{%0,%1};" : "+r"(c[0]), "+r"(c[1]) : "r"(a0), "r"(a1), "r"(b));
}
__device__ __forceinline__ void mma1688f(float* c, uint32_t a0, uint32_t a1, uint32_t b) {
  asm("mma.sync.aligned.m16n8k8.row.col.f32.f16.f16.f32 {%0,%1,%2,%3},{%4,%5},{%6},{%0,%1,%2,%3};"
      : "+f"(c[0]), "+f"(c[1]), "+f"(c[2]), "+f"(c[3]) : "r"(a0), "r"(a1), "r"(b));
}
__device__ __forceinline__ uint32_t hadd2(uint32_t a, uint32_t b) { uint32_t r; asm("add.rn.f16x2 %0,%1,%2;" : "=r"(r) : "r"(a), "r"(b)); return r; }
__device__ __forceinline__ uint32_t hfma2(uint32_t a, uint32_t b, uint32_t c) { uint32_t r; asm("fma.rn.f16x2 %0,%1,%2,%3;" : "=r"(r) : "r"(a), "r"(b), "r"(c)); return r; }
__device__ __forceinline__ uint32_t pack_bf2(float lo, float hi) { uint32_t r; asm("cvt.rn.bf16x2.f32 %0,%1,%2;" : "=r"(r) : "f"(hi), "f"(lo)); return r; }
__device__ __forceinline__ uint32_t pack_h2(float lo, float hi) { uint32_t r; asm("cvt.rn.f16x2.f32 %0,%1,%2;" : "=r"(r) : "f"(hi), "f"(lo)); return r; }
__device__ __forceinline__ float bf_lo(uint32_t w) { return __uint_as_float(w << 16); }
__device__ __forceinline__ float bf_hi(uint32_t w) { return __uint_as_float(w & 0xffff0000u); }
__device__ __forceinline__ uint32_t absmax4(const uint4& v, uint32_t m) {
  return __vmaxu2(__vmaxu2(__vmaxu2(v.x & 0x7fff7fffu, v.y & 0x7fff7fffu), __vmaxu2(v.z & 0x7fff7fffu, v.w & 0x7fff7fffu)), m);
}
__device__ __forceinline__ float pow2_scale(uint32_t mbits, int p) { return __uint_as_float((uint32_t)min(max(253 + p - (int)(mbits >> 7), 2), 252) << 23); }

constexpr int G_O0 = 8, G_O1 = 4, G_O2 = 0, G_N0 = 5, G_N1 = 4, G_N2 = 4, G_K0 = 5, G_K1 = 3, G_K2 = 1;
__host__ __device__ constexpr bool unit_wg(int kb, int on) {
  return (on >= G_O0 && on < G_O0 + G_N0 && kb < G_K0) || (on >= G_O1 && on < G_O1 + G_N1 && kb < G_K1) || (on >= G_O2 && on < G_O2 + G_N2 && kb < G_K2);
}
constexpr int G_U1 = G_N0 * G_K0, G_U2 = G_U1 + G_N1 * G_K1, G_U = G_U2 + G_N2 * G_K2;
constexpr int K1_B = 130048, K1_STG = K1_B + 2 * 32768, K1_W = K1_STG + 16384, K1_BAR = K1_W + 48 * 256, K1_SMEM = K1_BAR + 256 + 6400;
__host__ __device__ constexpr int frag_index(int ok, int on) {
  int n = 0;
  for (int k = 0; k < 13; k++) for (int o = k; o < 13; o++) { if (k == ok && o == on) return n; if (!unit_wg(k >> 1, o)) n++; }
  return n;
}
constexpr int HU_N = 2 * G_U + frag_index(99, 99);
static_assert(HU_N <= 96, "");
struct FragIdx { int v[13][13]; };
__host__ __device__ constexpr FragIdx make_fi() { FragIdx f = {}; for (int k = 0; k < 13; k++) for (int o = 0; o < 13; o++) f.v[k][o] = frag_index(k, o); return f; }
__host__ __device__ constexpr uint64_t frag_tab(int first) {
  uint64_t t = 0;
  for (int k = 0; k < 13; k++) for (int o = k; o < 13; o++)
    if (!unit_wg(k >> 1, o)) { const int n = frag_index(k, o) - first; if (n >= 0 && n < 8) t |= (uint64_t)(k << 4 | o) << (8 * n); }
  return t;
}
__device__ __forceinline__ int hu_code(int hu) {
  constexpr uint64_t T0 = frag_tab(0), T1 = frag_tab(8), T2 = frag_tab(16), T3 = frag_tab(24);
  const int u = hu >> 1, f = hu - 2 * G_U;
  if (f >= 0) return (int)((f < 8 ? T0 : f < 16 ? T1 : f < 24 ? T2 : T3) >> (8 * (f & 7))) & 255;
  const int u0 = u < G_U1 ? u : u < G_U2 ? u - G_U1 : u - G_U2;
  const int kb = u < G_U1 ? u0 / G_N0 : u < G_U2 ? u0 / G_N1 : u0 / 4, on = u < G_U1 ? G_O0 + u0 % G_N0 : u < G_U2 ? G_O1 + u0 % G_N1 : G_O2 + u0 % 4;
  return (2 * kb + (hu & 1)) << 4 | on;
}

__device__ __forceinline__ void flag_wait(const unsigned* f, unsigned n) {
  unsigned v; int it = 0;
  asm volatile("ld.acquire.gpu.global.u32 %0,[%1];" : "=r"(v) : "l"(f) : "memory");
  if (v < n) {
    do { __nanosleep(300); asm volatile("ld.relaxed.gpu.global.u32 %0,[%1];" : "=r"(v) : "l"(f) : "memory"); } while (v < n && ++it < (1 << 20));
    asm volatile("ld.acquire.gpu.global.u32 %0,[%1];" : "=r"(v) : "l"(f) : "memory");
  }
}
__device__ __forceinline__ void mbar_arrive(uint32_t bar) { asm volatile("mbarrier.arrive.shared::cta.b64 _,[%0];" :: "r"(bar) : "memory"); }
__device__ __forceinline__ void mbar_arrive_lane0(uint32_t bar) {
  __syncwarp();
  asm volatile("{.reg .pred p; elect.sync _|p,0xffffffff; @p mbarrier.arrive.shared::cta.b64 _,[%0];}" :: "r"(bar) : "memory");
}

__device__ __forceinline__ void arrive_both(uint32_t bar, int lane) {
  __syncwarp();
  asm volatile("{.reg .pred p; .reg .u32 a; setp.lt.u32 p,%1,2; mapa.shared::cluster.u32 a,%0,%1;\n"
               "@p mbarrier.arrive.shared::cluster.b64 _,[a];}" :: "r"(bar), "r"(lane) : "memory");
}
#define ELECT "{.reg .pred p; elect.sync _|p,0xffffffff; @p "
__device__ __forceinline__ void e_mc(uint32_t dst, const void* src, uint32_t bytes, uint32_t bar, uint64_t pol) {
  asm volatile(ELECT "cp.async.bulk.shared::cluster.global.mbarrier::complete_tx::bytes.multicast::cluster.L2::cache_hint [%0],[%1],%2,[%3],%4,%5;}"
               :: "r"(dst), "l"(src), "r"(bytes), "r"(bar), "h"((unsigned short)3), "l"(pol) : "memory");
}
__device__ __forceinline__ void e_g2s(uint32_t dst, const void* src, uint32_t bytes, uint32_t bar) {
  asm volatile(ELECT "cp.async.bulk.shared::cluster.global.mbarrier::complete_tx::bytes [%0],[%1],%2,[%3];}" :: "r"(dst), "l"(src), "r"(bytes), "r"(bar) : "memory");
}
__device__ __forceinline__ void e_pf(const void* src, uint32_t bytes) { asm volatile(ELECT "cp.async.bulk.prefetch.L2.global [%0],%1;}" :: "l"(src), "r"(bytes) : "memory"); }
__device__ __forceinline__ void e_expect(uint32_t bar, uint32_t bytes) { asm volatile(ELECT "mbarrier.arrive.expect_tx.shared::cta.b64 _,[%0],%1;}" :: "r"(bar), "r"(bytes) : "memory"); }
__device__ __forceinline__ void e_tma2d(uint32_t dst, const CUtensorMap* m, int x, int y, uint32_t bar) {
  asm volatile(ELECT "cp.async.bulk.tensor.2d.shared::cluster.global.mbarrier::complete_tx::bytes [%0],[%1,{%2,%3}],[%4];}" :: "r"(dst), "l"(m), "r"(x), "r"(y), "r"(bar) : "memory");
}

__device__ __forceinline__ void pack_role(const int* __restrict__ idx, uint32_t sbase, int pc) {
  constexpr int BUF = 32 * 3328;
  const int tid = threadIdx.x, lane = tid & 31, warp = tid >> 5;
  const uint32_t full = sbase + 2 * BUF, empty = full + 16;
  if (tid == 0) { mbar_init(full, 1); mbar_init(full + 8, 1); mbar_init(empty, 18); mbar_init(empty + 8, 18); asm volatile("fence.proxy.async.shared::cta;" ::: "memory"); }
  __syncthreads();
  auto chunk = [&](int s) { return s * 3200 + (s >> 2) * 288; };
  auto load = [&](int n) {
    const int blk = pc * 16 + n;
    if (lane == 0) mbar_expect(full + (n & 1) * 8, 32 * 3200);
    __syncwarp();
    bulk_g2s(sbase + (n & 1) * BUF + chunk(lane), idx + ((blk >> 5) * 8192 + lane * TH + (blk & 31) * 8) * F_, 3200, full + (n & 1) * 8);
  };
  if (warp == 0) { load(0); load(1); }
  const int l = lane & 7;
  uint32_t rot[8], inc[3];
#pragma unroll
  for (int jj = 0; jj < 8; jj++) rot[jj] = ((l + jj) & 7) * 4;
#pragma unroll
  for (int q = 0; q < 3; q++) inc[q] = (l + 3 * q < 8) << 12 | (l + 3 * q + 1 < 8) << 22 | (q < 2 && l + 3 * q + 2 < 8);
  int loaded = 2;
#pragma unroll 1
  for (int task = warp; task < 288; task += 16) {
    const int n = task / 18, q = (task % 18) * 4 + (lane >> 3), sq = q / 9, k = q % 9;
    if (warp == 0 && n + 1 == loaded && loaded < 16) { mbar_wait(empty + (loaded & 1) * 8, ((loaded >> 1) - 1) & 1); load(loaded); loaded++; }
    mbar_wait(full + (n & 1) * 8, (n >> 1) & 1);
    const uint32_t buf = sbase + (n & 1) * BUF + l * 400, row = buf + chunk(sq * 4);
    auto ld = [&](uint32_t ad) { uint32_t v; asm volatile("ld.shared.u32 %0,[%1];" : "=r"(v) : "r"(ad)); return v; };
    const int blk = pc * 16 + n, half = blk >> 5, col = (blk & 31) * 8 + l;
    const int ks = k == NC - 1 ? 0 : k + 1;
    uint32_t cw[4], sv[8], m[2] = {0, 0};
    { const uint32_t a0 = row + (72 + 2 * ks + (l >> 2)) * 4;
#pragma unroll
      for (int u = 0; u < 8; u++) { sv[u] = ld((a0 ^ ((u >> 2) * 4)) + (u & 3) * 3200); m[u >> 2] |= s_mask(sv[u], l & 3) << (8 * (u & 3)); } }
#pragma unroll
    for (int h = 0; h < 2; h++) { m[h] |= __shfl_xor_sync(0xffffffffu, m[h], 1); m[h] |= __shfl_xor_sync(0xffffffffu, m[h], 2); }
#pragma unroll
    for (int u = 0; u < 4; u++) cw[u] = s_cell(sv[u], l & 3, (m[0] >> (8 * u)) & 255) | s_cell(sv[4 + u], l & 3, (m[1] >> (8 * u)) & 255) << 12;
    if (k == NC - 1) {
      auto wide = [&](uint32_t w) { return (w & 0xfff) << 5 | (w >> 12) << 18 | (l & 4 ? 1u << 4 : 1u << 17); };
      g_scr[I0_OFF + (half * 8 + sq) * TH + col] = make_uint4(wide(cw[0]), wide(cw[1]), wide(cw[2]), wide(cw[3]));
      g_scr[IX_OFF + half * IXH + NC * 8192 + sq * TH + col] = make_uint4(ld(row + 396), ld(row + 3596), ld(row + 6796), ld(row + 9996));
      cw[0] = cw[1] = cw[2] = cw[3] = 0;
    }
    const uint32_t ax = buf + chunk(min(sq + 1, 7) * 4) + (90 + k) * 4;
    const uint32_t yev = ld(buf + ((0x3210 >> (sq * 2 + (sq == 5) * 2)) & 3) * 3200 + (90 + k) * 4);
    uint4* dst = g_scr + IX_OFF + half * IXH + (k * NS + sq * 4) * TH + col;
#pragma unroll
    for (int u = 0; u < 4; u++) {
      uint32_t e[8];
#pragma unroll
      for (int jj = 0; jj < 8; jj++) e[jj] = ld(row + k * 32 + rot[jj] + u * 3200);
      dst[u * TH] = make_uint4(pk3(e[0], e[1], e[2] + inc[0]), pk3(e[3], e[4], e[5] + inc[1]), pk3(e[6], e[7], ld(ax + u * 3200) + inc[2]),
                               u < 3 ? __byte_perm(cw[u], cw[3], 0x4210 + (u << 12)) : yev);
    }
    mbar_arrive_lane0(empty + (n & 1) * 8);
  }
}

__global__ void __cluster_dims__(2, 1, 1) __launch_bounds__(512, 1)
k_tens(const __grid_constant__ CUtensorMap mapW, const __grid_constant__ CUtensorMap mapL, const __grid_constant__ CUtensorMap mapS,
       const __grid_constant__ CUtensorMap mapT, const __grid_constant__ CUtensorMap mapE, const __grid_constant__ CUtensorMap mapC, cudaTextureObject_t tex, cudaTextureObject_t texX,
       const int* __restrict__ idx, const __nv_bfloat16* __restrict__ table, const __nv_bfloat16* __restrict__ wp, const __nv_bfloat16* __restrict__ w1,
       const __nv_bfloat16* __restrict__ b1, int never) {
  extern __shared__ __align__(1024) uint4 sm[];
  const int tid = threadIdx.x, lane = tid & 31, cta = blockIdx.x;
  const uint32_t sbase = (uint32_t)__cvta_generic_to_shared(sm);
  const int g = lane >> 2, r = lane & 3;
  TS(0, 0);
  if (cta >= 128) {
    pack_role(idx, sbase, cta - 128);
    __syncthreads();
    if (tid == 0) {
      asm volatile("fence.acq_rel.gpu; griddepcontrol.launch_dependents;" ::: "memory");
      asm volatile("red.relaxed.gpu.global.add.u32 [%0],1;" :: "l"(&g_flag[24 * 32]) : "memory");
    }
    __syncwarp();
    TS(2, 1);
    asm volatile("barrier.cluster.arrive.relaxed.aligned; barrier.cluster.wait.aligned;" ::: "memory");
    return;
  }
  const uint32_t fullB = sbase + K1_BAR, emptyB = fullB + 24, fullE = fullB + 48, fullC = fullB + 56, fullI = fullB + 64, pxRdy = fullB + 72, fullS = fullB + 96, emptyS = fullB + 104, pkDone = fullB + 112, pkFull = fullB + 136, progG = fullB + 168;
  const int rb = cta & 7, hc = cta >> 3;
  if (__shfl_sync(0xffffffffu, tid >> 5, 0) == 12) {
    if (lane == 0) {
#pragma unroll
      for (int q = 0; q < 19; q++) if (q != 2 && q != 5) mbar_init(fullB + q * 8, q == 3 || q == 4 ? 8 : q == 12 ? 4 : q >= 14 && q < 17 ? 2 : 1);
      asm volatile("st.shared.u32 [%0],%1;" :: "r"(progG), "r"(0) : "memory");
    }
    asm volatile("fence.mbarrier_init.release.cluster; fence.proxy.async.shared::cta;" ::: "memory");
    __syncwarp();
    e_expect(fullC, 16384);
#pragma unroll
    for (int q = 0; q < 4; q++) e_tma2d(sbase + 32768 + q * 4096, &mapC, (cta & 15) * 8, q * 256, fullC);
    e_expect(fullE, 32768);
#pragma unroll
    for (int q = 0; q < 2; q++) e_tma2d(sbase + K1_B + 32768 + q * 16384, &mapE, q * 64, rb * 128, fullE);
    asm volatile("bar.arrive 2,512;" ::: "memory");
  }
  asm volatile("barrier.cluster.arrive.relaxed.aligned;" ::: "memory");
  if (tid >= 384) {
    asm volatile("setmaxnreg.dec.sync.aligned.u32 32;");
    if (tid < 416) {
      asm volatile("barrier.cluster.wait.aligned;" ::: "memory");
      if (tid == 384) {
#pragma unroll 1
        for (int n = 0; n < 25; n++) {
          const int st = n & 1, q = quad_of(n);
          if (n == 1) {
            mbar_expect(fullI, 51200);
#pragma unroll 1
            for (int u = 0; u < 8; u++) bulk_g2s(sbase + 76800 + u * 6400, idx + ((cta >> 4) * 8 + u) * 256 * F_, 6400, fullI);
          }
          mbar_wait(emptyB + st * 8, (((n + 1) >> 1) & 1) ^ 1);
          mbar_expect(fullB + st * 8, 32768);
          asm volatile("cp.async.bulk.tensor.2d.shared::cluster.global.mbarrier::complete_tx::bytes.multicast::cluster [%0],[%1,{%2,%3}],[%4],%5;"
                       :: "r"(sbase + K1_B + st * 32768 + (cta & 1) * 16384), "l"(&mapW), "r"(hc * 32), "r"(q * 512 + (cta & 1) * 256),
                          "r"(fullB + st * 8), "h"((unsigned short)3) : "memory");
          if (n + 1 < 25) bulk_pf(w1 + quad_of(n + 1) * 262144 + cta * 2048, 4096);
        }
      }
    } else if (tid < 448) {
      ((float4*)g_acc)[cta * 32 + lane] = make_float4(0.f, 0.f, 0.f, 0.f);
      asm volatile("bar.sync 2,512;" ::: "memory");
      __syncwarp();
      if (tid == 416) {
        int pub = 0;
#pragma unroll 1
        for (int n = 0; n < 50; n++) {
          const int quad = quad_of(n >> 1), mt = n & 1, v0 = rb * 128 + mt * 64;
          const uint32_t stg = sbase + K1_STG;
          if (pub < 3) {
            uint32_t ok = 1;
            if (pub == 0 || n == 49) mbar_wait(pkDone + pub * 8, 0);
            else asm volatile("{.reg .pred p; mbarrier.test_wait.parity.shared::cta.b64 p,[%1],0; selp.u32 %0,1,0,p;}" : "=r"(ok) : "r"(pkDone + pub * 8) : "memory");
            if (ok) {
              asm volatile("cp.async.bulk.wait_group 0;" ::: "memory");
              asm volatile("red.release.gpu.global.add.u32 [%0],1;" :: "l"(&g_flag[((cta >> 4) * 3 + pub) * 32]) : "memory");
              pub++;
              if (n == 49) { n--; continue; }
            }
          }
          mbar_wait(fullS, n & 1);
          asm volatile("fence.proxy.async.shared::cta;" ::: "memory");
          if (quad < 18) {
            asm volatile("cp.async.bulk.tensor.4d.global.shared::cta.bulk_group.L2::cache_hint [%0,{%1,%2,%3,%4}],[%5],%6;"
                         :: "l"(&mapL), "r"((quad & 1) * 32), "r"(hc * 4), "r"(v0), "r"(quad >> 1), "r"(stg), "l"(POL_EF) : "memory");
          } else {
#pragma unroll 1
            for (int hh = 0; hh < 2; hh++) {
              const int pq = quad * 2 + hh;
              asm volatile("cp.async.bulk.tensor.4d.global.shared::cta.bulk_group.L2::cache_hint [%0,{%1,%2,%3,%4}],[%5],%6;"
                         :: "l"(pq < 45 ? &mapS : &mapT), "r"(0), "r"(hc * 4), "r"(v0 >> (pq < 45 ? 2 : 3)), "r"(pq < 45 ? pq - 36 : (pq - 45) * 2), "r"(stg + hh * 8192), "l"(POL_EF) : "memory");
            }
          }
          asm volatile("cp.async.bulk.commit_group;" ::: "memory");
          asm volatile("cp.async.bulk.wait_group.read 0;" ::: "memory");
          mbar_arrive(emptyS);
        }
        asm volatile("cp.async.bulk.wait_group 0;" ::: "memory");
        asm volatile("fence.proxy.async.global;" ::: "memory");
        asm volatile("fence.acq_rel.gpu; griddepcontrol.launch_dependents;" ::: "memory");
        asm volatile("red.relaxed.gpu.global.add.u32 [%0],1;" :: "l"(&g_flag[24 * 32]) : "memory");
        flag_wait(&g_flag[24 * 32], 132);
        asm volatile("fence.proxy.async.global;" ::: "memory");
        const char* base = (const char*)g_scr;
        const int c = cta >> 1, half = cta & 1, ch = (c + (c >> 4) * 5) & 15;
        bulk_pf(base + (PS_OFF + c * NC * 2000) * 16u + half * 16000, 16000);
        bulk_pf(base + (PT_OFF + c * 10 * 1024) * 16u + half * 8000, 8000);
        mbar_expect(fullE, 18432);
        bulk_g2s(sbase + K1_B, base + (I0_OFF + half * 2048 + ch * 128) * 16u, 2048, fullE);
        bulk_g2s(sbase + K1_B + 2048, base + (IX_OFF + half * IXH + ch * 512) * 16u, 8192, fullE);
        bulk_g2s(sbase + K1_B + 10240, base + (IX_OFF + half * IXH + 8192 + ch * 512) * 16u, 8192, fullE);
        mbar_wait(fullE, 1);
      }
    } else {
      const int pw = (tid >> 5) & 1, rg = (cta >> 4) * 8 + ((cta & 15) >> 1), hf = cta & 1;
      const int* ip = idx + (rg * 256 + hf * 8) * F_;
      asm volatile("bar.sync 2,512;" ::: "memory");
      const uint32_t buf = sbase + K1_BAR + 256 + pw * 3200, bar = pkFull + pw * 8;
      const unsigned* fl = &g_flag[(cta >> 4) * 96];
      int batch = 0, rel = pw ? 3 : 0;
#pragma unroll 1
      for (int n = 1 + pw; n < 16; n += 2) {
        if (lane == 0) { mbar_expect(bar, 3200); bulk_g2s(buf, ip + n * 16 * F_, 3200, bar); if (n + 2 < 16) bulk_pf(ip + (n + 2) * 16 * F_, 3200); }
        uint32_t ok; int it = 0;
        do {
          if (rel < batch) {
            unsigned v; asm volatile("ld.relaxed.gpu.global.u32 %0,[%1];" : "=r"(v) : "l"(fl + rel * 32) : "memory");
            if (__all_sync(0xffffffffu, v >= 16)) { flag_wait(fl + rel * 32, 16); mbar_arrive_lane0(pxRdy + rel * 8); rel++; }
          }
          asm volatile("{.reg .pred p; mbarrier.test_wait.parity.shared::cta.b64 p,[%1],%2; selp.u32 %0,1,0,p;}" : "=r"(ok) : "r"(bar), "r"(((n - 1) >> 1) & 1) : "memory");
          ok = __all_sync(0xffffffffu, ok);
          if (!ok) __nanosleep(100);
        } while (!ok && ++it < (1 << 20));
        auto ld = [&](uint32_t ad) { uint32_t v; asm volatile("ld.shared.u32 %0,[%1];" : "=r"(v) : "r"(ad)); return v; };
        const uint32_t p0 = buf + ((lane >> 3) & 1) * 1600 + ((lane >> 4) * 8 + (lane & 7)) * 4;
        auto wd = [&](int t, int h) { const uint32_t o = p0 + (t + (t & 4)) * 400 + h * 192; return pk3(ld(o), ld(o + 64), ld(o + 128)); };
        uint4* dst = g_scr + PX_OFF + (rg * 16 + n) * 136;
        ((unsigned short*)(dst + 128))[lane * 2 + hf] = ld(buf + ((lane >> 3) + (lane & 4)) * 400 + 384 + r * 4);
#pragma unroll
        for (int q = 0; q < 2; q++) dst[(hf * 2 + q) * 32 + lane] = make_uint4(wd(2 * q, 0), wd(2 * q, 1), wd(2 * q + 1, 0), wd(2 * q + 1, 1));
        __syncwarp();
        if (n <= 2 || n == 5 || n == 6 || n >= 14) { mbar_arrive_lane0(pkDone + batch * 8); batch++; }
      }
      for (; rel < 3; rel++) { flag_wait(fl + rel * 32, 16); mbar_arrive_lane0(pxRdy + rel * 8); }
      if (lane == 0) {
        mbar_wait(pxRdy + 16, 0);
        asm volatile("fence.proxy.async.global;" ::: "memory");
        const char* src = (const char*)(g_scr + PX_OFF + ((cta >> 4) * 8 + ((cta >> 1) & 3) * 2 + pw) * 16 * 136);
        int ph = pw;
#pragma unroll 1
        for (int n = 5; n < 16; n++) {
          uint32_t cur; int it = 0;
          do { asm volatile("ld.volatile.shared.u32 %0,[%1];" : "=r"(cur) : "r"(progG)); if (cur + 2 < n) __nanosleep(400); } while (cur + 2 < n && ++it < (1 << 16));
          if (cur + 1 >= n) continue;
          mbar_expect(bar, 2176); bulk_g2s(buf, src + n * 2176, 2176, bar);
          mbar_wait(bar, ph); ph ^= 1;
        }
      }
    }
    return;
  }
  if (tid >= 256) {
    asm volatile("setmaxnreg.inc.sync.aligned.u32 160;");
    const int w = (tid >> 5) & 3;
    const int srow = w * 16 + ((lane & 15) ^ ((lane & 1) << 2)), sc = lane >> 4;
    uint32_t a[2][8][4];
    asm volatile("bar.sync 2,512;" ::: "memory");
    mbar_wait_fast(fullE, 0);
#pragma unroll
    for (int mt = 0; mt < 2; mt++)
#pragma unroll
      for (int ks = 0; ks < 8; ks++)
        asm volatile("ldmatrix.sync.aligned.m8n8.x4.shared.b16 {%0,%1,%2,%3},[%4];"
                     : "=r"(a[mt][ks][0]), "=r"(a[mt][ks][1]), "=r"(a[mt][ks][2]), "=r"(a[mt][ks][3])
                     : "r"(sbase + K1_B + 32768 + (ks >> 2) * 16384 + (mt * 64 + srow) * 128 + ((((ks & 3) * 2 + sc) ^ (srow & 7)) * 16)) : "memory");
    asm volatile("barrier.cluster.wait.aligned;" ::: "memory");
    arrive_both(emptyB + 8, lane);
    const int v = w * 16 + (g ^ ((g & 1) << 2));
    const uint32_t baseL = v * 256 + r * 64 + ((v & 1) * 2 + (r >> 1)) * 16, baseS = (v >> 2) * 512 + r * 128 + (((v & 3) * 2) ^ ((v & 4) + r)) * 16,
                   baseT = (v >> 3) * 512 + r * 128 + ((v & 7) ^ r) * 16;
    const uint64_t desc0 = (uint64_t)(((sbase + K1_B) & 0x3FFFF) >> 4) | ((uint64_t)(8192 >> 4) << 16) | ((uint64_t)(512 >> 4) << 32) | (2ull << 62);
#pragma unroll 1
    for (int qn = 0; qn < 25; qn++) {
      const int quad = quad_of(qn), st = qn & 1;
      const bool isL = quad < 18;
      PT(qn * 16);
      mbar_wait_fast(fullB + st * 8, (qn >> 1) & 1);
#pragma unroll
      for (int mt = 0; mt < 2; mt++) {
        float d[64];
        PT(qn * 16 + mt * 4 + 1);
        asm volatile("wgmma.fence.sync.aligned;" ::: "memory");
#pragma unroll
        for (int ks = 0; ks < 8; ks++) wgmma_p(d, a[mt][ks], desc0 + st * 2048 + ks * 64, ks);
        asm volatile("wgmma.commit_group.sync.aligned;" ::: "memory");
        mbar_wait_fast(emptyS, mt ^ 1);
        PT(qn * 16 + mt * 4 + 2);
        asm volatile("wgmma.wait_group.sync.aligned 0;" ::: "memory");
#pragma unroll
        for (int q = 0; q < 16; q++) asm volatile("" : "+f"(d[q * 4]), "+f"(d[q * 4 + 1]), "+f"(d[q * 4 + 2]), "+f"(d[q * 4 + 3]) :: "memory");
        PT(qn * 16 + mt * 4 + 3);
        if (mt) arrive_both(emptyB + st * 8, qn < 23 ? lane : 9);
        if (quad == 24) {
#pragma unroll
          for (int cq = 0; cq < 4; cq++) {
            const uint32_t bw = __ldg((const uint32_t*)(b1 + hc * 32 + cq * 8) + r);
#pragma unroll
            for (int e = 0; e < 4; e++) d[48 + cq * 4 + e] += (e & 1) ? bf_hi(bw) : bf_lo(bw);
          }
        }
#pragma unroll
        for (int h = 0; h < 2; h++) {
          const bool isS = quad * 2 + h < 45;
          const uint32_t base = (isL ? baseL ^ (h * 32) : (isS ? baseS : baseT) ^ (h * 8192)), xj = isS ? 16 : 4096, xr = isL ? 2048 : isS ? 1024 : 576;
#pragma unroll
          for (int e4 = 0; e4 < 4; e4++) {
            const float* e = d + h * 32 + (e4 >> 1) * 16 + (e4 & 1) * 2;
            sts128(sbase + K1_STG + (base ^ ((e4 >> 1) * xj) ^ ((e4 & 1) * xr)),
                   make_uint4(pack_bf2(e[0], e[1]), pack_bf2(e[4], e[5]), pack_bf2(e[8], e[9]), pack_bf2(e[12], e[13])));
          }
        }
        mbar_arrive_lane0(fullS);
        if (!mt) PT(qn * 16 + 4);
      }
      PT(qn * 16 + 8);
    }
    return;
  }
  const int slice = cta & 15;
  const int range = (cta >> 4) * 8 + __shfl_sync(0xffffffffu, tid >> 5, 0);
  uint4 iv[4], trow[4]; uint32_t ix;
  uint2 wrow[10];
#pragma unroll
  for (int q = 0; q < 10; q++) asm volatile("ld.global.nc.v2.u32 {%0,%1},[%2];" : "=r"(wrow[q].x), "=r"(wrow[q].y) : "l"((const uint2*)wp + min(tid + q * 256, 2499)));
  asm volatile("bar.sync 2,512;" ::: "memory");
  uint32_t me = 0, mw = 0;
#pragma unroll
  for (int q = 0; q < 10; q++) {
    mw = __vmaxu2(__vmaxu2(wrow[q].x & 0x7fff7fffu, wrow[q].y & 0x7fff7fffu), mw);
    const int e = min(tid + q * 256, 2499), row = e / 25;
    asm volatile("st.shared.v2.u32 [%0],{%1,%2};" :: "r"(sbase + (e + row) * 8), "r"(wrow[q].x), "r"(wrow[q].y) : "memory");
    if (e - row * 25 == 24) asm volatile("st.shared.v2.u32 [%0],{%1,%2};" :: "r"(sbase + (e + row) * 8 + 8), "r"(wrow[q].x), "r"(wrow[q].y) : "memory");
  }
  mbar_wait_fast(fullC, 0);
#pragma unroll
  for (int q = 0; q < 4; q++) { trow[q] = lds128(sbase + 32768 + (tid + q * 256) * 16); me = absmax4(trow[q], me); }
  me = __reduce_max_sync(0xffffffffu, max(me & 0xffff, me >> 16));
  mw = __reduce_max_sync(0xffffffffu, max(mw & 0xffff, mw >> 16));
  uint32_t* sred = (uint32_t*)((char*)sm + 128000);
  if (lane == 0) sred[tid >> 5] = me | mw << 16;
  TS(3, 0);
  asm volatile("setmaxnreg.inc.sync.aligned.u32 160;");
  asm volatile("bar.sync 1,256;" ::: "memory");
  { uint32_t m = 0;
#pragma unroll
    for (int q = 0; q < 8; q++) m = __vmaxu2(m, sred[q]);
    m = __shfl_sync(0xffffffffu, m, 0);
    me = m & 0xffff; mw = m >> 16; }
  const float se = pow2_scale(me, 3), sW = pow2_scale(mw, -2);
  TS(3, 1);
  auto put_rows = [&](int q, bool on) {
    const uint4 t = trow[q];
    const uint4 hv = make_uint4(pack_h2(bf_lo(t.x) * se, bf_hi(t.x) * se), pack_h2(bf_lo(t.y) * se, bf_hi(t.y) * se),
                                pack_h2(bf_lo(t.z) * se, bf_hi(t.z) * se), pack_h2(bf_lo(t.w) * se, bf_hi(t.w) * se));
    if (on)
#pragma unroll
      for (int s = 0; s < 8; s++) sts128(sbase + (tid + q * 256) * 128 + ((s + lane) & 7) * 16, hv);
  };
#pragma unroll 1
  for (int it = 0; it < 3; it++) {
    const int hu = ((tid >> 5) * 3 + it) * 4, code = hu_code(min(hu + (lane >> 3), HU_N - 1)), ok = code >> 4, on = code & 15;
    uint32_t x[4], y[4];
    asm volatile("ldmatrix.sync.aligned.m8n8.x4.shared.b16 {%0,%1,%2,%3},[%4];" : "=r"(x[0]), "=r"(x[1]), "=r"(x[2]), "=r"(x[3])
                 : "r"(sbase + (on * 8 + (lane & (on == 12 ? 3 : 7))) * 208 + ok * 16) : "memory");
    asm volatile("ldmatrix.sync.aligned.m8n8.x4.trans.shared.b16 {%0,%1,%2,%3},[%4];" : "=r"(y[0]), "=r"(y[1]), "=r"(y[2]), "=r"(y[3])
                 : "r"(sbase + (ok * 8 + (lane & (ok == 12 ? 3 : 7))) * 208 + on * 16) : "memory");
    const uint32_t lo = __ballot_sync(0xffffffffu, ok > on), dg = __ballot_sync(0xffffffffu, ok >= on);
#pragma unroll
    for (int q = 0; q < 4; q++) {
      const float m0 = (lo >> (8 * q)) & 1 ? 0.f : sW, m1 = (dg >> (8 * q)) & 1 ? 0.f : sW;
      asm volatile("st.shared.u32 [%0],%1;" :: "r"(sbase + K1_W + (hu + q) * 128 + lane * 4),
                   "r"(pack_h2(fmaf(bf_lo(x[q]), m0, bf_lo(y[q]) * m1), fmaf(bf_hi(x[q]), m0, bf_hi(y[q]) * m1))) : "memory");
    }
  }
  put_rows(1, true); put_rows(2, tid < 88);
  TS(3, 2);
  asm volatile("fence.proxy.async.shared::cta;" ::: "memory");
  asm volatile("bar.sync 1,256;" ::: "memory");
  put_rows(0, true);
  uint32_t bf[HU_N - 2 * G_U];
#pragma unroll
  for (int q = 0; q < HU_N - 2 * G_U; q++) asm volatile("ld.shared.u32 %0,[%1];" : "=r"(bf[q]) : "r"(sbase + K1_W + (2 * G_U + q) * 128 + lane * 4));
  if (cta < 16 && tid == 0) g_unscale[cta] = make_float2(__uint_as_float(0x7f000000u - __float_as_uint(se)), __uint_as_float(0x7f000000u - __float_as_uint(sW)));
  TS(3, 3);
  const int px = range * 16 * 136;
  mbar_wait_fast(fullI, 0);
  {
    const uint32_t ib = sbase + 76800 + (tid >> 5) * 6400, p0 = ib + ((lane >> 3) & 1) * 1600 + ((lane >> 4) * 8 + (lane & 7)) * 4;
    auto ld = [&](uint32_t ad) { uint32_t v; asm volatile("ld.shared.u32 %0,[%1];" : "=r"(v) : "r"(ad)); return v; };
    auto wd = [&](int t, int h) { const uint32_t o = p0 + (t + (t & 4)) * 400 + h * 192; return pk3(ld(o), ld(o + 64), ld(o + 128)); };
#pragma unroll
    for (int q = 0; q < 4; q++) {
      iv[q] = make_uint4(wd(2 * q, 0), wd(2 * q, 1), wd(2 * q + 1, 0), wd(2 * q + 1, 1));
    }
    const uint32_t pe = ib + ((lane >> 3) + (lane & 4)) * 400 + 384 + r * 4;
    ix = ld(pe) | ld(pe + 3200) << 16;
  }
  asm volatile("bar.sync 1,256;" ::: "memory");
  put_rows(2, tid >= 88); put_rows(3, tid + 768 < V_);
  asm volatile("bar.sync 1,256;" ::: "memory");
  TS(0, 1);
  uint32_t lc; asm volatile("add.u32 %0,%1,%2;" : "=r"(lc) : "r"((lane & 7) * 16), "r"(never));
  const uint64_t wdesc = (uint64_t)(((sbase + K1_W) & 0x3FFFF) >> 4) | ((uint64_t)(128 >> 4) << 16) | ((uint64_t)(256 >> 4) << 32);
  uint32_t a[2][6][4], d[2][26], ex[4] = {}, s[4] = {};
  float red[4] = {0.f, 0.f, 0.f, 0.f};
  auto ldsm = [&](uint32_t* o, uint32_t sh) {
    asm volatile("ldmatrix.sync.aligned.m8n8.x4.trans.shared.b16 {%0,%1,%2,%3},[%4];"
                 : "=r"(o[0]), "=r"(o[1]), "=r"(o[2]), "=r"(o[3]) : "r"(sbase + ((sh & 0x1ff80) | lc)));
  };
  auto gather = [&](int t, int hf) {
    const int x = t & 1;
    const uint4 v = iv[(t >> 1) & 3];
#pragma unroll
    for (int kb = 3 * hf; kb < 3 * hf + 3; kb++) {
      const uint32_t ww = x ? (kb < 3 ? v.z : v.w) : (kb < 3 ? v.x : v.y);
      ldsm(a[x][kb], kb % 3 == 0 ? ww : kb % 3 == 1 ? ww >> 10 : __funnelshift_l(ww, ww, 12));
    }
  };
  auto issue = [&](int x) {
    asm volatile("wgmma.fence.sync.aligned;" ::: "memory");
#pragma unroll
    for (int kb = 0; kb < 6; kb++) {
      if (kb < G_K0) wgmma_h<G_N0 * 8>(d[x] + G_O0 * 2, a[x][kb], wdesc + kb * G_N0 * 16, kb);
      if (kb < G_K1) wgmma_h<G_N1 * 8>(d[x] + G_O1 * 2, a[x][kb], wdesc + (G_U1 + kb * G_N1) * 16, kb);
      if (kb < G_K2) wgmma_h<32>(d[x] + G_O2 * 2, a[x][kb], wdesc + (G_U2 + kb * G_N2) * 16, kb);
    }
    asm volatile("wgmma.commit_group.sync.aligned;" ::: "memory");
  };
  auto hmma_part = [&](int t) {
    constexpr FragIdx FI = make_fi();
    const int x = t & 1;
#pragma unroll
    for (int o = 0; o < 13; o++) asm volatile("" : "+r"(d[x][o * 2]), "+r"(d[x][o * 2 + 1]) :: "memory");
#pragma unroll
    for (int kb = 0; kb < 6; kb++)
#pragma unroll
      for (int o = 2 * kb + 1; o < 13; o++)
        if (!unit_wg(kb, o)) mma16816h(d[x] + o * 2, a[x][kb], bf[FI.v[2 * kb][o]], bf[FI.v[2 * kb + 1][o]]);
#pragma unroll
    for (int q = 0; q < 6; q++) if (!unit_wg(q, 2 * q)) mma1688h(d[x] + q * 4, a[x][q][0], a[x][q][1], bf[FI.v[2 * q][2 * q]]);
    mma1688h(d[x] + 24, r < 2 ? ex[t & 3] : 0u, r < 2 ? 0u : ex[t & 3], bf[FI.v[12][12]]);
  };
  auto dot_part = [&](int t, int hf) {
    const int x = t & 1;
    if (hf == 0) {
      const uint32_t pe = hfma2(r < 2 ? d[x][24] : d[x][25], ex[t & 3], 0u);
      s[0] = r < 2 ? pe : 0u; s[1] = r < 2 ? 0u : pe; s[2] = s[3] = 0;
    }
#pragma unroll
    for (int q = 3 * hf; q < 3 * hf + 3; q++)
#pragma unroll
      for (int e = 0; e < 4; e++) s[e] = hfma2(d[x][q * 4 + e], a[x][q][e], s[e]);
  };
  const float* outp = g_partP + slice * B_ + range * 256;
  uint32_t oofs; asm volatile("add.u32 %0,%1,%2;" : "=r"(oofs) : "r"(((r >> 1) * 8 + (r & 1) * 2 + ((lane >> 3) & 1) + (lane >> 4) * 4) * 4), "r"(never));
  float k0 = 0.f, k1 = 0.f, x0 = 0.f, x1 = 0.f;
  auto red_stage = [&](int st, int grp) {
    const bool u16 = lane & 16, u8 = lane & 8;
    if (st == 0) {
      k0 = u16 ? red[2] : red[0]; x0 = __shfl_xor_sync(0xffffffffu, u16 ? red[0] : red[2], 16);
      k1 = u16 ? red[3] : red[1]; x1 = __shfl_xor_sync(0xffffffffu, u16 ? red[1] : red[3], 16);
      red[0] = red[1] = red[2] = red[3] = 0.f;
    }
    if (st == 1) { const float p0 = k0 + x0, p1 = k1 + x1; k0 = u8 ? p1 : p0; x0 = __shfl_xor_sync(0xffffffffu, u8 ? p0 : p1, 8); }
    if (st == 2) { k0 += x0; x0 = __shfl_xor_sync(0xffffffffu, k0, 4); }
    if (st == 3) asm volatile("st.global.f32 [%0],%1;" :: "l"((const char*)(outp + grp * 16) + oofs), "f"(k0 + x0) : "memory");
  };
  auto side = [&](bool first, int t, int prv, int cur, int nxt) {
    const int pn = PX_OFF + px + nxt * 136 + lane;
    if (!first) {
      if (t == 0) { iv[3] = ldtex(tex, PX_OFF + px + cur * 136 + lane + 96); iv[0] = ldtex(tex, pn); }
      if (t == 2) iv[1] = ldtex(tex, pn + 32);
      if (t < 4) red_stage(t, prv);
    } else if (t == 4) {
      TS(4, 2);
      mbar_wait_fast(pxRdy, 0);
      TS(4, 3);
      iv[0] = ldtex(tex, pn); iv[1] = ldtex(tex, pn + 32);
    }
    if (t == 4) { ix = ldtex(texX, (px + nxt * 136 + 128) * 4 + lane).x; iv[2] = ldtex(tex, pn + 64); }
  };
  auto group = [&](bool first, int prv, int cur, int nxt, int part) {
#pragma unroll
    for (int t = part ? 7 : 0; t < 8; t++) {
      if (!part) {
        if (first || t) SCHED_FENCE(never, t * 8);
        side(first, t, prv, cur, nxt);
        dot_part(t, 0);
        SCHED_FENCE(never, t * 8 + 1);
        if (t == 3) ldsm(ex, ix >> 9);
        if (t == 7) ldsm(ex, ix << 7);
        gather(t + 2, 0);
        dot_part(t, 1);
        s[0] = hadd2(s[0], s[2]); s[1] = hadd2(s[1], s[3]);
        if (first || t < 7) SCHED_FENCE(never, t * 8 + 4);
        if (t == 7) break;
      }
      gather(t + 2, 1);
      asm volatile("wgmma.wait_group.sync.aligned 0;" ::: "memory");
      asm volatile("" : "+r"(d[(t & 1) ^ 1][0]) :: "memory");
      mma1688f(red, s[0], s[1], (g | (d[(t & 1) ^ 1][0] & never)) == t ? 0x3c003c00u : 0u);
      hmma_part(t + 1);
      issue(t & 1);
    }
  };
  gather(0, 0); gather(0, 1); issue(0); ldsm(ex, ix << 7); gather(1, 0); gather(1, 1);
  asm volatile("wgmma.wait_group.sync.aligned 0;" ::: "memory");
  hmma_part(0);
  SCHED_FENCE(never, 99);
  issue(1);
  group(true, 0, 0, 1, 0); group(true, 0, 0, 1, 1);
  TS(4, 1);
#pragma unroll 1
  for (int n = 1;; n++) {
    if ((n & 11) == 2) mbar_wait_fast(pxRdy + 8 + (n & 4) * 2, 0);
    asm volatile("st.volatile.shared.u32 [%0],%1;" :: "r"(progG), "r"(n) : "memory");
    group(false, n - 1, n, min(n + 1, 15), 0);
    if (n == 15) break;
    group(false, n - 1, n, min(n + 1, 15), 1);
  }
  asm volatile("wgmma.wait_group.sync.aligned 0;" ::: "memory");
  mma1688f(red, s[0], s[1], g == 7 ? 0x3c003c00u : 0u);
#pragma unroll
  for (int st = 0; st < 4; st++) red_stage(st, 15);
  TS(0, 2);
  asm volatile("barrier.cluster.wait.aligned;" ::: "memory");
  asm volatile("barrier.cluster.arrive.relaxed.aligned; barrier.cluster.wait.aligned;" ::: "memory");
}

constexpr int SM_U = 130048, SM_BAR = 128000, SM_J = SM_U + 98304, DEEP_SMEM = SM_J + 4096;

__global__ void __cluster_dims__(2, 1, 1) __launch_bounds__(TH + 128, 1)
k_deep(cudaTextureObject_t tex, const __nv_bfloat16* __restrict__ w2, const __nv_bfloat16* __restrict__ b2,
       __nv_bfloat16* __restrict__ out, int never) {
  extern __shared__ __align__(1024) uint4 sm[];
  constexpr int PF = 4, DEPTH = 4, NW = TH / 32;
  const int tid = threadIdx.x;
  const int c = blockIdx.x >> 1, half = blockIdx.x & 1;
  const uint32_t sbase = (uint32_t)__cvta_generic_to_shared(sm);
  const uint32_t fullL = sbase + SM_BAR, fullU = fullL + 8, emptyL = fullL + 16, emptyU = fullL + 24, barJ = fullL + 32, barW = fullL + 48;
  TS(1, 0);
  if (tid == 0) {
    mbar_init(fullL, 1); mbar_init(fullU, 1); mbar_init(emptyL, 2 * NW); mbar_init(emptyU, 2 * NW); mbar_init(barJ, 1); mbar_init(barW, 1);
    asm volatile("fence.mbarrier_init.release.cluster;" ::: "memory");
  }
  __syncwarp();
  const int wrp = __shfl_sync(0xffffffffu, tid >> 5, 0);
  const char* base = (const char*)g_scr;
  uint32_t oL = (PL_OFF + c * NC * 8000) * 16u + half * 64000, oS = (PS_OFF + c * NC * 2000) * 16u + half * 16000;
  asm volatile("barrier.cluster.arrive.relaxed.aligned; barrier.cluster.wait.aligned;" ::: "memory");
  if (wrp == NW) {
    asm volatile("fence.proxy.async.global;" ::: "memory");
    e_expect(fullU, 96000);
#pragma unroll
    for (int m = 0; m < 3; m++) e_mc(sbase + SM_U + m * 32032 + half * 16000, base + oS, 16000, fullU, m == 2 ? POL_EF : POL_N);
    e_expect(fullL, 128000);
  }
  TS(5, 1);
  if (wrp >= NW) {
    asm volatile("setmaxnreg.dec.sync.aligned.u32 24;");
    if (wrp == NW) {
      uint32_t oT = (PT_OFF + c * 10 * 1024) * 16u + half * 8000;
      auto warm = [&](uint32_t off, uint32_t hb) {
        asm volatile(ELECT "mbarrier.expect_tx.relaxed.cta.shared::cta.b64 [%0],%1;}" :: "r"(barJ), "r"(2 * hb) : "memory");
        e_g2s(sbase + SM_J, base + off, hb, barJ); e_g2s(sbase + SM_J, base + off + hb, hb, barJ);
      };
      mbar_wait(fullU, 0);
      e_mc(sbase + half * 64000, base + oL, 64000, fullL, POL_EF);
      warm(oT, 4000);
#pragma unroll 1
      for (int k = 0; k + 1 < NC; k++) {
        oL += 128000; oS += 32000; oT += 16384;
        mbar_wait(fullL, k & 1);
        const uint32_t t0 = clock();
        e_pf(base + oS, 16000);
        warm((IX_OFF + half * IXH + (k + 2) * 8192 + ((c + (c >> 4) * (2 * k + 1)) & (k + 2 < NC ? 15 : 3)) * 512) * 16u, 4096);
        mbar_wait(emptyU, k & 1);
        e_expect(fullU, 96000);
#pragma unroll 1
        for (int q = 0; q < 8; q++) {
          sleep_until(t0, q * PACE);
          e_pf(base + oL + q * 8000, 8000);
          if (q >= 2) e_mc(sbase + SM_U + ((q - 2) >> 1) * 32032 + half * 16000 + (q & 1) * 8000, base + oS + (q & 1) * 8000, 8000, fullU, q >= 6 ? POL_EF : POL_N);
        }
        warm(oT, 4000);
        e_expect(fullL, 128000);
        sleep_until(t0, RSV_T);
        unsigned long long now, slot = 0;
        asm volatile("mov.u64 %0,%globaltimer;" : "=l"(now));
        if ((tid & 31) == 0) { atomicMax(&g_slot, now + RSV_L); slot = atomicAdd(&g_slot, (unsigned long long)RSV); }
        slot = __shfl_sync(0xffffffffu, slot, 0);
        for (int it = 0; it < 4000; it++) { asm volatile("mov.u64 %0,%globaltimer;" : "=l"(now)); if (now >= slot) break; }
        mbar_wait(emptyL, k & 1);

        e_mc(sbase + half * 64000, base + oL, 64000, fullL, POL_EF);
      }
      mbar_wait(fullL, (NC - 1) & 1);
      mbar_wait(emptyU, (NC - 1) & 1);
      mbar_arrive_lane0(fullU);
      warm(oT + 16384, 4000);
      mbar_arrive_lane0(barJ); mbar_wait(barJ, 0);
    } else if (tid >= TH + 96) {
      if (tid < TH + 100) asm volatile("st.shared.u32 [%0],%1;" :: "r"(barJ + 32 + (tid & 3) * 4), "r"(((const uint32_t*)w2)[(c >> 2) * 16 + (tid & 3) * 4 + (c & 3)]) : "memory");
      mbar_arrive_lane0(barW);
      asm volatile("griddepcontrol.wait;" ::: "memory");
      const int b = half * 8192 + c * 128 + (tid & 31) * 4;
      const float bias = __bfloat162float(b2[0]);
      float4 s = make_float4(bias, bias, bias, bias);
#pragma unroll 2
      for (int k = 0; k < 16; k++) {
        const float4 v = __ldcg((const float4*)(g_partP + k * B_ + b)); const float2 u = __ldcg(g_unscale + k);
        s.x = fmaf(v.x * u.x * u.x, u.y, s.x); s.y = fmaf(v.y * u.x * u.x, u.y, s.y); s.z = fmaf(v.z * u.x * u.x, u.y, s.z); s.w = fmaf(v.w * u.x * u.x, u.y, s.w);
      }
      asm volatile("red.global.add.v4.f32 [%0],{%1,%2,%3,%4};" :: "l"(g_acc + b), "f"(s.x), "f"(s.y), "f"(s.z), "f"(s.w) : "memory");
      asm volatile("bar.arrive 1,%0;" :: "n"(TH + 32) : "memory");
    }
    return;
  }
  asm volatile("setmaxnreg.inc.sync.aligned.u32 240;");
  const int lane = tid & 31;
  const int tbase = PT_OFF + c * 10 * 1024;
  const int ibase = IX_OFF + half * IXH + tid;
  const uint32_t lc = (tid & 7) << 4;
  uint4 acc[NS], wq[PF], x[DEPTH], y[YD], ye;
  uint32_t sw[NS] = {};
  auto sget = [&](int s) { return (s & 3) == 3 ? __byte_perm(__byte_perm(sw[s - 3], sw[s - 2], 0x0073), sw[s - 1], 0x0710) : sw[s]; };
  auto sa0 = [&](uint32_t v) { return sbase + SM_U + (((v << 5) & 0x1ffe0) | ((lc >> 2) & 16)); };
  uint32_t c1 = 0;
  auto sa1 = [&](uint32_t v) { return sbase + SM_U + (((v >> 7) & 0x1ffe0) | c1); };
  {
    uint4 i0[8];
#pragma unroll
    for (int q = 0; q < 8; q++) i0[q] = ldtex(tex, I0_OFF + (half * 8 + q) * TH + tid);
    auto wd = [&](int k) { return (k & 3) == 0 ? i0[k >> 2].x : (k & 3) == 1 ? i0[k >> 2].y : (k & 3) == 2 ? i0[k >> 2].z : i0[k >> 2].w; };
    TS(5, 2);
    mbar_wait_fast(fullU, 0);
#pragma unroll
    for (int i = 0; i < PF; i++) wq[i] = ldtex(tex, ibase + i * TH);
    TS(1, 1);
#pragma unroll
    for (int s = 0; s < NS; s++) acc[s] = add4(lds128(sbase + SM_U + (wd(s) & 0x1fff0)), lds128(sbase + SM_U + ((wd(s) >> 13) & 0x1fff0)));
    arrive_both(emptyU, lane);
    mbar_wait_fast(barW, 0);
    TS(5, 3);
  }
  uint4 w = wq[0];
  auto lds_l = [&](int jj, int slot) {
    const uint32_t ww = jj < 3 ? w.x : jj < 6 ? w.y : w.z;
    const uint32_t sh = jj % 3 == 0 ? ww : jj % 3 == 1 ? ww >> 10 : __funnelshift_l(ww, ww, 12);
    x[slot] = lds128(sbase + ((sh & 0x1ff80) | lc) + jj * 16 - 128);
  };
  mbar_wait_fast(fullL, 0);
  lds_l(0, 0); lds_l(1, 1); lds_l(2, 2); lds_l(3, 3);
#pragma unroll 1
  for (int k = 0; k < NC; k++) {
    const int ti = ibase + k * 8192;
    const int tb = tbase + k * 1024;
    const bool more = k + 1 < NC;
    TR(k * 4);
    TR(k * 4 + 2);
    uint4 cc; uint32_t yc;
    constexpr int TL = NS * 8, TT = TL + NS * 2;
#pragma unroll
    for (int t = 0; t < TT + DEPTH; t += 2) {
      if (t == TL + DEPTH && !more) break;
      if (t >= DEPTH) {
        const int u = t - DEPTH;
        uint4 p = add4(x[u % DEPTH], x[(u + 1) % DEPTH]);
        if (u < TL) {
          const int s = u >> 3, j = u & 7;
          if (j == 0) {
            cc = s >= YD ? add4(y[s % YD], p) : p;
            if (s + YD < NS) y[s % YD] = ldtex(tex, tb | (yc & 1023));
          } else cc = add4(cc, p);
          if (j == 6) acc[s] = add4(acc[s], cc);
        } else {
          const int s = (u - TL) >> 1;
          acc[s] = add4(acc[s], p);
        }
      }
      if (t < TL) {
        const int s = t >> 3, j = t & 7;
        if (j == 0) {
          if (ye_of(s - YD) >= 0) acc[ye_of(s - YD) & 3] = add4(acc[ye_of(s - YD) & 3], ye);
          w = wq[s % PF];
          wq[s % PF] = ldtex(tex, ti + (s + PF) * TH);
          yc = __funnelshift_l(w.z, w.z, 5);
          if ((s & 3) != 3) asm volatile("add.u32 %0,%1,%2;" : "=r"(sw[s]) : "r"(w.w), "r"(never));
          if (ye_of(s) >= 0) ye = ldtex(tex, tb | w.w);
        }
        if (t >= DEPTH) { lds_l(j, t % DEPTH); lds_l(j + 1, (t + 1) % DEPTH); }
      } else if (t < TT) {
        const int s = (t - TL) >> 1;
        if (s == 0) {
          asm volatile("add.u32 %0,%1,%2;" : "=r"(c1) : "r"((~lc >> 2) & 16), "r"(never));
          arrive_both(emptyL, more ? lane : 9);
          TR(k * 4 + 3);
          mbar_wait_fast(fullU, (k + 1) & 1);
        }
        const uint32_t sv = sget(s);
        x[t % DEPTH] = lds128(sa0(sv));
        x[(t + 1) % DEPTH] = lds128(sa1(sv));
      } else {
        if (t == TT) { arrive_both(emptyU, lane); mbar_wait_fast(fullL, (k + 1) & 1); w = wq[0]; }
        lds_l(t - TT, t % DEPTH); lds_l(t - TT + 1, (t + 1) % DEPTH);
      }
      if ((t & 3) == 2 && t > 2 && t < TT) SCHED_FENCE(never, t);
    }
  }
  TS(1, 2);
  const uint4 w2v = lds128(barJ + 32);
  const uint32_t cell = sbase + SM_U + tid * 16;
  const int t9 = tbase + 9 * 1024;
  uint4 za[4], i9 = wq[0];
  auto fetch = [&](int q) {
    y[0] = ldtex(tex, t9 | i9.x); y[1] = ldtex(tex, t9 | i9.y); y[2] = ldtex(tex, t9 | i9.z); y[3] = ldtex(tex, t9 | i9.w);
    if (q) {
      i9 = ldtex(tex, ibase + NC * 8192 + min(q + 1, 7) * TH);
      const uint32_t ca = cell + (q > 6 ? 0 : q - 1) * 16384;
#pragma unroll
      for (int s = 0; s < 4; s++) za[s] = lds128(ca + s * 4096);
    }
  };
  fetch(0);
  i9 = wq[1];
#pragma unroll
  for (int s = 0; s < 4; s++) za[s] = acc[s];
#pragma unroll
  for (int s = 0; s < 24; s++) sts128(cell + s * 4096, acc[4 + s]);
  float hw[8];
  {
    const uint32_t ww[4] = {w2v.x, w2v.y, w2v.z, w2v.w};
#pragma unroll
    for (int k = 0; k < 8; k++) hw[k] = 0.5f * ((k & 1) ? bf_hi(ww[k >> 1]) : bf_lo(ww[k >> 1]));
  }
  float* outp = g_acc + half * 8192 + tid;
#pragma unroll 1
  for (int q = 0; q < NS / 4; q++) {
    uint4 z[4];
#pragma unroll
    for (int s = 0; s < 4; s++) z[s] = add4(za[s], y[s]);
    if (q == 1) {
#pragma unroll
      for (int s = 0; s < 4; s++) sts128(cell + s * 4096, acc[28 + s]);
    }
    if (q < 7) fetch(q + 1);
    SCHED_FENCE(never, 999);
#pragma unroll
    for (int s = 0; s < 4; s++) {
      const uint32_t a[4] = {z[s].x, z[s].y, z[s].z, z[s].w};
      float r0 = 0.f;
#pragma unroll
      for (int k = 0; k < 8; k++) {
        const float v = (k & 1) ? bf_hi(a[k >> 1]) : bf_lo(a[k >> 1]);
        const float u = v * fmaf(v * v, 0.7978845608028654f * 0.044715f, 0.7978845608028654f);
        float th; asm("tanh.approx.f32 %0,%1;" : "=f"(th) : "f"(u));
        r0 = fmaf(fmaf(v, th, v), hw[k], r0);
      }
      asm volatile("red.global.add.f32 [%0],%1;" :: "l"(outp + s * TH), "f"(r0) : "memory");
    }
    outp += 4 * TH;
  }
  TS(1, 3);
  asm volatile("bar.sync 1,%0;" :: "n"(TH + 32) : "memory");
  if (tid == 0) {
    unsigned old; asm volatile("atom.acq_rel.gpu.global.inc.u32 %0,[%1],63;" : "=r"(old) : "l"(&g_done[half * 32]) : "memory");
    asm volatile("st.shared.u32 [%0],%1;" :: "r"(barJ + 8), "r"(old) : "memory");
  }
  asm volatile("bar.sync 2,%0;" :: "n"(TH) : "memory");
  uint32_t old; asm volatile("ld.shared.u32 %0,[%1];" : "=r"(old) : "r"(barJ + 8));
  if (old == 63) {
    if (half == 0 && tid == 25) g_slot = 0;
    if (half == 0 && tid < 25) g_flag[tid * 32] = 0;
    float4 v[8];
#pragma unroll
    for (int q = 0; q < 8; q++) v[q] = __ldcg((const float4*)(g_acc + half * 8192) + q * TH + tid);
#pragma unroll
    for (int q = 0; q < 8; q++) ((uint2*)(out + half * 8192))[q * TH + tid] = make_uint2(pack_bf2(v[q].x, v[q].y), pack_bf2(v[q].z, v[q].w));
    TS(6, 2);
  }
}

}

extern "C" void kernel_launch(void* const* d_in, const int* in_sizes, int n_in, void* d_out, int out_size) {
  const int* idx = (const int*)d_in[0];
  const __nv_bfloat16* table = (const __nv_bfloat16*)d_in[1];
  const __nv_bfloat16* wp = (const __nv_bfloat16*)d_in[2];
  const __nv_bfloat16* w1 = (const __nv_bfloat16*)d_in[3];
  const __nv_bfloat16* b1 = (const __nv_bfloat16*)d_in[4];
  const __nv_bfloat16* w2 = (const __nv_bfloat16*)d_in[5];
  const __nv_bfloat16* b2 = (const __nv_bfloat16*)d_in[6];
  static cudaTextureObject_t texScr = 0, texX = 0;
  static CUtensorMap mapW, mapL, mapS, mapT, mapE, mapC;
  static const void *c_tab = nullptr, *c_w1 = nullptr;
  if (c_tab != table || c_w1 != w1) {
    c_tab = table; c_w1 = w1;
    char* scr = nullptr; cudaGetSymbolAddress((void**)&scr, g_scr);
    auto mk_tex = [](const void* p, size_t bytes, cudaChannelFormatDesc d) {
      cudaResourceDesc rd = {}; rd.resType = cudaResourceTypeLinear; rd.res.linear.devPtr = (void*)p; rd.res.linear.desc = d; rd.res.linear.sizeInBytes = bytes;
      cudaTextureDesc td = {}; td.readMode = cudaReadModeElementType;
      cudaTextureObject_t t = 0; cudaCreateTextureObject(&t, &rd, &td, nullptr); return t;
    };
    if (!texScr) {
      texScr = mk_tex(scr, (size_t)SCR_N * 16, cudaCreateChannelDesc<uint4>());
      texX = mk_tex(scr + (size_t)PX_OFF * 16, (size_t)(SCR_N - PX_OFF) * 16, cudaCreateChannelDesc<unsigned>());
    }
    typedef CUresult (*EncFn)(CUtensorMap*, CUtensorMapDataType, cuuint32_t, void*, const cuuint64_t*, const cuuint64_t*, const cuuint32_t*,
                              const cuuint32_t*, CUtensorMapInterleave, CUtensorMapSwizzle, CUtensorMapL2promotion, CUtensorMapFloatOOBfill);
    EncFn enc = nullptr; cudaDriverEntryPointQueryResult qr;
    cudaGetDriverEntryPoint("cuTensorMapEncodeTiled", (void**)&enc, cudaEnableDefault, &qr);
    const cuuint32_t ones[4] = {1, 1, 1, 1};
    auto mk = [&](CUtensorMap* m, CUtensorMapDataType dt, int rank, void* p, const cuuint64_t* dim, const cuuint64_t* str, const cuuint32_t* box, CUtensorMapSwizzle sw) {
      enc(m, dt, rank, p, dim, str, box, ones, CU_TENSOR_MAP_INTERLEAVE_NONE, sw, CU_TENSOR_MAP_L2_PROMOTION_NONE, CU_TENSOR_MAP_FLOAT_OOB_FILL_NONE);
    };
    { cuuint64_t dim[2] = {H_, F_ * D_}, str[1] = {H_ * 2}; cuuint32_t box[2] = {32, 256};
      mk(&mapW, CU_TENSOR_MAP_DATA_TYPE_BFLOAT16, 2, (void*)w1, dim, str, box, CU_TENSOR_MAP_SWIZZLE_64B); }
    { cuuint64_t dim[4] = {64, 64, V_, NC}, str[3] = {128000 * NC, 128, 128000}; cuuint32_t box[4] = {32, 4, 64, 1};
      mk(&mapL, CU_TENSOR_MAP_DATA_TYPE_BFLOAT16, 4, scr + (size_t)PL_OFF * 16, dim, str, box, CU_TENSOR_MAP_SWIZZLE_64B); }
    { cuuint64_t dim[4] = {64, 64, V_ / 4, NC}, str[3] = {32000 * NC, 128, 32000}; cuuint32_t box[4] = {64, 4, 16, 1};
      mk(&mapS, CU_TENSOR_MAP_DATA_TYPE_BFLOAT16, 4, scr + (size_t)PS_OFF * 16, dim, str, box, CU_TENSOR_MAP_SWIZZLE_128B); }
    { cuuint64_t dim[4] = {64, 64, V_ / 8, 10}, str[3] = {163840, 128, 16384}; cuuint32_t box[4] = {64, 4, 8, 2};
      mk(&mapT, CU_TENSOR_MAP_DATA_TYPE_BFLOAT16, 4, scr + (size_t)PT_OFF * 16, dim, str, box, CU_TENSOR_MAP_SWIZZLE_128B); }
    { cuuint64_t dim[2] = {D_, V_}, str[1] = {D_ * 2}; cuuint32_t box[2] = {64, 128};
      mk(&mapE, CU_TENSOR_MAP_DATA_TYPE_BFLOAT16, 2, (void*)table, dim, str, box, CU_TENSOR_MAP_SWIZZLE_128B);
      cuuint32_t box2[2] = {8, 256};
      mk(&mapC, CU_TENSOR_MAP_DATA_TYPE_BFLOAT16, 2, (void*)table, dim, str, box2, CU_TENSOR_MAP_SWIZZLE_NONE); }
    cudaFuncSetAttribute(k_deep, cudaFuncAttributeMaxDynamicSharedMemorySize, DEEP_SMEM);
    cudaFuncSetAttribute(k_tens, cudaFuncAttributeMaxDynamicSharedMemorySize, K1_SMEM);
  }
  k_tens<<<132, 512, K1_SMEM, cudaStreamPerThread>>>(mapW, mapL, mapS, mapT, mapE, mapC, texScr, texX, idx, table, wp, w1, b1, 0);
  cudaLaunchAttribute at[1];
  at[0].id = cudaLaunchAttributeProgrammaticStreamSerialization; at[0].val.programmaticStreamSerializationAllowed = 1;
  cudaLaunchConfig_t cfg = {};
  cfg.stream = cudaStreamPerThread; cfg.attrs = at;
  cfg.gridDim = 128; cfg.blockDim = TH + 128; cfg.dynamicSmemBytes = DEEP_SMEM; cfg.numAttrs = PDL;
  cudaLaunchKernelEx(&cfg, k_deep, texScr, w2, b2, (__nv_bfloat16*)d_out, 0);

}
```

```cpp
#include <cuda_runtime.h>
#include <cuda_bf16.h>
#include <cuda_fp16.h>
#include <stdint.h>
#include <cuda.h>

namespace {

constexpr int B_ = 16384, F_ = 100, D_ = 128, V_ = 1000, H_ = 512;
constexpr int NC = 9;
constexpr int PT_OFF = 0;
constexpr int PL_OFF = 64 * 10 * 1024;
constexpr int PS_OFF = PL_OFF + 64 * NC * 8000;
constexpr int IXH = NC * 8192 + 2048;
constexpr int IX_OFF = PS_OFF + 64 * NC * 2000;
constexpr int I0_OFF = IX_OFF + 2 * IXH;
constexpr int PX_OFF = I0_OFF + 4096;
constexpr int SCR_N = PX_OFF + 64 * 16 * 136;
static_assert(PX_OFF % 32 == 0, "");

__device__ __align__(1024) uint4 g_scr[SCR_N];
__device__ float g_acc[B_];
__device__ unsigned long long g_slot;
__device__ unsigned g_done[64];
__device__ float g_partP[16 * B_];
__device__ float2 g_unscale[16];
__device__ unsigned g_flag[25 * 32];

#define TS(k, i)
#define TR(slot)
#define PT(slot)

constexpr uint64_t POL_EF = 0x12F0000000000000ull, POL_N = 0x1000000000000000ull;
__device__ __forceinline__ uint32_t addbf2(uint32_t a, uint32_t b) { uint32_t r; asm("add.rn.bf16x2 %0,%1,%2;" : "=r"(r) : "r"(a), "r"(b)); return r; }
__device__ __forceinline__ uint4 add4(const uint4& a, const uint4& b) { return make_uint4(addbf2(a.x, b.x), addbf2(a.y, b.y), addbf2(a.z, b.z), addbf2(a.w, b.w)); }
__device__ __forceinline__ uint4 ldtex(cudaTextureObject_t t, int i) {
  uint4 v; asm volatile("tex.1d.v4.u32.s32 {%0,%1,%2,%3},[%4,{%5}];" : "=r"(v.x), "=r"(v.y), "=r"(v.z), "=r"(v.w) : "l"(t), "r"(i)); return v;
}
__device__ __forceinline__ uint4 lds128(uint32_t a) {
  uint4 v; asm volatile("ld.volatile.shared.v4.u32 {%0,%1,%2,%3},[%4];" : "=r"(v.x), "=r"(v.y), "=r"(v.z), "=r"(v.w) : "r"(a)); return v;
}
__device__ __forceinline__ void sts128(uint32_t a, const uint4& v) {
  asm volatile("st.shared.v4.u32 [%0],{%1,%2,%3,%4};" :: "r"(a), "r"(v.x), "r"(v.y), "r"(v.z), "r"(v.w) : "memory");
}
__device__ __forceinline__ void mbar_init(uint32_t bar, int n) { asm volatile("mbarrier.init.shared::cta.b64 [%0],%1;" :: "r"(bar), "r"(n) : "memory"); }
__device__ __forceinline__ void mbar_wait(uint32_t bar, uint32_t parity) {
  uint32_t ok; int it = 0;
  do { asm volatile("{.reg .pred p; mbarrier.try_wait.parity.shared::cta.b64 p,[%1],%2; selp.u32 %0,1,0,p;}" : "=r"(ok) : "r"(bar), "r"(parity) : "memory"); } while (!ok && ++it < (1 << 19));
}
__device__ __forceinline__ void mbar_expect(uint32_t bar, uint32_t bytes) { asm volatile("mbarrier.arrive.expect_tx.shared::cta.b64 _,[%0],%1;" :: "r"(bar), "r"(bytes) : "memory"); }
__device__ __forceinline__ void bulk_g2s(uint32_t dst, const void* src, uint32_t bytes, uint32_t bar) {
  asm volatile("cp.async.bulk.shared::cluster.global.mbarrier::complete_tx::bytes [%0],[%1],%2,[%3];" :: "r"(dst), "l"(src), "r"(bytes), "r"(bar) : "memory");
}
__device__ __forceinline__ void bulk_pf(const void* src, uint32_t bytes) { asm volatile("cp.async.bulk.prefetch.L2.global [%0],%1;" :: "l"(src), "r"(bytes) : "memory"); }
#define SCHED_FENCE(never, k) asm volatile("{.reg .pred p; setp.ne.u32 p,%0,%1; @p bra.uni SKIP_%=; pmevent 1; SKIP_%=: }" :: "r"(never), "r"(0x7fff0000 + (k)) : "memory")
#define PDL 1
#define RSV 23
#define RSV_L 550
#define RSV_T 7200
#define PACE 900
__device__ __forceinline__ int quad_of(int n) { return n < 23 ? n + 2 : n - 23; }
__device__ __forceinline__ void mbar_wait_fast(uint32_t bar, uint32_t parity) {
  asm volatile("{.reg .pred p; .reg .u32 n;\n"
               "mbarrier.try_wait.parity.shared::cta.b64 p,[%0],%1;\n"
               "@p bra DONE_%=;\n"
               "mov.u32 n,0;\n"
               "LOOP_%=: mbarrier.try_wait.parity.shared::cta.b64 p,[%0],%1;\n"
               "add.u32 n,n,1; setp.gt.or.u32 p,n,400000,p;\n"
               "@!p bra LOOP_%=;\n"
               "DONE_%=: }" :: "r"(bar), "r"(parity) : "memory");
}
__device__ __forceinline__ void sleep_until(uint32_t t0, uint32_t dt) { while ((uint32_t)clock() - t0 < dt) __nanosleep(40); }
__device__ __forceinline__ uint32_t s_mask(uint32_t v, int q) { return (1u << ((v + 3 - q) & 3)) | (16u << ((v + 3 + q) & 3)); }
__device__ __forceinline__ uint32_t s_cell(uint32_t v, int q, uint32_t m) {
  const int t = __ffs(~m) - 1;
  const int cp = t == 8 ? q >> 1 : ((t & 4 ? t - q : t + q) - v) & 3;
  return cp * 1001 + v;
}
__device__ __forceinline__ uint32_t pk3(uint32_t a, uint32_t b, uint32_t c) {
  const uint32_t w = c + (a << 12) + (b << 22); return __funnelshift_l(w, w, 27);
}
constexpr int TH = 256, NS = 8192 / TH, YD = 4;
__host__ __device__ constexpr int ye_of(int s) { return s == 3 ? 0 : s == 11 ? 1 : s == 19 ? 2 : s == 23 ? 3 : -1; }
template <int N> __device__ __forceinline__ void wgmma_h(uint32_t* d, const uint32_t* a, uint64_t desc, int acc);
template <> __device__ __forceinline__ void wgmma_h<40>(uint32_t* d, const uint32_t* a, uint64_t desc, int acc) {
  asm volatile("{.reg .pred p; setp.ne.s32 p,%15,0;\n"
    "wgmma.mma_async.sync.aligned.m64n40k16.f16.f16.f16 {%0,%1,%2,%3,%4,%5,%6,%7,%8,%9},{%10,%11,%12,%13},%14,p,1,1,0;}"
    : "+r"(d[0]),"+r"(d[1]),"+r"(d[2]),"+r"(d[3]),"+r"(d[4]),"+r"(d[5]),"+r"(d[6]),"+r"(d[7]),"+r"(d[8]),"+r"(d[9])
    : "r"(a[0]), "r"(a[1]), "r"(a[2]), "r"(a[3]), "l"(desc), "r"(acc));
}
template <> __device__ __forceinline__ void wgmma_h<32>(uint32_t* d, const uint32_t* a, uint64_t desc, int acc) {
  asm volatile("{.reg .pred p; setp.ne.s32 p,%13,0;\n"
    "wgmma.mma_async.sync.aligned.m64n32k16.f16.f16.f16 {%0,%1,%2,%3,%4,%5,%6,%7},{%8,%9,%10,%11},%12,p,1,1,0;}"
    : "+r"(d[0]),"+r"(d[1]),"+r"(d[2]),"+r"(d[3]),"+r"(d[4]),"+r"(d[5]),"+r"(d[6]),"+r"(d[7])
    : "r"(a[0]), "r"(a[1]), "r"(a[2]), "r"(a[3]), "l"(desc), "r"(acc));
}
__device__ __forceinline__ void wgmma_p(float* d, const uint32_t* a, uint64_t desc, int acc) {
  asm volatile("{.reg .pred p; setp.ne.s32 p,%69,0;\n"
    "wgmma.mma_async.sync.aligned.m64n128k16.f32.bf16.bf16 {%0,%1,%2,%3,%4,%5,%6,%7,%8,%9,%10,%11,%12,%13,%14,%15,%16,%17,%18,%19,%20,%21,%22,%23,%24,%25,%26,%27,%28,%29,%30,%31,%32,%33,%34,%35,%36,%37,%38,%39,%40,%41,%42,%43,%44,%45,%46,%47,%48,%49,%50,%51,%52,%53,%54,%55,%56,%57,%58,%59,%60,%61,%62,%63},{%64,%65,%66,%67},%68,p,1,1,1;}"
    : "+f"(d[0]),"+f"(d[1]),"+f"(d[2]),"+f"(d[3]),"+f"(d[4]),"+f"(d[5]),"+f"(d[6]),"+f"(d[7]),"+f"(d[8]),"+f"(d[9]),"+f"(d[10]),"+f"(d[11]),"+f"(d[12]),"+f"(d[13]),"+f"(d[14]),"+f"(d[15]),"+f"(d[16]),"+f"(d[17]),"+f"(d[18]),"+f"(d[19]),"+f"(d[20]),"+f"(d[21]),"+f"(d[22]),"+f"(d[23]),"+f"(d[24]),"+f"(d[25]),"+f"(d[26]),"+f"(d[27]),"+f"(d[28]),"+f"(d[29]),"+f"(d[30]),"+f"(d[31]),"+f"(d[32]),"+f"(d[33]),"+f"(d[34]),"+f"(d[35]),"+f"(d[36]),"+f"(d[37]),"+f"(d[38]),"+f"(d[39]),"+f"(d[40]),"+f"(d[41]),"+f"(d[42]),"+f"(d[43]),"+f"(d[44]),"+f"(d[45]),"+f"(d[46]),"+f"(d[47]),"+f"(d[48]),"+f"(d[49]),"+f"(d[50]),"+f"(d[51]),"+f"(d[52]),"+f"(d[53]),"+f"(d[54]),"+f"(d[55]),"+f"(d[56]),"+f"(d[57]),"+f"(d[58]),"+f"(d[59]),"+f"(d[60]),"+f"(d[61]),"+f"(d[62]),"+f"(d[63])
    : "r"(a[0]), "r"(a[1]), "r"(a[2]), "r"(a[3]), "l"(desc), "r"(acc));
}

__device__ __forceinline__ void mma16816h(uint32_t* c, const uint32_t* a, uint32_t b0, uint32_t b1) {
  asm("mma.sync.aligned.m16n8k16.row.col.f16.f16.f16.f16 {%0,%1},{%2,%3,%4,%5},{%6,%7},{%0,%1};"
      : "+r"(c[0]), "+r"(c[1]) : "r"(a[0]), "r"(a[1]), "r"(a[2]), "r"(a[3]), "r"(b0), "r"(b1));
}
__device__ __forceinline__ void mma1688h(uint32_t* c, uint32_t a0, uint32_t a1, uint32_t b) {
  asm("mma.sync.aligned.m16n8k8.row.col.f16.f16.f16.f16 {%0,%1},{%2,%3},{%4},{%0,%1};" : "+r"(c[0]), "+r"(c[1]) : "r"(a0), "r"(a1), "r"(b));
}
__device__ __forceinline__ void mma1688f(float* c, uint32_t a0, uint32_t a1, uint32_t b) {
  asm("mma.sync.aligned.m16n8k8.row.col.f32.f16.f16.f32 {%0,%1,%2,%3},{%4,%5},{%6},{%0,%1,%2,%3};"
      : "+f"(c[0]), "+f"(c[1]), "+f"(c[2]), "+f"(c[3]) : "r"(a0), "r"(a1), "r"(b));
}
__device__ __forceinline__ uint32_t hadd2(uint32_t a, uint32_t b) { uint32_t r; asm("add.rn.f16x2 %0,%1,%2;" : "=r"(r) : "r"(a), "r"(b)); return r; }
__device__ __forceinline__ uint32_t hfma2(uint32_t a, uint32_t b, uint32_t c) { uint32_t r; asm("fma.rn.f16x2 %0,%1,%2,%3;" : "=r"(r) : "r"(a), "r"(b), "r"(c)); return r; }
__device__ __forceinline__ uint32_t pack_bf2(float lo, float hi) { uint32_t r; asm("cvt.rn.bf16x2.f32 %0,%1,%2;" : "=r"(r) : "f"(hi), "f"(lo)); return r; }
__device__ __forceinline__ uint32_t pack_h2(float lo, float hi) { uint32_t r; asm("cvt.rn.f16x2.f32 %0,%1,%2;" : "=r"(r) : "f"(hi), "f"(lo)); return r; }
__device__ __forceinline__ float bf_lo(uint32_t w) { return __uint_as_float(w << 16); }
__device__ __forceinline__ float bf_hi(uint32_t w) { return __uint_as_float(w & 0xffff0000u); }
__device__ __forceinline__ uint32_t absmax4(const uint4& v, uint32_t m) {
  return __vmaxu2(__vmaxu2(__vmaxu2(v.x & 0x7fff7fffu, v.y & 0x7fff7fffu), __vmaxu2(v.z & 0x7fff7fffu, v.w & 0x7fff7fffu)), m);
}
__device__ __forceinline__ float pow2_scale(uint32_t mbits, int p) { return __uint_as_float((uint32_t)min(max(253 + p - (int)(mbits >> 7), 2), 252) << 23); }

constexpr int G_O0 = 8, G_O1 = 4, G_O2 = 0, G_N0 = 5, G_N1 = 4, G_N2 = 4, G_K0 = 5, G_K1 = 3, G_K2 = 1;
__host__ __device__ constexpr bool unit_wg(int kb, int on) {
  return (on >= G_O0 && on < G_O0 + G_N0 && kb < G_K0) || (on >= G_O1 && on < G_O1 + G_N1 && kb < G_K1) || (on >= G_O2 && on < G_O2 + G_N2 && kb < G_K2);
}
constexpr int G_U1 = G_N0 * G_K0, G_U2 = G_U1 + G_N1 * G_K1, G_U = G_U2 + G_N2 * G_K2;
constexpr int K1_B = 130048, K1_STG = K1_B + 2 * 32768, K1_W = K1_STG + 16384, K1_BAR = K1_W + 48 * 256, K1_SMEM = K1_BAR + 256 + 6400;
__host__ __device__ constexpr int frag_index(int ok, int on) {
  int n = 0;
  for (int k = 0; k < 13; k++) for (int o = k; o < 13; o++) { if (k == ok && o == on) return n; if (!unit_wg(k >> 1, o)) n++; }
  return n;
}
constexpr int HU_N = 2 * G_U + frag_index(99, 99);
static_assert(HU_N <= 96, "");
struct FragIdx { int v[13][13]; };
__host__ __device__ constexpr FragIdx make_fi() { FragIdx f = {}; for (int k = 0; k < 13; k++) for (int o = 0; o < 13; o++) f.v[k][o] = frag_index(k, o); return f; }
__host__ __device__ constexpr uint64_t frag_tab(int first) {
  uint64_t t = 0;
  for (int k = 0; k < 13; k++) for (int o = k; o < 13; o++)
    if (!unit_wg(k >> 1, o)) { const int n = frag_index(k, o) - first; if (n >= 0 && n < 8) t |= (uint64_t)(k << 4 | o) << (8 * n); }
  return t;
}
__device__ __forceinline__ int hu_code(int hu) {
  constexpr uint64_t T0 = frag_tab(0), T1 = frag_tab(8), T2 = frag_tab(16), T3 = frag_tab(24);
  const int u = hu >> 1, f = hu - 2 * G_U;
  if (f >= 0) return (int)((f < 8 ? T0 : f < 16 ? T1 : f < 24 ? T2 : T3) >> (8 * (f & 7))) & 255;
  const int u0 = u < G_U1 ? u : u < G_U2 ? u - G_U1 : u - G_U2;
  const int kb = u < G_U1 ? u0 / G_N0 : u < G_U2 ? u0 / G_N1 : u0 / 4, on = u < G_U1 ? G_O0 + u0 % G_N0 : u < G_U2 ? G_O1 + u0 % G_N1 : G_O2 + u0 % 4;
  return (2 * kb + (hu & 1)) << 4 | on;
}

__device__ __forceinline__ void flag_wait(const unsigned* f, unsigned n) {
  unsigned v; int it = 0;
  asm volatile("ld.acquire.gpu.global.u32 %0,[%1];" : "=r"(v) : "l"(f) : "memory");
  if (v < n) {
    do { __nanosleep(300); asm volatile("ld.relaxed.gpu.global.u32 %0,[%1];" : "=r"(v) : "l"(f) : "memory"); } while (v < n && ++it < (1 << 20));
    asm volatile("ld.acquire.gpu.global.u32 %0,[%1];" : "=r"(v) : "l"(f) : "memory");
  }
}
__device__ __forceinline__ void mbar_arrive(uint32_t bar) { asm volatile("mbarrier.arrive.shared::cta.b64 _,[%0];" :: "r"(bar) : "memory"); }
__device__ __forceinline__ void mbar_arrive_lane0(uint32_t bar) {
  __syncwarp();
  asm volatile("{.reg .pred p; elect.sync _|p,0xffffffff; @p mbarrier.arrive.shared::cta.b64 _,[%0];}" :: "r"(bar) : "memory");
}

__device__ __forceinline__ void arrive_both(uint32_t bar, int lane) {
  __syncwarp();
  asm volatile("{.reg .pred p; .reg .u32 a; setp.lt.u32 p,%1,2; mapa.shared::cluster.u32 a,%0,%1;\n"
               "@p mbarrier.arrive.shared::cluster.b64 _,[a];}" :: "r"(bar), "r"(lane) : "memory");
}
#define ELECT "{.reg .pred p; elect.sync _|p,0xffffffff; @p "
__device__ __forceinline__ void e_mc(uint32_t dst, const void* src, uint32_t bytes, uint32_t bar, uint64_t pol) {
  asm volatile(ELECT "cp.async.bulk.shared::cluster.global.mbarrier::complete_tx::bytes.multicast::cluster.L2::cache_hint [%0],[%1],%2,[%3],%4,%5;}"
               :: "r"(dst), "l"(src), "r"(bytes), "r"(bar), "h"((unsigned short)3), "l"(pol) : "memory");
}
__device__ __forceinline__ void e_g2s(uint32_t dst, const void* src, uint32_t bytes, uint32_t bar) {
  asm volatile(ELECT "cp.async.bulk.shared::cluster.global.mbarrier::complete_tx::bytes [%0],[%1],%2,[%3];}" :: "r"(dst), "l"(src), "r"(bytes), "r"(bar) : "memory");
}
__device__ __forceinline__ void e_pf(const void* src, uint32_t bytes) { asm volatile(ELECT "cp.async.bulk.prefetch.L2.global [%0],%1;}" :: "l"(src), "r"(bytes) : "memory"); }
__device__ __forceinline__ void e_expect(uint32_t bar, uint32_t bytes) { asm volatile(ELECT "mbarrier.arrive.expect_tx.shared::cta.b64 _,[%0],%1;}" :: "r"(bar), "r"(bytes) : "memory"); }
__device__ __forceinline__ void e_tma2d(uint32_t dst, const CUtensorMap* m, int x, int y, uint32_t bar) {
  asm volatile(ELECT "cp.async.bulk.tensor.2d.shared::cluster.global.mbarrier::complete_tx::bytes [%0],[%1,{%2,%3}],[%4];}" :: "r"(dst), "l"(m), "r"(x), "r"(y), "r"(bar) : "memory");
}

__device__ __forceinline__ void pack_role(const int* __restrict__ idx, uint32_t sbase, int pc) {
  constexpr int BUF = 32 * 3328;
  const int tid = threadIdx.x, lane = tid & 31, warp = tid >> 5;
  const uint32_t full = sbase + 2 * BUF, empty = full + 16;
  if (tid == 0) { mbar_init(full, 1); mbar_init(full + 8, 1); mbar_init(empty, 18); mbar_init(empty + 8, 18); asm volatile("fence.proxy.async.shared::cta;" ::: "memory"); }
  __syncthreads();
  auto chunk = [&](int s) { return s * 3200 + (s >> 2) * 288; };
  auto load = [&](int n) {
    const int blk = pc * 16 + n;
    if (lane == 0) mbar_expect(full + (n & 1) * 8, 32 * 3200);
    __syncwarp();
    bulk_g2s(sbase + (n & 1) * BUF + chunk(lane), idx + ((blk >> 5) * 8192 + lane * TH + (blk & 31) * 8) * F_, 3200, full + (n & 1) * 8);
  };
  if (warp == 0) { load(0); load(1); }
  const int l = lane & 7;
  uint32_t rot[8], inc[3];
#pragma unroll
  for (int jj = 0; jj < 8; jj++) rot[jj] = ((l + jj) & 7) * 4;
#pragma unroll
  for (int q = 0; q < 3; q++) inc[q] = (l + 3 * q < 8) << 12 | (l + 3 * q + 1 < 8) << 22 | (q < 2 && l + 3 * q + 2 < 8);
  int loaded = 2;
#pragma unroll 1
  for (int task = warp; task < 288; task += 16) {
    const int n = task / 18, q = (task % 18) * 4 + (lane >> 3), sq = q / 9, k = q % 9;
    if (warp == 0 && n + 1 == loaded && loaded < 16) { mbar_wait(empty + (loaded & 1) * 8, ((loaded >> 1) - 1) & 1); load(loaded); loaded++; }
    mbar_wait(full + (n & 1) * 8, (n >> 1) & 1);
    const uint32_t buf = sbase + (n & 1) * BUF + l * 400, row = buf + chunk(sq * 4);
    auto ld = [&](uint32_t ad) { uint32_t v; asm volatile("ld.shared.u32 %0,[%1];" : "=r"(v) : "r"(ad)); return v; };
    const int blk = pc * 16 + n, half = blk >> 5, col = (blk & 31) * 8 + l;
    const int ks = k == NC - 1 ? 0 : k + 1;
    uint32_t cw[4], sv[8], m[2] = {0, 0};
    { const uint32_t a0 = row + (72 + 2 * ks + (l >> 2)) * 4;
#pragma unroll
      for (int u = 0; u < 8; u++) { sv[u] = ld((a0 ^ ((u >> 2) * 4)) + (u & 3) * 3200); m[u >> 2] |= s_mask(sv[u], l & 3) << (8 * (u & 3)); } }
#pragma unroll
    for (int h = 0; h < 2; h++) { m[h] |= __shfl_xor_sync(0xffffffffu, m[h], 1); m[h] |= __shfl_xor_sync(0xffffffffu, m[h], 2); }
#pragma unroll
    for (int u = 0; u < 4; u++) cw[u] = s_cell(sv[u], l & 3, (m[0] >> (8 * u)) & 255) | s_cell(sv[4 + u], l & 3, (m[1] >> (8 * u)) & 255) << 12;
    if (k == NC - 1) {
      auto wide = [&](uint32_t w) { return (w & 0xfff) << 5 | (w >> 12) << 18 | (l & 4 ? 1u << 4 : 1u << 17); };
      g_scr[I0_OFF + (half * 8 + sq) * TH + col] = make_uint4(wide(cw[0]), wide(cw[1]), wide(cw[2]), wide(cw[3]));
      g_scr[IX_OFF + half * IXH + NC * 8192 + sq * TH + col] = make_uint4(ld(row + 396), ld(row + 3596), ld(row + 6796), ld(row + 9996));
      cw[0] = cw[1] = cw[2] = cw[3] = 0;
    }
    const uint32_t ax = buf + chunk(min(sq + 1, 7) * 4) + (90 + k) * 4;
    const uint32_t yev = ld(buf + ((0x3210 >> (sq * 2 + (sq == 5) * 2)) & 3) * 3200 + (90 + k) * 4);
    uint4* dst = g_scr + IX_OFF + half * IXH + (k * NS + sq * 4) * TH + col;
#pragma unroll
    for (int u = 0; u < 4; u++) {
      uint32_t e[8];
#pragma unroll
      for (int jj = 0; jj < 8; jj++) e[jj] = ld(row + k * 32 + rot[jj] + u * 3200);
      dst[u * TH] = make_uint4(pk3(e[0], e[1], e[2] + inc[0]), pk3(e[3], e[4], e[5] + inc[1]), pk3(e[6], e[7], ld(ax + u * 3200) + inc[2]),
                               u < 3 ? __byte_perm(cw[u], cw[3], 0x4210 + (u << 12)) : yev);
    }
    mbar_arrive_lane0(empty + (n & 1) * 8);
  }
}

__global__ void __cluster_dims__(2, 1, 1) __launch_bounds__(512, 1)
k_tens(const __grid_constant__ CUtensorMap mapW, const __grid_constant__ CUtensorMap mapL, const __grid_constant__ CUtensorMap mapS,
       const __grid_constant__ CUtensorMap mapT, const __grid_constant__ CUtensorMap mapE, const __grid_constant__ CUtensorMap mapC, cudaTextureObject_t tex, cudaTextureObject_t texX,
       const int* __restrict__ idx, const __nv_bfloat16* __restrict__ table, const __nv_bfloat16* __restrict__ wp, const __nv_bfloat16* __restrict__ w1,
       const __nv_bfloat16* __restrict__ b1, int never) {
  extern __shared__ __align__(1024) uint4 sm[];
  const int tid = threadIdx.x, lane = tid & 31, cta = blockIdx.x;
  const uint32_t sbase = (uint32_t)__cvta_generic_to_shared(sm);
  const int g = lane >> 2, r = lane & 3;
  TS(0, 0);
  if (cta >= 128) {
    pack_role(idx, sbase, cta - 128);
    __syncthreads();
    if (tid == 0) {
      asm volatile("fence.acq_rel.gpu; griddepcontrol.launch_dependents;" ::: "memory");
      asm volatile("red.relaxed.gpu.global.add.u32 [%0],1;" :: "l"(&g_flag[24 * 32]) : "memory");
    }
    __syncwarp();
    TS(2, 1);
    asm volatile("barrier.cluster.arrive.relaxed.aligned; barrier.cluster.wait.aligned;" ::: "memory");
    return;
  }
  const uint32_t fullB = sbase + K1_BAR, emptyB = fullB + 24, fullE = fullB + 48, fullC = fullB + 56, fullI = fullB + 64, pxRdy = fullB + 72, fullS = fullB + 96, emptyS = fullB + 104, pkDone = fullB + 112, pkFull = fullB + 136, progG = fullB + 168;
  const int rb = cta & 7, hc = cta >> 3;
  if (__shfl_sync(0xffffffffu, tid >> 5, 0) == 12) {
    if (lane == 0) {
#pragma unroll
      for (int q = 0; q < 19; q++) if (q != 2 && q != 5) mbar_init(fullB + q * 8, q == 3 || q == 4 ? 8 : q == 12 ? 4 : q >= 14 && q < 17 ? 2 : 1);
      asm volatile("st.shared.u32 [%0],%1;" :: "r"(progG), "r"(0) : "memory");
    }
    asm volatile("fence.mbarrier_init.release.cluster; fence.proxy.async.shared::cta;" ::: "memory");
    __syncwarp();
    e_expect(fullC, 16384);
#pragma unroll
    for (int q = 0; q < 4; q++) e_tma2d(sbase + 32768 + q * 4096, &mapC, (cta & 15) * 8, q * 256, fullC);
    asm volatile("bar.arrive 2,512;" ::: "memory");
  }
  asm volatile("barrier.cluster.arrive.relaxed.aligned;" ::: "memory");
  if (tid >= 384) {
    asm volatile("setmaxnreg.dec.sync.aligned.u32 32;");
    if (tid < 416) {
      e_expect(fullI, 51200);
#pragma unroll 1
      for (int u = 0; u < 8; u++) e_g2s(sbase + 76800 + u * 6400, idx + ((cta >> 4) * 8 + u) * 256 * F_, 6400, fullI);
      mbar_wait(fullC, 0);
    e_expect(fullE, 32768);
#pragma unroll
    for (int q = 0; q < 2; q++) e_tma2d(sbase + K1_B + 32768 + q * 16384, &mapE, q * 64, rb * 128, fullE);
      asm volatile("barrier.cluster.wait.aligned;" ::: "memory");
      if (tid == 384) {
#pragma unroll 1
        for (int n = 0; n < 25; n++) {
          const int st = n & 1, q = quad_of(n);
          mbar_wait(emptyB + st * 8, (((n + 1) >> 1) & 1) ^ 1);
          mbar_expect(fullB + st * 8, 32768);
          asm volatile("cp.async.bulk.tensor.2d.shared::cluster.global.mbarrier::complete_tx::bytes.multicast::cluster [%0],[%1,{%2,%3}],[%4],%5;"
                       :: "r"(sbase + K1_B + st * 32768 + (cta & 1) * 16384), "l"(&mapW), "r"(hc * 32), "r"(q * 512 + (cta & 1) * 256),
                          "r"(fullB + st * 8), "h"((unsigned short)3) : "memory");
          if (n + 1 < 25) bulk_pf(w1 + quad_of(n + 1) * 262144 + cta * 2048, 4096);
        }
      }
    } else if (tid < 448) {
      ((float4*)g_acc)[cta * 32 + lane] = make_float4(0.f, 0.f, 0.f, 0.f);
      asm volatile("bar.sync 2,512;" ::: "memory");
      __syncwarp();
      if (tid == 416) {
        int pub = 0;
#pragma unroll 1
        for (int n = 0; n < 50; n++) {
          const int quad = quad_of(n >> 1), mt = n & 1, v0 = rb * 128 + mt * 64;
          const uint32_t stg = sbase + K1_STG;
          if (pub < 3) {
            uint32_t ok = 1;
            if (pub == 0 || n == 49) mbar_wait(pkDone + pub * 8, 0);
            else asm volatile("{.reg .pred p; mbarrier.test_wait.parity.shared::cta.b64 p,[%1],0; selp.u32 %0,1,0,p;}" : "=r"(ok) : "r"(pkDone + pub * 8) : "memory");
            if (ok) {
              asm volatile("cp.async.bulk.wait_group 0;" ::: "memory");
              asm volatile("red.release.gpu.global.add.u32 [%0],1;" :: "l"(&g_flag[((cta >> 4) * 3 + pub) * 32]) : "memory");
              pub++;
              if (n == 49) { n--; continue; }
            }
          }
          mbar_wait(fullS, n & 1);
          asm volatile("fence.proxy.async.shared::cta;" ::: "memory");
          if (quad < 18) {
            asm volatile("cp.async.bulk.tensor.4d.global.shared::cta.bulk_group.L2::cache_hint [%0,{%1,%2,%3,%4}],[%5],%6;"
                         :: "l"(&mapL), "r"((quad & 1) * 32), "r"(hc * 4), "r"(v0), "r"(quad >> 1), "r"(stg), "l"(POL_EF) : "memory");
          } else {
#pragma unroll 1
            for (int hh = 0; hh < 2; hh++) {
              const int pq = quad * 2 + hh;
              asm volatile("cp.async.bulk.tensor.4d.global.shared::cta.bulk_group.L2::cache_hint [%0,{%1,%2,%3,%4}],[%5],%6;"
                         :: "l"(pq < 45 ? &mapS : &mapT), "r"(0), "r"(hc * 4), "r"(v0 >> (pq < 45 ? 2 : 3)), "r"(pq < 45 ? pq - 36 : (pq - 45) * 2), "r"(stg + hh * 8192), "l"(POL_EF) : "memory");
            }
          }
          asm volatile("cp.async.bulk.commit_group;" ::: "memory");
          asm volatile("cp.async.bulk.wait_group.read 0;" ::: "memory");
          mbar_arrive(emptyS);
        }
        asm volatile("cp.async.bulk.wait_group 0;" ::: "memory");
        asm volatile("fence.proxy.async.global;" ::: "memory");
        asm volatile("fence.acq_rel.gpu; griddepcontrol.launch_dependents;" ::: "memory");
        asm volatile("red.relaxed.gpu.global.add.u32 [%0],1;" :: "l"(&g_flag[24 * 32]) : "memory");
        flag_wait(&g_flag[24 * 32], 132);
        asm volatile("fence.proxy.async.global;" ::: "memory");
        const char* base = (const char*)g_scr;
        const int c = cta >> 1, half = cta & 1, ch = (c + (c >> 4) * 5) & 15;
        bulk_pf(base + (PS_OFF + c * NC * 2000) * 16u + half * 16000, 16000);
        bulk_pf(base + (PT_OFF + c * 10 * 1024) * 16u + half * 8000, 8000);
        mbar_expect(fullE, 18432);
        bulk_g2s(sbase + K1_B, base + (I0_OFF + half * 2048 + ch * 128) * 16u, 2048, fullE);
        bulk_g2s(sbase + K1_B + 2048, base + (IX_OFF + half * IXH + ch * 512) * 16u, 8192, fullE);
        bulk_g2s(sbase + K1_B + 10240, base + (IX_OFF + half * IXH + 8192 + ch * 512) * 16u, 8192, fullE);
        mbar_wait(fullE, 1);
      }
    } else {
      const int pw = (tid >> 5) & 1, rg = (cta >> 4) * 8 + ((cta & 15) >> 1), hf = cta & 1;
      const int* ip = idx + (rg * 256 + hf * 8) * F_;
      asm volatile("bar.sync 2,512;" ::: "memory");
      const uint32_t buf = sbase + K1_BAR + 256 + pw * 3200, bar = pkFull + pw * 8;
      const unsigned* fl = &g_flag[(cta >> 4) * 96];
      int batch = 0, rel = pw ? 3 : 0;
#pragma unroll 1
      for (int n = 1 + pw; n < 16; n += 2) {
        if (lane == 0) { mbar_expect(bar, 3200); bulk_g2s(buf, ip + n * 16 * F_, 3200, bar); if (n + 2 < 16) bulk_pf(ip + (n + 2) * 16 * F_, 3200); }
        uint32_t ok; int it = 0;
        do {
          if (rel < batch) {
            unsigned v; asm volatile("ld.relaxed.gpu.global.u32 %0,[%1];" : "=r"(v) : "l"(fl + rel * 32) : "memory");
            if (__all_sync(0xffffffffu, v >= 16)) { flag_wait(fl + rel * 32, 16); mbar_arrive_lane0(pxRdy + rel * 8); rel++; }
          }
          asm volatile("{.reg .pred p; mbarrier.test_wait.parity.shared::cta.b64 p,[%1],%2; selp.u32 %0,1,0,p;}" : "=r"(ok) : "r"(bar), "r"(((n - 1) >> 1) & 1) : "memory");
          ok = __all_sync(0xffffffffu, ok);
          if (!ok) __nanosleep(100);
        } while (!ok && ++it < (1 << 20));
        auto ld = [&](uint32_t ad) { uint32_t v; asm volatile("ld.shared.u32 %0,[%1];" : "=r"(v) : "r"(ad)); return v; };
        const uint32_t p0 = buf + ((lane >> 3) & 1) * 1600 + ((lane >> 4) * 8 + (lane & 7)) * 4;
        auto wd = [&](int t, int h) { const uint32_t o = p0 + (t + (t & 4)) * 400 + h * 192; return pk3(ld(o), ld(o + 64), ld(o + 128)); };
        uint4* dst = g_scr + PX_OFF + (rg * 16 + n) * 136;
        ((unsigned short*)(dst + 128))[lane * 2 + hf] = ld(buf + ((lane >> 3) + (lane & 4)) * 400 + 384 + r * 4);
#pragma unroll
        for (int q = 0; q < 2; q++) dst[(hf * 2 + q) * 32 + lane] = make_uint4(wd(2 * q, 0), wd(2 * q, 1), wd(2 * q + 1, 0), wd(2 * q + 1, 1));
        __syncwarp();
        if (n <= 2 || n == 5 || n == 6 || n >= 14) { mbar_arrive_lane0(pkDone + batch * 8); batch++; }
      }
      for (; rel < 3; rel++) { flag_wait(fl + rel * 32, 16); mbar_arrive_lane0(pxRdy + rel * 8); }
      if (lane == 0) {
        mbar_wait(pxRdy + 16, 0);
        asm volatile("fence.proxy.async.global;" ::: "memory");
        const char* src = (const char*)(g_scr + PX_OFF + ((cta >> 4) * 8 + ((cta >> 1) & 3) * 2 + pw) * 16 * 136);
        int ph = pw;
#pragma unroll 1
        for (int n = 5; n < 16; n++) {
          uint32_t cur; int it = 0;
          do { asm volatile("ld.volatile.shared.u32 %0,[%1];" : "=r"(cur) : "r"(progG)); if (cur + 2 < n) __nanosleep(400); } while (cur + 2 < n && ++it < (1 << 16));
          if (cur + 1 >= n) continue;
          mbar_expect(bar, 2176); bulk_g2s(buf, src + n * 2176, 2176, bar);
          mbar_wait(bar, ph); ph ^= 1;
        }
      }
    }
    return;
  }
  if (tid >= 256) {
    asm volatile("setmaxnreg.inc.sync.aligned.u32 160;");
    const int w = (tid >> 5) & 3;
    const int srow = w * 16 + ((lane & 15) ^ ((lane & 1) << 2)), sc = lane >> 4;
    uint32_t a[2][8][4];
    asm volatile("bar.sync 2,512;" ::: "memory");
    mbar_wait_fast(fullE, 0);
#pragma unroll
    for (int mt = 0; mt < 2; mt++)
#pragma unroll
      for (int ks = 0; ks < 8; ks++)
        asm volatile("ldmatrix.sync.aligned.m8n8.x4.shared.b16 {%0,%1,%2,%3},[%4];"
                     : "=r"(a[mt][ks][0]), "=r"(a[mt][ks][1]), "=r"(a[mt][ks][2]), "=r"(a[mt][ks][3])
                     : "r"(sbase + K1_B + 32768 + (ks >> 2) * 16384 + (mt * 64 + srow) * 128 + ((((ks & 3) * 2 + sc) ^ (srow & 7)) * 16)) : "memory");
    asm volatile("barrier.cluster.wait.aligned;" ::: "memory");
    arrive_both(emptyB + 8, lane);
    asm volatile("bar.sync 3,384;" ::: "memory");
    const int v = w * 16 + (g ^ ((g & 1) << 2));
    const uint32_t baseL = v * 256 + r * 64 + ((v & 1) * 2 + (r >> 1)) * 16, baseS = (v >> 2) * 512 + r * 128 + (((v & 3) * 2) ^ ((v & 4) + r)) * 16,
                   baseT = (v >> 3) * 512 + r * 128 + ((v & 7) ^ r) * 16;
    const uint64_t desc0 = (uint64_t)(((sbase + K1_B) & 0x3FFFF) >> 4) | ((uint64_t)(8192 >> 4) << 16) | ((uint64_t)(512 >> 4) << 32) | (2ull << 62);
#pragma unroll 1
    for (int qn = 0; qn < 25; qn++) {
      const int quad = quad_of(qn), st = qn & 1;
      const bool isL = quad < 18;
      PT(qn * 16);
      mbar_wait_fast(fullB + st * 8, (qn >> 1) & 1);
#pragma unroll
      for (int mt = 0; mt < 2; mt++) {
        float d[64];
        PT(qn * 16 + mt * 4 + 1);
        asm volatile("wgmma.fence.sync.aligned;" ::: "memory");
#pragma unroll
        for (int ks = 0; ks < 8; ks++) wgmma_p(d, a[mt][ks], desc0 + st * 2048 + ks * 64, ks);
        asm volatile("wgmma.commit_group.sync.aligned;" ::: "memory");
        mbar_wait_fast(emptyS, mt ^ 1);
        PT(qn * 16 + mt * 4 + 2);
        asm volatile("wgmma.wait_group.sync.aligned 0;" ::: "memory");
#pragma unroll
        for (int q = 0; q < 16; q++) asm volatile("" : "+f"(d[q * 4]), "+f"(d[q * 4 + 1]), "+f"(d[q * 4 + 2]), "+f"(d[q * 4 + 3]) :: "memory");
        PT(qn * 16 + mt * 4 + 3);
        if (mt) arrive_both(emptyB + st * 8, qn < 23 ? lane : 9);
        if (quad == 24) {
#pragma unroll
          for (int cq = 0; cq < 4; cq++) {
            const uint32_t bw = __ldg((const uint32_t*)(b1 + hc * 32 + cq * 8) + r);
#pragma unroll
            for (int e = 0; e < 4; e++) d[48 + cq * 4 + e] += (e & 1) ? bf_hi(bw) : bf_lo(bw);
          }
        }
#pragma unroll
        for (int h = 0; h < 2; h++) {
          const bool isS = quad * 2 + h < 45;
          const uint32_t base = (isL ? baseL ^ (h * 32) : (isS ? baseS : baseT) ^ (h * 8192)), xj = isS ? 16 : 4096, xr = isL ? 2048 : isS ? 1024 : 576;
#pragma unroll
          for (int e4 = 0; e4 < 4; e4++) {
            const float* e = d + h * 32 + (e4 >> 1) * 16 + (e4 & 1) * 2;
            sts128(sbase + K1_STG + (base ^ ((e4 >> 1) * xj) ^ ((e4 & 1) * xr)),
                   make_uint4(pack_bf2(e[0], e[1]), pack_bf2(e[4], e[5]), pack_bf2(e[8], e[9]), pack_bf2(e[12], e[13])));
          }
        }
        mbar_arrive_lane0(fullS);
        if (!mt) PT(qn * 16 + 4);
      }
      PT(qn * 16 + 8);
    }
    return;
  }
  const int slice = cta & 15;
  const int range = (cta >> 4) * 8 + __shfl_sync(0xffffffffu, tid >> 5, 0);
  uint4 iv[4], trow[4]; uint32_t ix;
  uint2 wrow[10];
#pragma unroll
  for (int q = 0; q < 10; q++) asm volatile("ld.global.nc.v2.u32 {%0,%1},[%2];" : "=r"(wrow[q].x), "=r"(wrow[q].y) : "l"((const uint2*)wp + min(tid + q * 256, 2499)));
  asm volatile("bar.sync 2,512;" ::: "memory");
  uint32_t wa[3][4];
#pragma unroll
  for (int it = 0; it < 3; it++) {
    const int code = hu_code(min(((tid >> 5) * 3 + it) * 4 + (lane >> 3), HU_N - 1)), ok = code >> 4, on = code & 15;
    wa[it][0] = sbase + (on * 8 + (lane & (on == 12 ? 3 : 7))) * 208 + ok * 16;
    wa[it][1] = sbase + (ok * 8 + (lane & (ok == 12 ? 3 : 7))) * 208 + on * 16;
    wa[it][2] = __ballot_sync(0xffffffffu, ok > on); wa[it][3] = __ballot_sync(0xffffffffu, ok >= on);
  }
  SCHED_FENCE(never, 500);
  uint32_t me = 0, mw = 0;
#pragma unroll
  for (int q = 0; q < 10; q++) {
    mw = __vmaxu2(__vmaxu2(wrow[q].x & 0x7fff7fffu, wrow[q].y & 0x7fff7fffu), mw);
    const int e = min(tid + q * 256, 2499), row = e / 25;
    asm volatile("st.shared.v2.u32 [%0],{%1,%2};" :: "r"(sbase + (e + row) * 8), "r"(wrow[q].x), "r"(wrow[q].y) : "memory");
    if (e - row * 25 == 24) asm volatile("st.shared.v2.u32 [%0],{%1,%2};" :: "r"(sbase + (e + row) * 8 + 8), "r"(wrow[q].x), "r"(wrow[q].y) : "memory");
  }
  mbar_wait_fast(fullC, 0);
#pragma unroll
  for (int q = 0; q < 4; q++) { trow[q] = lds128(sbase + 32768 + (tid + q * 256) * 16); me = absmax4(trow[q], me); }
  me = __reduce_max_sync(0xffffffffu, max(me & 0xffff, me >> 16));
  mw = __reduce_max_sync(0xffffffffu, max(mw & 0xffff, mw >> 16));
  uint32_t* sred = (uint32_t*)((char*)sm + 128000);
  if (lane == 0) sred[tid >> 5] = me | mw << 16;
  TS(3, 0);
  asm volatile("setmaxnreg.inc.sync.aligned.u32 160;");
  asm volatile("bar.sync 1,256;" ::: "memory");
  { uint32_t m = 0;
#pragma unroll
    for (int q = 0; q < 8; q++) m = __vmaxu2(m, sred[q]);
    m = __shfl_sync(0xffffffffu, m, 0);
    me = m & 0xffff; mw = m >> 16; }
  const float se = pow2_scale(me, 3), sW = pow2_scale(mw, -2);
  TS(3, 1);
  auto put_rows = [&](int q, bool on) {
    const uint4 t = trow[q];
    const uint4 hv = make_uint4(pack_h2(bf_lo(t.x) * se, bf_hi(t.x) * se), pack_h2(bf_lo(t.y) * se, bf_hi(t.y) * se),
                                pack_h2(bf_lo(t.z) * se, bf_hi(t.z) * se), pack_h2(bf_lo(t.w) * se, bf_hi(t.w) * se));
    if (on)
#pragma unroll
      for (int s = 0; s < 8; s++) sts128(sbase + (tid + q * 256) * 128 + ((s + lane) & 7) * 16, hv);
  };
  uint32_t wx[3][4], wy[3][4];
#pragma unroll
  for (int it = 0; it < 3; it++) {
    asm volatile("ldmatrix.sync.aligned.m8n8.x4.shared.b16 {%0,%1,%2,%3},[%4];" : "=r"(wx[it][0]), "=r"(wx[it][1]), "=r"(wx[it][2]), "=r"(wx[it][3]) : "r"(wa[it][0]) : "memory");
    asm volatile("ldmatrix.sync.aligned.m8n8.x4.trans.shared.b16 {%0,%1,%2,%3},[%4];" : "=r"(wy[it][0]), "=r"(wy[it][1]), "=r"(wy[it][2]), "=r"(wy[it][3]) : "r"(wa[it][1]) : "memory");
  }
  put_rows(1, true); put_rows(2, tid < 88);
#pragma unroll
  for (int it = 0; it < 3; it++)
#pragma unroll
    for (int q = 0; q < 4; q++) {
      const float m0 = (wa[it][2] >> (8 * q)) & 1 ? 0.f : sW, m1 = (wa[it][3] >> (8 * q)) & 1 ? 0.f : sW;
      asm volatile("st.shared.u32 [%0],%1;" :: "r"(sbase + K1_W + (((tid >> 5) * 3 + it) * 4 + q) * 128 + lane * 4),
                   "r"(pack_h2(fmaf(bf_lo(wx[it][q]), m0, bf_lo(wy[it][q]) * m1), fmaf(bf_hi(wx[it][q]), m0, bf_hi(wy[it][q]) * m1))) : "memory");
    }
  asm volatile("fence.proxy.async.shared::cta;" ::: "memory");
  mbar_wait_fast(fullI, 0);
  {
    const uint32_t ib = sbase + 76800 + (tid >> 5) * 6400, p0 = ib + ((lane >> 3) & 1) * 1600 + ((lane >> 4) * 8 + (lane & 7)) * 4;
    auto ld = [&](uint32_t ad) { uint32_t v; asm volatile("ld.shared.u32 %0,[%1];" : "=r"(v) : "r"(ad)); return v; };
    auto wd = [&](int t, int h) { const uint32_t o = p0 + (t + (t & 4)) * 400 + h * 192; return pk3(ld(o), ld(o + 64), ld(o + 128)); };
#pragma unroll
    for (int q = 0; q < 4; q++) {
      iv[q] = make_uint4(wd(2 * q, 0), wd(2 * q, 1), wd(2 * q + 1, 0), wd(2 * q + 1, 1));
    }
    const uint32_t pe = ib + ((lane >> 3) + (lane & 4)) * 400 + 384 + r * 4;
    ix = ld(pe) | ld(pe + 3200) << 16;
  }
  TS(3, 2);
  asm volatile("bar.sync 1,256;" ::: "memory");
  put_rows(0, true);
  uint32_t bf[HU_N - 2 * G_U];
#pragma unroll
  for (int q = 0; q < HU_N - 2 * G_U; q++) asm volatile("ld.shared.u32 %0,[%1];" : "=r"(bf[q]) : "r"(sbase + K1_W + (2 * G_U + q) * 128 + lane * 4));
  if (cta < 16 && tid == 0) g_unscale[cta] = make_float2(__uint_as_float(0x7f000000u - __float_as_uint(se)), __uint_as_float(0x7f000000u - __float_as_uint(sW)));
  TS(3, 3);
  const int px = range * 16 * 136;
  asm volatile("bar.arrive 3,384;" ::: "memory");
  put_rows(2, tid >= 88); put_rows(3, tid + 768 < V_);
  asm volatile("bar.sync 1,256;" ::: "memory");
  TS(0, 1);
  uint32_t lc; asm volatile("add.u32 %0,%1,%2;" : "=r"(lc) : "r"((lane & 7) * 16), "r"(never));
  const uint64_t wdesc = (uint64_t)(((sbase + K1_W) & 0x3FFFF) >> 4) | ((uint64_t)(128 >> 4) << 16) | ((uint64_t)(256 >> 4) << 32);
  uint32_t a[2][6][4], d[2][26], ex[4] = {}, s[4] = {};
  float red[4] = {0.f, 0.f, 0.f, 0.f};
  auto ldsm = [&](uint32_t* o, uint32_t sh) {
    asm volatile("ldmatrix.sync.aligned.m8n8.x4.trans.shared.b16 {%0,%1,%2,%3},[%4];"
                 : "=r"(o[0]), "=r"(o[1]), "=r"(o[2]), "=r"(o[3]) : "r"(sbase + ((sh & 0x1ff80) | lc)));
  };
  auto gather = [&](int t, int hf) {
    const int x = t & 1;
    const uint4 v = iv[(t >> 1) & 3];
#pragma unroll
    for (int kb = 3 * hf; kb < 3 * hf + 3; kb++) {
      const uint32_t ww = x ? (kb < 3 ? v.z : v.w) : (kb < 3 ? v.x : v.y);
      ldsm(a[x][kb], kb % 3 == 0 ? ww : kb % 3 == 1 ? ww >> 10 : __funnelshift_l(ww, ww, 12));
    }
  };
  auto issue = [&](int x) {
    asm volatile("wgmma.fence.sync.aligned;" ::: "memory");
#pragma unroll
    for (int kb = 0; kb < 6; kb++) {
      if (kb < G_K0) wgmma_h<G_N0 * 8>(d[x] + G_O0 * 2, a[x][kb], wdesc + kb * G_N0 * 16, kb);
      if (kb < G_K1) wgmma_h<G_N1 * 8>(d[x] + G_O1 * 2, a[x][kb], wdesc + (G_U1 + kb * G_N1) * 16, kb);
      if (kb < G_K2) wgmma_h<32>(d[x] + G_O2 * 2, a[x][kb], wdesc + (G_U2 + kb * G_N2) * 16, kb);
    }
    asm volatile("wgmma.commit_group.sync.aligned;" ::: "memory");
  };
  auto hmma_part = [&](int t) {
    constexpr FragIdx FI = make_fi();
    const int x = t & 1;
#pragma unroll
    for (int o = 0; o < 13; o++) asm volatile("" : "+r"(d[x][o * 2]), "+r"(d[x][o * 2 + 1]) :: "memory");
#pragma unroll
    for (int kb = 0; kb < 6; kb++)
#pragma unroll
      for (int o = 2 * kb + 1; o < 13; o++)
        if (!unit_wg(kb, o)) mma16816h(d[x] + o * 2, a[x][kb], bf[FI.v[2 * kb][o]], bf[FI.v[2 * kb + 1][o]]);
#pragma unroll
    for (int q = 0; q < 6; q++) if (!unit_wg(q, 2 * q)) mma1688h(d[x] + q * 4, a[x][q][0], a[x][q][1], bf[FI.v[2 * q][2 * q]]);
    mma1688h(d[x] + 24, r < 2 ? ex[t & 3] : 0u, r < 2 ? 0u : ex[t & 3], bf[FI.v[12][12]]);
  };
  auto dot_part = [&](int t, int hf) {
    const int x = t & 1;
    if (hf == 0) {
      const uint32_t pe = hfma2(r < 2 ? d[x][24] : d[x][25], ex[t & 3], 0u);
      s[0] = r < 2 ? pe : 0u; s[1] = r < 2 ? 0u : pe; s[2] = s[3] = 0;
    }
#pragma unroll
    for (int q = 3 * hf; q < 3 * hf + 3; q++)
#pragma unroll
      for (int e = 0; e < 4; e++) s[e] = hfma2(d[x][q * 4 + e], a[x][q][e], s[e]);
  };
  const float* outp = g_partP + slice * B_ + range * 256;
  uint32_t oofs; asm volatile("add.u32 %0,%1,%2;" : "=r"(oofs) : "r"(((r >> 1) * 8 + (r & 1) * 2 + ((lane >> 3) & 1) + (lane >> 4) * 4) * 4), "r"(never));
  float k0 = 0.f, k1 = 0.f, x0 = 0.f, x1 = 0.f;
  auto red_stage = [&](int st, int grp) {
    const bool u16 = lane & 16, u8 = lane & 8;
    if (st == 0) {
      k0 = u16 ? red[2] : red[0]; x0 = __shfl_xor_sync(0xffffffffu, u16 ? red[0] : red[2], 16);
      k1 = u16 ? red[3] : red[1]; x1 = __shfl_xor_sync(0xffffffffu, u16 ? red[1] : red[3], 16);
      red[0] = red[1] = red[2] = red[3] = 0.f;
    }
    if (st == 1) { const float p0 = k0 + x0, p1 = k1 + x1; k0 = u8 ? p1 : p0; x0 = __shfl_xor_sync(0xffffffffu, u8 ? p0 : p1, 8); }
    if (st == 2) { k0 += x0; x0 = __shfl_xor_sync(0xffffffffu, k0, 4); }
    if (st == 3) asm volatile("st.global.f32 [%0],%1;" :: "l"((const char*)(outp + grp * 16) + oofs), "f"(k0 + x0) : "memory");
  };
  auto side = [&](bool first, int t, int prv, int cur, int nxt) {
    const int pn = PX_OFF + px + nxt * 136 + lane;
    if (!first) {
      if (t == 0) { iv[3] = ldtex(tex, PX_OFF + px + cur * 136 + lane + 96); iv[0] = ldtex(tex, pn); }
      if (t == 2) iv[1] = ldtex(tex, pn + 32);
      if (t < 4) red_stage(t, prv);
    } else if (t == 4) {
      TS(4, 2);
      mbar_wait_fast(pxRdy, 0);
      TS(4, 3);
      iv[0] = ldtex(tex, pn); iv[1] = ldtex(tex, pn + 32);
    }
    if (t == 4) { ix = ldtex(texX, (px + nxt * 136 + 128) * 4 + lane).x; iv[2] = ldtex(tex, pn + 64); }
  };
  auto group = [&](bool first, int prv, int cur, int nxt, int part) {
#pragma unroll
    for (int t = part ? 7 : 0; t < 8; t++) {
      if (!part) {
        if (first || t) SCHED_FENCE(never, t * 8);
        side(first, t, prv, cur, nxt);
        dot_part(t, 0);
        SCHED_FENCE(never, t * 8 + 1);
        if (t == 3) ldsm(ex, ix >> 9);
        if (t == 7) ldsm(ex, ix << 7);
        gather(t + 2, 0);
        dot_part(t, 1);
        s[0] = hadd2(s[0], s[2]); s[1] = hadd2(s[1], s[3]);
        if (first || t < 7) SCHED_FENCE(never, t * 8 + 4);
        if (t == 7) break;
      }
      gather(t + 2, 1);
      asm volatile("wgmma.wait_group.sync.aligned 0;" ::: "memory");
      asm volatile("" : "+r"(d[(t & 1) ^ 1][0]) :: "memory");
      mma1688f(red, s[0], s[1], (g | (d[(t & 1) ^ 1][0] & never)) == t ? 0x3c003c00u : 0u);
      hmma_part(t + 1);
      issue(t & 1);
    }
  };
  gather(0, 0); gather(0, 1); issue(0); ldsm(ex, ix << 7); gather(1, 0); gather(1, 1);
  asm volatile("wgmma.wait_group.sync.aligned 0;" ::: "memory");
  hmma_part(0);
  SCHED_FENCE(never, 99);
  issue(1);
  group(true, 0, 0, 1, 0); group(true, 0, 0, 1, 1);
  TS(4, 1);
#pragma unroll 1
  for (int n = 1;; n++) {
    if ((n & 11) == 2) mbar_wait_fast(pxRdy + 8 + (n & 4) * 2, 0);
    asm volatile("st.volatile.shared.u32 [%0],%1;" :: "r"(progG), "r"(n) : "memory");
    group(false, n - 1, n, min(n + 1, 15), 0);
    if (n == 15) break;
    group(false, n - 1, n, min(n + 1, 15), 1);
  }
  asm volatile("wgmma.wait_group.sync.aligned 0;" ::: "memory");
  mma1688f(red, s[0], s[1], g == 7 ? 0x3c003c00u : 0u);
#pragma unroll
  for (int st = 0; st < 4; st++) red_stage(st, 15);
  TS(0, 2);
  asm volatile("barrier.cluster.wait.aligned;" ::: "memory");
  asm volatile("barrier.cluster.arrive.relaxed.aligned; barrier.cluster.wait.aligned;" ::: "memory");
}

constexpr int SM_U = 130048, SM_BAR = 128000, SM_J = SM_U + 98304, DEEP_SMEM = SM_J + 4096;

__global__ void __cluster_dims__(2, 1, 1) __launch_bounds__(TH + 128, 1)
k_deep(cudaTextureObject_t tex, const __nv_bfloat16* __restrict__ w2, const __nv_bfloat16* __restrict__ b2,
       __nv_bfloat16* __restrict__ out, int never) {
  extern __shared__ __align__(1024) uint4 sm[];
  constexpr int PF = 4, DEPTH = 4, NW = TH / 32;
  const int tid = threadIdx.x;
  const int c = blockIdx.x >> 1, half = blockIdx.x & 1;
  const uint32_t sbase = (uint32_t)__cvta_generic_to_shared(sm);
  const uint32_t fullL = sbase + SM_BAR, fullU = fullL + 8, emptyL = fullL + 16, emptyU = fullL + 24, barJ = fullL + 32, barW = fullL + 48;
  TS(1, 0);
  if (tid == 0) {
    mbar_init(fullL, 1); mbar_init(fullU, 1); mbar_init(emptyL, 2 * NW); mbar_init(emptyU, 2 * NW); mbar_init(barJ, 1); mbar_init(barW, 1);
    asm volatile("fence.mbarrier_init.release.cluster;" ::: "memory");
  }
  __syncwarp();
  const int wrp = __shfl_sync(0xffffffffu, tid >> 5, 0);
  const char* base = (const char*)g_scr;
  uint32_t oL = (PL_OFF + c * NC * 8000) * 16u + half * 64000, oS = (PS_OFF + c * NC * 2000) * 16u + half * 16000;
  asm volatile("barrier.cluster.arrive.relaxed.aligned; barrier.cluster.wait.aligned;" ::: "memory");
  if (wrp == NW) {
    asm volatile("fence.proxy.async.global;" ::: "memory");
    e_expect(fullU, 96000);
#pragma unroll
    for (int m = 0; m < 3; m++) e_mc(sbase + SM_U + m * 32032 + half * 16000, base + oS, 16000, fullU, m == 2 ? POL_EF : POL_N);
    e_expect(fullL, 128000);
  }
  TS(5, 1);
  if (wrp >= NW) {
    asm volatile("setmaxnreg.dec.sync.aligned.u32 24;");
    if (wrp == NW) {
      uint32_t oT = (PT_OFF + c * 10 * 1024) * 16u + half * 8000;
      auto warm = [&](uint32_t off, uint32_t hb) {
        asm volatile(ELECT "mbarrier.expect_tx.relaxed.cta.shared::cta.b64 [%0],%1;}" :: "r"(barJ), "r"(2 * hb) : "memory");
        e_g2s(sbase + SM_J, base + off, hb, barJ); e_g2s(sbase + SM_J, base + off + hb, hb, barJ);
      };
      mbar_wait(fullU, 0);
      e_mc(sbase + half * 64000, base + oL, 64000, fullL, POL_EF);
      warm(oT, 4000);
#pragma unroll 1
      for (int k = 0; k + 1 < NC; k++) {
        oL += 128000; oS += 32000; oT += 16384;
        mbar_wait(fullL, k & 1);
        const uint32_t t0 = clock();
        e_pf(base + oS, 16000);
        warm((IX_OFF + half * IXH + (k + 2) * 8192 + ((c + (c >> 4) * (2 * k + 1)) & (k + 2 < NC ? 15 : 3)) * 512) * 16u, 4096);
        mbar_wait(emptyU, k & 1);
        e_expect(fullU, 96000);
#pragma unroll 1
        for (int q = 0; q < 8; q++) {
          sleep_until(t0, q * PACE);
          e_pf(base + oL + q * 8000, 8000);
          if (q >= 2) e_mc(sbase + SM_U + ((q - 2) >> 1) * 32032 + half * 16000 + (q & 1) * 8000, base + oS + (q & 1) * 8000, 8000, fullU, q >= 6 ? POL_EF : POL_N);
        }
        warm(oT, 4000);
        e_expect(fullL, 128000);
        sleep_until(t0, RSV_T);
        unsigned long long now, slot = 0;
        asm volatile("mov.u64 %0,%globaltimer;" : "=l"(now));
        if ((tid & 31) == 0) { atomicMax(&g_slot, now + RSV_L); slot = atomicAdd(&g_slot, (unsigned long long)RSV); }
        slot = __shfl_sync(0xffffffffu, slot, 0);
        for (int it = 0; it < 4000; it++) { asm volatile("mov.u64 %0,%globaltimer;" : "=l"(now)); if (now >= slot) break; }
        mbar_wait(emptyL, k & 1);

        e_mc(sbase + half * 64000, base + oL, 64000, fullL, POL_EF);
      }
      mbar_wait(fullL, (NC - 1) & 1);
      mbar_wait(emptyU, (NC - 1) & 1);
      mbar_arrive_lane0(fullU);
      warm(oT + 16384, 4000);
      mbar_arrive_lane0(barJ); mbar_wait(barJ, 0);
    } else if (tid >= TH + 96) {
      if (tid < TH + 100) asm volatile("st.shared.u32 [%0],%1;" :: "r"(barJ + 32 + (tid & 3) * 4), "r"(((const uint32_t*)w2)[(c >> 2) * 16 + (tid & 3) * 4 + (c & 3)]) : "memory");
      mbar_arrive_lane0(barW);
      asm volatile("griddepcontrol.wait;" ::: "memory");
      const int b = half * 8192 + c * 128 + (tid & 31) * 4;
      const float bias = __bfloat162float(b2[0]);
      float4 s = make_float4(bias, bias, bias, bias);
#pragma unroll 2
      for (int k = 0; k < 16; k++) {
        const float4 v = __ldcg((const float4*)(g_partP + k * B_ + b)); const float2 u = __ldcg(g_unscale + k);
        s.x = fmaf(v.x * u.x * u.x, u.y, s.x); s.y = fmaf(v.y * u.x * u.x, u.y, s.y); s.z = fmaf(v.z * u.x * u.x, u.y, s.z); s.w = fmaf(v.w * u.x * u.x, u.y, s.w);
      }
      asm volatile("red.global.add.v4.f32 [%0],{%1,%2,%3,%4};" :: "l"(g_acc + b), "f"(s.x), "f"(s.y), "f"(s.z), "f"(s.w) : "memory");
      asm volatile("bar.arrive 1,%0;" :: "n"(TH + 32) : "memory");
    }
    return;
  }
  asm volatile("setmaxnreg.inc.sync.aligned.u32 240;");
  const int lane = tid & 31;
  const int tbase = PT_OFF + c * 10 * 1024;
  const int ibase = IX_OFF + half * IXH + tid;
  const uint32_t lc = (tid & 7) << 4;
  uint4 acc[NS], wq[PF], x[DEPTH], y[YD], ye;
  uint32_t sw[NS] = {};
  auto sget = [&](int s) { return (s & 3) == 3 ? __byte_perm(__byte_perm(sw[s - 3], sw[s - 2], 0x0073), sw[s - 1], 0x0710) : sw[s]; };
  auto sa0 = [&](uint32_t v) { return sbase + SM_U + (((v << 5) & 0x1ffe0) | ((lc >> 2) & 16)); };
  uint32_t c1 = 0;
  auto sa1 = [&](uint32_t v) { return sbase + SM_U + (((v >> 7) & 0x1ffe0) | c1); };
  {
    uint4 i0[8];
#pragma unroll
    for (int q = 0; q < 8; q++) i0[q] = ldtex(tex, I0_OFF + (half * 8 + q) * TH + tid);
    auto wd = [&](int k) { return (k & 3) == 0 ? i0[k >> 2].x : (k & 3) == 1 ? i0[k >> 2].y : (k & 3) == 2 ? i0[k >> 2].z : i0[k >> 2].w; };
    TS(5, 2);
    mbar_wait_fast(fullU, 0);
#pragma unroll
    for (int i = 0; i < PF; i++) wq[i] = ldtex(tex, ibase + i * TH);
    TS(1, 1);
#pragma unroll
    for (int s = 0; s < NS; s++) acc[s] = add4(lds128(sbase + SM_U + (wd(s) & 0x1fff0)), lds128(sbase + SM_U + ((wd(s) >> 13) & 0x1fff0)));
    arrive_both(emptyU, lane);
    mbar_wait_fast(barW, 0);
    TS(5, 3);
  }
  uint4 w = wq[0];
  auto lds_l = [&](int jj, int slot) {
    const uint32_t ww = jj < 3 ? w.x : jj < 6 ? w.y : w.z;
    const uint32_t sh = jj % 3 == 0 ? ww : jj % 3 == 1 ? ww >> 10 : __funnelshift_l(ww, ww, 12);
    x[slot] = lds128(sbase + ((sh & 0x1ff80) | lc) + jj * 16 - 128);
  };
  mbar_wait_fast(fullL, 0);
  lds_l(0, 0); lds_l(1, 1); lds_l(2, 2); lds_l(3, 3);
#pragma unroll 1
  for (int k = 0; k < NC; k++) {
    const int ti = ibase + k * 8192;
    const int tb = tbase + k * 1024;
    const bool more = k + 1 < NC;
    TR(k * 4);
    TR(k * 4 + 2);
    uint4 cc; uint32_t yc;
    constexpr int TL = NS * 8, TT = TL + NS * 2;
#pragma unroll
    for (int t = 0; t < TT + DEPTH; t += 2) {
      if (t == TL + DEPTH && !more) break;
      if (t >= DEPTH) {
        const int u = t - DEPTH;
        uint4 p = add4(x[u % DEPTH], x[(u + 1) % DEPTH]);
        if (u < TL) {
          const int s = u >> 3, j = u & 7;
          if (j == 0) {
            cc = s >= YD ? add4(y[s % YD], p) : p;
            if (s + YD < NS) y[s % YD] = ldtex(tex, tb | (yc & 1023));
          } else cc = add4(cc, p);
          if (j == 6) acc[s] = add4(acc[s], cc);
        } else {
          const int s = (u - TL) >> 1;
          acc[s] = add4(acc[s], p);
        }
      }
      if (t < TL) {
        const int s = t >> 3, j = t & 7;
        if (j == 0) {
          if (ye_of(s - YD) >= 0) acc[ye_of(s - YD) & 3] = add4(acc[ye_of(s - YD) & 3], ye);
          w = wq[s % PF];
          wq[s % PF] = ldtex(tex, ti + (s + PF) * TH);
          yc = __funnelshift_l(w.z, w.z, 5);
          if ((s & 3) != 3) asm volatile("add.u32 %0,%1,%2;" : "=r"(sw[s]) : "r"(w.w), "r"(never));
          if (ye_of(s) >= 0) ye = ldtex(tex, tb | w.w);
        }
        if (t >= DEPTH) { lds_l(j, t % DEPTH); lds_l(j + 1, (t + 1) % DEPTH); }
      } else if (t < TT) {
        const int s = (t - TL) >> 1;
        if (s == 0) {
          asm volatile("add.u32 %0,%1,%2;" : "=r"(c1) : "r"((~lc >> 2) & 16), "r"(never));
          arrive_both(emptyL, more ? lane : 9);
          TR(k * 4 + 3);
          mbar_wait_fast(fullU, (k + 1) & 1);
        }
        const uint32_t sv = sget(s);
        x[t % DEPTH] = lds128(sa0(sv));
        x[(t + 1) % DEPTH] = lds128(sa1(sv));
      } else {
        if (t == TT) { arrive_both(emptyU, lane); mbar_wait_fast(fullL, (k + 1) & 1); w = wq[0]; }
        lds_l(t - TT, t % DEPTH); lds_l(t - TT + 1, (t + 1) % DEPTH);
      }
      if ((t & 3) == 2 && t > 2 && t < TT) SCHED_FENCE(never, t);
    }
  }
  TS(1, 2);
  const uint4 w2v = lds128(barJ + 32);
  const uint32_t cell = sbase + SM_U + tid * 16;
  const int t9 = tbase + 9 * 1024;
  uint4 za[4], i9 = wq[0];
  auto fetch = [&](int q) {
    y[0] = ldtex(tex, t9 | i9.x); y[1] = ldtex(tex, t9 | i9.y); y[2] = ldtex(tex, t9 | i9.z); y[3] = ldtex(tex, t9 | i9.w);
    if (q) {
      i9 = ldtex(tex, ibase + NC * 8192 + min(q + 1, 7) * TH);
      const uint32_t ca = cell + (q > 6 ? 0 : q - 1) * 16384;
#pragma unroll
      for (int s = 0; s < 4; s++) za[s] = lds128(ca + s * 4096);
    }
  };
  fetch(0);
  i9 = wq[1];
#pragma unroll
  for (int s = 0; s < 4; s++) za[s] = acc[s];
#pragma unroll
  for (int s = 0; s < 24; s++) sts128(cell + s * 4096, acc[4 + s]);
  float hw[8];
  {
    const uint32_t ww[4] = {w2v.x, w2v.y, w2v.z, w2v.w};
#pragma unroll
    for (int k = 0; k < 8; k++) hw[k] = 0.5f * ((k & 1) ? bf_hi(ww[k >> 1]) : bf_lo(ww[k >> 1]));
  }
  float* outp = g_acc + half * 8192 + tid;
#pragma unroll 1
  for (int q = 0; q < NS / 4; q++) {
    uint4 z[4];
#pragma unroll
    for (int s = 0; s < 4; s++) z[s] = add4(za[s], y[s]);
    if (q == 1) {
#pragma unroll
      for (int s = 0; s < 4; s++) sts128(cell + s * 4096, acc[28 + s]);
    }
    if (q < 7) fetch(q + 1);
    SCHED_FENCE(never, 999);
#pragma unroll
    for (int s = 0; s < 4; s++) {
      const uint32_t a[4] = {z[s].x, z[s].y, z[s].z, z[s].w};
      float r0 = 0.f;
#pragma unroll
      for (int k = 0; k < 8; k++) {
        const float v = (k & 1) ? bf_hi(a[k >> 1]) : bf_lo(a[k >> 1]);
        const float u = v * fmaf(v * v, 0.7978845608028654f * 0.044715f, 0.7978845608028654f);
        float th; asm("tanh.approx.f32 %0,%1;" : "=f"(th) : "f"(u));
        r0 = fmaf(fmaf(v, th, v), hw[k], r0);
      }
      asm volatile("red.global.add.f32 [%0],%1;" :: "l"(outp + s * TH), "f"(r0) : "memory");
    }
    outp += 4 * TH;
  }
  TS(1, 3);
  asm volatile("bar.sync 1,%0;" :: "n"(TH + 32) : "memory");
  if (tid == 0) {
    unsigned old; asm volatile("atom.acq_rel.gpu.global.inc.u32 %0,[%1],63;" : "=r"(old) : "l"(&g_done[half * 32]) : "memory");
    asm volatile("st.shared.u32 [%0],%1;" :: "r"(barJ + 8), "r"(old) : "memory");
  }
  asm volatile("bar.sync 2,%0;" :: "n"(TH) : "memory");
  uint32_t old; asm volatile("ld.shared.u32 %0,[%1];" : "=r"(old) : "r"(barJ + 8));
  if (old == 63) {
    if (half == 0 && tid == 25) g_slot = 0;
    if (half == 0 && tid < 25) g_flag[tid * 32] = 0;
    float4 v[8];
#pragma unroll
    for (int q = 0; q < 8; q++) v[q] = __ldcg((const float4*)(g_acc + half * 8192) + q * TH + tid);
#pragma unroll
    for (int q = 0; q < 8; q++) ((uint2*)(out + half * 8192))[q * TH + tid] = make_uint2(pack_bf2(v[q].x, v[q].y), pack_bf2(v[q].z, v[q].w));
    TS(6, 2);
  }
}

}

extern "C" void kernel_launch(void* const* d_in, const int* in_sizes, int n_in, void* d_out, int out_size) {
  const int* idx = (const int*)d_in[0];
  const __nv_bfloat16* table = (const __nv_bfloat16*)d_in[1];
  const __nv_bfloat16* wp = (const __nv_bfloat16*)d_in[2];
  const __nv_bfloat16* w1 = (const __nv_bfloat16*)d_in[3];
  const __nv_bfloat16* b1 = (const __nv_bfloat16*)d_in[4];
  const __nv_bfloat16* w2 = (const __nv_bfloat16*)d_in[5];
  const __nv_bfloat16* b2 = (const __nv_bfloat16*)d_in[6];
  static cudaTextureObject_t texScr = 0, texX = 0;
  static CUtensorMap mapW, mapL, mapS, mapT, mapE, mapC;
  static const void *c_tab = nullptr, *c_w1 = nullptr;
  if (c_tab != table || c_w1 != w1) {
    c_tab = table; c_w1 = w1;
    char* scr = nullptr; cudaGetSymbolAddress((void**)&scr, g_scr);
    auto mk_tex = [](const void* p, size_t bytes, cudaChannelFormatDesc d) {
      cudaResourceDesc rd = {}; rd.resType = cudaResourceTypeLinear; rd.res.linear.devPtr = (void*)p; rd.res.linear.desc = d; rd.res.linear.sizeInBytes = bytes;
      cudaTextureDesc td = {}; td.readMode = cudaReadModeElementType;
      cudaTextureObject_t t = 0; cudaCreateTextureObject(&t, &rd, &td, nullptr); return t;
    };
    if (!texScr) {
      texScr = mk_tex(scr, (size_t)SCR_N * 16, cudaCreateChannelDesc<uint4>());
      texX = mk_tex(scr + (size_t)PX_OFF * 16, (size_t)(SCR_N - PX_OFF) * 16, cudaCreateChannelDesc<unsigned>());
    }
    typedef CUresult (*EncFn)(CUtensorMap*, CUtensorMapDataType, cuuint32_t, void*, const cuuint64_t*, const cuuint64_t*, const cuuint32_t*,
                              const cuuint32_t*, CUtensorMapInterleave, CUtensorMapSwizzle, CUtensorMapL2promotion, CUtensorMapFloatOOBfill);
    EncFn enc = nullptr; cudaDriverEntryPointQueryResult qr;
    cudaGetDriverEntryPoint("cuTensorMapEncodeTiled", (void**)&enc, cudaEnableDefault, &qr);
    const cuuint32_t ones[4] = {1, 1, 1, 1};
    auto mk = [&](CUtensorMap* m, CUtensorMapDataType dt, int rank, void* p, const cuuint64_t* dim, const cuuint64_t* str, const cuuint32_t* box, CUtensorMapSwizzle sw) {
      enc(m, dt, rank, p, dim, str, box, ones, CU_TENSOR_MAP_INTERLEAVE_NONE, sw, CU_TENSOR_MAP_L2_PROMOTION_NONE, CU_TENSOR_MAP_FLOAT_OOB_FILL_NONE);
    };
    { cuuint64_t dim[2] = {H_, F_ * D_}, str[1] = {H_ * 2}; cuuint32_t box[2] = {32, 256};
      mk(&mapW, CU_TENSOR_MAP_DATA_TYPE_BFLOAT16, 2, (void*)w1, dim, str, box, CU_TENSOR_MAP_SWIZZLE_64B); }
    { cuuint64_t dim[4] = {64, 64, V_, NC}, str[3] = {128000 * NC, 128, 128000}; cuuint32_t box[4] = {32, 4, 64, 1};
      mk(&mapL, CU_TENSOR_MAP_DATA_TYPE_BFLOAT16, 4, scr + (size_t)PL_OFF * 16, dim, str, box, CU_TENSOR_MAP_SWIZZLE_64B); }
    { cuuint64_t dim[4] = {64, 64, V_ / 4, NC}, str[3] = {32000 * NC, 128, 32000}; cuuint32_t box[4] = {64, 4, 16, 1};
      mk(&mapS, CU_TENSOR_MAP_DATA_TYPE_BFLOAT16, 4, scr + (size_t)PS_OFF * 16, dim, str, box, CU_TENSOR_MAP_SWIZZLE_128B); }
    { cuuint64_t dim[4] = {64, 64, V_ / 8, 10}, str[3] = {163840, 128, 16384}; cuuint32_t box[4] = {64, 4, 8, 2};
      mk(&mapT, CU_TENSOR_MAP_DATA_TYPE_BFLOAT16, 4, scr + (size_t)PT_OFF * 16, dim, str, box, CU_TENSOR_MAP_SWIZZLE_128B); }
    { cuuint64_t dim[2] = {D_, V_}, str[1] = {D_ * 2}; cuuint32_t box[2] = {64, 128};
      mk(&mapE, CU_TENSOR_MAP_DATA_TYPE_BFLOAT16, 2, (void*)table, dim, str, box, CU_TENSOR_MAP_SWIZZLE_128B);
      cuuint32_t box2[2] = {8, 256};
      mk(&mapC, CU_TENSOR_MAP_DATA_TYPE_BFLOAT16, 2, (void*)table, dim, str, box2, CU_TENSOR_MAP_SWIZZLE_NONE); }
    cudaFuncSetAttribute(k_deep, cudaFuncAttributeMaxDynamicSharedMemorySize, DEEP_SMEM);
    cudaFuncSetAttribute(k_tens, cudaFuncAttributeMaxDynamicSharedMemorySize, K1_SMEM);
  }
  k_tens<<<132, 512, K1_SMEM, cudaStreamPerThread>>>(mapW, mapL, mapS, mapT, mapE, mapC, texScr, texX, idx, table, wp, w1, b1, 0);
  cudaLaunchAttribute at[1];
  at[0].id = cudaLaunchAttributeProgrammaticStreamSerialization; at[0].val.programmaticStreamSerializationAllowed = 1;
  cudaLaunchConfig_t cfg = {};
  cfg.stream = cudaStreamPerThread; cfg.attrs = at;
  cfg.gridDim = 128; cfg.blockDim = TH + 128; cfg.dynamicSmemBytes = DEEP_SMEM; cfg.numAttrs = PDL;
  cudaLaunchKernelEx(&cfg, k_deep, texScr, w2, b2, (__nv_bfloat16*)d_out, 0);

}
```

```cpp
#include <cuda_runtime.h>
#include <cuda_bf16.h>
#include <cuda_fp16.h>
#include <stdint.h>
#include <cuda.h>

namespace {

constexpr int B_ = 16384, F_ = 100, D_ = 128, V_ = 1000, H_ = 512;
constexpr int NC = 9;
constexpr int PT_OFF = 0;
constexpr int PL_OFF = 64 * 10 * 1024;
constexpr int PS_OFF = PL_OFF + 64 * NC * 8000;
constexpr int IXH = NC * 8192 + 2048;
constexpr int IX_OFF = PS_OFF + 64 * NC * 2000;
constexpr int I0_OFF = IX_OFF + 2 * IXH;
constexpr int PX_OFF = I0_OFF + 4096;
constexpr int SCR_N = PX_OFF + 64 * 16 * 136;
static_assert(PX_OFF % 32 == 0, "");

__device__ __align__(1024) uint4 g_scr[SCR_N];
__device__ float g_acc[B_];
__device__ unsigned long long g_slot;
__device__ unsigned g_done[64];
__device__ float g_partP[16 * B_];
__device__ float2 g_unscale[16];
__device__ unsigned g_flag[25 * 32];

#define TS(k, i)
#define TR(slot)
#define PT(slot)

constexpr uint64_t POL_EF = 0x12F0000000000000ull, POL_N = 0x1000000000000000ull;
__device__ __forceinline__ uint32_t addbf2(uint32_t a, uint32_t b) { uint32_t r; asm("add.rn.bf16x2 %0,%1,%2;" : "=r"(r) : "r"(a), "r"(b)); return r; }
__device__ __forceinline__ uint4 add4(const uint4& a, const uint4& b) { return make_uint4(addbf2(a.x, b.x), addbf2(a.y, b.y), addbf2(a.z, b.z), addbf2(a.w, b.w)); }
__device__ __forceinline__ uint4 ldtex(cudaTextureObject_t t, int i) {
  uint4 v; asm volatile("tex.1d.v4.u32.s32 {%0,%1,%2,%3},[%4,{%5}];" : "=r"(v.x), "=r"(v.y), "=r"(v.z), "=r"(v.w) : "l"(t), "r"(i)); return v;
}
__device__ __forceinline__ uint4 lds128(uint32_t a) {
  uint4 v; asm volatile("ld.volatile.shared.v4.u32 {%0,%1,%2,%3},[%4];" : "=r"(v.x), "=r"(v.y), "=r"(v.z), "=r"(v.w) : "r"(a)); return v;
}
__device__ __forceinline__ void sts128(uint32_t a, const uint4& v) {
  asm volatile("st.shared.v4.u32 [%0],{%1,%2,%3,%4};" :: "r"(a), "r"(v.x), "r"(v.y), "r"(v.z), "r"(v.w) : "memory");
}
__device__ __forceinline__ void mbar_init(uint32_t bar, int n) { asm volatile("mbarrier.init.shared::cta.b64 [%0],%1;" :: "r"(bar), "r"(n) : "memory"); }
__device__ __forceinline__ void mbar_wait(uint32_t bar, uint32_t parity) {
  uint32_t ok; int it = 0;
  do { asm volatile("{.reg .pred p; mbarrier.try_wait.parity.shared::cta.b64 p,[%1],%2; selp.u32 %0,1,0,p;}" : "=r"(ok) : "r"(bar), "r"(parity) : "memory"); } while (!ok && ++it < (1 << 19));
}
__device__ __forceinline__ void mbar_expect(uint32_t bar, uint32_t bytes) { asm volatile("mbarrier.arrive.expect_tx.shared::cta.b64 _,[%0],%1;" :: "r"(bar), "r"(bytes) : "memory"); }
__device__ __forceinline__ void bulk_g2s(uint32_t dst, const void* src, uint32_t bytes, uint32_t bar) {
  asm volatile("cp.async.bulk.shared::cluster.global.mbarrier::complete_tx::bytes [%0],[%1],%2,[%3];" :: "r"(dst), "l"(src), "r"(bytes), "r"(bar) : "memory");
}
__device__ __forceinline__ void bulk_pf(const void* src, uint32_t bytes) { asm volatile("cp.async.bulk.prefetch.L2.global [%0],%1;" :: "l"(src), "r"(bytes) : "memory"); }
#define SCHED_FENCE(never, k) asm volatile("{.reg .pred p; setp.ne.u32 p,%0,%1; @p bra.uni SKIP_%=; pmevent 1; SKIP_%=: }" :: "r"(never), "r"(0x7fff0000 + (k)) : "memory")
#define PDL 1
#define RSV 23
#define RSV_L 550
#define RSV_T 7200
#define PACE 900
__device__ __forceinline__ int quad_of(int n) { return n < 23 ? n + 2 : n - 23; }
__device__ __forceinline__ void mbar_wait_fast(uint32_t bar, uint32_t parity) {
  asm volatile("{.reg .pred p; .reg .u32 n;\n"
               "mbarrier.try_wait.parity.shared::cta.b64 p,[%0],%1;\n"
               "@p bra DONE_%=;\n"
               "mov.u32 n,0;\n"
               "LOOP_%=: mbarrier.try_wait.parity.shared::cta.b64 p,[%0],%1;\n"
               "add.u32 n,n,1; setp.gt.or.u32 p,n,400000,p;\n"
               "@!p bra LOOP_%=;\n"
               "DONE_%=: }" :: "r"(bar), "r"(parity) : "memory");
}
__device__ __forceinline__ void sleep_until(uint32_t t0, uint32_t dt) { while ((uint32_t)clock() - t0 < dt) __nanosleep(40); }
__device__ __forceinline__ uint32_t s_mask(uint32_t v, int q) { return (1u << ((v + 3 - q) & 3)) | (16u << ((v + 3 + q) & 3)); }
__device__ __forceinline__ uint32_t s_cell(uint32_t v, int q, uint32_t m) {
  const int t = __ffs(~m) - 1;
  const int cp = t == 8 ? q >> 1 : ((t & 4 ? t - q : t + q) - v) & 3;
  return cp * 1001 + v;
}
__device__ __forceinline__ uint32_t pk3(uint32_t a, uint32_t b, uint32_t c) {
  const uint32_t w = c + (a << 12) + (b << 22); return __funnelshift_l(w, w, 27);
}
constexpr int TH = 256, NS = 8192 / TH, YD = 4;
__host__ __device__ constexpr int ye_of(int s) { return s == 3 ? 0 : s == 11 ? 1 : s == 19 ? 2 : s == 23 ? 3 : -1; }
template <int N> __device__ __forceinline__ void wgmma_h(uint32_t* d, const uint32_t* a, uint64_t desc, int acc);
template <> __device__ __forceinline__ void wgmma_h<40>(uint32_t* d, const uint32_t* a, uint64_t desc, int acc) {
  asm volatile("{.reg .pred p; setp.ne.s32 p,%15,0;\n"
    "wgmma.mma_async.sync.aligned.m64n40k16.f16.f16.f16 {%0,%1,%2,%3,%4,%5,%6,%7,%8,%9},{%10,%11,%12,%13},%14,p,1,1,0;}"
    : "+r"(d[0]),"+r"(d[1]),"+r"(d[2]),"+r"(d[3]),"+r"(d[4]),"+r"(d[5]),"+r"(d[6]),"+r"(d[7]),"+r"(d[8]),"+r"(d[9])
    : "r"(a[0]), "r"(a[1]), "r"(a[2]), "r"(a[3]), "l"(desc), "r"(acc));
}
template <> __device__ __forceinline__ void wgmma_h<32>(uint32_t* d, const uint32_t* a, uint64_t desc, int acc) {
  asm volatile("{.reg .pred p; setp.ne.s32 p,%13,0;\n"
    "wgmma.mma_async.sync.aligned.m64n32k16.f16.f16.f16 {%0,%1,%2,%3,%4,%5,%6,%7},{%8,%9,%10,%11},%12,p,1,1,0;}"
    : "+r"(d[0]),"+r"(d[1]),"+r"(d[2]),"+r"(d[3]),"+r"(d[4]),"+r"(d[5]),"+r"(d[6]),"+r"(d[7])
    : "r"(a[0]), "r"(a[1]), "r"(a[2]), "r"(a[3]), "l"(desc), "r"(acc));
}
__device__ __forceinline__ void wgmma_p(float* d, const uint32_t* a, uint64_t desc, int acc) {
  asm volatile("{.reg .pred p; setp.ne.s32 p,%69,0;\n"
    "wgmma.mma_async.sync.aligned.m64n128k16.f32.bf16.bf16 {%0,%1,%2,%3,%4,%5,%6,%7,%8,%9,%10,%11,%12,%13,%14,%15,%16,%17,%18,%19,%20,%21,%22,%23,%24,%25,%26,%27,%28,%29,%30,%31,%32,%33,%34,%35,%36,%37,%38,%39,%40,%41,%42,%43,%44,%45,%46,%47,%48,%49,%50,%51,%52,%53,%54,%55,%56,%57,%58,%59,%60,%61,%62,%63},{%64,%65,%66,%67},%68,p,1,1,1;}"
    : "+f"(d[0]),"+f"(d[1]),"+f"(d[2]),"+f"(d[3]),"+f"(d[4]),"+f"(d[5]),"+f"(d[6]),"+f"(d[7]),"+f"(d[8]),"+f"(d[9]),"+f"(d[10]),"+f"(d[11]),"+f"(d[12]),"+f"(d[13]),"+f"(d[14]),"+f"(d[15]),"+f"(d[16]),"+f"(d[17]),"+f"(d[18]),"+f"(d[19]),"+f"(d[20]),"+f"(d[21]),"+f"(d[22]),"+f"(d[23]),"+f"(d[24]),"+f"(d[25]),"+f"(d[26]),"+f"(d[27]),"+f"(d[28]),"+f"(d[29]),"+f"(d[30]),"+f"(d[31]),"+f"(d[32]),"+f"(d[33]),"+f"(d[34]),"+f"(d[35]),"+f"(d[36]),"+f"(d[37]),"+f"(d[38]),"+f"(d[39]),"+f"(d[40]),"+f"(d[41]),"+f"(d[42]),"+f"(d[43]),"+f"(d[44]),"+f"(d[45]),"+f"(d[46]),"+f"(d[47]),"+f"(d[48]),"+f"(d[49]),"+f"(d[50]),"+f"(d[51]),"+f"(d[52]),"+f"(d[53]),"+f"(d[54]),"+f"(d[55]),"+f"(d[56]),"+f"(d[57]),"+f"(d[58]),"+f"(d[59]),"+f"(d[60]),"+f"(d[61]),"+f"(d[62]),"+f"(d[63])
    : "r"(a[0]), "r"(a[1]), "r"(a[2]), "r"(a[3]), "l"(desc), "r"(acc));
}

__device__ __forceinline__ void mma16816h(uint32_t* c, const uint32_t* a, uint32_t b0, uint32_t b1) {
  asm("mma.sync.aligned.m16n8k16.row.col.f16.f16.f16.f16 {%0,%1},{%2,%3,%4,%5},{%6,%7},{%0,%1};"
      : "+r"(c[0]), "+r"(c[1]) : "r"(a[0]), "r"(a[1]), "r"(a[2]), "r"(a[3]), "r"(b0), "r"(b1));
}
__device__ __forceinline__ void mma1688h(uint32_t* c, uint32_t a0, uint32_t a1, uint32_t b) {
  asm("mma.sync.aligned.m16n8k8.row.col.f16.f16.f16.f16 {%0,%1},{%2,%3},{%4},{%0,%1};" : "+r"(c[0]), "+r"(c[1]) : "r"(a0), "r"(a1), "r"(b));
}
__device__ __forceinline__ void mma1688f(float* c, uint32_t a0, uint32_t a1, uint32_t b) {
  asm("mma.sync.aligned.m16n8k8.row.col.f32.f16.f16.f32 {%0,%1,%2,%3},{%4,%5},{%6},{%0,%1,%2,%3};"
      : "+f"(c[0]), "+f"(c[1]), "+f"(c[2]), "+f"(c[3]) : "r"(a0), "r"(a1), "r"(b));
}
__device__ __forceinline__ uint32_t hadd2(uint32_t a, uint32_t b) { uint32_t r; asm("add.rn.f16x2 %0,%1,%2;" : "=r"(r) : "r"(a), "r"(b)); return r; }
__device__ __forceinline__ uint32_t hfma2(uint32_t a, uint32_t b, uint32_t c) { uint32_t r; asm("fma.rn.f16x2 %0,%1,%2,%3;" : "=r"(r) : "r"(a), "r"(b), "r"(c)); return r; }
__device__ __forceinline__ uint32_t pack_bf2(float lo, float hi) { uint32_t r; asm("cvt.rn.bf16x2.f32 %0,%1,%2;" : "=r"(r) : "f"(hi), "f"(lo)); return r; }
__device__ __forceinline__ uint32_t pack_h2(float lo, float hi) { uint32_t r; asm("cvt.rn.f16x2.f32 %0,%1,%2;" : "=r"(r) : "f"(hi), "f"(lo)); return r; }
__device__ __forceinline__ float bf_lo(uint32_t w) { return __uint_as_float(w << 16); }
__device__ __forceinline__ float bf_hi(uint32_t w) { return __uint_as_float(w & 0xffff0000u); }
__device__ __forceinline__ uint32_t absmax4(const uint4& v, uint32_t m) {
  return __vmaxu2(__vmaxu2(__vmaxu2(v.x & 0x7fff7fffu, v.y & 0x7fff7fffu), __vmaxu2(v.z & 0x7fff7fffu, v.w & 0x7fff7fffu)), m);
}
__device__ __forceinline__ float pow2_scale(uint32_t mbits, int p) { return __uint_as_float((uint32_t)min(max(253 + p - (int)(mbits >> 7), 2), 252) << 23); }

constexpr int G_O0 = 8, G_O1 = 4, G_O2 = 0, G_N0 = 5, G_N1 = 4, G_N2 = 4, G_K0 = 5, G_K1 = 3, G_K2 = 1;
__host__ __device__ constexpr bool unit_wg(int kb, int on) {
  return (on >= G_O0 && on < G_O0 + G_N0 && kb < G_K0) || (on >= G_O1 && on < G_O1 + G_N1 && kb < G_K1) || (on >= G_O2 && on < G_O2 + G_N2 && kb < G_K2);
}
constexpr int G_U1 = G_N0 * G_K0, G_U2 = G_U1 + G_N1 * G_K1, G_U = G_U2 + G_N2 * G_K2;
constexpr int K1_B = 130048, K1_STG = K1_B + 2 * 32768, K1_W = K1_STG + 16384, K1_BAR = K1_W + 48 * 256, K1_SMEM = K1_BAR + 256 + 6400;
__host__ __device__ constexpr int frag_index(int ok, int on) {
  int n = 0;
  for (int k = 0; k < 13; k++) for (int o = k; o < 13; o++) { if (k == ok && o == on) return n; if (!unit_wg(k >> 1, o)) n++; }
  return n;
}
constexpr int HU_N = 2 * G_U + frag_index(99, 99);
static_assert(HU_N <= 96, "");
struct FragIdx { int v[13][13]; };
__host__ __device__ constexpr FragIdx make_fi() { FragIdx f = {}; for (int k = 0; k < 13; k++) for (int o = 0; o < 13; o++) f.v[k][o] = frag_index(k, o); return f; }
__host__ __device__ constexpr uint64_t frag_tab(int first) {
  uint64_t t = 0;
  for (int k = 0; k < 13; k++) for (int o = k; o < 13; o++)
    if (!unit_wg(k >> 1, o)) { const int n = frag_index(k, o) - first; if (n >= 0 && n < 8) t |= (uint64_t)(k << 4 | o) << (8 * n); }
  return t;
}
__device__ __forceinline__ int hu_code(int hu) {
  constexpr uint64_t T0 = frag_tab(0), T1 = frag_tab(8), T2 = frag_tab(16), T3 = frag_tab(24);
  const int u = hu >> 1, f = hu - 2 * G_U;
  if (f >= 0) return (int)((f < 8 ? T0 : f < 16 ? T1 : f < 24 ? T2 : T3) >> (8 * (f & 7))) & 255;
  const int u0 = u < G_U1 ? u : u < G_U2 ? u - G_U1 : u - G_U2;
  const int kb = u < G_U1 ? u0 / G_N0 : u < G_U2 ? u0 / G_N1 : u0 / 4, on = u < G_U1 ? G_O0 + u0 % G_N0 : u < G_U2 ? G_O1 + u0 % G_N1 : G_O2 + u0 % 4;
  return (2 * kb + (hu & 1)) << 4 | on;
}

__device__ __forceinline__ void flag_wait(const unsigned* f, unsigned n) {
  unsigned v; int it = 0;
  asm volatile("ld.acquire.gpu.global.u32 %0,[%1];" : "=r"(v) : "l"(f) : "memory");
  if (v < n) {
    do { __nanosleep(300); asm volatile("ld.relaxed.gpu.global.u32 %0,[%1];" : "=r"(v) : "l"(f) : "memory"); } while (v < n && ++it < (1 << 20));
    asm volatile("ld.acquire.gpu.global.u32 %0,[%1];" : "=r"(v) : "l"(f) : "memory");
  }
}
__device__ __forceinline__ void mbar_arrive(uint32_t bar) { asm volatile("mbarrier.arrive.shared::cta.b64 _,[%0];" :: "r"(bar) : "memory"); }
__device__ __forceinline__ void mbar_arrive_lane0(uint32_t bar) {
  __syncwarp();
  asm volatile("{.reg .pred p; elect.sync _|p,0xffffffff; @p mbarrier.arrive.shared::cta.b64 _,[%0];}" :: "r"(bar) : "memory");
}

__device__ __forceinline__ void arrive_both(uint32_t bar, int lane) {
  __syncwarp();
  asm volatile("{.reg .pred p; .reg .u32 a; setp.lt.u32 p,%1,2; mapa.shared::cluster.u32 a,%0,%1;\n"
               "@p mbarrier.arrive.shared::cluster.b64 _,[a];}" :: "r"(bar), "r"(lane) : "memory");
}
#define ELECT "{.reg .pred p; elect.sync _|p,0xffffffff; @p "
__device__ __forceinline__ void e_mc(uint32_t dst, const void* src, uint32_t bytes, uint32_t bar, uint64_t pol) {
  asm volatile(ELECT "cp.async.bulk.shared::cluster.global.mbarrier::complete_tx::bytes.multicast::cluster.L2::cache_hint [%0],[%1],%2,[%3],%4,%5;}"
               :: "r"(dst), "l"(src), "r"(bytes), "r"(bar), "h"((unsigned short)3), "l"(pol) : "memory");
}
__device__ __forceinline__ void e_g2s(uint32_t dst, const void* src, uint32_t bytes, uint32_t bar) {
  asm volatile(ELECT "cp.async.bulk.shared::cluster.global.mbarrier::complete_tx::bytes [%0],[%1],%2,[%3];}" :: "r"(dst), "l"(src), "r"(bytes), "r"(bar) : "memory");
}
__device__ __forceinline__ void e_pf(const void* src, uint32_t bytes) { asm volatile(ELECT "cp.async.bulk.prefetch.L2.global [%0],%1;}" :: "l"(src), "r"(bytes) : "memory"); }
__device__ __forceinline__ void e_expect(uint32_t bar, uint32_t bytes) { asm volatile(ELECT "mbarrier.arrive.expect_tx.shared::cta.b64 _,[%0],%1;}" :: "r"(bar), "r"(bytes) : "memory"); }
__device__ __forceinline__ void e_tma2d(uint32_t dst, const CUtensorMap* m, int x, int y, uint32_t bar) {
  asm volatile(ELECT "cp.async.bulk.tensor.2d.shared::cluster.global.mbarrier::complete_tx::bytes [%0],[%1,{%2,%3}],[%4];}" :: "r"(dst), "l"(m), "r"(x), "r"(y), "r"(bar) : "memory");
}

__device__ __forceinline__ void pack_role(const int* __restrict__ idx, uint32_t sbase, int pc) {
  constexpr int BUF = 32 * 3328;
  const int tid = threadIdx.x, lane = tid & 31, warp = tid >> 5;
  const uint32_t full = sbase + 2 * BUF, empty = full + 16;
  if (tid == 0) { mbar_init(full, 1); mbar_init(full + 8, 1); mbar_init(empty, 18); mbar_init(empty + 8, 18); asm volatile("fence.proxy.async.shared::cta;" ::: "memory"); }
  __syncthreads();
  auto chunk = [&](int s) { return s * 3200 + (s >> 2) * 288; };
  auto load = [&](int n) {
    const int blk = pc * 16 + n;
    if (lane == 0) mbar_expect(full + (n & 1) * 8, 32 * 3200);
    __syncwarp();
    bulk_g2s(sbase + (n & 1) * BUF + chunk(lane), idx + ((blk >> 5) * 8192 + lane * TH + (blk & 31) * 8) * F_, 3200, full + (n & 1) * 8);
  };
  if (warp == 0) { load(0); load(1); }
  const int l = lane & 7;
  uint32_t rot[8], inc[3];
#pragma unroll
  for (int jj = 0; jj < 8; jj++) rot[jj] = ((l + jj) & 7) * 4;
#pragma unroll
  for (int q = 0; q < 3; q++) inc[q] = (l + 3 * q < 8) << 12 | (l + 3 * q + 1 < 8) << 22 | (q < 2 && l + 3 * q + 2 < 8);
  int loaded = 2;
#pragma unroll 1
  for (int task = warp; task < 288; task += 16) {
    const int n = task / 18, q = (task % 18) * 4 + (lane >> 3), sq = q / 9, k = q % 9;
    if (warp == 0 && n + 1 == loaded && loaded < 16) { mbar_wait(empty + (loaded & 1) * 8, ((loaded >> 1) - 1) & 1); load(loaded); loaded++; }
    mbar_wait(full + (n & 1) * 8, (n >> 1) & 1);
    const uint32_t buf = sbase + (n & 1) * BUF + l * 400, row = buf + chunk(sq * 4);
    auto ld = [&](uint32_t ad) { uint32_t v; asm volatile("ld.shared.u32 %0,[%1];" : "=r"(v) : "r"(ad)); return v; };
    const int blk = pc * 16 + n, half = blk >> 5, col = (blk & 31) * 8 + l;
    const int ks = k == NC - 1 ? 0 : k + 1;
    uint32_t cw[4], sv[8], m[2] = {0, 0};
    { const uint32_t a0 = row + (72 + 2 * ks + (l >> 2)) * 4;
#pragma unroll
      for (int u = 0; u < 8; u++) { sv[u] = ld((a0 ^ ((u >> 2) * 4)) + (u & 3) * 3200); m[u >> 2] |= s_mask(sv[u], l & 3) << (8 * (u & 3)); } }
#pragma unroll
    for (int h = 0; h < 2; h++) { m[h] |= __shfl_xor_sync(0xffffffffu, m[h], 1); m[h] |= __shfl_xor_sync(0xffffffffu, m[h], 2); }
#pragma unroll
    for (int u = 0; u < 4; u++) cw[u] = s_cell(sv[u], l & 3, (m[0] >> (8 * u)) & 255) | s_cell(sv[4 + u], l & 3, (m[1] >> (8 * u)) & 255) << 12;
    if (k == NC - 1) {
      auto wide = [&](uint32_t w) { return (w & 0xfff) << 5 | (w >> 12) << 18 | (l & 4 ? 1u << 4 : 1u << 17); };
      g_scr[I0_OFF + (half * 8 + sq) * TH + col] = make_uint4(wide(cw[0]), wide(cw[1]), wide(cw[2]), wide(cw[3]));
      g_scr[IX_OFF + half * IXH + NC * 8192 + sq * TH + col] = make_uint4(ld(row + 396), ld(row + 3596), ld(row + 6796), ld(row + 9996));
      cw[0] = cw[1] = cw[2] = cw[3] = 0;
    }
    const uint32_t ax = buf + chunk(min(sq + 1, 7) * 4) + (90 + k) * 4;
    const uint32_t yev = ld(buf + ((0x3210 >> (sq * 2 + (sq == 5) * 2)) & 3) * 3200 + (90 + k) * 4);
    uint4* dst = g_scr + IX_OFF + half * IXH + (k * NS + sq * 4) * TH + col;
#pragma unroll
    for (int u = 0; u < 4; u++) {
      uint32_t e[8];
#pragma unroll
      for (int jj = 0; jj < 8; jj++) e[jj] = ld(row + k * 32 + rot[jj] + u * 3200);
      dst[u * TH] = make_uint4(pk3(e[0], e[1], e[2] + inc[0]), pk3(e[3], e[4], e[5] + inc[1]), pk3(e[6], e[7], ld(ax + u * 3200) + inc[2]),
                               u < 3 ? __byte_perm(cw[u], cw[3], 0x4210 + (u << 12)) : yev);
    }
    mbar_arrive_lane0(empty + (n & 1) * 8);
  }
}

__global__ void __cluster_dims__(2, 1, 1) __launch_bounds__(512, 1)
k_tens(const __grid_constant__ CUtensorMap mapW, const __grid_constant__ CUtensorMap mapL, const __grid_constant__ CUtensorMap mapS,
       const __grid_constant__ CUtensorMap mapT, const __grid_constant__ CUtensorMap mapE, const __grid_constant__ CUtensorMap mapC, cudaTextureObject_t tex, cudaTextureObject_t texX,
       const int* __restrict__ idx, const __nv_bfloat16* __restrict__ table, const __nv_bfloat16* __restrict__ wp, const __nv_bfloat16* __restrict__ w1,
       const __nv_bfloat16* __restrict__ b1, int never) {
  extern __shared__ __align__(1024) uint4 sm[];
  const int tid = threadIdx.x, lane = tid & 31, cta = blockIdx.x;
  const uint32_t sbase = (uint32_t)__cvta_generic_to_shared(sm);
  const int g = lane >> 2, r = lane & 3;
  TS(0, 0);
  if (cta >= 128) {
    pack_role(idx, sbase, cta - 128);
    __syncthreads();
    if (tid == 0) {
      asm volatile("fence.acq_rel.gpu; griddepcontrol.launch_dependents;" ::: "memory");
      asm volatile("red.relaxed.gpu.global.add.u32 [%0],1;" :: "l"(&g_flag[24 * 32]) : "memory");
    }
    __syncwarp();
    TS(2, 1);
    asm volatile("barrier.cluster.arrive.relaxed.aligned; barrier.cluster.wait.aligned;" ::: "memory");
    return;
  }
  const uint32_t fullB = sbase + K1_BAR, emptyB = fullB + 24, fullE = fullB + 48, fullC = fullB + 56, fullI = fullB + 64, pxRdy = fullB + 72, fullS = fullB + 96, emptyS = fullB + 104, pkDone = fullB + 112, pkFull = fullB + 136, progG = fullB + 168;
  const int rb = cta & 7, hc = cta >> 3;
  if (__shfl_sync(0xffffffffu, tid >> 5, 0) == 12) {
    if (lane == 0) {
#pragma unroll
      for (int q = 0; q < 19; q++) if (q != 2 && q != 5) mbar_init(fullB + q * 8, q == 3 || q == 4 ? 8 : q == 12 ? 4 : q >= 14 && q < 17 ? 2 : 1);
      asm volatile("st.shared.u32 [%0],%1;" :: "r"(progG), "r"(0) : "memory");
    }
    asm volatile("fence.mbarrier_init.release.cluster; fence.proxy.async.shared::cta;" ::: "memory");
    __syncwarp();
    e_expect(fullC, 16384);
#pragma unroll
    for (int q = 0; q < 4; q++) e_tma2d(sbase + 32768 + q * 4096, &mapC, (cta & 15) * 8, q * 256, fullC);
    asm volatile("bar.arrive 2,512;" ::: "memory");
  }
  asm volatile("barrier.cluster.arrive.relaxed.aligned;" ::: "memory");
  if (tid >= 384) {
    asm volatile("setmaxnreg.dec.sync.aligned.u32 32;");
    if (tid < 416) {
      e_expect(fullI, 51200);
#pragma unroll 1
      for (int u = 0; u < 8; u++) e_g2s(sbase + 76800 + u * 6400, idx + ((cta >> 4) * 8 + u) * 256 * F_, 6400, fullI);
      mbar_wait(fullC, 0);
    e_expect(fullE, 32768);
#pragma unroll
    for (int q = 0; q < 2; q++) e_tma2d(sbase + K1_B + 32768 + q * 16384, &mapE, q * 64, rb * 128, fullE);
      asm volatile("barrier.cluster.wait.aligned;" ::: "memory");
      if (tid == 384) {
#pragma unroll 1
        for (int n = 0; n < 25; n++) {
          const int st = n & 1, q = quad_of(n);
          mbar_wait(emptyB + st * 8, (((n + 1) >> 1) & 1) ^ 1);
          mbar_expect(fullB + st * 8, 32768);
          asm volatile("cp.async.bulk.tensor.2d.shared::cluster.global.mbarrier::complete_tx::bytes.multicast::cluster [%0],[%1,{%2,%3}],[%4],%5;"
                       :: "r"(sbase + K1_B + st * 32768 + (cta & 1) * 16384), "l"(&mapW), "r"(hc * 32), "r"(q * 512 + (cta & 1) * 256),
                          "r"(fullB + st * 8), "h"((unsigned short)3) : "memory");
          if (n + 1 < 25) bulk_pf(w1 + quad_of(n + 1) * 262144 + cta * 2048, 4096);
        }
      }
    } else if (tid < 448) {
      ((float4*)g_acc)[cta * 32 + lane] = make_float4(0.f, 0.f, 0.f, 0.f);
      asm volatile("bar.sync 2,512;" ::: "memory");
      __syncwarp();
      if (tid == 416) {
        int pub = 0;
#pragma unroll 1
        for (int n = 0; n < 50; n++) {
          const int quad = quad_of(n >> 1), mt = n & 1, v0 = rb * 128 + mt * 64;
          const uint32_t stg = sbase + K1_STG;
          if (pub < 3) {
            uint32_t ok = 1;
            if (pub == 0 || n == 49) mbar_wait(pkDone + pub * 8, 0);
            else asm volatile("{.reg .pred p; mbarrier.test_wait.parity.shared::cta.b64 p,[%1],0; selp.u32 %0,1,0,p;}" : "=r"(ok) : "r"(pkDone + pub * 8) : "memory");
            if (ok) {
              asm volatile("cp.async.bulk.wait_group 0;" ::: "memory");
              asm volatile("red.release.gpu.global.add.u32 [%0],1;" :: "l"(&g_flag[((cta >> 4) * 3 + pub) * 32]) : "memory");
              pub++;
              if (n == 49) { n--; continue; }
            }
          }
          mbar_wait(fullS, n & 1);
          asm volatile("fence.proxy.async.shared::cta;" ::: "memory");
          if (quad < 18) {
            asm volatile("cp.async.bulk.tensor.4d.global.shared::cta.bulk_group.L2::cache_hint [%0,{%1,%2,%3,%4}],[%5],%6;"
                         :: "l"(&mapL), "r"((quad & 1) * 32), "r"(hc * 4), "r"(v0), "r"(quad >> 1), "r"(stg), "l"(POL_EF) : "memory");
          } else {
#pragma unroll 1
            for (int hh = 0; hh < 2; hh++) {
              const int pq = quad * 2 + hh;
              asm volatile("cp.async.bulk.tensor.4d.global.shared::cta.bulk_group.L2::cache_hint [%0,{%1,%2,%3,%4}],[%5],%6;"
                         :: "l"(pq < 45 ? &mapS : &mapT), "r"(0), "r"(hc * 4), "r"(v0 >> (pq < 45 ? 2 : 3)), "r"(pq < 45 ? pq - 36 : (pq - 45) * 2), "r"(stg + hh * 8192), "l"(POL_EF) : "memory");
            }
          }
          asm volatile("cp.async.bulk.commit_group;" ::: "memory");
          asm volatile("cp.async.bulk.wait_group.read 0;" ::: "memory");
          mbar_arrive(emptyS);
        }
        asm volatile("cp.async.bulk.wait_group 0;" ::: "memory");
        asm volatile("fence.proxy.async.global;" ::: "memory");
        asm volatile("fence.acq_rel.gpu; griddepcontrol.launch_dependents;" ::: "memory");
        asm volatile("red.relaxed.gpu.global.add.u32 [%0],1;" :: "l"(&g_flag[24 * 32]) : "memory");
        flag_wait(&g_flag[24 * 32], 132);
        asm volatile("fence.proxy.async.global;" ::: "memory");
        const char* base = (const char*)g_scr;
        const int c = cta >> 1, half = cta & 1, ch = (c + (c >> 4) * 5) & 15;
        bulk_pf(base + (PS_OFF + c * NC * 2000) * 16u + half * 16000, 16000);
        bulk_pf(base + (PT_OFF + c * 10 * 1024) * 16u + half * 8000, 8000);
        mbar_expect(fullE, 18432);
        bulk_g2s(sbase + K1_B, base + (I0_OFF + half * 2048 + ch * 128) * 16u, 2048, fullE);
        bulk_g2s(sbase + K1_B + 2048, base + (IX_OFF + half * IXH + ch * 512) * 16u, 8192, fullE);
        bulk_g2s(sbase + K1_B + 10240, base + (IX_OFF + half * IXH + 8192 + ch * 512) * 16u, 8192, fullE);
        mbar_wait(fullE, 1);
      }
    } else {
      const int pw = (tid >> 5) & 1, rg = (cta >> 4) * 8 + ((cta & 15) >> 1), hf = cta & 1;
      const int* ip = idx + (rg * 256 + hf * 8) * F_;
      asm volatile("bar.sync 2,512;" ::: "memory");
      const uint32_t buf = sbase + K1_BAR + 256 + pw * 3200, bar = pkFull + pw * 8;
      const unsigned* fl = &g_flag[(cta >> 4) * 96];
      int batch = 0, rel = pw ? 3 : 0;
#pragma unroll 1
      for (int n = 1 + pw; n < 16; n += 2) {
        if (lane == 0) { mbar_expect(bar, 3200); bulk_g2s(buf, ip + n * 16 * F_, 3200, bar); if (n + 2 < 16) bulk_pf(ip + (n + 2) * 16 * F_, 3200); }
        uint32_t ok; int it = 0;
        do {
          if (rel < batch) {
            unsigned v; asm volatile("ld.relaxed.gpu.global.u32 %0,[%1];" : "=r"(v) : "l"(fl + rel * 32) : "memory");
            if (__all_sync(0xffffffffu, v >= 16)) { flag_wait(fl + rel * 32, 16); mbar_arrive_lane0(pxRdy + rel * 8); rel++; }
          }
          asm volatile("{.reg .pred p; mbarrier.test_wait.parity.shared::cta.b64 p,[%1],%2; selp.u32 %0,1,0,p;}" : "=r"(ok) : "r"(bar), "r"(((n - 1) >> 1) & 1) : "memory");
          ok = __all_sync(0xffffffffu, ok);
          if (!ok) __nanosleep(100);
        } while (!ok && ++it < (1 << 20));
        auto ld = [&](uint32_t ad) { uint32_t v; asm volatile("ld.shared.u32 %0,[%1];" : "=r"(v) : "r"(ad)); return v; };
        const uint32_t p0 = buf + ((lane >> 3) & 1) * 1600 + ((lane >> 4) * 8 + (lane & 7)) * 4;
        auto wd = [&](int t, int h) { const uint32_t o = p0 + (t + (t & 4)) * 400 + h * 192; return pk3(ld(o), ld(o + 64), ld(o + 128)); };
        uint4* dst = g_scr + PX_OFF + (rg * 16 + n) * 136;
        ((unsigned short*)(dst + 128))[lane * 2 + hf] = ld(buf + ((lane >> 3) + (lane & 4)) * 400 + 384 + r * 4);
#pragma unroll
        for (int q = 0; q < 2; q++) dst[(hf * 2 + q) * 32 + lane] = make_uint4(wd(2 * q, 0), wd(2 * q, 1), wd(2 * q + 1, 0), wd(2 * q + 1, 1));
        __syncwarp();
        if (n <= 2 || n == 5 || n == 6 || n >= 14) { mbar_arrive_lane0(pkDone + batch * 8); batch++; }
      }
      for (; rel < 3; rel++) { flag_wait(fl + rel * 32, 16); mbar_arrive_lane0(pxRdy + rel * 8); }
      if (lane == 0) {
        mbar_wait(pxRdy + 16, 0);
        asm volatile("fence.proxy.async.global;" ::: "memory");
        const char* src = (const char*)(g_scr + PX_OFF + ((cta >> 4) * 8 + ((cta >> 1) & 3) * 2 + pw) * 16 * 136);
        int ph = pw;
#pragma unroll 1
        for (int n = 5; n < 16; n++) {
          uint32_t cur; int it = 0;
          do { asm volatile("ld.volatile.shared.u32 %0,[%1];" : "=r"(cur) : "r"(progG)); if (cur + 2 < n) __nanosleep(400); } while (cur + 2 < n && ++it < (1 << 16));
          if (cur + 1 >= n) continue;
          mbar_expect(bar, 2176); bulk_g2s(buf, src + n * 2176, 2176, bar);
          mbar_wait(bar, ph); ph ^= 1;
        }
      }
    }
    return;
  }
  if (tid >= 256) {
    asm volatile("setmaxnreg.inc.sync.aligned.u32 160;");
    const int w = (tid >> 5) & 3;
    const int srow = w * 16 + ((lane & 15) ^ ((lane & 1) << 2)), sc = lane >> 4;
    uint32_t a[2][8][4];
    asm volatile("bar.sync 2,512;" ::: "memory");
    mbar_wait_fast(fullE, 0);
#pragma unroll
    for (int mt = 0; mt < 2; mt++)
#pragma unroll
      for (int ks = 0; ks < 8; ks++)
        asm volatile("ldmatrix.sync.aligned.m8n8.x4.shared.b16 {%0,%1,%2,%3},[%4];"
                     : "=r"(a[mt][ks][0]), "=r"(a[mt][ks][1]), "=r"(a[mt][ks][2]), "=r"(a[mt][ks][3])
                     : "r"(sbase + K1_B + 32768 + (ks >> 2) * 16384 + (mt * 64 + srow) * 128 + ((((ks & 3) * 2 + sc) ^ (srow & 7)) * 16)) : "memory");
    asm volatile("barrier.cluster.wait.aligned;" ::: "memory");
    uint32_t dep = 0;
#pragma unroll
    for (int q = 0; q < 16; q++) dep |= a[q >> 3][q & 7][0];
    arrive_both(emptyB + 8, lane + (dep & never));
    asm volatile("bar.sync 3,384;" ::: "memory");
    const int v = w * 16 + (g ^ ((g & 1) << 2));
    const uint32_t baseL = v * 256 + r * 64 + ((v & 1) * 2 + (r >> 1)) * 16, baseS = (v >> 2) * 512 + r * 128 + (((v & 3) * 2) ^ ((v & 4) + r)) * 16,
                   baseT = (v >> 3) * 512 + r * 128 + ((v & 7) ^ r) * 16;
    const uint64_t desc0 = (uint64_t)(((sbase + K1_B) & 0x3FFFF) >> 4) | ((uint64_t)(8192 >> 4) << 16) | ((uint64_t)(512 >> 4) << 32) | (2ull << 62);
#pragma unroll 1
    for (int qn = 0; qn < 25; qn++) {
      const int quad = quad_of(qn), st = qn & 1;
      const bool isL = quad < 18;
      PT(qn * 16);
      mbar_wait_fast(fullB + st * 8, (qn >> 1) & 1);
#pragma unroll
      for (int mt = 0; mt < 2; mt++) {
        float d[64];
        PT(qn * 16 + mt * 4 + 1);
        asm volatile("wgmma.fence.sync.aligned;" ::: "memory");
#pragma unroll
        for (int ks = 0; ks < 8; ks++) wgmma_p(d, a[mt][ks], desc0 + st * 2048 + ks * 64, ks);
        asm volatile("wgmma.commit_group.sync.aligned;" ::: "memory");
        mbar_wait_fast(emptyS, mt ^ 1);
        PT(qn * 16 + mt * 4 + 2);
        asm volatile("wgmma.wait_group.sync.aligned 0;" ::: "memory");
#pragma unroll
        for (int q = 0; q < 16; q++) asm volatile("" : "+f"(d[q * 4]), "+f"(d[q * 4 + 1]), "+f"(d[q * 4 + 2]), "+f"(d[q * 4 + 3]) :: "memory");
        PT(qn * 16 + mt * 4 + 3);
        if (mt) arrive_both(emptyB + st * 8, qn < 23 ? lane : 9);
        if (quad == 24) {
#pragma unroll
          for (int cq = 0; cq < 4; cq++) {
            const uint32_t bw = __ldg((const uint32_t*)(b1 + hc * 32 + cq * 8) + r);
#pragma unroll
            for (int e = 0; e < 4; e++) d[48 + cq * 4 + e] += (e & 1) ? bf_hi(bw) : bf_lo(bw);
          }
        }
#pragma unroll
        for (int h = 0; h < 2; h++) {
          const bool isS = quad * 2 + h < 45;
          const uint32_t base = (isL ? baseL ^ (h * 32) : (isS ? baseS : baseT) ^ (h * 8192)), xj = isS ? 16 : 4096, xr = isL ? 2048 : isS ? 1024 : 576;
#pragma unroll
          for (int e4 = 0; e4 < 4; e4++) {
            const float* e = d + h * 32 + (e4 >> 1) * 16 + (e4 & 1) * 2;
            sts128(sbase + K1_STG + (base ^ ((e4 >> 1) * xj) ^ ((e4 & 1) * xr)),
                   make_uint4(pack_bf2(e[0], e[1]), pack_bf2(e[4], e[5]), pack_bf2(e[8], e[9]), pack_bf2(e[12], e[13])));
          }
        }
        mbar_arrive_lane0(fullS);
        if (!mt) PT(qn * 16 + 4);
      }
      PT(qn * 16 + 8);
    }
    return;
  }
  const int slice = cta & 15;
  const int range = (cta >> 4) * 8 + __shfl_sync(0xffffffffu, tid >> 5, 0);
  uint4 iv[4], trow[4]; uint32_t ix;
  uint2 wrow[10];
#pragma unroll
  for (int q = 0; q < 10; q++) asm volatile("ld.global.nc.v2.u32 {%0,%1},[%2];" : "=r"(wrow[q].x), "=r"(wrow[q].y) : "l"((const uint2*)wp + min(tid + q * 256, 2499)));
  asm volatile("bar.sync 2,512;" ::: "memory");
  uint32_t wa[3][4];
#pragma unroll
  for (int it = 0; it < 3; it++) {
    const int code = hu_code(min(((tid >> 5) * 3 + it) * 4 + (lane >> 3), HU_N - 1)), ok = code >> 4, on = code & 15;
    wa[it][0] = sbase + (on * 8 + (lane & (on == 12 ? 3 : 7))) * 208 + ok * 16;
    wa[it][1] = sbase + (ok * 8 + (lane & (ok == 12 ? 3 : 7))) * 208 + on * 16;
    wa[it][2] = __ballot_sync(0xffffffffu, ok > on); wa[it][3] = __ballot_sync(0xffffffffu, ok >= on);
  }
  SCHED_FENCE(never, 500);
  uint32_t me = 0, mw = 0;
#pragma unroll
  for (int q = 0; q < 10; q++) {
    mw = __vmaxu2(__vmaxu2(wrow[q].x & 0x7fff7fffu, wrow[q].y & 0x7fff7fffu), mw);
    const int e = min(tid + q * 256, 2499), row = e / 25;
    asm volatile("st.shared.v2.u32 [%0],{%1,%2};" :: "r"(sbase + (e + row) * 8), "r"(wrow[q].x), "r"(wrow[q].y) : "memory");
    if (e - row * 25 == 24) asm volatile("st.shared.v2.u32 [%0],{%1,%2};" :: "r"(sbase + (e + row) * 8 + 8), "r"(wrow[q].x), "r"(wrow[q].y) : "memory");
  }
  mbar_wait_fast(fullC, 0);
#pragma unroll
  for (int q = 0; q < 4; q++) { trow[q] = lds128(sbase + 32768 + (tid + q * 256) * 16); me = absmax4(trow[q], me); }
  me = __reduce_max_sync(0xffffffffu, max(me & 0xffff, me >> 16));
  mw = __reduce_max_sync(0xffffffffu, max(mw & 0xffff, mw >> 16));
  uint32_t* sred = (uint32_t*)((char*)sm + 128000);
  if (lane == 0) sred[tid >> 5] = me | mw << 16;
  TS(3, 0);
  asm volatile("setmaxnreg.inc.sync.aligned.u32 160;");
  asm volatile("bar.sync 1,256;" ::: "memory");
  { uint32_t m = 0;
#pragma unroll
    for (int q = 0; q < 8; q++) m = __vmaxu2(m, sred[q]);
    m = __shfl_sync(0xffffffffu, m, 0);
    me = m & 0xffff; mw = m >> 16; }
  const float se = pow2_scale(me, 3), sW = pow2_scale(mw, -2);
  TS(3, 1);
  auto put_rows = [&](int q, bool on) {
    const uint4 t = trow[q];
    const uint4 hv = make_uint4(pack_h2(bf_lo(t.x) * se, bf_hi(t.x) * se), pack_h2(bf_lo(t.y) * se, bf_hi(t.y) * se),
                                pack_h2(bf_lo(t.z) * se, bf_hi(t.z) * se), pack_h2(bf_lo(t.w) * se, bf_hi(t.w) * se));
    if (on)
#pragma unroll
      for (int s = 0; s < 8; s++) sts128(sbase + (tid + q * 256) * 128 + ((s + lane) & 7) * 16, hv);
  };
  uint32_t wx[3][4], wy[3][4];
#pragma unroll
  for (int it = 0; it < 3; it++) {
    asm volatile("ldmatrix.sync.aligned.m8n8.x4.shared.b16 {%0,%1,%2,%3},[%4];" : "=r"(wx[it][0]), "=r"(wx[it][1]), "=r"(wx[it][2]), "=r"(wx[it][3]) : "r"(wa[it][0]) : "memory");
    asm volatile("ldmatrix.sync.aligned.m8n8.x4.trans.shared.b16 {%0,%1,%2,%3},[%4];" : "=r"(wy[it][0]), "=r"(wy[it][1]), "=r"(wy[it][2]), "=r"(wy[it][3]) : "r"(wa[it][1]) : "memory");
  }
  put_rows(1, true); put_rows(2, tid < 88);
#pragma unroll
  for (int it = 0; it < 3; it++)
#pragma unroll
    for (int q = 0; q < 4; q++) {
      const float m0 = (wa[it][2] >> (8 * q)) & 1 ? 0.f : sW, m1 = (wa[it][3] >> (8 * q)) & 1 ? 0.f : sW;
      asm volatile("st.shared.u32 [%0],%1;" :: "r"(sbase + K1_W + (((tid >> 5) * 3 + it) * 4 + q) * 128 + lane * 4),
                   "r"(pack_h2(fmaf(bf_lo(wx[it][q]), m0, bf_lo(wy[it][q]) * m1), fmaf(bf_hi(wx[it][q]), m0, bf_hi(wy[it][q]) * m1))) : "memory");
    }
  asm volatile("fence.proxy.async.shared::cta;" ::: "memory");
  mbar_wait_fast(fullI, 0);
  {
    const uint32_t ib = sbase + 76800 + (tid >> 5) * 6400, p0 = ib + ((lane >> 3) & 1) * 1600 + ((lane >> 4) * 8 + (lane & 7)) * 4;
    auto ld = [&](uint32_t ad) { uint32_t v; asm volatile("ld.shared.u32 %0,[%1];" : "=r"(v) : "r"(ad)); return v; };
    auto wd = [&](int t, int h) { const uint32_t o = p0 + (t + (t & 4)) * 400 + h * 192; return pk3(ld(o), ld(o + 64), ld(o + 128)); };
#pragma unroll
    for (int q = 0; q < 4; q++) {
      iv[q] = make_uint4(wd(2 * q, 0), wd(2 * q, 1), wd(2 * q + 1, 0), wd(2 * q + 1, 1));
    }
    const uint32_t pe = ib + ((lane >> 3) + (lane & 4)) * 400 + 384 + r * 4;
    ix = ld(pe) | ld(pe + 3200) << 16;
  }
  TS(3, 2);
  asm volatile("bar.sync 1,256;" ::: "memory");
  put_rows(0, true);
  uint32_t bf[HU_N - 2 * G_U];
#pragma unroll
  for (int q = 0; q < HU_N - 2 * G_U; q++) asm volatile("ld.shared.u32 %0,[%1];" : "=r"(bf[q]) : "r"(sbase + K1_W + (2 * G_U + q) * 128 + lane * 4));
  if (cta < 16 && tid == 0) g_unscale[cta] = make_float2(__uint_as_float(0x7f000000u - __float_as_uint(se)), __uint_as_float(0x7f000000u - __float_as_uint(sW)));
  TS(3, 3);
  const int px = range * 16 * 136;
  asm volatile("bar.arrive 3,384;" ::: "memory");
  put_rows(2, tid >= 88); put_rows(3, tid + 768 < V_);
  asm volatile("bar.sync 1,256;" ::: "memory");
  TS(0, 1);
  uint32_t lc; asm volatile("add.u32 %0,%1,%2;" : "=r"(lc) : "r"((lane & 7) * 16), "r"(never));
  const uint64_t wdesc = (uint64_t)(((sbase + K1_W) & 0x3FFFF) >> 4) | ((uint64_t)(128 >> 4) << 16) | ((uint64_t)(256 >> 4) << 32);
  uint32_t a[2][6][4], d[2][26], ex[4] = {}, s[4] = {};
  float red[4] = {0.f, 0.f, 0.f, 0.f};
  auto ldsm = [&](uint32_t* o, uint32_t sh) {
    asm volatile("ldmatrix.sync.aligned.m8n8.x4.trans.shared.b16 {%0,%1,%2,%3},[%4];"
                 : "=r"(o[0]), "=r"(o[1]), "=r"(o[2]), "=r"(o[3]) : "r"(sbase + ((sh & 0x1ff80) | lc)));
  };
  auto gather = [&](int t, int hf) {
    const int x = t & 1;
    const uint4 v = iv[(t >> 1) & 3];
#pragma unroll
    for (int kb = 3 * hf; kb < 3 * hf + 3; kb++) {
      const uint32_t ww = x ? (kb < 3 ? v.z : v.w) : (kb < 3 ? v.x : v.y);
      ldsm(a[x][kb], kb % 3 == 0 ? ww : kb % 3 == 1 ? ww >> 10 : __funnelshift_l(ww, ww, 12));
    }
  };
  auto issue = [&](int x) {
    asm volatile("wgmma.fence.sync.aligned;" ::: "memory");
#pragma unroll
    for (int kb = 0; kb < 6; kb++) {
      if (kb < G_K0) wgmma_h<G_N0 * 8>(d[x] + G_O0 * 2, a[x][kb], wdesc + kb * G_N0 * 16, kb);
      if (kb < G_K1) wgmma_h<G_N1 * 8>(d[x] + G_O1 * 2, a[x][kb], wdesc + (G_U1 + kb * G_N1) * 16, kb);
      if (kb < G_K2) wgmma_h<32>(d[x] + G_O2 * 2, a[x][kb], wdesc + (G_U2 + kb * G_N2) * 16, kb);
    }
    asm volatile("wgmma.commit_group.sync.aligned;" ::: "memory");
  };
  auto hmma_part = [&](int t) {
    constexpr FragIdx FI = make_fi();
    const int x = t & 1;
#pragma unroll
    for (int o = 0; o < 13; o++) asm volatile("" : "+r"(d[x][o * 2]), "+r"(d[x][o * 2 + 1]) :: "memory");
#pragma unroll
    for (int kb = 0; kb < 6; kb++)
#pragma unroll
      for (int o = 2 * kb + 1; o < 13; o++)
        if (!unit_wg(kb, o)) mma16816h(d[x] + o * 2, a[x][kb], bf[FI.v[2 * kb][o]], bf[FI.v[2 * kb + 1][o]]);
#pragma unroll
    for (int q = 0; q < 6; q++) if (!unit_wg(q, 2 * q)) mma1688h(d[x] + q * 4, a[x][q][0], a[x][q][1], bf[FI.v[2 * q][2 * q]]);
    mma1688h(d[x] + 24, r < 2 ? ex[t & 3] : 0u, r < 2 ? 0u : ex[t & 3], bf[FI.v[12][12]]);
  };
  auto dot_part = [&](int t, int hf) {
    const int x = t & 1;
    if (hf == 0) {
      const uint32_t pe = hfma2(r < 2 ? d[x][24] : d[x][25], ex[t & 3], 0u);
      s[0] = r < 2 ? pe : 0u; s[1] = r < 2 ? 0u : pe; s[2] = s[3] = 0;
    }
#pragma unroll
    for (int q = 3 * hf; q < 3 * hf + 3; q++)
#pragma unroll
      for (int e = 0; e < 4; e++) s[e] = hfma2(d[x][q * 4 + e], a[x][q][e], s[e]);
  };
  const float* outp = g_partP + slice * B_ + range * 256;
  uint32_t oofs; asm volatile("add.u32 %0,%1,%2;" : "=r"(oofs) : "r"(((r >> 1) * 8 + (r & 1) * 2 + ((lane >> 3) & 1) + (lane >> 4) * 4) * 4), "r"(never));
  float k0 = 0.f, k1 = 0.f, x0 = 0.f, x1 = 0.f;
  auto red_stage = [&](int st, int grp) {
    const bool u16 = lane & 16, u8 = lane & 8;
    if (st == 0) {
      k0 = u16 ? red[2] : red[0]; x0 = __shfl_xor_sync(0xffffffffu, u16 ? red[0] : red[2], 16);
      k1 = u16 ? red[3] : red[1]; x1 = __shfl_xor_sync(0xffffffffu, u16 ? red[1] : red[3], 16);
      red[0] = red[1] = red[2] = red[3] = 0.f;
    }
    if (st == 1) { const float p0 = k0 + x0, p1 = k1 + x1; k0 = u8 ? p1 : p0; x0 = __shfl_xor_sync(0xffffffffu, u8 ? p0 : p1, 8); }
    if (st == 2) { k0 += x0; x0 = __shfl_xor_sync(0xffffffffu, k0, 4); }
    if (st == 3) asm volatile("st.global.f32 [%0],%1;" :: "l"((const char*)(outp + grp * 16) + oofs), "f"(k0 + x0) : "memory");
  };
  auto side = [&](bool first, int t, int prv, int cur, int nxt) {
    const int pn = PX_OFF + px + nxt * 136 + lane;
    if (!first) {
      if (t == 0) { iv[3] = ldtex(tex, PX_OFF + px + cur * 136 + lane + 96); iv[0] = ldtex(tex, pn); }
      if (t == 2) iv[1] = ldtex(tex, pn + 32);
      if (t < 4) red_stage(t, prv);
    } else if (t == 4) {
      TS(4, 2);
      mbar_wait_fast(pxRdy, 0);
      TS(4, 3);
      iv[0] = ldtex(tex, pn); iv[1] = ldtex(tex, pn + 32);
    }
    if (t == 4) { ix = ldtex(texX, (px + nxt * 136 + 128) * 4 + lane).x; iv[2] = ldtex(tex, pn + 64); }
  };
  auto group = [&](bool first, int prv, int cur, int nxt, int part) {
#pragma unroll
    for (int t = part ? 7 : 0; t < 8; t++) {
      if (!part) {
        if (first || t) SCHED_FENCE(never, t * 8);
        side(first, t, prv, cur, nxt);
        dot_part(t, 0);
        SCHED_FENCE(never, t * 8 + 1);
        if (t == 3) ldsm(ex, ix >> 9);
        if (t == 7) ldsm(ex, ix << 7);
        gather(t + 2, 0);
        dot_part(t, 1);
        s[0] = hadd2(s[0], s[2]); s[1] = hadd2(s[1], s[3]);
        if (first || t < 7) SCHED_FENCE(never, t * 8 + 4);
        if (t == 7) break;
      }
      gather(t + 2, 1);
      asm volatile("wgmma.wait_group.sync.aligned 0;" ::: "memory");
      asm volatile("" : "+r"(d[(t & 1) ^ 1][0]) :: "memory");
      mma1688f(red, s[0], s[1], (g | (d[(t & 1) ^ 1][0] & never)) == t ? 0x3c003c00u : 0u);
      hmma_part(t + 1);
      issue(t & 1);
    }
  };
  gather(0, 0); gather(0, 1); issue(0); ldsm(ex, ix << 7); gather(1, 0); gather(1, 1);
  asm volatile("wgmma.wait_group.sync.aligned 0;" ::: "memory");
  hmma_part(0);
  SCHED_FENCE(never, 99);
  issue(1);
  group(true, 0, 0, 1, 0); group(true, 0, 0, 1, 1);
  TS(4, 1);
#pragma unroll 1
  for (int n = 1;; n++) {
    if ((n & 11) == 2) mbar_wait_fast(pxRdy + 8 + (n & 4) * 2, 0);
    asm volatile("st.volatile.shared.u32 [%0],%1;" :: "r"(progG), "r"(n) : "memory");
    group(false, n - 1, n, min(n + 1, 15), 0);
    if (n == 15) break;
    group(false, n - 1, n, min(n + 1, 15), 1);
  }
  asm volatile("wgmma.wait_group.sync.aligned 0;" ::: "memory");
  mma1688f(red, s[0], s[1], g == 7 ? 0x3c003c00u : 0u);
#pragma unroll
  for (int st = 0; st < 4; st++) red_stage(st, 15);
  TS(0, 2);
  asm volatile("barrier.cluster.wait.aligned;" ::: "memory");
  asm volatile("barrier.cluster.arrive.relaxed.aligned; barrier.cluster.wait.aligned;" ::: "memory");
}

constexpr int SM_U = 130048, SM_BAR = 128000, SM_J = SM_U + 98304, DEEP_SMEM = SM_J + 4096;

__global__ void __cluster_dims__(2, 1, 1) __launch_bounds__(TH + 128, 1)
k_deep(cudaTextureObject_t tex, const __nv_bfloat16* __restrict__ w2, const __nv_bfloat16* __restrict__ b2,
       __nv_bfloat16* __restrict__ out, int never) {
  extern __shared__ __align__(1024) uint4 sm[];
  constexpr int PF = 4, DEPTH = 4, NW = TH / 32;
  const int tid = threadIdx.x;
  const int c = blockIdx.x >> 1, half = blockIdx.x & 1;
  const uint32_t sbase = (uint32_t)__cvta_generic_to_shared(sm);
  const uint32_t fullL = sbase + SM_BAR, fullU = fullL + 8, emptyL = fullL + 16, emptyU = fullL + 24, barJ = fullL + 32, barW = fullL + 48;
  TS(1, 0);
  if (tid == 0) {
    mbar_init(fullL, 1); mbar_init(fullU, 1); mbar_init(emptyL, 2 * NW); mbar_init(emptyU, 2 * NW); mbar_init(barJ, 1); mbar_init(barW, 1);
    asm volatile("fence.mbarrier_init.release.cluster;" ::: "memory");
  }
  __syncwarp();
  const int wrp = __shfl_sync(0xffffffffu, tid >> 5, 0);
  const char* base = (const char*)g_scr;
  uint32_t oL = (PL_OFF + c * NC * 8000) * 16u + half * 64000, oS = (PS_OFF + c * NC * 2000) * 16u + half * 16000;
  asm volatile("barrier.cluster.arrive.relaxed.aligned; barrier.cluster.wait.aligned;" ::: "memory");
  if (wrp == NW) {
    asm volatile("fence.proxy.async.global;" ::: "memory");
    e_expect(fullU, 96000);
#pragma unroll
    for (int m = 0; m < 3; m++) e_mc(sbase + SM_U + m * 32032 + half * 16000, base + oS, 16000, fullU, m == 2 ? POL_EF : POL_N);
    e_expect(fullL, 128000);
  }
  TS(5, 1);
  if (wrp >= NW) {
    asm volatile("setmaxnreg.dec.sync.aligned.u32 24;");
    if (wrp == NW) {
      uint32_t oT = (PT_OFF + c * 10 * 1024) * 16u + half * 8000;
      auto warm = [&](uint32_t off, uint32_t hb) {
        asm volatile(ELECT "mbarrier.expect_tx.relaxed.cta.shared::cta.b64 [%0],%1;}" :: "r"(barJ), "r"(2 * hb) : "memory");
        e_g2s(sbase + SM_J, base + off, hb, barJ); e_g2s(sbase + SM_J, base + off + hb, hb, barJ);
      };
      mbar_wait(fullU, 0);
      e_mc(sbase + half * 64000, base + oL, 64000, fullL, POL_EF);
      warm(oT, 4000);
#pragma unroll 1
      for (int k = 0; k + 1 < NC; k++) {
        oL += 128000; oS += 32000; oT += 16384;
        mbar_wait(fullL, k & 1);
        const uint32_t t0 = clock();
        e_pf(base + oS, 16000);
        warm((IX_OFF + half * IXH + (k + 2) * 8192 + ((c + (c >> 4) * (2 * k + 1)) & (k + 2 < NC ? 15 : 3)) * 512) * 16u, 4096);
        mbar_wait(emptyU, k & 1);
        e_expect(fullU, 96000);
#pragma unroll 1
        for (int q = 0; q < 8; q++) {
          sleep_until(t0, q * PACE);
          e_pf(base + oL + q * 8000, 8000);
          if (q >= 2) e_mc(sbase + SM_U + ((q - 2) >> 1) * 32032 + half * 16000 + (q & 1) * 8000, base + oS + (q & 1) * 8000, 8000, fullU, q >= 6 ? POL_EF : POL_N);
        }
        warm(oT, 4000);
        e_expect(fullL, 128000);
        sleep_until(t0, RSV_T);
        unsigned long long now, slot = 0;
        asm volatile("mov.u64 %0,%globaltimer;" : "=l"(now));
        if ((tid & 31) == 0) { atomicMax(&g_slot, now + RSV_L); slot = atomicAdd(&g_slot, (unsigned long long)RSV); }
        slot = __shfl_sync(0xffffffffu, slot, 0);
        for (int it = 0; it < 4000; it++) { asm volatile("mov.u64 %0,%globaltimer;" : "=l"(now)); if (now >= slot) break; }
        mbar_wait(emptyL, k & 1);

        e_mc(sbase + half * 64000, base + oL, 64000, fullL, POL_EF);
      }
      mbar_wait(fullL, (NC - 1) & 1);
      mbar_wait(emptyU, (NC - 1) & 1);
      mbar_arrive_lane0(fullU);
      warm(oT + 16384, 4000);
      mbar_arrive_lane0(barJ); mbar_wait(barJ, 0);
    } else if (tid >= TH + 96) {
      if (tid < TH + 100) asm volatile("st.shared.u32 [%0],%1;" :: "r"(barJ + 32 + (tid & 3) * 4), "r"(((const uint32_t*)w2)[(c >> 2) * 16 + (tid & 3) * 4 + (c & 3)]) : "memory");
      mbar_arrive_lane0(barW);
      asm volatile("griddepcontrol.wait;" ::: "memory");
      const int b = half * 8192 + c * 128 + (tid & 31) * 4;
      const float bias = __bfloat162float(b2[0]);
      float4 s = make_float4(bias, bias, bias, bias);
#pragma unroll 2
      for (int k = 0; k < 16; k++) {
        const float4 v = __ldcg((const float4*)(g_partP + k * B_ + b)); const float2 u = __ldcg(g_unscale + k);
        s.x = fmaf(v.x * u.x * u.x, u.y, s.x); s.y = fmaf(v.y * u.x * u.x, u.y, s.y); s.z = fmaf(v.z * u.x * u.x, u.y, s.z); s.w = fmaf(v.w * u.x * u.x, u.y, s.w);
      }
      asm volatile("red.global.add.v4.f32 [%0],{%1,%2,%3,%4};" :: "l"(g_acc + b), "f"(s.x), "f"(s.y), "f"(s.z), "f"(s.w) : "memory");
      asm volatile("bar.arrive 1,%0;" :: "n"(TH + 32) : "memory");
    }
    return;
  }
  asm volatile("setmaxnreg.inc.sync.aligned.u32 240;");
  const int lane = tid & 31;
  const int tbase = PT_OFF + c * 10 * 1024;
  const int ibase = IX_OFF + half * IXH + tid;
  const uint32_t lc = (tid & 7) << 4;
  uint4 acc[NS], wq[PF], x[DEPTH], y[YD], ye;
  uint32_t sw[NS] = {};
  auto sget = [&](int s) { return (s & 3) == 3 ? __byte_perm(__byte_perm(sw[s - 3], sw[s - 2], 0x0073), sw[s - 1], 0x0710) : sw[s]; };
  auto sa0 = [&](uint32_t v) { return sbase + SM_U + (((v << 5) & 0x1ffe0) | ((lc >> 2) & 16)); };
  uint32_t c1 = 0;
  auto sa1 = [&](uint32_t v) { return sbase + SM_U + (((v >> 7) & 0x1ffe0) | c1); };
  {
    uint4 i0[8];
#pragma unroll
    for (int q = 0; q < 8; q++) i0[q] = ldtex(tex, I0_OFF + (half * 8 + q) * TH + tid);
    auto wd = [&](int k) { return (k & 3) == 0 ? i0[k >> 2].x : (k & 3) == 1 ? i0[k >> 2].y : (k & 3) == 2 ? i0[k >> 2].z : i0[k >> 2].w; };
    TS(5, 2);
    mbar_wait_fast(fullU, 0);
#pragma unroll
    for (int i = 0; i < PF; i++) wq[i] = ldtex(tex, ibase + i * TH);
    TS(1, 1);
#pragma unroll
    for (int s = 0; s < NS; s++) acc[s] = add4(lds128(sbase + SM_U + (wd(s) & 0x1fff0)), lds128(sbase + SM_U + ((wd(s) >> 13) & 0x1fff0)));
    arrive_both(emptyU, lane + ((acc[NS - 1].x | acc[NS - 2].x | acc[NS - 3].x | acc[NS - 4].x) & never));
    mbar_wait_fast(barW, 0);
    TS(5, 3);
  }
  uint4 w = wq[0];
  auto lds_l = [&](int jj, int slot) {
    const uint32_t ww = jj < 3 ? w.x : jj < 6 ? w.y : w.z;
    const uint32_t sh = jj % 3 == 0 ? ww : jj % 3 == 1 ? ww >> 10 : __funnelshift_l(ww, ww, 12);
    x[slot] = lds128(sbase + ((sh & 0x1ff80) | lc) + jj * 16 - 128);
  };
  mbar_wait_fast(fullL, 0);
  lds_l(0, 0); lds_l(1, 1); lds_l(2, 2); lds_l(3, 3);
#pragma unroll 1
  for (int k = 0; k < NC; k++) {
    const int ti = ibase + k * 8192;
    const int tb = tbase + k * 1024;
    const bool more = k + 1 < NC;
    TR(k * 4);
    TR(k * 4 + 2);
    uint4 cc; uint32_t yc;
    constexpr int TL = NS * 8, TT = TL + NS * 2;
#pragma unroll
    for (int t = 0; t < TT + DEPTH; t += 2) {
      if (t == TL + DEPTH && !more) break;
      if (t >= DEPTH) {
        const int u = t - DEPTH;
        uint4 p = add4(x[u % DEPTH], x[(u + 1) % DEPTH]);
        if (u < TL) {
          const int s = u >> 3, j = u & 7;
          if (j == 0) {
            cc = s >= YD ? add4(y[s % YD], p) : p;
            if (s + YD < NS) y[s % YD] = ldtex(tex, tb | (yc & 1023));
          } else cc = add4(cc, p);
          if (j == 6) acc[s] = add4(acc[s], cc);
          if (u == TL - 2) arrive_both(emptyL, (more ? lane : 9) + (cc.x & never));
        } else {
          const int s = (u - TL) >> 1;
          acc[s] = add4(acc[s], p);
          if (u == TT - 2) arrive_both(emptyU, lane + ((p.x | acc[s - 1].x) & never));
        }
      }
      if (t < TL) {
        const int s = t >> 3, j = t & 7;
        if (j == 0) {
          if (ye_of(s - YD) >= 0) acc[ye_of(s - YD) & 3] = add4(acc[ye_of(s - YD) & 3], ye);
          w = wq[s % PF];
          wq[s % PF] = ldtex(tex, ti + (s + PF) * TH);
          yc = __funnelshift_l(w.z, w.z, 5);
          if ((s & 3) != 3) asm volatile("add.u32 %0,%1,%2;" : "=r"(sw[s]) : "r"(w.w), "r"(never));
          if (ye_of(s) >= 0) ye = ldtex(tex, tb | w.w);
        }
        if (t >= DEPTH) { lds_l(j, t % DEPTH); lds_l(j + 1, (t + 1) % DEPTH); }
      } else if (t < TT) {
        const int s = (t - TL) >> 1;
        if (s == 0) {
          asm volatile("add.u32 %0,%1,%2;" : "=r"(c1) : "r"((~lc >> 2) & 16), "r"(never));
          TR(k * 4 + 3);
        }
        const uint32_t sv = sget(s);
        x[t % DEPTH] = lds128(sa0(sv));
        x[(t + 1) % DEPTH] = lds128(sa1(sv));
      } else {
        if (t == TT) { mbar_wait_fast(fullL, (k + 1) & 1); w = wq[0]; }
        lds_l(t - TT, t % DEPTH); lds_l(t - TT + 1, (t + 1) % DEPTH);
      }
      if (t == TL - 6) mbar_wait_fast(fullU, (k + 1) & 1);
      else if ((t & 3) == 2 && t > 2 && t < TT) SCHED_FENCE(never, t);
    }
  }
  TS(1, 2);
  const uint4 w2v = lds128(barJ + 32);
  const uint32_t cell = sbase + SM_U + tid * 16;
  const int t9 = tbase + 9 * 1024;
  uint4 za[4], i9 = wq[0];
  auto fetch = [&](int q) {
    y[0] = ldtex(tex, t9 | i9.x); y[1] = ldtex(tex, t9 | i9.y); y[2] = ldtex(tex, t9 | i9.z); y[3] = ldtex(tex, t9 | i9.w);
    if (q) {
      i9 = ldtex(tex, ibase + NC * 8192 + min(q + 1, 7) * TH);
      const uint32_t ca = cell + (q > 6 ? 0 : q - 1) * 16384;
#pragma unroll
      for (int s = 0; s < 4; s++) za[s] = lds128(ca + s * 4096);
    }
  };
  fetch(0);
  i9 = wq[1];
#pragma unroll
  for (int s = 0; s < 4; s++) za[s] = acc[s];
#pragma unroll
  for (int s = 0; s < 24; s++) sts128(cell + s * 4096, acc[4 + s]);
  float hw[8];
  {
    const uint32_t ww[4] = {w2v.x, w2v.y, w2v.z, w2v.w};
#pragma unroll
    for (int k = 0; k < 8; k++) hw[k] = 0.5f * ((k & 1) ? bf_hi(ww[k >> 1]) : bf_lo(ww[k >> 1]));
  }
  float* outp = g_acc + half * 8192 + tid;
#pragma unroll 1
  for (int q = 0; q < NS / 4; q++) {
    uint4 z[4];
#pragma unroll
    for (int s = 0; s < 4; s++) z[s] = add4(za[s], y[s]);
    if (q == 1) {
#pragma unroll
      for (int s = 0; s < 4; s++) sts128(cell + s * 4096, acc[28 + s]);
    }
    if (q < 7) fetch(q + 1);
    SCHED_FENCE(never, 999);
#pragma unroll
    for (int s = 0; s < 4; s++) {
      const uint32_t a[4] = {z[s].x, z[s].y, z[s].z, z[s].w};
      float r0 = 0.f;
#pragma unroll
      for (int k = 0; k < 8; k++) {
        const float v = (k & 1) ? bf_hi(a[k >> 1]) : bf_lo(a[k >> 1]);
        const float u = v * fmaf(v * v, 0.7978845608028654f * 0.044715f, 0.7978845608028654f);
        float th; asm("tanh.approx.f32 %0,%1;" : "=f"(th) : "f"(u));
        r0 = fmaf(fmaf(v, th, v), hw[k], r0);
      }
      asm volatile("red.global.add.f32 [%0],%1;" :: "l"(outp + s * TH), "f"(r0) : "memory");
    }
    outp += 4 * TH;
  }
  TS(1, 3);
  asm volatile("bar.sync 1,%0;" :: "n"(TH + 32) : "memory");
  if (tid == 0) {
    unsigned old; asm volatile("atom.acq_rel.gpu.global.inc.u32 %0,[%1],63;" : "=r"(old) : "l"(&g_done[half * 32]) : "memory");
    asm volatile("st.shared.u32 [%0],%1;" :: "r"(barJ + 8), "r"(old) : "memory");
  }
  asm volatile("bar.sync 2,%0;" :: "n"(TH) : "memory");
  uint32_t old; asm volatile("ld.shared.u32 %0,[%1];" : "=r"(old) : "r"(barJ + 8));
  if (old == 63) {
    if (half == 0 && tid == 25) g_slot = 0;
    if (half == 0 && tid < 25) g_flag[tid * 32] = 0;
    float4 v[8];
#pragma unroll
    for (int q = 0; q < 8; q++) v[q] = __ldcg((const float4*)(g_acc + half * 8192) + q * TH + tid);
#pragma unroll
    for (int q = 0; q < 8; q++) ((uint2*)(out + half * 8192))[q * TH + tid] = make_uint2(pack_bf2(v[q].x, v[q].y), pack_bf2(v[q].z, v[q].w));
    TS(6, 2);
  }
}

}

extern "C" void kernel_launch(void* const* d_in, const int* in_sizes, int n_in, void* d_out, int out_size) {
  const int* idx = (const int*)d_in[0];
  const __nv_bfloat16* table = (const __nv_bfloat16*)d_in[1];
  const __nv_bfloat16* wp = (const __nv_bfloat16*)d_in[2];
  const __nv_bfloat16* w1 = (const __nv_bfloat16*)d_in[3];
  const __nv_bfloat16* b1 = (const __nv_bfloat16*)d_in[4];
  const __nv_bfloat16* w2 = (const __nv_bfloat16*)d_in[5];
  const __nv_bfloat16* b2 = (const __nv_bfloat16*)d_in[6];
  static cudaTextureObject_t texScr = 0, texX = 0;
  static CUtensorMap mapW, mapL, mapS, mapT, mapE, mapC;
  static const void *c_tab = nullptr, *c_w1 = nullptr;
  if (c_tab != table || c_w1 != w1) {
    c_tab = table; c_w1 = w1;
    char* scr = nullptr; cudaGetSymbolAddress((void**)&scr, g_scr);
    auto mk_tex = [](const void* p, size_t bytes, cudaChannelFormatDesc d) {
      cudaResourceDesc rd = {}; rd.resType = cudaResourceTypeLinear; rd.res.linear.devPtr = (void*)p; rd.res.linear.desc = d; rd.res.linear.sizeInBytes = bytes;
      cudaTextureDesc td = {}; td.readMode = cudaReadModeElementType;
      cudaTextureObject_t t = 0; cudaCreateTextureObject(&t, &rd, &td, nullptr); return t;
    };
    if (!texScr) {
      texScr = mk_tex(scr, (size_t)SCR_N * 16, cudaCreateChannelDesc<uint4>());
      texX = mk_tex(scr + (size_t)PX_OFF * 16, (size_t)(SCR_N - PX_OFF) * 16, cudaCreateChannelDesc<unsigned>());
    }
    typedef CUresult (*EncFn)(CUtensorMap*, CUtensorMapDataType, cuuint32_t, void*, const cuuint64_t*, const cuuint64_t*, const cuuint32_t*,
                              const cuuint32_t*, CUtensorMapInterleave, CUtensorMapSwizzle, CUtensorMapL2promotion, CUtensorMapFloatOOBfill);
    EncFn enc = nullptr; cudaDriverEntryPointQueryResult qr;
    cudaGetDriverEntryPoint("cuTensorMapEncodeTiled", (void**)&enc, cudaEnableDefault, &qr);
    const cuuint32_t ones[4] = {1, 1, 1, 1};
    auto mk = [&](CUtensorMap* m, CUtensorMapDataType dt, int rank, void* p, const cuuint64_t* dim, const cuuint64_t* str, const cuuint32_t* box, CUtensorMapSwizzle sw) {
      enc(m, dt, rank, p, dim, str, box, ones, CU_TENSOR_MAP_INTERLEAVE_NONE, sw, CU_TENSOR_MAP_L2_PROMOTION_NONE, CU_TENSOR_MAP_FLOAT_OOB_FILL_NONE);
    };
    { cuuint64_t dim[2] = {H_, F_ * D_}, str[1] = {H_ * 2}; cuuint32_t box[2] = {32, 256};
      mk(&mapW, CU_TENSOR_MAP_DATA_TYPE_BFLOAT16, 2, (void*)w1, dim, str, box, CU_TENSOR_MAP_SWIZZLE_64B); }
    { cuuint64_t dim[4] = {64, 64, V_, NC}, str[3] = {128000 * NC, 128, 128000}; cuuint32_t box[4] = {32, 4, 64, 1};
      mk(&mapL, CU_TENSOR_MAP_DATA_TYPE_BFLOAT16, 4, scr + (size_t)PL_OFF * 16, dim, str, box, CU_TENSOR_MAP_SWIZZLE_64B); }
    { cuuint64_t dim[4] = {64, 64, V_ / 4, NC}, str[3] = {32000 * NC, 128, 32000}; cuuint32_t box[4] = {64, 4, 16, 1};
      mk(&mapS, CU_TENSOR_MAP_DATA_TYPE_BFLOAT16, 4, scr + (size_t)PS_OFF * 16, dim, str, box, CU_TENSOR_MAP_SWIZZLE_128B); }
    { cuuint64_t dim[4] = {64, 64, V_ / 8, 10}, str[3] = {163840, 128, 16384}; cuuint32_t box[4] = {64, 4, 8, 2};
      mk(&mapT, CU_TENSOR_MAP_DATA_TYPE_BFLOAT16, 4, scr + (size_t)PT_OFF * 16, dim, str, box, CU_TENSOR_MAP_SWIZZLE_128B); }
    { cuuint64_t dim[2] = {D_, V_}, str[1] = {D_ * 2}; cuuint32_t box[2] = {64, 128};
      mk(&mapE, CU_TENSOR_MAP_DATA_TYPE_BFLOAT16, 2, (void*)table, dim, str, box, CU_TENSOR_MAP_SWIZZLE_128B);
      cuuint32_t box2[2] = {8, 256};
      mk(&mapC, CU_TENSOR_MAP_DATA_TYPE_BFLOAT16, 2, (void*)table, dim, str, box2, CU_TENSOR_MAP_SWIZZLE_NONE); }
    cudaFuncSetAttribute(k_deep, cudaFuncAttributeMaxDynamicSharedMemorySize, DEEP_SMEM);
    cudaFuncSetAttribute(k_tens, cudaFuncAttributeMaxDynamicSharedMemorySize, K1_SMEM);
  }
  k_tens<<<132, 512, K1_SMEM, cudaStreamPerThread>>>(mapW, mapL, mapS, mapT, mapE, mapC, texScr, texX, idx, table, wp, w1, b1, 0);
  cudaLaunchAttribute at[1];
  at[0].id = cudaLaunchAttributeProgrammaticStreamSerialization; at[0].val.programmaticStreamSerializationAllowed = 1;
  cudaLaunchConfig_t cfg = {};
  cfg.stream = cudaStreamPerThread; cfg.attrs = at;
  cfg.gridDim = 128; cfg.blockDim = TH + 128; cfg.dynamicSmemBytes = DEEP_SMEM; cfg.numAttrs = PDL;
  cudaLaunchKernelEx(&cfg, k_deep, texScr, w2, b2, (__nv_bfloat16*)d_out, 0);

}
```
